```python
import torch

def _softmax(x, axis=-1):
    return torch.softmax(x, dim=axis)

def _gelu(x):
    return torch.nn.functional.gelu(x, approximate='tanh')

def _silu(x):
    return torch.nn.functional.silu(x)

def _sigmoid(x):
    return torch.sigmoid(x)

def _layernorm(x, axis=-1, eps=1e-05):
    m = x.mean(dim=axis, keepdim=True)
    v = x.var(dim=axis, keepdim=True, unbiased=False)
    return (x - m) / torch.sqrt(v + eps)

def _scatter_add(tgt, idx, src, axis=0):
    return tgt.clone().index_add_(axis, idx, src)

def _segment_sum(src, seg, n):
    out = torch.zeros((n,) + src.shape[1:], dtype=src.dtype)
    return out.index_add_(0, seg, src)

def _pad(x, pw):
    flat = tuple((v for pair in reversed(pw) for v in pair))
    return torch.nn.functional.pad(x, flat)
kernel_name = 'adaLN_cond__sliding_local_dilated__swiglu_ffn__prompt'

def setup_inputs():

    _w = lambda a: (lambda t: t.to(torch.bfloat16) if t.is_floating_point() else t)(torch.as_tensor(a))

    def _A_setup():
        B, S, D = (1, 2048, 1024)
        return {'x': _w((lambda *s: torch.randn(*s, dtype=torch.bfloat16) * 0.05)(B, S, D)), 'wqkv': _w((lambda *s: torch.randn(*s, dtype=torch.bfloat16) * 0.05)(D, 3 * D)), 'wo': _w((lambda *s: torch.randn(*s, dtype=torch.bfloat16) * 0.05)(D, D))}
    _A_in = _A_setup()

    def _B_setup():
        B, S, D, F = (1, 2048, 1024, 3584)
        return {'x': _w((lambda *s: torch.randn(*s, dtype=torch.bfloat16) * 0.05)(B, S, D)), 'w_gate': _w((lambda *s: torch.randn(*s, dtype=torch.bfloat16) * 0.05)(D, F)), 'w_up': _w((lambda *s: torch.randn(*s, dtype=torch.bfloat16) * 0.05)(D, F)), 'w_down': _w((lambda *s: torch.randn(*s, dtype=torch.bfloat16) * 0.05)(F, D))}
    _B_in = _B_setup()
    return {'A_x': _A_in['x'], 'A_wqkv': _A_in['wqkv'], 'A_wo': _A_in['wo'], 'B_x': _B_in['x'], 'B_w_gate': _B_in['w_gate'], 'B_w_up': _B_in['w_up'], 'B_w_down': _B_in['w_down'], 'c': _w((lambda *s: torch.randn(*s, dtype=torch.bfloat16) * 0.1)(1, 1024) * 8.0), 'w_mod': _w((lambda *s: torch.randn(*s, dtype=torch.bfloat16) * 0.1)(1024, 6 * 1024) * 1024 ** (-0.5) * 8.0)}

def reference(A_x, A_wqkv, A_wo, B_x, B_w_gate, B_w_up, B_w_down, c, w_mod):

    def _A_ref(x, wqkv, wo):
        B, S, D = x.shape
        H = 32
        Dh = D // H
        W, dil = (8, 2)
        qkv = (lambda x, *d: x.permute(*d))((x @ wqkv).reshape(B, S, 3, H, Dh), 2, 0, 3, 1, 4)
        q, k, v = (qkv[0], qkv[1], qkv[2])
        scale = Dh ** (-0.5)
        pos = torch.arange(S)
        off = torch.arange(W) * dil
        idx = pos[:, None] - off[None, :]
        mask = idx >= 0
        idx_c = torch.where(mask, idx, 0).reshape(-1)
        kg = k[:, :, idx_c, :].reshape(B, H, S, W, Dh)
        vg = v[:, :, idx_c, :].reshape(B, H, S, W, Dh)
        logits = torch.einsum('bhsd,bhswd->bhsw', q, kg) * scale
        logits = torch.where(mask[None, None, :, :], logits, -1000000000.0)
        attn = _softmax(logits, axis=-1)
        o = torch.einsum('bhsw,bhswd->bhsd', attn, vg)
        return (lambda x, *d: x.permute(*d))(o, 0, 2, 1, 3).reshape(B, S, D) @ wo

    def _B_ref(x, w_gate, w_up, w_down):
        g = _silu(x @ w_gate)
        u = x @ w_up
        return g * u @ w_down
    x = A_x
    mod = (_silu(c) @ w_mod).reshape(c.shape[0], 6, 1, -1)
    sa, ca, ga, sb, cb, gb = (mod[:, 0].clone(), mod[:, 1].clone(), mod[:, 2].clone(), mod[:, 3].clone(), mod[:, 4].clone(), mod[:, 5].clone())
    h = _layernorm(x, axis=-1) * (1 + ca) + sa
    x = x + ga * _A_ref(h, A_wqkv, A_wo)
    h = _layernorm(x, axis=-1) * (1 + cb) + sb
    x = x + gb * _B_ref(h, B_w_gate, B_w_up, B_w_down)
    return x
```

```cpp
#include <cuda_runtime.h>
#include <cuda_bf16.h>
#include <cuda.h>
#include <stdint.h>

typedef __nv_bfloat16 bf16;

#define MAPPING 0

__device__ __forceinline__ void wgmma_ss_n128(float (&d)[64], uint64_t da, uint64_t db, int scale_d) {
  asm volatile("{\n.reg .pred p;\nsetp.ne.b32 p, %66, 0;\n"
    "wgmma.mma_async.sync.aligned.m64n128k16.f32.bf16.bf16 "
    "{%0, %1, %2, %3, %4, %5, %6, %7, %8, %9, %10, %11, %12, %13, %14, %15, "
    "%16, %17, %18, %19, %20, %21, %22, %23, %24, %25, %26, %27, %28, %29, %30, %31, "
    "%32, %33, %34, %35, %36, %37, %38, %39, %40, %41, %42, %43, %44, %45, %46, %47, "
    "%48, %49, %50, %51, %52, %53, %54, %55, %56, %57, %58, %59, %60, %61, %62, %63}, "
    "%64, %65, p, 1, 1, 0, 1;\n}\n"
    : "+f"(d[0]), "+f"(d[1]), "+f"(d[2]), "+f"(d[3]), "+f"(d[4]), "+f"(d[5]), "+f"(d[6]), "+f"(d[7]),
      "+f"(d[8]), "+f"(d[9]), "+f"(d[10]), "+f"(d[11]), "+f"(d[12]), "+f"(d[13]), "+f"(d[14]), "+f"(d[15]),
      "+f"(d[16]), "+f"(d[17]), "+f"(d[18]), "+f"(d[19]), "+f"(d[20]), "+f"(d[21]), "+f"(d[22]), "+f"(d[23]),
      "+f"(d[24]), "+f"(d[25]), "+f"(d[26]), "+f"(d[27]), "+f"(d[28]), "+f"(d[29]), "+f"(d[30]), "+f"(d[31]),
      "+f"(d[32]), "+f"(d[33]), "+f"(d[34]), "+f"(d[35]), "+f"(d[36]), "+f"(d[37]), "+f"(d[38]), "+f"(d[39]),
      "+f"(d[40]), "+f"(d[41]), "+f"(d[42]), "+f"(d[43]), "+f"(d[44]), "+f"(d[45]), "+f"(d[46]), "+f"(d[47]),
      "+f"(d[48]), "+f"(d[49]), "+f"(d[50]), "+f"(d[51]), "+f"(d[52]), "+f"(d[53]), "+f"(d[54]), "+f"(d[55]),
      "+f"(d[56]), "+f"(d[57]), "+f"(d[58]), "+f"(d[59]), "+f"(d[60]), "+f"(d[61]), "+f"(d[62]), "+f"(d[63])
    : "l"(da), "l"(db), "r"(scale_d));
}

__device__ __forceinline__ void wgmma_ss_n192(float (&d)[96], uint64_t da, uint64_t db, int scale_d) {
  asm volatile("{\n.reg .pred p;\nsetp.ne.b32 p, %98, 0;\n"
    "wgmma.mma_async.sync.aligned.m64n192k16.f32.bf16.bf16 "
    "{%0, %1, %2, %3, %4, %5, %6, %7, %8, %9, %10, %11, %12, %13, %14, %15, "
    "%16, %17, %18, %19, %20, %21, %22, %23, %24, %25, %26, %27, %28, %29, %30, %31, "
    "%32, %33, %34, %35, %36, %37, %38, %39, %40, %41, %42, %43, %44, %45, %46, %47, "
    "%48, %49, %50, %51, %52, %53, %54, %55, %56, %57, %58, %59, %60, %61, %62, %63, "
    "%64, %65, %66, %67, %68, %69, %70, %71, %72, %73, %74, %75, %76, %77, %78, %79, "
    "%80, %81, %82, %83, %84, %85, %86, %87, %88, %89, %90, %91, %92, %93, %94, %95}, "
    "%96, %97, p, 1, 1, 0, 1;\n}\n"
    : "+f"(d[0]), "+f"(d[1]), "+f"(d[2]), "+f"(d[3]), "+f"(d[4]), "+f"(d[5]), "+f"(d[6]), "+f"(d[7]),
      "+f"(d[8]), "+f"(d[9]), "+f"(d[10]), "+f"(d[11]), "+f"(d[12]), "+f"(d[13]), "+f"(d[14]), "+f"(d[15]),
      "+f"(d[16]), "+f"(d[17]), "+f"(d[18]), "+f"(d[19]), "+f"(d[20]), "+f"(d[21]), "+f"(d[22]), "+f"(d[23]),
      "+f"(d[24]), "+f"(d[25]), "+f"(d[26]), "+f"(d[27]), "+f"(d[28]), "+f"(d[29]), "+f"(d[30]), "+f"(d[31]),
      "+f"(d[32]), "+f"(d[33]), "+f"(d[34]), "+f"(d[35]), "+f"(d[36]), "+f"(d[37]), "+f"(d[38]), "+f"(d[39]),
      "+f"(d[40]), "+f"(d[41]), "+f"(d[42]), "+f"(d[43]), "+f"(d[44]), "+f"(d[45]), "+f"(d[46]), "+f"(d[47]),
      "+f"(d[48]), "+f"(d[49]), "+f"(d[50]), "+f"(d[51]), "+f"(d[52]), "+f"(d[53]), "+f"(d[54]), "+f"(d[55]),
      "+f"(d[56]), "+f"(d[57]), "+f"(d[58]), "+f"(d[59]), "+f"(d[60]), "+f"(d[61]), "+f"(d[62]), "+f"(d[63]),
      "+f"(d[64]), "+f"(d[65]), "+f"(d[66]), "+f"(d[67]), "+f"(d[68]), "+f"(d[69]), "+f"(d[70]), "+f"(d[71]),
      "+f"(d[72]), "+f"(d[73]), "+f"(d[74]), "+f"(d[75]), "+f"(d[76]), "+f"(d[77]), "+f"(d[78]), "+f"(d[79]),
      "+f"(d[80]), "+f"(d[81]), "+f"(d[82]), "+f"(d[83]), "+f"(d[84]), "+f"(d[85]), "+f"(d[86]), "+f"(d[87]),
      "+f"(d[88]), "+f"(d[89]), "+f"(d[90]), "+f"(d[91]), "+f"(d[92]), "+f"(d[93]), "+f"(d[94]), "+f"(d[95])
    : "l"(da), "l"(db), "r"(scale_d));
}

__device__ __forceinline__ void wgmma_ss_n256(float (&d)[128], uint64_t da, uint64_t db, int scale_d) {
  asm volatile("{\n.reg .pred p;\nsetp.ne.b32 p, %130, 0;\n"
    "wgmma.mma_async.sync.aligned.m64n256k16.f32.bf16.bf16 "
    "{%0, %1, %2, %3, %4, %5, %6, %7, %8, %9, %10, %11, %12, %13, %14, %15, "
    "%16, %17, %18, %19, %20, %21, %22, %23, %24, %25, %26, %27, %28, %29, %30, %31, "
    "%32, %33, %34, %35, %36, %37, %38, %39, %40, %41, %42, %43, %44, %45, %46, %47, "
    "%48, %49, %50, %51, %52, %53, %54, %55, %56, %57, %58, %59, %60, %61, %62, %63, "
    "%64, %65, %66, %67, %68, %69, %70, %71, %72, %73, %74, %75, %76, %77, %78, %79, "
    "%80, %81, %82, %83, %84, %85, %86, %87, %88, %89, %90, %91, %92, %93, %94, %95, "
    "%96, %97, %98, %99, %100, %101, %102, %103, %104, %105, %106, %107, %108, %109, %110, %111, "
    "%112, %113, %114, %115, %116, %117, %118, %119, %120, %121, %122, %123, %124, %125, %126, %127}, "
    "%128, %129, p, 1, 1, 0, 1;\n}\n"
    : "+f"(d[0]), "+f"(d[1]), "+f"(d[2]), "+f"(d[3]), "+f"(d[4]), "+f"(d[5]), "+f"(d[6]), "+f"(d[7]),
      "+f"(d[8]), "+f"(d[9]), "+f"(d[10]), "+f"(d[11]), "+f"(d[12]), "+f"(d[13]), "+f"(d[14]), "+f"(d[15]),
      "+f"(d[16]), "+f"(d[17]), "+f"(d[18]), "+f"(d[19]), "+f"(d[20]), "+f"(d[21]), "+f"(d[22]), "+f"(d[23]),
      "+f"(d[24]), "+f"(d[25]), "+f"(d[26]), "+f"(d[27]), "+f"(d[28]), "+f"(d[29]), "+f"(d[30]), "+f"(d[31]),
      "+f"(d[32]), "+f"(d[33]), "+f"(d[34]), "+f"(d[35]), "+f"(d[36]), "+f"(d[37]), "+f"(d[38]), "+f"(d[39]),
      "+f"(d[40]), "+f"(d[41]), "+f"(d[42]), "+f"(d[43]), "+f"(d[44]), "+f"(d[45]), "+f"(d[46]), "+f"(d[47]),
      "+f"(d[48]), "+f"(d[49]), "+f"(d[50]), "+f"(d[51]), "+f"(d[52]), "+f"(d[53]), "+f"(d[54]), "+f"(d[55]),
      "+f"(d[56]), "+f"(d[57]), "+f"(d[58]), "+f"(d[59]), "+f"(d[60]), "+f"(d[61]), "+f"(d[62]), "+f"(d[63]),
      "+f"(d[64]), "+f"(d[65]), "+f"(d[66]), "+f"(d[67]), "+f"(d[68]), "+f"(d[69]), "+f"(d[70]), "+f"(d[71]),
      "+f"(d[72]), "+f"(d[73]), "+f"(d[74]), "+f"(d[75]), "+f"(d[76]), "+f"(d[77]), "+f"(d[78]), "+f"(d[79]),
      "+f"(d[80]), "+f"(d[81]), "+f"(d[82]), "+f"(d[83]), "+f"(d[84]), "+f"(d[85]), "+f"(d[86]), "+f"(d[87]),
      "+f"(d[88]), "+f"(d[89]), "+f"(d[90]), "+f"(d[91]), "+f"(d[92]), "+f"(d[93]), "+f"(d[94]), "+f"(d[95]),
      "+f"(d[96]), "+f"(d[97]), "+f"(d[98]), "+f"(d[99]), "+f"(d[100]), "+f"(d[101]), "+f"(d[102]), "+f"(d[103]),
      "+f"(d[104]), "+f"(d[105]), "+f"(d[106]), "+f"(d[107]), "+f"(d[108]), "+f"(d[109]), "+f"(d[110]), "+f"(d[111]),
      "+f"(d[112]), "+f"(d[113]), "+f"(d[114]), "+f"(d[115]), "+f"(d[116]), "+f"(d[117]), "+f"(d[118]), "+f"(d[119]),
      "+f"(d[120]), "+f"(d[121]), "+f"(d[122]), "+f"(d[123]), "+f"(d[124]), "+f"(d[125]), "+f"(d[126]), "+f"(d[127])
    : "l"(da), "l"(db), "r"(scale_d));
}

namespace {

constexpr int SEQ = 2048, DM = 1024, FF = 3584;
constexpr int NCTA = 128;

constexpr uint32_t STG_OFF = 196608;
constexpr uint32_t MISC_OFF = STG_OFF + 32768;
constexpr uint32_t SMEM_BYTES = MISC_OFF + 3072;
constexpr uint32_t MODB_OFF = MISC_OFF + 512;
constexpr uint32_t REDB_OFF = MODB_OFF + 2048;

enum { B_FQ = 0, B_EQ = 4, B_FW = 8, B_EW = 14, B_FG = 20, B_EG = 24, B_FD = 28, B_ED = 34,
       B_STGF = 40, B_STGE = 41, B_MODB = 42, B_COUNT = 43 };
enum { C_H = 0, C_O = 1, C_H2 = 3, C_ACT = 4 };

struct Params {
  CUtensorMap h, o_ld, o_st, h2, act, out, wqkv, wo, wg, wu, wd;
  const bf16* x;
  const bf16* c;
  const bf16* wmod;
};

__device__ bf16 g_h[SEQ * DM];
__device__ bf16 g_o[SEQ * DM];
__device__ bf16 g_h2[SEQ * DM];
__device__ bf16 g_act[SEQ * FF];
__device__ uint4 g_x1[NCTA * 8 * 256];
__device__ uint4 g_modll[3072 / 2];
__device__ uint4 g_halo[16 * 8 * 2 * 2 * 8 * 32];
__device__ uint4 g_stats[SEQ * 8];
__device__ unsigned g_cnt[16 * 8 * 32];
__device__ unsigned g_epoch;

__device__ __forceinline__ uint32_t smem_u32(const void* p) { return (uint32_t)__cvta_generic_to_shared(p); }
__device__ __forceinline__ void mbar_init(uint32_t bar, uint32_t count) {
  asm volatile("mbarrier.init.shared::cta.b64 [%0], %1;" ::"r"(bar), "r"(count));
}
__device__ __forceinline__ void mbar_expect_tx(uint32_t bar, uint32_t bytes) {
  asm volatile("mbarrier.arrive.expect_tx.shared::cta.b64 _, [%0], %1;" ::"r"(bar), "r"(bytes) : "memory");
}
__device__ __forceinline__ void mbar_arrive(uint32_t bar) {
  asm volatile("mbarrier.arrive.shared::cta.b64 _, [%0];" ::"r"(bar) : "memory");
}
__device__ __forceinline__ void mbar_arrive_cluster(uint32_t cluster_addr) {
  asm volatile("mbarrier.arrive.shared::cluster.b64 _, [%0];" ::"r"(cluster_addr) : "memory");
}
__device__ __forceinline__ uint32_t mapa(uint32_t addr, uint32_t cta) {
  uint32_t r;
  asm volatile("mapa.shared::cluster.u32 %0, %1, %2;" : "=r"(r) : "r"(addr), "r"(cta));
  return r;
}
__device__ __forceinline__ void mbar_wait(uint32_t bar, uint32_t parity) {
  asm volatile(
      "{\n.reg .pred p;\n.reg .u32 n;\nmov.u32 n, 0;\n"
      "WAIT_%=:\n"
      "mbarrier.try_wait.parity.shared::cta.b64 p, [%0], %1;\n"
      "@p bra DONE_%=;\n"
      "add.u32 n, n, 1;\n"
      "setp.lt.u32 p, n, 2097152;\n"
      "@p bra WAIT_%=;\n"
      "trap;\n"
      "DONE_%=:\n}\n" ::"r"(bar), "r"(parity) : "memory");
}
__device__ __forceinline__ void cnt_wait(const unsigned* p, unsigned target) {
  asm volatile(
      "{\n.reg .pred p;\n.reg .u32 n, v;\n.reg .s32 d;\nmov.u32 n, 0;\n"
      "WAIT_%=:\n"
      "ld.acquire.gpu.global.u32 v, [%0];\n"
      "sub.s32 d, v, %1;\n"
      "setp.ge.s32 p, d, 0;\n"
      "@p bra DONE_%=;\n"
      "add.u32 n, n, 1;\n"
      "setp.lt.u32 p, n, 4194304;\n"
      "@p bra WAIT_%=;\n"
      "trap;\n"
      "DONE_%=:\n"
      "fence.proxy.async.global;\n}\n" ::"l"(p), "r"(target) : "memory");
}
__device__ __forceinline__ void cnt_signal(unsigned* p) {
  asm volatile("red.release.gpu.global.add.u32 [%0], 1;" ::"l"(p) : "memory");
}
__device__ __forceinline__ void ll_store(uint4* p, uint32_t a, uint32_t b, uint32_t tag) {
  asm volatile("st.relaxed.gpu.global.v2.b64 [%0], {%1, %2};" ::"l"(p), "l"((uint64_t)a | ((uint64_t)tag << 32)),
               "l"((uint64_t)b | ((uint64_t)tag << 32)) : "memory");
}
__device__ __forceinline__ void ll_load(const uint4* p, uint32_t tag, uint32_t& a, uint32_t& b) {
  asm volatile(
      "{\n.reg .pred p, q;\n.reg .u32 n, t0, t1;\n.reg .b64 x, y;\nmov.u32 n, 0;\n"
      "WAIT_%=:\n"
      "ld.relaxed.gpu.global.v2.b64 {x, y}, [%2];\n"
      "mov.b64 {%0, t0}, x;\n"
      "mov.b64 {%1, t1}, y;\n"
      "setp.eq.u32 q, t0, %3;\n"
      "setp.eq.and.u32 p, t1, %3, q;\n"
      "@p bra DONE_%=;\n"
      "add.u32 n, n, 1;\n"
      "setp.lt.u32 p, n, 4194304;\n"
      "@p bra WAIT_%=;\n"
      "trap;\n"
      "DONE_%=:\n}\n" : "=r"(a), "=r"(b) : "l"(p), "r"(tag) : "memory");
}
__device__ __forceinline__ uint4 ll_peek(const uint4* p) {
  uint4 v;
  asm volatile("ld.relaxed.gpu.global.v4.u32 {%0, %1, %2, %3}, [%4];" : "=r"(v.x), "=r"(v.y), "=r"(v.z), "=r"(v.w) : "l"(p) : "memory");
  return v;
}
__device__ __forceinline__ void tma_load(uint32_t dst, const CUtensorMap* m, uint32_t bar, int c0, int c1) {
  asm volatile("cp.async.bulk.tensor.2d.shared::cluster.global.mbarrier::complete_tx::bytes [%0], [%1, {%3, %4}], [%2];"
               ::"r"(dst), "l"(m), "r"(bar), "r"(c0), "r"(c1) : "memory");
}
__device__ __forceinline__ void tma_load_mc(uint32_t dst, const CUtensorMap* m, uint32_t bar, int c0, int c1) {
  asm volatile("cp.async.bulk.tensor.2d.shared::cluster.global.mbarrier::complete_tx::bytes.multicast::cluster [%0], [%1, {%3, %4}], [%2], %5;"
               ::"r"(dst), "l"(m), "r"(bar), "r"(c0), "r"(c1), "h"((uint16_t)3) : "memory");
}
__device__ __forceinline__ void tma_store2(const CUtensorMap* m, uint32_t src, int c0, int c1) {
  asm volatile("cp.async.bulk.tensor.2d.global.shared::cta.bulk_group [%0, {%2, %3}], [%1];"
               ::"l"(m), "r"(src), "r"(c0), "r"(c1) : "memory");
}
__device__ __forceinline__ void tma_store3(const CUtensorMap* m, uint32_t src, int c0, int c1, int c2) {
  asm volatile("cp.async.bulk.tensor.3d.global.shared::cta.bulk_group [%0, {%2, %3, %4}], [%1];"
               ::"l"(m), "r"(src), "r"(c0), "r"(c1), "r"(c2) : "memory");
}
__device__ __forceinline__ void prefetch_map(const CUtensorMap* m) {
  asm volatile("prefetch.tensormap [%0];" ::"l"(m) : "memory");
}
__device__ __forceinline__ void wg_fence() { asm volatile("wgmma.fence.sync.aligned;" ::: "memory"); }
__device__ __forceinline__ void wg_commit() { asm volatile("wgmma.commit_group.sync.aligned;" ::: "memory"); }
template <int N>
__device__ __forceinline__ void wg_wait() { asm volatile("wgmma.wait_group.sync.aligned %0;" ::"n"(N) : "memory"); }
__device__ __forceinline__ void bar_sync(int id, int n) { asm volatile("bar.sync %0, %1;" ::"r"(id), "r"(n) : "memory"); }
__device__ __forceinline__ void cluster_sync() {
  asm volatile("barrier.cluster.arrive.release.aligned;\nbarrier.cluster.wait.acquire.aligned;" ::: "memory");
}
__device__ __forceinline__ uint32_t pack2(float lo, float hi) {
  uint32_t r;
  asm("cvt.rn.bf16x2.f32 %0, %1, %2;" : "=r"(r) : "f"(hi), "f"(lo));
  return r;
}
__device__ __forceinline__ float bf_lo(uint32_t v) { return __uint_as_float(v << 16); }
__device__ __forceinline__ float bf_hi(uint32_t v) { return __uint_as_float(v & 0xffff0000u); }
__device__ __forceinline__ float bf_round(float v) { return __bfloat162float(__float2bfloat16_rn(v)); }
__device__ __forceinline__ float silu_f(float v) { return __fdividef(v, 1.0f + __expf(-v)); }
__device__ __forceinline__ uint4 ldg_nc(const void* p) {
  uint4 v;
  asm volatile("ld.global.nc.L1::no_allocate.v4.u32 {%0, %1, %2, %3}, [%4];" : "=r"(v.x), "=r"(v.y), "=r"(v.z), "=r"(v.w) : "l"(p));
  return v;
}
__device__ __forceinline__ void stmatrix4(uint32_t addr, uint32_t a, uint32_t b, uint32_t c, uint32_t d) {
  asm volatile("stmatrix.sync.aligned.m8n8.x4.shared.b16 [%0], {%1, %2, %3, %4};" ::"r"(addr), "r"(a), "r"(b), "r"(c), "r"(d) : "memory");
}
__device__ __forceinline__ uint32_t movmatrix(uint32_t a) {
  uint32_t d;
  asm volatile("movmatrix.sync.aligned.m8n8.trans.b16 %0, %1;" : "=r"(d) : "r"(a));
  return d;
}
__device__ __forceinline__ void mma16816(float (&d)[4], uint32_t a0, uint32_t a1, uint32_t a2, uint32_t a3, uint32_t b0, uint32_t b1) {
  asm volatile("mma.sync.aligned.m16n8k16.row.col.f32.bf16.bf16.f32 {%0, %1, %2, %3}, {%4, %5, %6, %7}, {%8, %9}, {%0, %1, %2, %3};"
               : "+f"(d[0]), "+f"(d[1]), "+f"(d[2]), "+f"(d[3]) : "r"(a0), "r"(a1), "r"(a2), "r"(a3), "r"(b0), "r"(b1));
}
__device__ __forceinline__ void mma1688(float (&d)[4], uint32_t a0, uint32_t a1, uint32_t b0) {
  asm volatile("mma.sync.aligned.m16n8k8.row.col.f32.bf16.bf16.f32 {%0, %1, %2, %3}, {%4, %5}, {%6}, {%0, %1, %2, %3};"
               : "+f"(d[0]), "+f"(d[1]), "+f"(d[2]), "+f"(d[3]) : "r"(a0), "r"(a1), "r"(b0));
}
__device__ __forceinline__ void sts128(uint32_t addr, uint32_t a, uint32_t b, uint32_t c, uint32_t d) {
  asm volatile("st.shared.v4.u32 [%0], {%1, %2, %3, %4};" ::"r"(addr), "r"(a), "r"(b), "r"(c), "r"(d) : "memory");
}
__device__ __forceinline__ uint4 lds128(uint32_t addr) {
  uint4 v;
  asm volatile("ld.shared.v4.u32 {%0, %1, %2, %3}, [%4];" : "=r"(v.x), "=r"(v.y), "=r"(v.z), "=r"(v.w) : "r"(addr) : "memory");
  return v;
}
__device__ __forceinline__ float2 lds64f(uint32_t addr) {
  float2 v;
  asm volatile("ld.shared.v2.f32 {%0, %1}, [%2];" : "=f"(v.x), "=f"(v.y) : "r"(addr) : "memory");
  return v;
}
__device__ __forceinline__ void sts32f(uint32_t addr, float v) {
  asm volatile("st.shared.f32 [%0], %1;" ::"r"(addr), "f"(v) : "memory");
}
__device__ __forceinline__ float lds32f(uint32_t addr) {
  float v;
  asm volatile("ld.shared.f32 %0, [%1];" : "=f"(v) : "r"(addr) : "memory");
  return v;
}
#define PROF_AT(cond, slot) do {} while (0)

constexpr uint64_t DESC_A = ((uint64_t)1 << 62) | ((uint64_t)(1024 >> 4) << 32) | ((uint64_t)1 << 16);
constexpr uint64_t DESC_B = ((uint64_t)1 << 62) | ((uint64_t)(1024 >> 4) << 32) | ((uint64_t)(8192 >> 4) << 16);

template <int BN> struct Wg;
template <> struct Wg<128> { static __device__ __forceinline__ void mma(float (&d)[64], uint64_t a, uint64_t b, int s) { wgmma_ss_n128(d, a, b, s); } };
template <> struct Wg<192> { static __device__ __forceinline__ void mma(float (&d)[96], uint64_t a, uint64_t b, int s) { wgmma_ss_n192(d, a, b, s); } };
template <> struct Wg<256> { static __device__ __forceinline__ void mma(float (&d)[128], uint64_t a, uint64_t b, int s) { wgmma_ss_n256(d, a, b, s); } };

template <int BN, int NST, uint32_t STAGE>
__device__ __forceinline__ void mainloop(float (&acc)[BN / 2], uint32_t a_base, uint32_t b_base, uint32_t full0,
                                         uint32_t rel0, bool releaser, int nkb, int& s, uint32_t& ph) {
  int prev = 0;
  for (int kb = 0; kb < nkb; kb++) {
    mbar_wait(full0 + 8 * s, ph);
    const uint64_t da = DESC_A | (uint64_t)((a_base + s * STAGE) >> 4);
    const uint64_t db = DESC_B | (uint64_t)((b_base + s * STAGE) >> 4);
    wg_fence();
#pragma unroll
    for (int k = 0; k < 4; k++) Wg<BN>::mma(acc, da + k * 2, db + k * 128, (kb | k) != 0);
    wg_commit();
    wg_wait<1>();
    if (kb > 0 && releaser) mbar_arrive_cluster(rel0 + 8 * prev);
    prev = s;
    if (++s == NST) { s = 0; ph ^= 1; }
  }
  wg_wait<0>();
  if (releaser) mbar_arrive_cluster(rel0 + 8 * prev);
}

__device__ __forceinline__ void stage_slab(uint32_t chunk, int warp, int lane, const uint32_t (&lo)[8], const uint32_t (&hi)[8]) {
  const int row = warp * 16 + (lane & 7) + ((lane >> 3) & 1) * 8;
  const uint32_t rbase = chunk + row * 128;
#pragma unroll
  for (int q = 0; q < 4; q++) {
    const int grp = 2 * q + (lane >> 4);
    stmatrix4(rbase + ((grp ^ (row & 7)) << 4), lo[2 * q], hi[2 * q], lo[2 * q + 1], hi[2 * q + 1]);
  }
}
__device__ __forceinline__ void stage_done(uint32_t bar, int lane) {
  asm volatile("fence.proxy.async.shared::cta;" ::: "memory");
  __syncwarp();
  if (lane == 0) mbar_arrive(bar);
}

__global__ void __launch_bounds__(384, 1) fused_kernel(const __grid_constant__ Params p) {
  extern __shared__ __align__(1024) uint8_t smem_raw[];
  const uint32_t sm = smem_u32(smem_raw);
  const uint32_t bars = sm + MISC_OFF;
  const uint32_t stg = sm + STG_OFF;
  const int rank = blockIdx.x & 1;
  const int cl = blockIdx.x >> 1;
  const int g = cl >> 2, jp = cl & 3;
  const int j = jp * 2 + rank;
  const int cta = g * 8 + j;
  PROF_AT(threadIdx.x == 0, 0);

  if (threadIdx.x == 0) {
    if (sm & 1023) asm volatile("trap;");
    for (int i = 0; i < 4; i++) { mbar_init(bars + 8 * (B_FQ + i), 1); mbar_init(bars + 8 * (B_EQ + i), 4); }
    for (int i = 0; i < 6; i++) { mbar_init(bars + 8 * (B_FW + i), 1); mbar_init(bars + 8 * (B_EW + i), 4); }
    for (int i = 0; i < 4; i++) { mbar_init(bars + 8 * (B_FG + i), 1); mbar_init(bars + 8 * (B_EG + i), 4); }
    for (int i = 0; i < 6; i++) { mbar_init(bars + 8 * (B_FD + i), 1); mbar_init(bars + 8 * (B_ED + i), 4); }
    mbar_init(bars + 8 * B_STGF, 8);
    mbar_init(bars + 8 * B_STGE, 1);
    mbar_init(bars + 8 * B_MODB, 2);
    asm volatile("fence.mbarrier_init.release.cluster;" ::: "memory");
  }
  unsigned epoch;
  asm volatile("ld.relaxed.gpu.global.u32 %0, [%1];" : "=r"(epoch) : "l"(&g_epoch) : "memory");
  const uint32_t tag = epoch + 1;
  const unsigned target = tag * 8;
  unsigned* cnt = g_cnt + g * 8 * 32;

  if (threadIdx.x < 128) {
    asm volatile("setmaxnreg.dec.sync.aligned.u32 40;");
    cluster_sync();
    const int warp = threadIdx.x >> 5, lane = threadIdx.x & 31;
    if (warp == 0) {
      if (lane == 0) {
        const int arow = g * 128 + rank * 64;
        const uint32_t aoff = rank * 8192;
        prefetch_map(&p.wqkv); prefetch_map(&p.h);
        for (int it = 0; it < 32; it++) {
          const int s = it & 3, kb = it & 15, col = j * 128 + (it >> 4) * 64;
          const uint32_t st = sm + s * 49152, fb = bars + 8 * (B_FQ + s);
          if (it >= 4) mbar_wait(bars + 8 * (B_EQ + s), ((it >> 2) - 1) & 1);
          mbar_expect_tx(fb, 40960);
          tma_load(st + 16384, &p.wqkv, fb, col, kb * 64);
          tma_load(st + 24576, &p.wqkv, fb, col + 1024, kb * 64);
          tma_load(st + 32768, &p.wqkv, fb, col + 2048, kb * 64);
          if (it == 3) {
            cnt_wait(cnt + C_H * 32, target);
            PROF_AT(true, 16);
            for (int i = 0; i < 4; i++) tma_load_mc(sm + i * 49152 + aoff, &p.h, bars + 8 * (B_FQ + i), i * 64, arow);
            prefetch_map(&p.wo); prefetch_map(&p.o_ld); prefetch_map(&p.wg); prefetch_map(&p.wu);
            prefetch_map(&p.h2); prefetch_map(&p.wd); prefetch_map(&p.act);
          } else if (it > 3) {
            tma_load_mc(st + aoff, &p.h, fb, kb * 64, arow);
          }
        }
        for (int it = 0; it < 16; it++) {
          const int s = it % 6, k0 = ((it + jp * 2) & 7) * 128 + (it >> 3) * 64;
          const uint32_t st = sm + s * 32768, fb = bars + 8 * (B_FW + s);
          if (it < 6) {
            mbar_wait(bars + 8 * (B_EQ + (it * 2) / 3), 1);
            mbar_wait(bars + 8 * (B_EQ + (it * 2 + 1) / 3), 1);
          } else {
            mbar_wait(bars + 8 * (B_EW + s), (it / 6 - 1) & 1);
          }
          mbar_expect_tx(fb, 32768);
          tma_load(st + 16384, &p.wo, fb, j * 128, k0);
          tma_load(st + 24576, &p.wo, fb, j * 128 + 64, k0);
          if ((it & 7) == 0) { cnt_wait(cnt + (C_O + (it >> 3)) * 32, target); PROF_AT(true, 17 + (it >> 3)); }
          tma_load_mc(st + aoff, &p.o_ld, fb, k0, arow);
        }
        for (int it = 0; it < 64; it++) {
          const int s = it & 3, kb = it & 15, t = it >> 4, col = j * 448 + t * 128;
          const uint32_t st = sm + s * 49152, fb = bars + 8 * (B_FG + s);
          if (it < 4) {
            const int w0 = (it * 3) / 2, w1 = (it * 3 + 2) / 2;
            mbar_wait(bars + 8 * (B_EW + w0), w0 < 4 ? 0 : 1);
            mbar_wait(bars + 8 * (B_EW + w1), w1 < 4 ? 0 : 1);
          } else {
            mbar_wait(bars + 8 * (B_EG + s), ((it >> 2) - 1) & 1);
          }
          if (t < 3) {
            mbar_expect_tx(fb, 49152);
            tma_load(st + 16384, &p.wg, fb, col, kb * 64);
            tma_load(st + 24576, &p.wg, fb, col + 64, kb * 64);
            tma_load(st + 32768, &p.wu, fb, col, kb * 64);
            tma_load(st + 40960, &p.wu, fb, col + 64, kb * 64);
          } else {
            mbar_expect_tx(fb, 32768);
            tma_load(st + 16384, &p.wg, fb, col, kb * 64);
            tma_load(st + 24576, &p.wu, fb, col, kb * 64);
          }
          if (it == 3) {
            cnt_wait(cnt + C_H2 * 32, target);
            PROF_AT(true, 19);
            for (int i = 0; i < 4; i++) tma_load_mc(sm + i * 49152 + aoff, &p.h2, bars + 8 * (B_FG + i), i * 64, arow);
          } else if (it > 3) {
            tma_load_mc(st + aoff, &p.h2, fb, kb * 64, arow);
          }
        }
        for (int it = 0; it < 56; it++) {
          const int s = it % 6, r = it >> 4, idx = it & 15;
          const int jj = ((r < 3 ? idx >> 1 : idx) + jp * 2) & 7;
          const int k0 = jj * 448 + r * 128 + (r < 3 ? (idx & 1) * 64 : 0);
          const uint32_t st = sm + s * 32768, fb = bars + 8 * (B_FD + s);
          if (it < 6) {
            mbar_wait(bars + 8 * (B_EG + (it * 2) / 3), 1);
            mbar_wait(bars + 8 * (B_EG + (it * 2 + 1) / 3), 1);
          } else {
            mbar_wait(bars + 8 * (B_ED + s), (it / 6 - 1) & 1);
          }
          mbar_expect_tx(fb, 32768);
          tma_load(st + 16384, &p.wd, fb, j * 128, k0);
          tma_load(st + 24576, &p.wd, fb, j * 128 + 64, k0);
          if (idx == 0) { cnt_wait(cnt + (C_ACT + r) * 32, target); PROF_AT(true, 20 + r); }
          tma_load_mc(st + aoff, &p.act, fb, k0, arow);
        }
      }
    } else if (warp == 1) {
      if (lane == 0) {
        prefetch_map(&p.o_st); prefetch_map(&p.out);
        for (int n = 0; n < 8; n++) {
          mbar_wait(bars + 8 * B_STGF, n & 1);
          if (n < 2) {
            tma_store3(&p.o_st, stg, j * 128 + n * 64, 0, g * 64);
            tma_store3(&p.o_st, stg + 8192, j * 128 + n * 64, 1, g * 64);
          } else {
            const CUtensorMap* m = n == 2 ? &p.h2 : (n == 7 ? &p.out : &p.act);
            const int col = (n == 2 || n == 7) ? j * 128 : j * 448 + (n - 3) * 128;
            tma_store2(m, stg, col, g * 128);
            tma_store2(m, stg + 16384, col, g * 128 + 64);
            if (n != 6) {
              tma_store2(m, stg + 8192, col + 64, g * 128);
              tma_store2(m, stg + 24576, col + 64, g * 128 + 64);
            }
          }
          asm volatile("cp.async.bulk.commit_group;" ::: "memory");
          asm volatile("cp.async.bulk.wait_group 0;" ::: "memory");
          if (n < 7) cnt_signal(cnt + (C_O + n) * 32);
          mbar_arrive(bars + 8 * B_STGE);
          PROF_AT(true, 24 + n);
        }
      }
    } else {
      const int t = threadIdx.x - 64;
      const bf16* wp = p.wmod + 2048 + cta * 32 + (t & 3) * 8;
      float v[8];
#pragma unroll
      for (int q = 0; q < 8; q++) v[q] = 0.f;
#pragma unroll 4
      for (int i = 0; i < 64; i++) {
        const int k = (t >> 2) + 16 * i;
        const uint4 w = ldg_nc(wp + (size_t)k * 6144);
        const float sv = bf_round(silu_f(__bfloat162float(p.c[k])));
        v[0] += sv * bf_lo(w.x); v[1] += sv * bf_hi(w.x); v[2] += sv * bf_lo(w.y); v[3] += sv * bf_hi(w.y);
        v[4] += sv * bf_lo(w.z); v[5] += sv * bf_hi(w.z); v[6] += sv * bf_lo(w.w); v[7] += sv * bf_hi(w.w);
      }
      {
        const bool b4 = lane & 16, b3 = lane & 8, b2 = lane & 4;
#pragma unroll
        for (int q = 0; q < 4; q++) v[q] = (b4 ? v[q + 4] : v[q]) + __shfl_xor_sync(~0u, b4 ? v[q] : v[q + 4], 16);
#pragma unroll
        for (int q = 0; q < 2; q++) v[q] = (b3 ? v[q + 2] : v[q]) + __shfl_xor_sync(~0u, b3 ? v[q] : v[q + 2], 8);
        v[0] = (b2 ? v[1] : v[0]) + __shfl_xor_sync(~0u, b2 ? v[0] : v[1], 4);
      }
      const int col = (lane & 3) * 8 + ((lane >> 4) & 1) * 4 + ((lane >> 3) & 1) * 2 + ((lane >> 2) & 1);
      if (warp == 3) sts32f(sm + REDB_OFF + col * 4, v[0]);
      bar_sync(4, 64);
      if (warp == 2) {
        v[0] += lds32f(sm + REDB_OFF + col * 4);
        __syncwarp();
        sts32f(sm + REDB_OFF + col * 4, v[0]);
        __syncwarp();
        if (lane < 8) {
          const float2 a = lds64f(sm + REDB_OFF + lane * 16), b = lds64f(sm + REDB_OFF + lane * 16 + 8);
          ll_store(g_modll + 512 + cta * 8 + lane, pack2(a.x, a.y), pack2(b.x, b.y), tag);
        }
      }
      {
        const int vec = t >> 4, e = t & 15;
        const uint4* src = g_modll + 512 + vec * 256 + j * 32 + e * 2;
        uint32_t m[4];
        ll_load(src, tag, m[0], m[1]);
        ll_load(src + 1, tag, m[2], m[3]);
        const float add = vec == 2 ? 1.0f : 0.0f;
#pragma unroll
        for (int q = 0; q < 4; q++) {
          sts32f(sm + MODB_OFF + (vec * 128 + e * 8 + q * 2) * 4, bf_round(bf_lo(m[q]) + add));
          sts32f(sm + MODB_OFF + (vec * 128 + e * 8 + q * 2 + 1) * 4, bf_round(bf_hi(m[q]) + add));
        }
        __syncwarp();
        if (lane == 0) mbar_arrive(bars + 8 * B_MODB);
        PROF_AT(t == 0, 15);
      }
    }
    __syncwarp();
    cluster_sync();
  } else {
    asm volatile("setmaxnreg.inc.sync.aligned.u32 232;");
    const int tid = threadIdx.x - 128;
    const int cw = tid >> 7, warp = (tid >> 5) & 3, lane = tid & 31;
    const int r = lane >> 2, c = lane & 3;

    {
      const int w8 = tid >> 5;
      uint4 wv[8], xv[2][4];
      float sv[8];
      const bf16* wp = p.wmod + cta * 16 + (tid & 1) * 8;
#pragma unroll
      for (int i = 0; i < 8; i++) wv[i] = ldg_nc(wp + (size_t)(i * 128 + (tid >> 1)) * 6144);
#pragma unroll
      for (int i = 0; i < 8; i++) sv[i] = __bfloat162float(p.c[i * 128 + (tid >> 1)]);
#pragma unroll
      for (int i = 0; i < 2; i++)
#pragma unroll
        for (int q = 0; q < 4; q++) xv[i][q] = ldg_nc(p.x + (size_t)(cta * 16 + w8 * 2 + i) * DM + q * 256 + lane * 8);
      cluster_sync();
      float v[8];
#pragma unroll
      for (int q = 0; q < 8; q++) v[q] = 0.f;
#pragma unroll
      for (int i = 0; i < 8; i++) {
        const float s = bf_round(silu_f(sv[i]));
        v[0] += s * bf_lo(wv[i].x); v[1] += s * bf_hi(wv[i].x); v[2] += s * bf_lo(wv[i].y); v[3] += s * bf_hi(wv[i].y);
        v[4] += s * bf_lo(wv[i].z); v[5] += s * bf_hi(wv[i].z); v[6] += s * bf_lo(wv[i].w); v[7] += s * bf_hi(wv[i].w);
      }
      {
        const bool b4 = lane & 16, b3 = lane & 8, b2 = lane & 4;
#pragma unroll
        for (int q = 0; q < 4; q++) v[q] = (b4 ? v[q + 4] : v[q]) + __shfl_xor_sync(~0u, b4 ? v[q] : v[q + 4], 16);
#pragma unroll
        for (int q = 0; q < 2; q++) v[q] = (b3 ? v[q + 2] : v[q]) + __shfl_xor_sync(~0u, b3 ? v[q] : v[q + 2], 8);
        v[0] = (b2 ? v[1] : v[0]) + __shfl_xor_sync(~0u, b2 ? v[0] : v[1], 4);
        v[0] += __shfl_xor_sync(~0u, v[0], 2);
      }
      const uint32_t red = stg + 8192;
      if ((lane & 2) == 0) {
        const int col = (lane & 1) * 8 + ((lane >> 4) & 1) * 4 + ((lane >> 3) & 1) * 2 + ((lane >> 2) & 1);
        sts32f(red + (w8 * 16 + col) * 4, v[0]);
      }
      bar_sync(1, 256);
      if (tid < 4) {
        float a[4] = {0.f, 0.f, 0.f, 0.f};
#pragma unroll
        for (int w = 0; w < 8; w++) {
          const uint4 t4 = lds128(red + (w * 16 + tid * 4) * 4);
          a[0] += __uint_as_float(t4.x); a[1] += __uint_as_float(t4.y); a[2] += __uint_as_float(t4.z); a[3] += __uint_as_float(t4.w);
        }
        ll_store(g_modll + cta * 4 + tid, pack2(a[0], a[1]), pack2(a[2], a[3]), tag);
      }
      PROF_AT(tid == 0, 1);
      float mean[2], rstd[2];
#pragma unroll
      for (int i = 0; i < 2; i++) {
        float s = 0.f;
#pragma unroll
        for (int q = 0; q < 4; q++)
          s += (bf_lo(xv[i][q].x) + bf_hi(xv[i][q].x)) + (bf_lo(xv[i][q].y) + bf_hi(xv[i][q].y)) +
               (bf_lo(xv[i][q].z) + bf_hi(xv[i][q].z)) + (bf_lo(xv[i][q].w) + bf_hi(xv[i][q].w));
#pragma unroll
        for (int o = 16; o > 0; o >>= 1) s += __shfl_xor_sync(~0u, s, o);
        const float m = s * (1.0f / DM);
        float q2 = 0.f;
#pragma unroll
        for (int q = 0; q < 4; q++) {
          const uint32_t u[4] = {xv[i][q].x, xv[i][q].y, xv[i][q].z, xv[i][q].w};
#pragma unroll
          for (int e = 0; e < 4; e++) {
            const float d0 = bf_lo(u[e]) - m, d1 = bf_hi(u[e]) - m;
            q2 += d0 * d0 + d1 * d1;
          }
        }
#pragma unroll
        for (int o = 16; o > 0; o >>= 1) q2 += __shfl_xor_sync(~0u, q2, o);
        mean[i] = m;
        rstd[i] = rsqrtf(q2 * (1.0f / DM) + 1e-5f);
      }
      {
        uint32_t m[4];
        ll_load(g_modll + tid * 2, tag, m[0], m[1]);
        ll_load(g_modll + tid * 2 + 1, tag, m[2], m[3]);
        sts128(stg + tid * 16, m[0], m[1], m[2], m[3]);
      }
      bar_sync(1, 256);
      PROF_AT(tid == 0, 2);
#pragma unroll
      for (int q = 0; q < 4; q++) {
        const uint4 sa4 = lds128(stg + (q * 256 + lane * 8) * 2), ca4 = lds128(stg + 2048 + (q * 256 + lane * 8) * 2);
        const uint32_t sa[4] = {sa4.x, sa4.y, sa4.z, sa4.w}, ca[4] = {ca4.x, ca4.y, ca4.z, ca4.w};
#pragma unroll
        for (int i = 0; i < 2; i++) {
          const uint32_t u[4] = {xv[i][q].x, xv[i][q].y, xv[i][q].z, xv[i][q].w};
          uint32_t o[4];
#pragma unroll
          for (int e = 0; e < 4; e++) {
            const float c0 = bf_round(1.0f + bf_lo(ca[e])), c1 = bf_round(1.0f + bf_hi(ca[e]));
            o[e] = pack2((bf_lo(u[e]) - mean[i]) * rstd[i] * c0 + bf_lo(sa[e]), (bf_hi(u[e]) - mean[i]) * rstd[i] * c1 + bf_hi(sa[e]));
          }
          const int row = g * 128 + i * 64 + j * 8 + w8;
          *(uint4*)(g_h + (size_t)row * DM + q * 256 + lane * 8) = make_uint4(o[0], o[1], o[2], o[3]);
        }
      }
      asm volatile("fence.proxy.async.global;" ::: "memory");
      bar_sync(1, 256);
      if (tid == 0) cnt_signal(cnt + C_H * 32);
      PROF_AT(tid == 0, 3);
    }

    const bool releaser = (tid & 95) == 0;
    const uint32_t rbars = mapa(bars, (tid & 32) ? (rank ^ 1) : rank);
    const uint32_t a_base = (sm & 0x3FFFF) + cw * 8192, b_base = (sm & 0x3FFFF) + 16384;

    {
      int s = 0; uint32_t ph = 0;
      for (int rho = 0; rho < 2; rho++) {
        float acc[96];
        mainloop<192, 4, 49152>(acc, a_base, b_base, bars + 8 * B_FQ, rbars + 8 * B_EQ, releaser, 16, s, ph);
        PROF_AT(tid == 0, 4 + rho * 2);
        uint32_t ql[8], qh[8], k0[8], k1[8], v0[8], v1[8], kp[8], vp[8];
#pragma unroll
        for (int t = 0; t < 8; t++) {
          k1[t] = pack2(acc[4 * (8 + t) + 2], acc[4 * (8 + t) + 3]);
          v1[t] = movmatrix(pack2(acc[4 * (16 + t) + 2], acc[4 * (16 + t) + 3]));
        }
        const uint32_t xch = stg + 16384 + (cw * 4 + warp) * 2048 + lane * 16;
        if (warp < 3) {
          sts128(xch, k1[0], k1[1], k1[2], k1[3]);
          sts128(xch + 512, k1[4], k1[5], k1[6], k1[7]);
          sts128(xch + 1024, v1[0], v1[1], v1[2], v1[3]);
          sts128(xch + 1536, v1[4], v1[5], v1[6], v1[7]);
        } else if (g < 15) {
          uint4* dst = g_halo + (((g * 8 + j) * 2 + rho) * 2 + cw) * 256 + lane;
#pragma unroll
          for (int t = 0; t < 4; t++) {
            ll_store(dst + t * 32, k1[2 * t], k1[2 * t + 1], tag);
            ll_store(dst + (4 + t) * 32, v1[2 * t], v1[2 * t + 1], tag);
          }
        }
#pragma unroll
        for (int t = 0; t < 8; t++) {
          ql[t] = pack2(acc[4 * t], acc[4 * t + 1]);
          qh[t] = pack2(acc[4 * t + 2], acc[4 * t + 3]);
          k0[t] = pack2(acc[4 * (8 + t)], acc[4 * (8 + t) + 1]);
          v0[t] = movmatrix(pack2(acc[4 * (16 + t)], acc[4 * (16 + t) + 1]));
        }
        bar_sync(2 + cw, 128);
        if (warp > 0) {
          const uint4 a = lds128(xch - 2048), b = lds128(xch - 2048 + 512), d = lds128(xch - 2048 + 1024), e = lds128(xch - 2048 + 1536);
          kp[0] = a.x; kp[1] = a.y; kp[2] = a.z; kp[3] = a.w; kp[4] = b.x; kp[5] = b.y; kp[6] = b.z; kp[7] = b.w;
          vp[0] = d.x; vp[1] = d.y; vp[2] = d.z; vp[3] = d.w; vp[4] = e.x; vp[5] = e.y; vp[6] = e.z; vp[7] = e.w;
        } else if (g > 0) {
          const uint4* src = g_halo + ((((g - 1) * 8 + j) * 2 + rho) * 2 + cw) * 256 + lane;
#pragma unroll
          for (int t = 0; t < 4; t++) {
            ll_load(src + t * 32, tag, kp[2 * t], kp[2 * t + 1]);
            ll_load(src + (4 + t) * 32, tag, vp[2 * t], vp[2 * t + 1]);
          }
          __syncwarp();
        } else {
#pragma unroll
          for (int t = 0; t < 8; t++) { kp[t] = 0; vp[t] = 0; }
        }
        bar_sync(2 + cw, 128);
        const bool first = (g == 0) && (warp == 0);
        const bool up0 = 2 * c > r, up1 = 2 * c + 1 > r;
        const float scale = 0.17677669529663687f;
        const float log2e = 1.4426950408889634f;
        uint32_t ol[8], oh[8];
#pragma unroll
        for (int h = 0; h < 2; h++) {
          float sp[4] = {0.f, 0.f, 0.f, 0.f}, s0[4] = {0.f, 0.f, 0.f, 0.f}, s1[4] = {0.f, 0.f, 0.f, 0.f};
#pragma unroll
          for (int ks = 0; ks < 2; ks++) {
            const int t = 4 * h + 2 * ks;
            mma16816(sp, ql[t], qh[t], ql[t + 1], qh[t + 1], kp[t], kp[t + 1]);
            mma16816(s0, ql[t], qh[t], ql[t + 1], qh[t + 1], k0[t], k0[t + 1]);
            mma16816(s1, ql[t], qh[t], ql[t + 1], qh[t + 1], k1[t], k1[t + 1]);
          }
          float l0 = (up0 ? sp[0] : s0[0]) * scale, l1 = (up1 ? sp[1] : s0[1]) * scale;
          const float h0 = (up0 ? s0[2] : s1[2]) * scale, h1 = (up1 ? s0[3] : s1[3]) * scale;
          if (first && up0) l0 = -1000000000.0f;
          if (first && up1) l1 = -1000000000.0f;
          float ml = fmaxf(l0, l1), mh = fmaxf(h0, h1);
          ml = fmaxf(ml, __shfl_xor_sync(~0u, ml, 1)); mh = fmaxf(mh, __shfl_xor_sync(~0u, mh, 1));
          ml = fmaxf(ml, __shfl_xor_sync(~0u, ml, 2)); mh = fmaxf(mh, __shfl_xor_sync(~0u, mh, 2));
          float pl0 = exp2f((l0 - ml) * log2e), pl1 = exp2f((l1 - ml) * log2e);
          float ph0 = exp2f((h0 - mh) * log2e), ph1 = exp2f((h1 - mh) * log2e);
          float sl = pl0 + pl1, sh = ph0 + ph1;
          sl += __shfl_xor_sync(~0u, sl, 1); sh += __shfl_xor_sync(~0u, sh, 1);
          sl += __shfl_xor_sync(~0u, sl, 2); sh += __shfl_xor_sync(~0u, sh, 2);
          const float il = __fdividef(1.0f, sl), ih = __fdividef(1.0f, sh);
          pl0 *= il; pl1 *= il; ph0 *= ih; ph1 *= ih;
          const uint32_t a0 = pack2(up0 ? pl0 : 0.f, up1 ? pl1 : 0.f);
          const uint32_t a2 = pack2(up0 ? 0.f : pl0, up1 ? 0.f : pl1);
          const uint32_t a3 = pack2(up0 ? ph0 : 0.f, up1 ? ph1 : 0.f);
          const uint32_t a5 = pack2(up0 ? 0.f : ph0, up1 ? 0.f : ph1);
#pragma unroll
          for (int t = 0; t < 4; t++) {
            float o[4] = {0.f, 0.f, 0.f, 0.f};
            mma16816(o, a0, 0u, a2, a3, vp[4 * h + t], v0[4 * h + t]);
            mma1688(o, 0u, a5, v1[4 * h + t]);
            ol[4 * h + t] = pack2(o[0], o[1]);
            oh[4 * h + t] = pack2(o[2], o[3]);
          }
        }
        if (rho == 1) mbar_wait(bars + 8 * B_STGE, 0);
        stage_slab(stg + cw * 8192, warp, lane, ol, oh);
        stage_done(bars + 8 * B_STGF, lane);
        PROF_AT(tid == 0, 5 + rho * 2);
      }
    }

    const int row0 = g * 128 + cw * 64 + warp * 16 + r;
    {
      uint32_t xl[16], xh[16];
      const bf16* xp = p.x + (size_t)row0 * DM + j * 128 + 2 * c;
#pragma unroll
      for (int n = 0; n < 16; n++) {
        xl[n] = __ldg((const uint32_t*)(xp + 8 * n));
        xh[n] = __ldg((const uint32_t*)(xp + 8 * DM + 8 * n));
      }
      float acc[64];
      int s = 0; uint32_t ph = 0;
      mainloop<128, 6, 32768>(acc, a_base, b_base, bars + 8 * B_FW, rbars + 8 * B_EW, releaser, 16, s, ph);
      PROF_AT(tid == 0, 8);
      mbar_wait(bars + 8 * B_MODB, 0);
      float sl = 0.f, sh = 0.f;
#pragma unroll
      for (int n = 0; n < 16; n++) {
        const float2 ga = lds64f(sm + MODB_OFF + (8 * n + 2 * c) * 4);
        xl[n] = pack2(bf_lo(xl[n]) + ga.x * acc[4 * n], bf_hi(xl[n]) + ga.y * acc[4 * n + 1]);
        xh[n] = pack2(bf_lo(xh[n]) + ga.x * acc[4 * n + 2], bf_hi(xh[n]) + ga.y * acc[4 * n + 3]);
        acc[4 * n] = bf_lo(xl[n]); acc[4 * n + 1] = bf_hi(xl[n]);
        acc[4 * n + 2] = bf_lo(xh[n]); acc[4 * n + 3] = bf_hi(xh[n]);
        sl += acc[4 * n] + acc[4 * n + 1];
        sh += acc[4 * n + 2] + acc[4 * n + 3];
      }
      sl += __shfl_xor_sync(~0u, sl, 1); sh += __shfl_xor_sync(~0u, sh, 1);
      sl += __shfl_xor_sync(~0u, sl, 2); sh += __shfl_xor_sync(~0u, sh, 2);
      const float ml = sl * (1.0f / 128), mh = sh * (1.0f / 128);
      float ql = 0.f, qh = 0.f;
#pragma unroll
      for (int n = 0; n < 16; n++) {
        const float d0 = acc[4 * n] - ml, d1 = acc[4 * n + 1] - ml, d2 = acc[4 * n + 2] - mh, d3 = acc[4 * n + 3] - mh;
        ql += d0 * d0 + d1 * d1;
        qh += d2 * d2 + d3 * d3;
      }
      ql += __shfl_xor_sync(~0u, ql, 1); qh += __shfl_xor_sync(~0u, qh, 1);
      ql += __shfl_xor_sync(~0u, ql, 2); qh += __shfl_xor_sync(~0u, qh, 2);
      if (c < 2) ll_store(g_stats + (row0 + c * 8) * 8 + j, __float_as_uint(c ? mh : ml), __float_as_uint(c ? qh : ql), tag);
      uint4* x1p = g_x1 + (size_t)cta * 2048 + tid;
#pragma unroll
      for (int q = 0; q < 4; q++) {
        x1p[q * 256] = make_uint4(xl[4 * q], xl[4 * q + 1], xl[4 * q + 2], xl[4 * q + 3]);
        x1p[(4 + q) * 256] = make_uint4(xh[4 * q], xh[4 * q + 1], xh[4 * q + 2], xh[4 * q + 3]);
      }
      float mean[2], rstd[2];
#pragma unroll
      for (int i = 0; i < 2; i++) {
        uint32_t m0, q0, m1, q1;
        const uint4* sp = g_stats + (row0 + i * 8) * 8 + 2 * c;
        ll_load(sp, tag, m0, q0);
        ll_load(sp + 1, tag, m1, q1);
        __syncwarp();
        float ms = __uint_as_float(m0) + __uint_as_float(m1);
        ms += __shfl_xor_sync(~0u, ms, 1);
        ms += __shfl_xor_sync(~0u, ms, 2);
        ms *= 0.125f;
        const float e0 = __uint_as_float(m0) - ms, e1 = __uint_as_float(m1) - ms;
        float qs = __uint_as_float(q0) + __uint_as_float(q1) + 128.0f * (e0 * e0 + e1 * e1);
        qs += __shfl_xor_sync(~0u, qs, 1);
        qs += __shfl_xor_sync(~0u, qs, 2);
        mean[i] = ms;
        rstd[i] = rsqrtf(qs * (1.0f / DM) + 1e-5f);
      }
      PROF_AT(tid == 0, 9);
      mbar_wait(bars + 8 * B_STGE, 1);
#pragma unroll
      for (int ch = 0; ch < 2; ch++) {
        uint32_t lo[8], hi[8];
#pragma unroll
        for (int t = 0; t < 8; t++) {
          const int n = ch * 8 + t;
          const float2 sb = lds64f(sm + MODB_OFF + (128 + 8 * n + 2 * c) * 4), cb = lds64f(sm + MODB_OFF + (256 + 8 * n + 2 * c) * 4);
          lo[t] = pack2((acc[4 * n] - mean[0]) * rstd[0] * cb.x + sb.x, (acc[4 * n + 1] - mean[0]) * rstd[0] * cb.y + sb.y);
          hi[t] = pack2((acc[4 * n + 2] - mean[1]) * rstd[1] * cb.x + sb.x, (acc[4 * n + 3] - mean[1]) * rstd[1] * cb.y + sb.y);
        }
        stage_slab(stg + cw * 16384 + ch * 8192, warp, lane, lo, hi);
      }
      stage_done(bars + 8 * B_STGF, lane);
      PROF_AT(tid == 0, 10);
    }

    {
      int s = 0; uint32_t ph = 0;
      for (int t = 0; t < 3; t++) {
        float acc[128];
        mainloop<256, 4, 49152>(acc, a_base, b_base, bars + 8 * B_FG, rbars + 8 * B_EG, releaser, 16, s, ph);
        mbar_wait(bars + 8 * B_STGE, t & 1);
#pragma unroll
        for (int ch = 0; ch < 2; ch++) {
          uint32_t lo[8], hi[8];
#pragma unroll
          for (int q = 0; q < 8; q++) {
            const int n = 4 * (ch * 8 + q);
            lo[q] = pack2(silu_f(acc[n]) * acc[64 + n], silu_f(acc[n + 1]) * acc[64 + n + 1]);
            hi[q] = pack2(silu_f(acc[n + 2]) * acc[64 + n + 2], silu_f(acc[n + 3]) * acc[64 + n + 3]);
          }
          stage_slab(stg + cw * 16384 + ch * 8192, warp, lane, lo, hi);
        }
        stage_done(bars + 8 * B_STGF, lane);
      }
      PROF_AT(tid == 0, 11);
      float acc[64];
      mainloop<128, 4, 49152>(acc, a_base, b_base, bars + 8 * B_FG, rbars + 8 * B_EG, releaser, 16, s, ph);
      mbar_wait(bars + 8 * B_STGE, 1);
      uint32_t lo[8], hi[8];
#pragma unroll
      for (int q = 0; q < 8; q++) {
        const int n = 4 * q;
        lo[q] = pack2(silu_f(acc[n]) * acc[32 + n], silu_f(acc[n + 1]) * acc[32 + n + 1]);
        hi[q] = pack2(silu_f(acc[n + 2]) * acc[32 + n + 2], silu_f(acc[n + 3]) * acc[32 + n + 3]);
      }
      stage_slab(stg + cw * 16384, warp, lane, lo, hi);
      stage_done(bars + 8 * B_STGF, lane);
      PROF_AT(tid == 0, 12);
    }

    {
      uint4 x1[8];
      const uint4* x1p = g_x1 + (size_t)cta * 2048 + tid;
#pragma unroll
      for (int q = 0; q < 8; q++) x1[q] = ll_peek(x1p + q * 256);
      float acc[64];
      int s = 0; uint32_t ph = 0;
      mainloop<128, 6, 32768>(acc, a_base, b_base, bars + 8 * B_FD, rbars + 8 * B_ED, releaser, 56, s, ph);
      PROF_AT(tid == 0, 13);
      mbar_wait(bars + 8 * B_STGE, 0);
#pragma unroll
      for (int ch = 0; ch < 2; ch++) {
        uint32_t lo[8], hi[8];
#pragma unroll
        for (int t = 0; t < 8; t++) {
          const int n = ch * 8 + t;
          const float2 gb = lds64f(sm + MODB_OFF + (384 + 8 * n + 2 * c) * 4);
          const uint4 a = x1[n >> 2], b = x1[4 + (n >> 2)];
          const uint32_t xl = (n & 3) == 0 ? a.x : (n & 3) == 1 ? a.y : (n & 3) == 2 ? a.z : a.w;
          const uint32_t xh = (n & 3) == 0 ? b.x : (n & 3) == 1 ? b.y : (n & 3) == 2 ? b.z : b.w;
          lo[t] = pack2(bf_lo(xl) + gb.x * acc[4 * n], bf_hi(xl) + gb.y * acc[4 * n + 1]);
          hi[t] = pack2(bf_lo(xh) + gb.x * acc[4 * n + 2], bf_hi(xh) + gb.y * acc[4 * n + 3]);
        }
        stage_slab(stg + cw * 16384 + ch * 8192, warp, lane, lo, hi);
      }
      stage_done(bars + 8 * B_STGF, lane);
      PROF_AT(tid == 0, 14);
    }
    if (blockIdx.x == 0 && tid == 0) asm volatile("st.relaxed.gpu.global.u32 [%0], %1;" ::"l"(&g_epoch), "r"(tag) : "memory");
    cluster_sync();
  }
}

typedef CUresult (*EncodeFn)(CUtensorMap*, CUtensorMapDataType, cuuint32_t, void*, const cuuint64_t*, const cuuint64_t*,
                             const cuuint32_t*, const cuuint32_t*, CUtensorMapInterleave, CUtensorMapSwizzle,
                             CUtensorMapL2promotion, CUtensorMapFloatOOBfill);

void encode2d(EncodeFn fn, CUtensorMap* m, const void* ptr, uint64_t cols, uint64_t rows) {
  cuuint64_t dims[2] = {cols, rows};
  cuuint64_t strides[1] = {cols * 2};
  cuuint32_t box[2] = {64, 64};
  cuuint32_t es[2] = {1, 1};
  fn(m, CU_TENSOR_MAP_DATA_TYPE_BFLOAT16, 2, (void*)ptr, dims, strides, box, es, CU_TENSOR_MAP_INTERLEAVE_NONE,
     CU_TENSOR_MAP_SWIZZLE_128B, CU_TENSOR_MAP_L2_PROMOTION_L2_128B, CU_TENSOR_MAP_FLOAT_OOB_FILL_NONE);
}

}

extern "C" void kernel_launch(void* const* d_in, const int* in_sizes, int n_in, void* d_out, int out_size) {
  (void)in_sizes; (void)n_in; (void)out_size;
  void* fp = nullptr;
  cudaDriverEntryPointQueryResult qr;
  cudaGetDriverEntryPoint("cuTensorMapEncodeTiled", &fp, cudaEnableDefault, &qr);
  EncodeFn fn = (EncodeFn)fp;
  void *ph, *po, *ph2, *pact;
  cudaGetSymbolAddress(&ph, g_h);
  cudaGetSymbolAddress(&po, g_o);
  cudaGetSymbolAddress(&ph2, g_h2);
  cudaGetSymbolAddress(&pact, g_act);
  Params p;
  encode2d(fn, &p.h, ph, DM, SEQ);
  encode2d(fn, &p.o_ld, po, DM, SEQ);
  encode2d(fn, &p.h2, ph2, DM, SEQ);
  encode2d(fn, &p.act, pact, FF, SEQ);
  encode2d(fn, &p.out, d_out, DM, SEQ);
  encode2d(fn, &p.wqkv, d_in[1], 3 * DM, DM);
  encode2d(fn, &p.wo, d_in[2], DM, DM);
  encode2d(fn, &p.wg, d_in[4], FF, DM);
  encode2d(fn, &p.wu, d_in[5], FF, DM);
  encode2d(fn, &p.wd, d_in[6], DM, FF);
  {
    cuuint64_t dims[3] = {DM, 2, SEQ / 2};
    cuuint64_t strides[2] = {DM * 2, DM * 4};
    cuuint32_t box[3] = {64, 1, 64};
    cuuint32_t es[3] = {1, 1, 1};
    fn(&p.o_st, CU_TENSOR_MAP_DATA_TYPE_BFLOAT16, 3, po, dims, strides, box, es, CU_TENSOR_MAP_INTERLEAVE_NONE,
       CU_TENSOR_MAP_SWIZZLE_128B, CU_TENSOR_MAP_L2_PROMOTION_L2_128B, CU_TENSOR_MAP_FLOAT_OOB_FILL_NONE);
  }
  p.x = (const bf16*)d_in[0];
  p.c = (const bf16*)d_in[7];
  p.wmod = (const bf16*)d_in[8];

  cudaFuncSetAttribute(fused_kernel, cudaFuncAttributeMaxDynamicSharedMemorySize, SMEM_BYTES);
  cudaLaunchConfig_t cfg = {};
  cfg.gridDim = dim3(NCTA);
  cfg.blockDim = dim3(384);
  cfg.dynamicSmemBytes = SMEM_BYTES;
  cfg.stream = cudaStreamPerThread;
  cudaLaunchAttribute at[1];
  at[0].id = cudaLaunchAttributeClusterDimension;
  at[0].val.clusterDim.x = 2; at[0].val.clusterDim.y = 1; at[0].val.clusterDim.z = 1;
  cfg.attrs = at;
  cfg.numAttrs = 1;
  cudaLaunchKernelEx(&cfg, fused_kernel, p);
}
```

```cpp
#include <cuda_runtime.h>
#include <cuda_bf16.h>
#include <cuda.h>
#include <stdint.h>

typedef __nv_bfloat16 bf16;

#define MAPPING 2

#define ALIGN 0

#define PF 0

#define EF 1

#define ALIGNE 3

#define CW 0

__device__ __forceinline__ void wgmma_ss_n128(float (&d)[64], uint64_t da, uint64_t db, int scale_d) {
  asm volatile("{\n.reg .pred p;\nsetp.ne.b32 p, %66, 0;\n"
    "wgmma.mma_async.sync.aligned.m64n128k16.f32.bf16.bf16 "
    "{%0, %1, %2, %3, %4, %5, %6, %7, %8, %9, %10, %11, %12, %13, %14, %15, "
    "%16, %17, %18, %19, %20, %21, %22, %23, %24, %25, %26, %27, %28, %29, %30, %31, "
    "%32, %33, %34, %35, %36, %37, %38, %39, %40, %41, %42, %43, %44, %45, %46, %47, "
    "%48, %49, %50, %51, %52, %53, %54, %55, %56, %57, %58, %59, %60, %61, %62, %63}, "
    "%64, %65, p, 1, 1, 0, 1;\n}\n"
    : "+f"(d[0]), "+f"(d[1]), "+f"(d[2]), "+f"(d[3]), "+f"(d[4]), "+f"(d[5]), "+f"(d[6]), "+f"(d[7]),
      "+f"(d[8]), "+f"(d[9]), "+f"(d[10]), "+f"(d[11]), "+f"(d[12]), "+f"(d[13]), "+f"(d[14]), "+f"(d[15]),
      "+f"(d[16]), "+f"(d[17]), "+f"(d[18]), "+f"(d[19]), "+f"(d[20]), "+f"(d[21]), "+f"(d[22]), "+f"(d[23]),
      "+f"(d[24]), "+f"(d[25]), "+f"(d[26]), "+f"(d[27]), "+f"(d[28]), "+f"(d[29]), "+f"(d[30]), "+f"(d[31]),
      "+f"(d[32]), "+f"(d[33]), "+f"(d[34]), "+f"(d[35]), "+f"(d[36]), "+f"(d[37]), "+f"(d[38]), "+f"(d[39]),
      "+f"(d[40]), "+f"(d[41]), "+f"(d[42]), "+f"(d[43]), "+f"(d[44]), "+f"(d[45]), "+f"(d[46]), "+f"(d[47]),
      "+f"(d[48]), "+f"(d[49]), "+f"(d[50]), "+f"(d[51]), "+f"(d[52]), "+f"(d[53]), "+f"(d[54]), "+f"(d[55]),
      "+f"(d[56]), "+f"(d[57]), "+f"(d[58]), "+f"(d[59]), "+f"(d[60]), "+f"(d[61]), "+f"(d[62]), "+f"(d[63])
    : "l"(da), "l"(db), "r"(scale_d));
}

__device__ __forceinline__ void wgmma_ss_n192(float (&d)[96], uint64_t da, uint64_t db, int scale_d) {
  asm volatile("{\n.reg .pred p;\nsetp.ne.b32 p, %98, 0;\n"
    "wgmma.mma_async.sync.aligned.m64n192k16.f32.bf16.bf16 "
    "{%0, %1, %2, %3, %4, %5, %6, %7, %8, %9, %10, %11, %12, %13, %14, %15, "
    "%16, %17, %18, %19, %20, %21, %22, %23, %24, %25, %26, %27, %28, %29, %30, %31, "
    "%32, %33, %34, %35, %36, %37, %38, %39, %40, %41, %42, %43, %44, %45, %46, %47, "
    "%48, %49, %50, %51, %52, %53, %54, %55, %56, %57, %58, %59, %60, %61, %62, %63, "
    "%64, %65, %66, %67, %68, %69, %70, %71, %72, %73, %74, %75, %76, %77, %78, %79, "
    "%80, %81, %82, %83, %84, %85, %86, %87, %88, %89, %90, %91, %92, %93, %94, %95}, "
    "%96, %97, p, 1, 1, 0, 1;\n}\n"
    : "+f"(d[0]), "+f"(d[1]), "+f"(d[2]), "+f"(d[3]), "+f"(d[4]), "+f"(d[5]), "+f"(d[6]), "+f"(d[7]),
      "+f"(d[8]), "+f"(d[9]), "+f"(d[10]), "+f"(d[11]), "+f"(d[12]), "+f"(d[13]), "+f"(d[14]), "+f"(d[15]),
      "+f"(d[16]), "+f"(d[17]), "+f"(d[18]), "+f"(d[19]), "+f"(d[20]), "+f"(d[21]), "+f"(d[22]), "+f"(d[23]),
      "+f"(d[24]), "+f"(d[25]), "+f"(d[26]), "+f"(d[27]), "+f"(d[28]), "+f"(d[29]), "+f"(d[30]), "+f"(d[31]),
      "+f"(d[32]), "+f"(d[33]), "+f"(d[34]), "+f"(d[35]), "+f"(d[36]), "+f"(d[37]), "+f"(d[38]), "+f"(d[39]),
      "+f"(d[40]), "+f"(d[41]), "+f"(d[42]), "+f"(d[43]), "+f"(d[44]), "+f"(d[45]), "+f"(d[46]), "+f"(d[47]),
      "+f"(d[48]), "+f"(d[49]), "+f"(d[50]), "+f"(d[51]), "+f"(d[52]), "+f"(d[53]), "+f"(d[54]), "+f"(d[55]),
      "+f"(d[56]), "+f"(d[57]), "+f"(d[58]), "+f"(d[59]), "+f"(d[60]), "+f"(d[61]), "+f"(d[62]), "+f"(d[63]),
      "+f"(d[64]), "+f"(d[65]), "+f"(d[66]), "+f"(d[67]), "+f"(d[68]), "+f"(d[69]), "+f"(d[70]), "+f"(d[71]),
      "+f"(d[72]), "+f"(d[73]), "+f"(d[74]), "+f"(d[75]), "+f"(d[76]), "+f"(d[77]), "+f"(d[78]), "+f"(d[79]),
      "+f"(d[80]), "+f"(d[81]), "+f"(d[82]), "+f"(d[83]), "+f"(d[84]), "+f"(d[85]), "+f"(d[86]), "+f"(d[87]),
      "+f"(d[88]), "+f"(d[89]), "+f"(d[90]), "+f"(d[91]), "+f"(d[92]), "+f"(d[93]), "+f"(d[94]), "+f"(d[95])
    : "l"(da), "l"(db), "r"(scale_d));
}

__device__ __forceinline__ void wgmma_ss_n256(float (&d)[128], uint64_t da, uint64_t db, int scale_d) {
  asm volatile("{\n.reg .pred p;\nsetp.ne.b32 p, %130, 0;\n"
    "wgmma.mma_async.sync.aligned.m64n256k16.f32.bf16.bf16 "
    "{%0, %1, %2, %3, %4, %5, %6, %7, %8, %9, %10, %11, %12, %13, %14, %15, "
    "%16, %17, %18, %19, %20, %21, %22, %23, %24, %25, %26, %27, %28, %29, %30, %31, "
    "%32, %33, %34, %35, %36, %37, %38, %39, %40, %41, %42, %43, %44, %45, %46, %47, "
    "%48, %49, %50, %51, %52, %53, %54, %55, %56, %57, %58, %59, %60, %61, %62, %63, "
    "%64, %65, %66, %67, %68, %69, %70, %71, %72, %73, %74, %75, %76, %77, %78, %79, "
    "%80, %81, %82, %83, %84, %85, %86, %87, %88, %89, %90, %91, %92, %93, %94, %95, "
    "%96, %97, %98, %99, %100, %101, %102, %103, %104, %105, %106, %107, %108, %109, %110, %111, "
    "%112, %113, %114, %115, %116, %117, %118, %119, %120, %121, %122, %123, %124, %125, %126, %127}, "
    "%128, %129, p, 1, 1, 0, 1;\n}\n"
    : "+f"(d[0]), "+f"(d[1]), "+f"(d[2]), "+f"(d[3]), "+f"(d[4]), "+f"(d[5]), "+f"(d[6]), "+f"(d[7]),
      "+f"(d[8]), "+f"(d[9]), "+f"(d[10]), "+f"(d[11]), "+f"(d[12]), "+f"(d[13]), "+f"(d[14]), "+f"(d[15]),
      "+f"(d[16]), "+f"(d[17]), "+f"(d[18]), "+f"(d[19]), "+f"(d[20]), "+f"(d[21]), "+f"(d[22]), "+f"(d[23]),
      "+f"(d[24]), "+f"(d[25]), "+f"(d[26]), "+f"(d[27]), "+f"(d[28]), "+f"(d[29]), "+f"(d[30]), "+f"(d[31]),
      "+f"(d[32]), "+f"(d[33]), "+f"(d[34]), "+f"(d[35]), "+f"(d[36]), "+f"(d[37]), "+f"(d[38]), "+f"(d[39]),
      "+f"(d[40]), "+f"(d[41]), "+f"(d[42]), "+f"(d[43]), "+f"(d[44]), "+f"(d[45]), "+f"(d[46]), "+f"(d[47]),
      "+f"(d[48]), "+f"(d[49]), "+f"(d[50]), "+f"(d[51]), "+f"(d[52]), "+f"(d[53]), "+f"(d[54]), "+f"(d[55]),
      "+f"(d[56]), "+f"(d[57]), "+f"(d[58]), "+f"(d[59]), "+f"(d[60]), "+f"(d[61]), "+f"(d[62]), "+f"(d[63]),
      "+f"(d[64]), "+f"(d[65]), "+f"(d[66]), "+f"(d[67]), "+f"(d[68]), "+f"(d[69]), "+f"(d[70]), "+f"(d[71]),
      "+f"(d[72]), "+f"(d[73]), "+f"(d[74]), "+f"(d[75]), "+f"(d[76]), "+f"(d[77]), "+f"(d[78]), "+f"(d[79]),
      "+f"(d[80]), "+f"(d[81]), "+f"(d[82]), "+f"(d[83]), "+f"(d[84]), "+f"(d[85]), "+f"(d[86]), "+f"(d[87]),
      "+f"(d[88]), "+f"(d[89]), "+f"(d[90]), "+f"(d[91]), "+f"(d[92]), "+f"(d[93]), "+f"(d[94]), "+f"(d[95]),
      "+f"(d[96]), "+f"(d[97]), "+f"(d[98]), "+f"(d[99]), "+f"(d[100]), "+f"(d[101]), "+f"(d[102]), "+f"(d[103]),
      "+f"(d[104]), "+f"(d[105]), "+f"(d[106]), "+f"(d[107]), "+f"(d[108]), "+f"(d[109]), "+f"(d[110]), "+f"(d[111]),
      "+f"(d[112]), "+f"(d[113]), "+f"(d[114]), "+f"(d[115]), "+f"(d[116]), "+f"(d[117]), "+f"(d[118]), "+f"(d[119]),
      "+f"(d[120]), "+f"(d[121]), "+f"(d[122]), "+f"(d[123]), "+f"(d[124]), "+f"(d[125]), "+f"(d[126]), "+f"(d[127])
    : "l"(da), "l"(db), "r"(scale_d));
}

namespace {

constexpr int SEQ = 2048, DM = 1024, FF = 3584;
constexpr int NCTA = 128;

constexpr uint32_t STG_OFF = 196608;
constexpr uint32_t MISC_OFF = STG_OFF + 32768;
constexpr uint32_t SMEM_BYTES = MISC_OFF + 3072;
constexpr uint32_t MODB_OFF = MISC_OFF + 512;

enum { B_FQ = 0, B_EQ = 4, B_FW = 8, B_EW = 14, B_FG = 20, B_EG = 24, B_FD = 28, B_ED = 34,
       B_STGF = 40, B_STGE = 41, B_MODB = 42, B_SPF = 43, B_WM = 44, B_RDY = 48, B_COUNT = 56 };
enum { C_H = 0, C_O = 1, C_H2 = 3, C_ACT = 4, C_AL = 8 };

struct Params {
  CUtensorMap h, o_ld, o_st, h2, act, out, wqkv, wqkv32, wo, wg, wu, wd, wm;
  const bf16* x;
  const bf16* c;
  const bf16* wmod;
  uint4* x1;
  uint4* modll;
  uint4* halo;
  uint4* stats1;
  uint4* stats2;
  unsigned* cnt;
  unsigned* epoch;
};

__device__ bf16 g_h[SEQ * DM];
__device__ bf16 g_o[SEQ * DM];
__device__ bf16 g_h2[SEQ * DM];
__device__ bf16 g_act[SEQ * FF];
__device__ uint4 g_x1[NCTA * 8 * 256];
__device__ uint4 g_modll[3072 / 2];
__device__ uint4 g_halo[16 * 8 * 2 * 2 * 8 * 32];
__device__ uint4 g_stats[2 * SEQ * 8];
__device__ unsigned g_cnt[16 * 32];
__device__ unsigned g_epoch;

__device__ __forceinline__ uint32_t smem_u32(const void* p) { return (uint32_t)__cvta_generic_to_shared(p); }
__device__ __forceinline__ void mbar_init(uint32_t bar, uint32_t count) {
  asm volatile("mbarrier.init.shared::cta.b64 [%0], %1;" ::"r"(bar), "r"(count));
}
__device__ __forceinline__ void mbar_expect_tx(uint32_t bar, uint32_t bytes) {
  asm volatile("mbarrier.arrive.expect_tx.shared::cta.b64 _, [%0], %1;" ::"r"(bar), "r"(bytes) : "memory");
}
__device__ __forceinline__ void mbar_arrive(uint32_t bar) {
  asm volatile("mbarrier.arrive.shared::cta.b64 _, [%0];" ::"r"(bar) : "memory");
}
__device__ __forceinline__ void mbar_arrive_cluster(uint32_t cluster_addr) {
  asm volatile("mbarrier.arrive.shared::cluster.b64 _, [%0];" ::"r"(cluster_addr) : "memory");
}
__device__ __forceinline__ uint32_t mapa(uint32_t addr, uint32_t cta) {
  uint32_t r;
  asm volatile("mapa.shared::cluster.u32 %0, %1, %2;" : "=r"(r) : "r"(addr), "r"(cta));
  return r;
}
__device__ __forceinline__ void mbar_wait(uint32_t bar, uint32_t parity) {
  asm volatile(
      "{\n.reg .pred p;\n.reg .u32 n;\nmov.u32 n, 0;\n"
      "WAIT_%=:\n"
      "mbarrier.try_wait.parity.shared::cta.b64 p, [%0], %1;\n"
      "@p bra DONE_%=;\n"
      "add.u32 n, n, 1;\n"
      "setp.lt.u32 p, n, 2097152;\n"
      "@p bra WAIT_%=;\n"
      "trap;\n"
      "DONE_%=:\n}\n" ::"r"(bar), "r"(parity) : "memory");
}
__device__ __forceinline__ void cnt_wait(const unsigned* p, unsigned target) {
  asm volatile(
      "{\n.reg .pred p;\n.reg .u32 n, v;\n.reg .s32 d;\nmov.u32 n, 0;\n"
      "WAIT_%=:\n"
      "ld.acquire.gpu.global.u32 v, [%0];\n"
      "sub.s32 d, v, %1;\n"
      "setp.ge.s32 p, d, 0;\n"
      "@p bra DONE_%=;\n"
      "add.u32 n, n, 1;\n"
      "setp.lt.u32 p, n, 4194304;\n"
      "@p bra WAIT_%=;\n"
      "trap;\n"
      "DONE_%=:\n"
#if !(CW & 2)
      "fence.proxy.async.global;\n"
#endif
      "}\n" ::"l"(p), "r"(target) : "memory");
}
__device__ __forceinline__ void cnt_signal(unsigned* p) {
  asm volatile("{\n.reg .pred p;\nelect.sync _|p, 0xffffffff;\n@p red.relaxed.gpu.global.add.u32 [%0], 1;\n}\n" ::"l"(p) : "memory");
}
__device__ __forceinline__ void ll_store(uint4* p, uint32_t a, uint32_t b, uint32_t tag) {
  asm volatile("st.relaxed.gpu.global.v2.b64 [%0], {%1, %2};" ::"l"(p), "l"((uint64_t)a | ((uint64_t)tag << 32)),
               "l"((uint64_t)b | ((uint64_t)tag << 32)) : "memory");
}
__device__ __forceinline__ uint4 ll_peek(const uint4* p) {
  uint4 v;
  asm volatile("ld.relaxed.gpu.global.v4.u32 {%0, %1, %2, %3}, [%4];" : "=r"(v.x), "=r"(v.y), "=r"(v.z), "=r"(v.w) : "l"(p) : "memory");
  return v;
}
template <int N, class F>
__device__ __forceinline__ void ll_poll(F addr, uint32_t tag, uint32_t (&out)[2 * N]) {
  for (int n = 0;; n++) {
    uint4 v[N];
#pragma unroll
    for (int i = 0; i < N; i++) v[i] = ll_peek(addr(i));
    bool ok = true;
#pragma unroll
    for (int i = 0; i < N; i++) {
      ok = ok && v[i].y == tag && v[i].w == tag;
      out[2 * i] = v[i].x;
      out[2 * i + 1] = v[i].z;
    }
    if (ok) break;
    if (n > 2000000) asm volatile("trap;");
  }
  __syncwarp();
}
constexpr uint64_t POLICY_EVICT_FIRST = 0x12F0000000000000ull;
__device__ __forceinline__ void expect_tx_elect(uint32_t bar, uint32_t bytes) {
  asm volatile("{\n.reg .pred p;\nelect.sync _|p, 0xffffffff;\n@p mbarrier.arrive.expect_tx.shared::cta.b64 _, [%0], %1;\n}\n" ::"r"(bar), "r"(bytes) : "memory");
}
__device__ __forceinline__ void arrive_elect(uint32_t bar) {
  asm volatile("{\n.reg .pred p;\nelect.sync _|p, 0xffffffff;\n@p mbarrier.arrive.shared::cta.b64 _, [%0];\n}\n" ::"r"(bar) : "memory");
}
__device__ __forceinline__ void tma_load(uint32_t dst, const CUtensorMap* m, uint32_t bar, int c0, int c1) {
  asm volatile("{\n.reg .pred p;\nelect.sync _|p, 0xffffffff;\n"
               "@p cp.async.bulk.tensor.2d.shared::cluster.global.mbarrier::complete_tx::bytes [%0], [%1, {%3, %4}], [%2];\n}\n"
               ::"r"(dst), "l"(m), "r"(bar), "r"(c0), "r"(c1) : "memory");
}
__device__ __forceinline__ void tma_load_mc(uint32_t dst, const CUtensorMap* m, uint32_t bar, int c0, int c1) {
  asm volatile("{\n.reg .pred p;\nelect.sync _|p, 0xffffffff;\n"
               "@p cp.async.bulk.tensor.2d.shared::cluster.global.mbarrier::complete_tx::bytes.multicast::cluster.L2::cache_hint [%0], [%1, {%3, %4}], [%2], %5, %6;\n}\n"
               ::"r"(dst), "l"(m), "r"(bar), "r"(c0), "r"(c1), "h"((uint16_t)3), "l"(POLICY_EVICT_FIRST) : "memory");
}
__device__ __forceinline__ void tma_load_ef(uint32_t dst, const CUtensorMap* m, uint32_t bar, int c0, int c1) {
  asm volatile("{\n.reg .pred p;\nelect.sync _|p, 0xffffffff;\n"
               "@p cp.async.bulk.tensor.2d.shared::cluster.global.mbarrier::complete_tx::bytes.L2::cache_hint [%0], [%1, {%3, %4}], [%2], %5;\n}\n"
               ::"r"(dst), "l"(m), "r"(bar), "r"(c0), "r"(c1), "l"(POLICY_EVICT_FIRST) : "memory");
}
__device__ __forceinline__ void tma_store2(const CUtensorMap* m, uint32_t src, int c0, int c1) {
  asm volatile("{\n.reg .pred p;\nelect.sync _|p, 0xffffffff;\n"
               "@p cp.async.bulk.tensor.2d.global.shared::cta.bulk_group [%0, {%2, %3}], [%1];\n}\n"
               ::"l"(m), "r"(src), "r"(c0), "r"(c1) : "memory");
}
__device__ __forceinline__ void tma_store3(const CUtensorMap* m, uint32_t src, int c0, int c1, int c2) {
  asm volatile("{\n.reg .pred p;\nelect.sync _|p, 0xffffffff;\n"
               "@p cp.async.bulk.tensor.3d.global.shared::cta.bulk_group [%0, {%2, %3, %4}], [%1];\n}\n"
               ::"l"(m), "r"(src), "r"(c0), "r"(c1), "r"(c2) : "memory");
}
__device__ __forceinline__ void l2_prefetch_tile(const CUtensorMap* m, int c0, int c1) {
  asm volatile("cp.async.bulk.prefetch.tensor.2d.L2.global [%0, {%1, %2}];" ::"l"(m), "r"(c0), "r"(c1) : "memory");
}
__device__ __forceinline__ void prefetch_map(const CUtensorMap* m) {
  asm volatile("prefetch.tensormap [%0];" ::"l"(m) : "memory");
}
__device__ __forceinline__ void wg_fence() { asm volatile("wgmma.fence.sync.aligned;" ::: "memory"); }
__device__ __forceinline__ void wg_commit() { asm volatile("wgmma.commit_group.sync.aligned;" ::: "memory"); }
template <int N>
__device__ __forceinline__ void wg_wait() { asm volatile("wgmma.wait_group.sync.aligned %0;" ::"n"(N) : "memory"); }
__device__ __forceinline__ void bar_sync(int id, int n) { asm volatile("bar.sync %0, %1;" ::"r"(id), "r"(n) : "memory"); }
__device__ __forceinline__ void cluster_arrive() { asm volatile("barrier.cluster.arrive.release.aligned;" ::: "memory"); }
__device__ __forceinline__ void cluster_arrive_relaxed() { asm volatile("barrier.cluster.arrive.relaxed.aligned;" ::: "memory"); }
__device__ __forceinline__ void cluster_wait() { asm volatile("barrier.cluster.wait.acquire.aligned;" ::: "memory"); }
__device__ __forceinline__ uint32_t load_epoch(const unsigned* p) {
  uint32_t e;
  asm volatile("ld.relaxed.gpu.global.u32 %0, [%1];" : "=r"(e) : "l"(p) : "memory");
  return e;
}
__device__ __forceinline__ uint32_t pack2(float lo, float hi) {
  uint32_t r;
  asm("cvt.rn.bf16x2.f32 %0, %1, %2;" : "=r"(r) : "f"(hi), "f"(lo));
  return r;
}
__device__ __forceinline__ float bf_lo(uint32_t v) { return __uint_as_float(v << 16); }
__device__ __forceinline__ float bf_hi(uint32_t v) { return __uint_as_float(v & 0xffff0000u); }
__device__ __forceinline__ float bf_round(float v) { return __bfloat162float(__float2bfloat16_rn(v)); }
__device__ __forceinline__ float silu_f(float v) { return __fdividef(v, 1.0f + __expf(-v)); }
__device__ __forceinline__ uint4 ldg_nc(const void* p) {
  uint4 v;
  asm volatile("ld.global.nc.L1::no_allocate.v4.u32 {%0, %1, %2, %3}, [%4];" : "=r"(v.x), "=r"(v.y), "=r"(v.z), "=r"(v.w) : "l"(p));
  return v;
}
__device__ __forceinline__ uint4 ldg_stream(const void* p) {
  uint4 v;
  asm volatile("ld.global.nc.L1::no_allocate.L2::cache_hint.v4.u32 {%0, %1, %2, %3}, [%4], %5;" : "=r"(v.x), "=r"(v.y), "=r"(v.z), "=r"(v.w) : "l"(p), "l"(POLICY_EVICT_FIRST));
  return v;
}
__device__ __forceinline__ void stmatrix4(uint32_t addr, uint32_t a, uint32_t b, uint32_t c, uint32_t d) {
  asm volatile("stmatrix.sync.aligned.m8n8.x4.shared.b16 [%0], {%1, %2, %3, %4};" ::"r"(addr), "r"(a), "r"(b), "r"(c), "r"(d) : "memory");
}
__device__ __forceinline__ uint32_t movmatrix(uint32_t a) {
  uint32_t d;
  asm volatile("movmatrix.sync.aligned.m8n8.trans.b16 %0, %1;" : "=r"(d) : "r"(a));
  return d;
}
__device__ __forceinline__ void mma16816(float (&d)[4], uint32_t a0, uint32_t a1, uint32_t a2, uint32_t a3, uint32_t b0, uint32_t b1) {
  asm volatile("mma.sync.aligned.m16n8k16.row.col.f32.bf16.bf16.f32 {%0, %1, %2, %3}, {%4, %5, %6, %7}, {%8, %9}, {%0, %1, %2, %3};"
               : "+f"(d[0]), "+f"(d[1]), "+f"(d[2]), "+f"(d[3]) : "r"(a0), "r"(a1), "r"(a2), "r"(a3), "r"(b0), "r"(b1));
}
__device__ __forceinline__ void mma1688(float (&d)[4], uint32_t a0, uint32_t a1, uint32_t b0) {
  asm volatile("mma.sync.aligned.m16n8k8.row.col.f32.bf16.bf16.f32 {%0, %1, %2, %3}, {%4, %5}, {%6}, {%0, %1, %2, %3};"
               : "+f"(d[0]), "+f"(d[1]), "+f"(d[2]), "+f"(d[3]) : "r"(a0), "r"(a1), "r"(b0));
}
__device__ __forceinline__ void sts128(uint32_t addr, uint32_t a, uint32_t b, uint32_t c, uint32_t d) {
  asm volatile("st.shared.v4.u32 [%0], {%1, %2, %3, %4};" ::"r"(addr), "r"(a), "r"(b), "r"(c), "r"(d) : "memory");
}
__device__ __forceinline__ uint4 lds128(uint32_t addr) {
  uint4 v;
  asm volatile("ld.shared.v4.u32 {%0, %1, %2, %3}, [%4];" : "=r"(v.x), "=r"(v.y), "=r"(v.z), "=r"(v.w) : "r"(addr) : "memory");
  return v;
}
__device__ __forceinline__ float2 lds64f(uint32_t addr) {
  float2 v;
  asm volatile("ld.shared.v2.f32 {%0, %1}, [%2];" : "=f"(v.x), "=f"(v.y) : "r"(addr) : "memory");
  return v;
}
__device__ __forceinline__ void sts32f(uint32_t addr, float v) {
  asm volatile("st.shared.f32 [%0], %1;" ::"r"(addr), "f"(v) : "memory");
}
__device__ __forceinline__ float lds32f(uint32_t addr) {
  float v;
  asm volatile("ld.shared.f32 %0, [%1];" : "=f"(v) : "r"(addr) : "memory");
  return v;
}
#define PROF_AT(cond, slot) do {} while (0)

constexpr uint64_t DESC_A = ((uint64_t)1 << 62) | ((uint64_t)(1024 >> 4) << 32) | ((uint64_t)1 << 16);
constexpr uint64_t DESC_B = ((uint64_t)1 << 62) | ((uint64_t)(1024 >> 4) << 32) | ((uint64_t)(8192 >> 4) << 16);

template <int BN> struct Wg;
template <> struct Wg<128> { static __device__ __forceinline__ void mma(float (&d)[64], uint64_t a, uint64_t b, int s) { wgmma_ss_n128(d, a, b, s); } };
template <> struct Wg<192> { static __device__ __forceinline__ void mma(float (&d)[96], uint64_t a, uint64_t b, int s) { wgmma_ss_n192(d, a, b, s); } };
template <> struct Wg<256> { static __device__ __forceinline__ void mma(float (&d)[128], uint64_t a, uint64_t b, int s) { wgmma_ss_n256(d, a, b, s); } };

template <int BN, int NST, uint32_t STAGE>
__device__ __forceinline__ void mainloop(float (&acc)[BN / 2], uint32_t a_base, uint32_t b_base, uint32_t a_own, uint32_t full0,
                                         uint32_t rel0, bool releaser, int nkb, int& s, uint32_t& ph) {
  int prev = 0;
#pragma unroll 1
  for (int kb = 0; kb < nkb; kb++) {
    mbar_wait(full0 + 8 * s, ph);
    const uint32_t aa = (a_own != 0 && kb < 2) ? a_own + kb * 16384 : a_base + s * STAGE;
    const uint64_t da = DESC_A | (uint64_t)(aa >> 4);
    const uint64_t db = DESC_B | (uint64_t)((b_base + s * STAGE) >> 4);
    wg_fence();
#pragma unroll
    for (int k = 0; k < 4; k++) Wg<BN>::mma(acc, da + k * 2, db + k * 128, (kb | k) != 0);
    wg_commit();
    wg_wait<1>();
    if (kb > 0 && releaser) mbar_arrive_cluster(rel0 + 8 * prev);
    prev = s;
    if (++s == NST) { s = 0; ph ^= 1; }
  }
  wg_wait<0>();
  if (releaser) mbar_arrive_cluster(rel0 + 8 * prev);
}

__device__ __forceinline__ int own_first(int it, int j) {
  return it >= 16 ? (it & 15) : (it < 2 ? 2 * j + it : (it - 2 < 2 * j ? it - 2 : it));
}
__device__ __forceinline__ int down_k(int it) {
  const int r = (it >> 4) - 1, idx = it & 15;
  return r < 0 ? idx * 64 : (r < 3 ? (idx >> 1) * 448 + r * 128 + (idx & 1) * 64 : idx * 448 + 384);
}
__device__ __forceinline__ void wait_p3_free(uint32_t empty3, int i) {
  mbar_wait(empty3 + 8 * ((i * 2) / 3), 1);
  mbar_wait(empty3 + 8 * ((i * 2 + 1) / 3), 1);
}
__device__ __forceinline__ void wait_p2_free(uint32_t empty2, int i) {
  const int w0 = (i * 3) / 2, w1 = (i * 3 + 2) / 2;
  mbar_wait(empty2 + 8 * w0, w0 < 4 ? 0 : 1);
  mbar_wait(empty2 + 8 * w1, w1 < 4 ? 0 : 1);
}

__device__ __forceinline__ void chan(float& m, float& q, float m2, float q2, float n) {
  const float d = m2 - m;
  m = 0.5f * (m + m2);
  q = q + q2 + d * d * (0.5f * n);
}

template <int N>
__device__ __forceinline__ void row_stats(const uint32_t (&ll)[N], float& mean, float& rstd) {
  float ma = __uint_as_float(ll[0]), qa = __uint_as_float(ll[1]), mb = __uint_as_float(ll[4]), qb = __uint_as_float(ll[5]);
  chan(ma, qa, __uint_as_float(ll[2]), __uint_as_float(ll[3]), 128.f);
  chan(mb, qb, __uint_as_float(ll[6]), __uint_as_float(ll[7]), 128.f);
  chan(ma, qa, mb, qb, 256.f);
  const float mo = __shfl_xor_sync(~0u, ma, 16), qo = __shfl_xor_sync(~0u, qa, 16);
  chan(ma, qa, mo, qo, 512.f);
  mean = ma;
  rstd = rsqrtf(qa * (1.0f / DM) + 1e-5f);
}

__device__ __forceinline__ void stage_slab(uint32_t chunk, int warp, int lane, const uint32_t (&lo)[8], const uint32_t (&hi)[8]) {
  const int row = warp * 16 + (lane & 7) + ((lane >> 3) & 1) * 8;
  const uint32_t rbase = chunk + row * 128;
#pragma unroll
  for (int q = 0; q < 4; q++) {
    const int grp = 2 * q + (lane >> 4);
    stmatrix4(rbase + ((grp ^ (row & 7)) << 4), lo[2 * q], hi[2 * q], lo[2 * q + 1], hi[2 * q + 1]);
  }
}
__device__ __forceinline__ void stage_done(uint32_t bar, int lane) {
  asm volatile("fence.proxy.async.shared::cta;" ::: "memory");
  __syncwarp();
  if (lane == 0) mbar_arrive(bar);
}

__global__ void __launch_bounds__(384, 1) fused_kernel(const __grid_constant__ Params p) {
  extern __shared__ __align__(1024) uint8_t smem_raw[];
  const uint32_t sm = smem_u32(smem_raw);
  const uint32_t bars = sm + MISC_OFF;
  const uint32_t stg = sm + STG_OFF;
  const int rank = blockIdx.x & 1;
  const int cl = blockIdx.x >> 1;
  const int grp = cl < 4 ? 0 : (cl < 36 ? (cl - 4) & 7 : 1 + (cl - 36) % 7);
  const int j = cl < 4 ? 4 + cl : (cl < 36 ? (cl - 4) >> 3 : 4 + (cl - 36) / 7);
  const int rb = grp * 2 + rank;
  const int cta = rb * 8 + j;
  PROF_AT(threadIdx.x == 0, 0);

  if (threadIdx.x < 128) {
    asm volatile("setmaxnreg.dec.sync.aligned.u32 40;");
    const int warp = __shfl_sync(~0u, (int)(threadIdx.x >> 5), 0), lane = threadIdx.x & 31;
    if (threadIdx.x == 0) {
      if (sm & 1023) asm volatile("trap;");
      for (int i = 0; i < 4; i++) { mbar_init(bars + 8 * (B_FQ + i), 1); mbar_init(bars + 8 * (B_EQ + i), 4); }
      for (int i = 0; i < 6; i++) { mbar_init(bars + 8 * (B_FW + i), 1); mbar_init(bars + 8 * (B_EW + i), 4); }
      for (int i = 0; i < 4; i++) { mbar_init(bars + 8 * (B_FG + i), 1); mbar_init(bars + 8 * (B_EG + i), 4); }
      for (int i = 0; i < 6; i++) { mbar_init(bars + 8 * (B_FD + i), 1); mbar_init(bars + 8 * (B_ED + i), 4); }
      mbar_init(bars + 8 * B_STGF, 8);
      mbar_init(bars + 8 * B_STGE, 1);
      mbar_init(bars + 8 * B_MODB, 1);
      mbar_init(bars + 8 * B_SPF, 2);
      for (int i = 0; i < 4; i++) mbar_init(bars + 8 * (B_WM + i), 1);
      for (int i = 0; i < 8; i++) mbar_init(bars + 8 * (B_RDY + i), 1);
      asm volatile("fence.mbarrier_init.release.cluster;" ::: "memory");
    }
    __syncwarp();
    cluster_arrive();
    const uint32_t tag = load_epoch(p.epoch) + 1;
    const unsigned target = tag * 8;
    unsigned* cnt = p.cnt + rb * 32;
    cluster_wait();
    if (warp == 0) {
      const CUtensorMap* wgu = rank ? &p.wu : &p.wg;
      uint32_t st = sm + 16384, fb = bars + 8 * B_FQ, ph = 1;
#pragma unroll 1
      for (int it = 0; it < 32; it++) {
        const int kb = own_first(it, j), col = j * 128 + (it >> 4) * 64;
        mbar_wait(fb + 8 * (B_EQ - B_FQ), ph);
        expect_tx_elect(fb, it < 2 ? 24576 : 40960);
        tma_load_mc(st + rank * 8192, &p.wqkv, fb, col + rank * 1024, kb * 64);
        tma_load_mc(st + 16384 + rank * 4096, &p.wqkv32, fb, col + 2048, kb * 64 + rank * 32);
        st += 49152; fb += 8;
        if ((it & 3) == 3) { st -= 4 * 49152; fb -= 32; ph ^= 1; }
      }
      mbar_wait(bars + 8 * B_SPF, 0);
      fb = bars + 8 * B_FW; ph = 1;
#pragma unroll 1
      for (int it = 0, s = 0; it < 16; it++) {
        if (it < 6) wait_p3_free(bars + 8 * B_EQ, it);
        mbar_wait(fb + 8 * (B_EW - B_FW), ph);
        expect_tx_elect(fb, 32768);
        tma_load_mc(st + rank * 8192, &p.wo, fb, j * 128 + rank * 64, (it & 7) * 128 + (it >> 3) * 64);
        st += 32768; fb += 8;
        if (++s == 6) { s = 0; st -= 6 * 32768; fb -= 48; ph ^= 1; }
      }
      st = sm + 16384; fb = bars + 8 * B_FG; ph = 1;
#pragma unroll 1
      for (int it = 0; it < 48; it++) {
        const int kb = own_first(it, j), col = j * 448 + (it >> 4) * 128;
        if (it < 4) wait_p2_free(bars + 8 * B_EW, it);
        mbar_wait(fb + 8 * (B_EG - B_FG), ph);
        expect_tx_elect(fb, it < 2 ? 32768 : 49152);
        tma_load_mc(st + rank * 16384, wgu, fb, col, kb * 64);
        tma_load_mc(st + rank * 16384 + 8192, wgu, fb, col + 64, kb * 64);
        st += 49152; fb += 8;
        if ((it & 3) == 3) { st -= 4 * 49152; fb -= 32; ph ^= 1; }
      }
      fb = bars + 8 * B_FD; ph = 1;
#pragma unroll 1
      for (int it = 0, s = 0; it < 72; it++) {
        if (it < 6) wait_p3_free(bars + 8 * B_EG, it);
        mbar_wait(fb + 8 * (B_ED - B_FD), ph);
        expect_tx_elect(fb, 32768);
        tma_load_mc(st + rank * 8192, it < 16 ? wgu : &p.wd, fb, it < 16 ? j * 448 + 384 : j * 128 + rank * 64, down_k(it));
        st += 32768; fb += 8;
        if (++s == 6) { s = 0; st -= 6 * 32768; fb -= 48; ph ^= 1; }
      }
    } else if (warp == 1) {
      const int arow = rb * 128;
      uint32_t st = sm + 2 * 49152, fb = bars + 8 * (B_FQ + 2), ph = 1;
      cnt_wait(cnt + C_H, target);
      PROF_AT(lane == 0, 16);
#pragma unroll 1
      for (int it = 2; it < 32; it++) {
        mbar_wait(fb + 8 * (B_EQ - B_FQ), ph);
        tma_load(st, &p.h, fb, own_first(it, j) * 64, arow);
        st += 49152; fb += 8;
        if ((it & 3) == 3) { st -= 4 * 49152; fb -= 32; ph ^= 1; }
      }
      mbar_wait(bars + 8 * B_SPF, 0);
      fb = bars + 8 * B_FW; ph = 1;
#pragma unroll 1
      for (int it = 0, s = 0; it < 16; it++) {
        if (it < 6) wait_p3_free(bars + 8 * B_EQ, it);
        mbar_wait(fb + 8 * (B_EW - B_FW), ph);
        if ((it & 7) == 0) { mbar_wait(bars + 8 * (B_RDY + C_O + (it >> 3)), 0); PROF_AT(lane == 0, 17 + (it >> 3)); }
        tma_load(st, &p.o_ld, fb, (it & 7) * 128 + (it >> 3) * 64, arow);
        st += 32768; fb += 8;
        if (++s == 6) { s = 0; st -= 6 * 32768; fb -= 48; ph ^= 1; }
      }
      st = sm + 2 * 49152; fb = bars + 8 * (B_FG + 2); ph = 1;
      mbar_wait(bars + 8 * (B_RDY + C_H2), 0);
      PROF_AT(lane == 0, 19);
#pragma unroll 1
      for (int it = 2; it < 48; it++) {
        mbar_wait(fb + 8 * (B_EG - B_FG), ph);
        tma_load(st, &p.h2, fb, own_first(it, j) * 64, arow);
        st += 49152; fb += 8;
        if ((it & 3) == 3) { st -= 4 * 49152; fb -= 32; ph ^= 1; }
      }
      fb = bars + 8 * B_FD; ph = 1;
#pragma unroll 1
      for (int it = 0, s = 0; it < 72; it++) {
        if (it < 6) wait_p3_free(bars + 8 * B_EG, it);
        mbar_wait(fb + 8 * (B_ED - B_FD), ph);
        if ((it & 15) == 0 && it > 0) { mbar_wait(bars + 8 * (B_RDY + C_ACT - 1 + (it >> 4)), 0); PROF_AT(lane == 0, 19 + (it >> 4)); }
        tma_load(st, it < 16 ? &p.h2 : &p.act, fb, down_k(it), arow);
        st += 32768; fb += 8;
        if (++s == 6) { s = 0; st -= 6 * 32768; fb -= 48; ph ^= 1; }
      }
    } else if (warp == 2) {
      if (lane < 13) prefetch_map(&p.h + lane);
      __syncwarp();
#pragma unroll 1
      for (int n = 0; n < 9; n++) {
        mbar_wait(bars + 8 * B_STGF, n & 1);
        if (n == 1 || n == 2) {
          tma_store3(&p.o_st, stg, j * 128 + (n - 1) * 64, rb * 64, 0);
        } else {
          const CUtensorMap* m = n == 0 ? &p.h : (n == 3 ? &p.h2 : (n == 8 ? &p.out : &p.act));
          const int col = (n < 4 || n == 8) ? j * 128 : j * 448 + (n - 4) * 128;
          tma_store2(m, stg, col, rb * 128);
          if (n != 7) tma_store2(m, stg + 16384, col + 64, rb * 128);
        }
        asm volatile("cp.async.bulk.commit_group;" ::: "memory");
        asm volatile("cp.async.bulk.wait_group 0;" ::: "memory");
        __syncwarp();
        if (n < 8) cnt_signal(cnt + n);
        arrive_elect(bars + 8 * B_STGE);
        PROF_AT(lane == 0, n == 0 ? 33 : 23 + n);
      }
    } else {
      if (lane < 8) ll_store(p.modll + 512 + cta * 8 + lane, 0u, 0u, 0u);
      __syncwarp();
#pragma unroll
      for (int hh = 0; hh < 4; hh++) {
        const uint4 c0 = ldg_nc(p.c + hh * 256 + lane * 8);
        sts128(sm + MODB_OFF + hh * 512 + lane * 16, pack2(silu_f(bf_lo(c0.x)), silu_f(bf_hi(c0.x))), pack2(silu_f(bf_lo(c0.y)), silu_f(bf_hi(c0.y))),
               pack2(silu_f(bf_lo(c0.z)), silu_f(bf_hi(c0.z))), pack2(silu_f(bf_lo(c0.w)), silu_f(bf_hi(c0.w))));
      }
      mbar_wait(bars + 8 * B_STGE, 0);
      __syncwarp();
#pragma unroll
      for (int i = 0; i < 4; i++) {
        expect_tx_elect(bars + 8 * (B_WM + i), 8192);
        tma_load_ef(sm + i * 49152 + 40960, &p.wm, bars + 8 * (B_WM + i), 2048 + cta * 32, i * 128);
      }
      float v[8];
#pragma unroll
      for (int q = 0; q < 8; q++) v[q] = 0.f;
#pragma unroll 1
      for (int i = 0; i < 8; i++) {
        const uint32_t buf = sm + (i & 3) * 49152 + 40960;
        mbar_wait(bars + 8 * (B_WM + (i & 3)), i >> 2);
#pragma unroll 4
        for (int e = 0; e < 16; e++) {
          const uint4 w = lds128(buf + e * 512 + lane * 16);
          uint16_t sh;
          asm volatile("ld.shared.u16 %0, [%1];" : "=h"(sh) : "r"(sm + MODB_OFF + (i * 128 + e * 8 + (lane >> 2)) * 2));
          const float sv = bf_lo(sh);
          v[0] += sv * bf_lo(w.x); v[1] += sv * bf_hi(w.x); v[2] += sv * bf_lo(w.y); v[3] += sv * bf_hi(w.y);
          v[4] += sv * bf_lo(w.z); v[5] += sv * bf_hi(w.z); v[6] += sv * bf_lo(w.w); v[7] += sv * bf_hi(w.w);
        }
        __syncwarp();
        if (i < 4) {
          expect_tx_elect(bars + 8 * (B_WM + i), 8192);
          tma_load_ef(buf, &p.wm, bars + 8 * (B_WM + i), 2048 + cta * 32, (i + 4) * 128);
        }
      }
      if (lane < 2) mbar_arrive_cluster(mapa(bars + 8 * B_SPF, lane));
      __syncwarp();
      {
        const bool b4 = lane & 16, b3 = lane & 8;
#pragma unroll
        for (int q = 0; q < 4; q++) v[q] = (b4 ? v[q + 4] : v[q]) + __shfl_xor_sync(~0u, b4 ? v[q] : v[q + 4], 16);
#pragma unroll
        for (int q = 0; q < 4; q++) v[q] += __shfl_xor_sync(~0u, v[q], 8);
#pragma unroll
        for (int q = 0; q < 4; q++) v[q] += __shfl_xor_sync(~0u, v[q], 4);
        if (!b3 && !(lane & 4)) ll_store(p.modll + 512 + cta * 8 + (lane & 3) * 2 + (lane >> 4), pack2(v[0], v[1]), pack2(v[2], v[3]), tag);
        __syncwarp();
      }
      PROF_AT(lane == 0, 34);
      {
        uint32_t m[8];
        const uint4* src = p.modll + 512 + j * 32 + lane;
        ll_poll<4>([&](int i) { return src + i * 256; }, tag, m);
#pragma unroll
        for (int vec = 0; vec < 4; vec++) {
          const float add = vec == 2 ? 1.0f : 0.0f;
          sts128(sm + MODB_OFF + (vec * 128 + lane * 4) * 4, __float_as_uint(bf_round(bf_lo(m[2 * vec]) + add)), __float_as_uint(bf_round(bf_hi(m[2 * vec]) + add)),
                 __float_as_uint(bf_round(bf_lo(m[2 * vec + 1]) + add)), __float_as_uint(bf_round(bf_hi(m[2 * vec + 1]) + add)));
        }
        __syncwarp();
        if (lane == 0) mbar_arrive(bars + 8 * B_MODB);
        PROF_AT(lane == 0, 15);
      }
      __syncwarp();
#pragma unroll 1
      for (int n = C_O; n < 8; n++) {
        cnt_wait(cnt + n, target);
        arrive_elect(bars + 8 * (B_RDY + n));
      }
    }
    __syncwarp();
    cluster_arrive_relaxed();
    cluster_wait();
  } else {
    const int tid = threadIdx.x - 128;
    const int cw = tid >> 7, warp = (tid >> 5) & 3, lane = tid & 31;
    uint32_t tag;

    {
      const int l16 = lane & 15, half = lane >> 4;
      uint4 wv[8], xv[8];
      uint16_t cv[8];
      const bf16* wp = p.wmod + cta * 16 + (tid & 1) * 8;
#pragma unroll
      for (int i = 0; i < 8; i++) wv[i] = ldg_stream(wp + (size_t)(i * 128 + (tid >> 1)) * 6144);
      const int tok0 = rb * 128 + (warp * 16 + half) * 2 + cw;
#pragma unroll
      for (int i = 0; i < 8; i++) xv[i] = ldg_nc(p.x + (size_t)(tok0 + 4 * i) * DM + j * 128 + l16 * 8);
#pragma unroll
      for (int i = 0; i < 8; i++)
        asm volatile("ld.global.nc.u16 %0, [%1];" : "=h"(cv[i]) : "l"(p.c + i * 128 + (tid >> 1)));
      tag = load_epoch(p.epoch) + 1;
      uint4* st1 = p.stats1 + (rb * 8 + j) * 128 + cw * 64 + warp * 16 + (l16 >> 1) * 2 + half;
      if ((lane & 1) == 0) ll_store(st1, 0u, 0u, 0u);
      if (tid < 4) ll_store(p.modll + cta * 4 + tid, 0u, 0u, 0u);
      __syncwarp();
      cluster_arrive_relaxed();
      asm volatile("setmaxnreg.inc.sync.aligned.u32 232;");
      PROF_AT(tid == 0, 32);
      float v[8];
#pragma unroll
      for (int q = 0; q < 8; q++) v[q] = 0.f;
#pragma unroll
      for (int i = 0; i < 8; i++) {
        const float s = bf_round(silu_f(bf_lo(cv[i])));
        v[0] += s * bf_lo(wv[i].x); v[1] += s * bf_hi(wv[i].x); v[2] += s * bf_lo(wv[i].y); v[3] += s * bf_hi(wv[i].y);
        v[4] += s * bf_lo(wv[i].z); v[5] += s * bf_hi(wv[i].z); v[6] += s * bf_lo(wv[i].w); v[7] += s * bf_hi(wv[i].w);
      }
      {
        const bool b4 = lane & 16, b3 = lane & 8, b2 = lane & 4;
#pragma unroll
        for (int q = 0; q < 4; q++) v[q] = (b4 ? v[q + 4] : v[q]) + __shfl_xor_sync(~0u, b4 ? v[q] : v[q + 4], 16);
#pragma unroll
        for (int q = 0; q < 2; q++) v[q] = (b3 ? v[q + 2] : v[q]) + __shfl_xor_sync(~0u, b3 ? v[q] : v[q + 2], 8);
        v[0] = (b2 ? v[1] : v[0]) + __shfl_xor_sync(~0u, b2 ? v[0] : v[1], 4);
        v[0] += __shfl_xor_sync(~0u, v[0], 2);
      }
      const uint32_t red = sm;
      if ((lane & 2) == 0) {
        const int col = (lane & 1) * 8 + ((lane >> 4) & 1) * 4 + ((lane >> 3) & 1) * 2 + ((lane >> 2) & 1);
        sts32f(red + ((tid >> 5) * 16 + col) * 4, v[0]);
      }
      bar_sync(1, 256);
      if (tid < 4) {
        float a[4] = {0.f, 0.f, 0.f, 0.f};
#pragma unroll
        for (int w = 0; w < 8; w++) {
          const uint4 t4 = lds128(red + (w * 16 + tid * 4) * 4);
          a[0] += __uint_as_float(t4.x); a[1] += __uint_as_float(t4.y); a[2] += __uint_as_float(t4.z); a[3] += __uint_as_float(t4.w);
        }
        ll_store(p.modll + cta * 4 + tid, pack2(a[0], a[1]), pack2(a[2], a[3]), tag);
      }
      __syncwarp();
      PROF_AT(tid == 0, 1);
#pragma unroll
      for (int i = 0; i < 8; i++) asm volatile("" : "+r"(xv[i].x), "+r"(xv[i].y), "+r"(xv[i].z), "+r"(xv[i].w));
      float m[8], q[8];
#pragma unroll
      for (int i = 0; i < 8; i++) {
        const float e[8] = {bf_lo(xv[i].x), bf_hi(xv[i].x), bf_lo(xv[i].y), bf_hi(xv[i].y), bf_lo(xv[i].z), bf_hi(xv[i].z), bf_lo(xv[i].w), bf_hi(xv[i].w)};
        m[i] = (((e[0] + e[1]) + (e[2] + e[3])) + ((e[4] + e[5]) + (e[6] + e[7]))) * 0.125f;
        q[i] = 0.f;
#pragma unroll
        for (int k = 0; k < 8; k++) q[i] += (e[k] - m[i]) * (e[k] - m[i]);
      }
      {
        const bool b3 = lane & 8, b2 = lane & 4, b1 = lane & 2;
#pragma unroll
        for (int i = 0; i < 4; i++) {
          const float mo = __shfl_xor_sync(~0u, b3 ? m[i] : m[i + 4], 8), qo = __shfl_xor_sync(~0u, b3 ? q[i] : q[i + 4], 8);
          m[i] = b3 ? m[i + 4] : m[i]; q[i] = b3 ? q[i + 4] : q[i];
          chan(m[i], q[i], mo, qo, 8.f);
        }
#pragma unroll
        for (int i = 0; i < 2; i++) {
          const float mo = __shfl_xor_sync(~0u, b2 ? m[i] : m[i + 2], 4), qo = __shfl_xor_sync(~0u, b2 ? q[i] : q[i + 2], 4);
          m[i] = b2 ? m[i + 2] : m[i]; q[i] = b2 ? q[i + 2] : q[i];
          chan(m[i], q[i], mo, qo, 16.f);
        }
        {
          const float mo = __shfl_xor_sync(~0u, b1 ? m[0] : m[1], 2), qo = __shfl_xor_sync(~0u, b1 ? q[0] : q[1], 2);
          m[0] = b1 ? m[1] : m[0]; q[0] = b1 ? q[1] : q[0];
          chan(m[0], q[0], mo, qo, 32.f);
        }
        {
          const float mo = __shfl_xor_sync(~0u, m[0], 1), qo = __shfl_xor_sync(~0u, q[0], 1);
          chan(m[0], q[0], mo, qo, 64.f);
        }
      }
      if ((lane & 1) == 0) ll_store(st1, __float_as_uint(m[0]), __float_as_uint(q[0]), tag);
      __syncwarp();
      uint32_t ll[12];
      {
        const uint4* sp = p.stats1 + (rb * 8 + half * 4) * 128 + cw * 64 + warp * 16 + l16;
        const uint4* mp = p.modll + j * 32 + lane;
        ll_poll<6>([&](int i) { return i < 4 ? sp + i * 128 : mp + (i & 1) * 256; }, tag, ll);
      }
      PROF_AT(tid == 0, 2);
      float mean, rstd;
      row_stats(ll, mean, rstd);
      float sa[8], ca[8];
#pragma unroll
      for (int e = 0; e < 4; e++) {
        const uint32_t sv = __shfl_sync(~0u, ll[8 + (e & 1)], l16 * 2 + (e >> 1)), cv2 = __shfl_sync(~0u, ll[10 + (e & 1)], l16 * 2 + (e >> 1));
        sa[2 * e] = bf_lo(sv); sa[2 * e + 1] = bf_hi(sv);
        ca[2 * e] = bf_round(1.0f + bf_lo(cv2)); ca[2 * e + 1] = bf_round(1.0f + bf_hi(cv2));
      }
#pragma unroll
      for (int i = 0; i < 8; i++) {
        const float mu = __shfl_sync(~0u, mean, i * 2 + half), rs = __shfl_sync(~0u, rstd, i * 2 + half);
        const uint32_t u[4] = {xv[i].x, xv[i].y, xv[i].z, xv[i].w};
        uint32_t o[4];
#pragma unroll
        for (int e = 0; e < 4; e++)
          o[e] = pack2((bf_lo(u[e]) - mu) * rs * ca[2 * e] + sa[2 * e], (bf_hi(u[e]) - mu) * rs * ca[2 * e + 1] + sa[2 * e + 1]);
        const int row = cw * 64 + warp * 16 + i * 2 + half;
        sts128(stg + (l16 >> 3) * 16384 + row * 128 + (((l16 & 7) ^ (row & 7)) << 4), o[0], o[1], o[2], o[3]);
      }
      cluster_wait();
      stage_done(bars + 8 * B_STGF, lane);
      bar_sync(2 + cw, 128);
      PROF_AT(tid == 0, 3);
    }

    const int r = lane >> 2, c = lane & 3;
    const bool releaser = (tid & 95) == 0;
    const uint32_t rbars = mapa(bars, (tid & 32) ? (rank ^ 1) : rank);
    const uint32_t a_base = (sm & 0x3FFFF) + cw * 8192, b_base = (sm & 0x3FFFF) + 16384;
    const uint32_t a_own = a_base + STG_OFF;
    uint4* st2 = p.stats2 + (rb * 8 + j) * 128 + cw * 64 + warp * 16 + r + (c & 1) * 8;
    if (c < 2) ll_store(st2, 0u, 0u, 0u);
    if (warp == 3) {
#pragma unroll
      for (int t = 0; t < 16; t++) ll_store(p.halo + ((cta * 2 + (t >> 3)) * 2 + cw) * 256 + (t & 7) * 32 + lane, 0u, 0u, 0u);
    }
    __syncwarp();

    {
      int s = 0; uint32_t ph = 0;
#pragma unroll 1
      for (int rho = 0; rho < 2; rho++) {
        float acc[96];
        mainloop<192, 4, 49152>(acc, a_base, b_base, rho == 0 ? a_own : 0u, bars + 8 * B_FQ, rbars + 8 * B_EQ, releaser, 16, s, ph);
        PROF_AT(tid == 0, 4 + rho * 2);
        uint32_t ql[8], qh[8], k0[8], k1[8], v0[8], v1[8], hp[16];
#pragma unroll
        for (int t = 0; t < 8; t++) {
          k1[t] = pack2(acc[4 * (8 + t) + 2], acc[4 * (8 + t) + 3]);
          v1[t] = movmatrix(pack2(acc[4 * (16 + t) + 2], acc[4 * (16 + t) + 3]));
        }
        mbar_wait(bars + 8 * B_STGE, rho);
        const uint32_t xch = stg + 16384 + (cw * 4 + warp) * 2048 + lane * 16;
        if (warp < 3) {
          sts128(xch, k1[0], k1[1], k1[2], k1[3]);
          sts128(xch + 512, k1[4], k1[5], k1[6], k1[7]);
          sts128(xch + 1024, v1[0], v1[1], v1[2], v1[3]);
          sts128(xch + 1536, v1[4], v1[5], v1[6], v1[7]);
        } else if (rb < 15) {
          uint4* dst = p.halo + ((cta * 2 + rho) * 2 + cw) * 256 + lane;
#pragma unroll
          for (int t = 0; t < 4; t++) {
            ll_store(dst + t * 32, k1[2 * t], k1[2 * t + 1], tag);
            ll_store(dst + (4 + t) * 32, v1[2 * t], v1[2 * t + 1], tag);
          }
        }
#pragma unroll
        for (int t = 0; t < 8; t++) {
          ql[t] = pack2(acc[4 * t], acc[4 * t + 1]);
          qh[t] = pack2(acc[4 * t + 2], acc[4 * t + 3]);
          k0[t] = pack2(acc[4 * (8 + t)], acc[4 * (8 + t) + 1]);
          v0[t] = movmatrix(pack2(acc[4 * (16 + t)], acc[4 * (16 + t) + 1]));
        }
        bar_sync(2 + cw, 128);
        if (warp > 0) {
#pragma unroll
          for (int t = 0; t < 4; t++) {
            const uint4 a = lds128(xch - 2048 + t * 512);
            hp[4 * t] = a.x; hp[4 * t + 1] = a.y; hp[4 * t + 2] = a.z; hp[4 * t + 3] = a.w;
          }
        } else if (rb > 0) {
          const uint4* src = p.halo + (((cta - 8) * 2 + rho) * 2 + cw) * 256 + lane;
          ll_poll<8>([&](int i) { return src + i * 32; }, tag, hp);
        } else {
#pragma unroll
          for (int t = 0; t < 16; t++) hp[t] = 0;
        }
        const bool first = (rb == 0) && (warp == 0);
        const bool up0 = 2 * c > r, up1 = 2 * c + 1 > r;
        const float scale = 0.17677669529663687f;
        const float log2e = 1.4426950408889634f;
        uint32_t ol[8], oh[8];
#pragma unroll
        for (int h = 0; h < 2; h++) {
          float sp[4] = {0.f, 0.f, 0.f, 0.f}, s0[4] = {0.f, 0.f, 0.f, 0.f}, s1[4] = {0.f, 0.f, 0.f, 0.f};
#pragma unroll
          for (int ks = 0; ks < 2; ks++) {
            const int t = 4 * h + 2 * ks;
            mma16816(sp, ql[t], qh[t], ql[t + 1], qh[t + 1], hp[t], hp[t + 1]);
            mma16816(s0, ql[t], qh[t], ql[t + 1], qh[t + 1], k0[t], k0[t + 1]);
            mma16816(s1, ql[t], qh[t], ql[t + 1], qh[t + 1], k1[t], k1[t + 1]);
          }
          float l0 = (up0 ? sp[0] : s0[0]) * scale, l1 = (up1 ? sp[1] : s0[1]) * scale;
          const float h0 = (up0 ? s0[2] : s1[2]) * scale, h1 = (up1 ? s0[3] : s1[3]) * scale;
          if (first && up0) l0 = -1000000000.0f;
          if (first && up1) l1 = -1000000000.0f;
          float ml = fmaxf(l0, l1), mh = fmaxf(h0, h1);
          ml = fmaxf(ml, __shfl_xor_sync(~0u, ml, 1)); mh = fmaxf(mh, __shfl_xor_sync(~0u, mh, 1));
          ml = fmaxf(ml, __shfl_xor_sync(~0u, ml, 2)); mh = fmaxf(mh, __shfl_xor_sync(~0u, mh, 2));
          float pl0 = exp2f((l0 - ml) * log2e), pl1 = exp2f((l1 - ml) * log2e);
          float ph0 = exp2f((h0 - mh) * log2e), ph1 = exp2f((h1 - mh) * log2e);
          float sl = pl0 + pl1, sh = ph0 + ph1;
          sl += __shfl_xor_sync(~0u, sl, 1); sh += __shfl_xor_sync(~0u, sh, 1);
          sl += __shfl_xor_sync(~0u, sl, 2); sh += __shfl_xor_sync(~0u, sh, 2);
          const float il = __fdividef(1.0f, sl), ih = __fdividef(1.0f, sh);
          pl0 *= il; pl1 *= il; ph0 *= ih; ph1 *= ih;
          const uint32_t a0 = pack2(up0 ? pl0 : 0.f, up1 ? pl1 : 0.f);
          const uint32_t a2 = pack2(up0 ? 0.f : pl0, up1 ? 0.f : pl1);
          const uint32_t a3 = pack2(up0 ? ph0 : 0.f, up1 ? ph1 : 0.f);
          const uint32_t a5 = pack2(up0 ? 0.f : ph0, up1 ? 0.f : ph1);
#pragma unroll
          for (int t = 0; t < 4; t++) {
            float o[4] = {0.f, 0.f, 0.f, 0.f};
            mma16816(o, a0, 0u, a2, a3, hp[8 + 4 * h + t], v0[4 * h + t]);
            mma1688(o, 0u, a5, v1[4 * h + t]);
            ol[4 * h + t] = pack2(o[0], o[1]);
            oh[4 * h + t] = pack2(o[2], o[3]);
          }
        }
        stage_slab(stg + cw * 8192, warp, lane, ol, oh);
        stage_done(bars + 8 * B_STGF, lane);
        PROF_AT(tid == 0, 5 + rho * 2);
      }
    }

    const int row0 = rb * 128 + cw * 64 + warp * 16 + r;
    {
      uint32_t xl[16], xh[16];
      const bf16* xp = p.x + (size_t)row0 * DM + j * 128 + 2 * c;
#pragma unroll
      for (int n = 0; n < 16; n++) {
        xl[n] = __ldg((const uint32_t*)(xp + 8 * n));
        xh[n] = __ldg((const uint32_t*)(xp + 8 * DM + 8 * n));
      }
      float acc[64];
      int s = 0; uint32_t ph = 0;
      mainloop<128, 6, 32768>(acc, a_base, b_base, 0u, bars + 8 * B_FW, rbars + 8 * B_EW, releaser, 16, s, ph);
      PROF_AT(tid == 0, 8);
      mbar_wait(bars + 8 * B_MODB, 0);
      float sl = 0.f, sh = 0.f;
#pragma unroll
      for (int n = 0; n < 16; n++) {
        const float2 ga = lds64f(sm + MODB_OFF + (8 * n + 2 * c) * 4);
        xl[n] = pack2(bf_lo(xl[n]) + ga.x * acc[4 * n], bf_hi(xl[n]) + ga.y * acc[4 * n + 1]);
        xh[n] = pack2(bf_lo(xh[n]) + ga.x * acc[4 * n + 2], bf_hi(xh[n]) + ga.y * acc[4 * n + 3]);
        acc[4 * n] = bf_lo(xl[n]); acc[4 * n + 1] = bf_hi(xl[n]);
        acc[4 * n + 2] = bf_lo(xh[n]); acc[4 * n + 3] = bf_hi(xh[n]);
        sl += acc[4 * n] + acc[4 * n + 1];
        sh += acc[4 * n + 2] + acc[4 * n + 3];
      }
      sl += __shfl_xor_sync(~0u, sl, 1); sh += __shfl_xor_sync(~0u, sh, 1);
      sl += __shfl_xor_sync(~0u, sl, 2); sh += __shfl_xor_sync(~0u, sh, 2);
      const float ml = sl * (1.0f / 128), mh = sh * (1.0f / 128);
      float ql = 0.f, qh = 0.f;
#pragma unroll
      for (int n = 0; n < 16; n++) {
        const float d0 = acc[4 * n] - ml, d1 = acc[4 * n + 1] - ml, d2 = acc[4 * n + 2] - mh, d3 = acc[4 * n + 3] - mh;
        ql += d0 * d0 + d1 * d1;
        qh += d2 * d2 + d3 * d3;
      }
      ql += __shfl_xor_sync(~0u, ql, 1); qh += __shfl_xor_sync(~0u, qh, 1);
      ql += __shfl_xor_sync(~0u, ql, 2); qh += __shfl_xor_sync(~0u, qh, 2);
      if (c < 2) ll_store(st2, __float_as_uint(c ? mh : ml), __float_as_uint(c ? qh : ql), tag);
      __syncwarp();
      uint4* x1p = p.x1 + (size_t)cta * 2048 + tid;
#pragma unroll
      for (int q = 0; q < 4; q++) {
        x1p[q * 256] = make_uint4(xl[4 * q], xl[4 * q + 1], xl[4 * q + 2], xl[4 * q + 3]);
        x1p[(4 + q) * 256] = make_uint4(xh[4 * q], xh[4 * q + 1], xh[4 * q + 2], xh[4 * q + 3]);
      }
      mbar_wait(bars + 8 * B_STGE, 0);
      float mean[2], rstd[2];
      {
        uint32_t st[8];
        const uint4* sp = p.stats2 + (rb * 8 + (lane >> 4) * 4) * 128 + cw * 64 + warp * 16 + (lane & 15);
        ll_poll<4>([&](int i) { return sp + i * 128; }, tag, st);
        float mu, rs;
        row_stats(st, mu, rs);
        mean[0] = __shfl_sync(~0u, mu, r); rstd[0] = __shfl_sync(~0u, rs, r);
        mean[1] = __shfl_sync(~0u, mu, r + 8); rstd[1] = __shfl_sync(~0u, rs, r + 8);
      }
      PROF_AT(tid == 0, 9);
#pragma unroll
      for (int ch = 0; ch < 2; ch++) {
        uint32_t lo[8], hi[8];
#pragma unroll
        for (int t = 0; t < 8; t++) {
          const int n = ch * 8 + t;
          const float2 sb = lds64f(sm + MODB_OFF + (128 + 8 * n + 2 * c) * 4), cb = lds64f(sm + MODB_OFF + (256 + 8 * n + 2 * c) * 4);
          lo[t] = pack2((acc[4 * n] - mean[0]) * rstd[0] * cb.x + sb.x, (acc[4 * n + 1] - mean[0]) * rstd[0] * cb.y + sb.y);
          hi[t] = pack2((acc[4 * n + 2] - mean[1]) * rstd[1] * cb.x + sb.x, (acc[4 * n + 3] - mean[1]) * rstd[1] * cb.y + sb.y);
        }
        stage_slab(stg + ch * 16384 + cw * 8192, warp, lane, lo, hi);
      }
      stage_done(bars + 8 * B_STGF, lane);
      bar_sync(2 + cw, 128);
      PROF_AT(tid == 0, 10);
    }

    {
      int s = 0; uint32_t ph = 0;
#pragma unroll 1
      for (int t = 0; t < 3; t++) {
        float acc[128];
        mainloop<256, 4, 49152>(acc, a_base, b_base, t == 0 ? a_own : 0u, bars + 8 * B_FG, rbars + 8 * B_EG, releaser, 16, s, ph);
        PROF_AT(tid == 0, 36 + t);
        mbar_wait(bars + 8 * B_STGE, (t + 1) & 1);
#pragma unroll
        for (int ch = 0; ch < 2; ch++) {
          uint32_t lo[8], hi[8];
#pragma unroll
          for (int q = 0; q < 8; q++) {
            const int n = 4 * (ch * 8 + q);
            lo[q] = pack2(silu_f(acc[n]) * acc[64 + n], silu_f(acc[n + 1]) * acc[64 + n + 1]);
            hi[q] = pack2(silu_f(acc[n + 2]) * acc[64 + n + 2], silu_f(acc[n + 3]) * acc[64 + n + 3]);
          }
          stage_slab(stg + ch * 16384 + cw * 8192, warp, lane, lo, hi);
        }
        stage_done(bars + 8 * B_STGF, lane);
      }
      PROF_AT(tid == 0, 11);
    }
    int sd = 0; uint32_t phd = 0;
    {
      float acc[64];
      mainloop<128, 6, 32768>(acc, a_base, b_base, 0u, bars + 8 * B_FD, rbars + 8 * B_ED, releaser, 16, sd, phd);
      PROF_AT(tid == 0, 39);
      mbar_wait(bars + 8 * B_STGE, 0);
      uint32_t lo[8], hi[8];
#pragma unroll
      for (int q = 0; q < 8; q++) {
        const int n = 4 * q;
        lo[q] = pack2(silu_f(acc[n]) * acc[32 + n], silu_f(acc[n + 1]) * acc[32 + n + 1]);
        hi[q] = pack2(silu_f(acc[n + 2]) * acc[32 + n + 2], silu_f(acc[n + 3]) * acc[32 + n + 3]);
      }
      stage_slab(stg + cw * 8192, warp, lane, lo, hi);
      stage_done(bars + 8 * B_STGF, lane);
      PROF_AT(tid == 0, 12);
    }

    {
      uint4 x1[8];
      const uint4* x1p = p.x1 + (size_t)cta * 2048 + tid;
#pragma unroll
      for (int q = 0; q < 8; q++) x1[q] = ll_peek(x1p + q * 256);
      float acc[64];
      mainloop<128, 6, 32768>(acc, a_base, b_base, 0u, bars + 8 * B_FD, rbars + 8 * B_ED, releaser, 56, sd, phd);
      PROF_AT(tid == 0, 13);
      mbar_wait(bars + 8 * B_STGE, 1);
#pragma unroll
      for (int ch = 0; ch < 2; ch++) {
        uint32_t lo[8], hi[8];
#pragma unroll
        for (int t = 0; t < 8; t++) {
          const int n = ch * 8 + t;
          const float2 gb = lds64f(sm + MODB_OFF + (384 + 8 * n + 2 * c) * 4);
          const uint4 a = x1[n >> 2], b = x1[4 + (n >> 2)];
          const uint32_t xl = (n & 3) == 0 ? a.x : (n & 3) == 1 ? a.y : (n & 3) == 2 ? a.z : a.w;
          const uint32_t xh = (n & 3) == 0 ? b.x : (n & 3) == 1 ? b.y : (n & 3) == 2 ? b.z : b.w;
          lo[t] = pack2(bf_lo(xl) + gb.x * acc[4 * n], bf_hi(xl) + gb.y * acc[4 * n + 1]);
          hi[t] = pack2(bf_lo(xh) + gb.x * acc[4 * n + 2], bf_hi(xh) + gb.y * acc[4 * n + 3]);
        }
        stage_slab(stg + ch * 16384 + cw * 8192, warp, lane, lo, hi);
      }
      stage_done(bars + 8 * B_STGF, lane);
      PROF_AT(tid == 0, 14);
    }
    if (blockIdx.x == 0 && tid == 0) asm volatile("st.relaxed.gpu.global.u32 [%0], %1;" ::"l"(p.epoch), "r"(tag) : "memory");
    __syncwarp();
    cluster_arrive_relaxed();
    cluster_wait();
  }
}

typedef CUresult (*EncodeFn)(CUtensorMap*, CUtensorMapDataType, cuuint32_t, void*, const cuuint64_t*, const cuuint64_t*,
                             const cuuint32_t*, const cuuint32_t*, CUtensorMapInterleave, CUtensorMapSwizzle,
                             CUtensorMapL2promotion, CUtensorMapFloatOOBfill);

void encode2d(EncodeFn fn, CUtensorMap* m, const void* ptr, uint64_t cols, uint64_t rows, uint32_t box_rows) {
  cuuint64_t dims[2] = {cols, rows};
  cuuint64_t strides[1] = {cols * 2};
  cuuint32_t box[2] = {64, box_rows};
  cuuint32_t es[2] = {1, 1};
  fn(m, CU_TENSOR_MAP_DATA_TYPE_BFLOAT16, 2, (void*)ptr, dims, strides, box, es, CU_TENSOR_MAP_INTERLEAVE_NONE,
     CU_TENSOR_MAP_SWIZZLE_128B, CU_TENSOR_MAP_L2_PROMOTION_L2_128B, CU_TENSOR_MAP_FLOAT_OOB_FILL_NONE);
}

}

extern "C" void kernel_launch(void* const* d_in, const int* in_sizes, int n_in, void* d_out, int out_size) {
  (void)in_sizes; (void)n_in; (void)out_size;
  void* fp = nullptr;
  cudaDriverEntryPointQueryResult qr;
  cudaGetDriverEntryPoint("cuTensorMapEncodeTiled", &fp, cudaEnableDefault, &qr);
  EncodeFn fn = (EncodeFn)fp;
  void *ph, *po, *ph2, *pact;
  cudaGetSymbolAddress(&ph, g_h);
  cudaGetSymbolAddress(&po, g_o);
  cudaGetSymbolAddress(&ph2, g_h2);
  cudaGetSymbolAddress(&pact, g_act);
  Params p;
  encode2d(fn, &p.h, ph, DM, SEQ, 128);
  encode2d(fn, &p.o_ld, po, DM, SEQ, 128);
  encode2d(fn, &p.h2, ph2, DM, SEQ, 128);
  encode2d(fn, &p.act, pact, FF, SEQ, 128);
  encode2d(fn, &p.out, d_out, DM, SEQ, 128);
  encode2d(fn, &p.wqkv, d_in[1], 3 * DM, DM, 64);
  encode2d(fn, &p.wqkv32, d_in[1], 3 * DM, DM, 32);
  encode2d(fn, &p.wo, d_in[2], DM, DM, 64);
  encode2d(fn, &p.wg, d_in[4], FF, DM, 64);
  encode2d(fn, &p.wu, d_in[5], FF, DM, 64);
  encode2d(fn, &p.wd, d_in[6], DM, FF, 64);
  {
    cuuint64_t dims[3] = {DM, SEQ / 2, 2};
    cuuint64_t strides[2] = {DM * 4, DM * 2};
    cuuint32_t box[3] = {64, 64, 2};
    cuuint32_t es[3] = {1, 1, 1};
    fn(&p.o_st, CU_TENSOR_MAP_DATA_TYPE_BFLOAT16, 3, po, dims, strides, box, es, CU_TENSOR_MAP_INTERLEAVE_NONE,
       CU_TENSOR_MAP_SWIZZLE_128B, CU_TENSOR_MAP_L2_PROMOTION_L2_128B, CU_TENSOR_MAP_FLOAT_OOB_FILL_NONE);
  }
  {
    cuuint64_t dims[2] = {6 * DM, DM};
    cuuint64_t strides[1] = {6 * DM * 2};
    cuuint32_t box[2] = {32, 128};
    cuuint32_t es[2] = {1, 1};
    fn(&p.wm, CU_TENSOR_MAP_DATA_TYPE_BFLOAT16, 2, d_in[8], dims, strides, box, es, CU_TENSOR_MAP_INTERLEAVE_NONE,
       CU_TENSOR_MAP_SWIZZLE_NONE, CU_TENSOR_MAP_L2_PROMOTION_NONE, CU_TENSOR_MAP_FLOAT_OOB_FILL_NONE);
  }
  p.x = (const bf16*)d_in[0];
  p.c = (const bf16*)d_in[7];
  p.wmod = (const bf16*)d_in[8];
  void* q;
  cudaGetSymbolAddress(&q, g_x1); p.x1 = (uint4*)q;
  cudaGetSymbolAddress(&q, g_modll); p.modll = (uint4*)q;
  cudaGetSymbolAddress(&q, g_halo); p.halo = (uint4*)q;
  cudaGetSymbolAddress(&q, g_stats); p.stats1 = (uint4*)q; p.stats2 = p.stats1 + SEQ * 8;
  cudaGetSymbolAddress(&q, g_cnt); p.cnt = (unsigned*)q;
  cudaGetSymbolAddress(&q, g_epoch); p.epoch = (unsigned*)q;

  cudaFuncSetAttribute(fused_kernel, cudaFuncAttributeMaxDynamicSharedMemorySize, SMEM_BYTES);
  cudaLaunchConfig_t cfg = {};
  cfg.gridDim = dim3(NCTA);
  cfg.blockDim = dim3(384);
  cfg.dynamicSmemBytes = SMEM_BYTES;
  cfg.stream = cudaStreamPerThread;
  cudaLaunchAttribute at[1];
  at[0].id = cudaLaunchAttributeClusterDimension;
  at[0].val.clusterDim.x = 2; at[0].val.clusterDim.y = 1; at[0].val.clusterDim.z = 1;
  cfg.attrs = at;
  cfg.numAttrs = 1;
  cudaLaunchKernelEx(&cfg, fused_kernel, p);
}
```

```cpp
#include <cuda_runtime.h>
#include <cuda_bf16.h>
#include <cuda.h>
#include <stdint.h>

typedef __nv_bfloat16 bf16;

#define MAPPING 2

#define ALIGN 0

#define PF 0

#define EF 1

#define ALIGNE 3

#define CW 0

#define PAUSE 200

#define WMD 2

__device__ __forceinline__ void wgmma_ss_n128(float (&d)[64], uint64_t da, uint64_t db, int scale_d) {
  asm volatile("{\n.reg .pred p;\nsetp.ne.b32 p, %66, 0;\n"
    "wgmma.mma_async.sync.aligned.m64n128k16.f32.bf16.bf16 "
    "{%0, %1, %2, %3, %4, %5, %6, %7, %8, %9, %10, %11, %12, %13, %14, %15, "
    "%16, %17, %18, %19, %20, %21, %22, %23, %24, %25, %26, %27, %28, %29, %30, %31, "
    "%32, %33, %34, %35, %36, %37, %38, %39, %40, %41, %42, %43, %44, %45, %46, %47, "
    "%48, %49, %50, %51, %52, %53, %54, %55, %56, %57, %58, %59, %60, %61, %62, %63}, "
    "%64, %65, p, 1, 1, 0, 1;\n}\n"
    : "+f"(d[0]), "+f"(d[1]), "+f"(d[2]), "+f"(d[3]), "+f"(d[4]), "+f"(d[5]), "+f"(d[6]), "+f"(d[7]),
      "+f"(d[8]), "+f"(d[9]), "+f"(d[10]), "+f"(d[11]), "+f"(d[12]), "+f"(d[13]), "+f"(d[14]), "+f"(d[15]),
      "+f"(d[16]), "+f"(d[17]), "+f"(d[18]), "+f"(d[19]), "+f"(d[20]), "+f"(d[21]), "+f"(d[22]), "+f"(d[23]),
      "+f"(d[24]), "+f"(d[25]), "+f"(d[26]), "+f"(d[27]), "+f"(d[28]), "+f"(d[29]), "+f"(d[30]), "+f"(d[31]),
      "+f"(d[32]), "+f"(d[33]), "+f"(d[34]), "+f"(d[35]), "+f"(d[36]), "+f"(d[37]), "+f"(d[38]), "+f"(d[39]),
      "+f"(d[40]), "+f"(d[41]), "+f"(d[42]), "+f"(d[43]), "+f"(d[44]), "+f"(d[45]), "+f"(d[46]), "+f"(d[47]),
      "+f"(d[48]), "+f"(d[49]), "+f"(d[50]), "+f"(d[51]), "+f"(d[52]), "+f"(d[53]), "+f"(d[54]), "+f"(d[55]),
      "+f"(d[56]), "+f"(d[57]), "+f"(d[58]), "+f"(d[59]), "+f"(d[60]), "+f"(d[61]), "+f"(d[62]), "+f"(d[63])
    : "l"(da), "l"(db), "r"(scale_d));
}

__device__ __forceinline__ void wgmma_ss_n192(float (&d)[96], uint64_t da, uint64_t db, int scale_d) {
  asm volatile("{\n.reg .pred p;\nsetp.ne.b32 p, %98, 0;\n"
    "wgmma.mma_async.sync.aligned.m64n192k16.f32.bf16.bf16 "
    "{%0, %1, %2, %3, %4, %5, %6, %7, %8, %9, %10, %11, %12, %13, %14, %15, "
    "%16, %17, %18, %19, %20, %21, %22, %23, %24, %25, %26, %27, %28, %29, %30, %31, "
    "%32, %33, %34, %35, %36, %37, %38, %39, %40, %41, %42, %43, %44, %45, %46, %47, "
    "%48, %49, %50, %51, %52, %53, %54, %55, %56, %57, %58, %59, %60, %61, %62, %63, "
    "%64, %65, %66, %67, %68, %69, %70, %71, %72, %73, %74, %75, %76, %77, %78, %79, "
    "%80, %81, %82, %83, %84, %85, %86, %87, %88, %89, %90, %91, %92, %93, %94, %95}, "
    "%96, %97, p, 1, 1, 0, 1;\n}\n"
    : "+f"(d[0]), "+f"(d[1]), "+f"(d[2]), "+f"(d[3]), "+f"(d[4]), "+f"(d[5]), "+f"(d[6]), "+f"(d[7]),
      "+f"(d[8]), "+f"(d[9]), "+f"(d[10]), "+f"(d[11]), "+f"(d[12]), "+f"(d[13]), "+f"(d[14]), "+f"(d[15]),
      "+f"(d[16]), "+f"(d[17]), "+f"(d[18]), "+f"(d[19]), "+f"(d[20]), "+f"(d[21]), "+f"(d[22]), "+f"(d[23]),
      "+f"(d[24]), "+f"(d[25]), "+f"(d[26]), "+f"(d[27]), "+f"(d[28]), "+f"(d[29]), "+f"(d[30]), "+f"(d[31]),
      "+f"(d[32]), "+f"(d[33]), "+f"(d[34]), "+f"(d[35]), "+f"(d[36]), "+f"(d[37]), "+f"(d[38]), "+f"(d[39]),
      "+f"(d[40]), "+f"(d[41]), "+f"(d[42]), "+f"(d[43]), "+f"(d[44]), "+f"(d[45]), "+f"(d[46]), "+f"(d[47]),
      "+f"(d[48]), "+f"(d[49]), "+f"(d[50]), "+f"(d[51]), "+f"(d[52]), "+f"(d[53]), "+f"(d[54]), "+f"(d[55]),
      "+f"(d[56]), "+f"(d[57]), "+f"(d[58]), "+f"(d[59]), "+f"(d[60]), "+f"(d[61]), "+f"(d[62]), "+f"(d[63]),
      "+f"(d[64]), "+f"(d[65]), "+f"(d[66]), "+f"(d[67]), "+f"(d[68]), "+f"(d[69]), "+f"(d[70]), "+f"(d[71]),
      "+f"(d[72]), "+f"(d[73]), "+f"(d[74]), "+f"(d[75]), "+f"(d[76]), "+f"(d[77]), "+f"(d[78]), "+f"(d[79]),
      "+f"(d[80]), "+f"(d[81]), "+f"(d[82]), "+f"(d[83]), "+f"(d[84]), "+f"(d[85]), "+f"(d[86]), "+f"(d[87]),
      "+f"(d[88]), "+f"(d[89]), "+f"(d[90]), "+f"(d[91]), "+f"(d[92]), "+f"(d[93]), "+f"(d[94]), "+f"(d[95])
    : "l"(da), "l"(db), "r"(scale_d));
}

__device__ __forceinline__ void wgmma_ss_n256(float (&d)[128], uint64_t da, uint64_t db, int scale_d) {
  asm volatile("{\n.reg .pred p;\nsetp.ne.b32 p, %130, 0;\n"
    "wgmma.mma_async.sync.aligned.m64n256k16.f32.bf16.bf16 "
    "{%0, %1, %2, %3, %4, %5, %6, %7, %8, %9, %10, %11, %12, %13, %14, %15, "
    "%16, %17, %18, %19, %20, %21, %22, %23, %24, %25, %26, %27, %28, %29, %30, %31, "
    "%32, %33, %34, %35, %36, %37, %38, %39, %40, %41, %42, %43, %44, %45, %46, %47, "
    "%48, %49, %50, %51, %52, %53, %54, %55, %56, %57, %58, %59, %60, %61, %62, %63, "
    "%64, %65, %66, %67, %68, %69, %70, %71, %72, %73, %74, %75, %76, %77, %78, %79, "
    "%80, %81, %82, %83, %84, %85, %86, %87, %88, %89, %90, %91, %92, %93, %94, %95, "
    "%96, %97, %98, %99, %100, %101, %102, %103, %104, %105, %106, %107, %108, %109, %110, %111, "
    "%112, %113, %114, %115, %116, %117, %118, %119, %120, %121, %122, %123, %124, %125, %126, %127}, "
    "%128, %129, p, 1, 1, 0, 1;\n}\n"
    : "+f"(d[0]), "+f"(d[1]), "+f"(d[2]), "+f"(d[3]), "+f"(d[4]), "+f"(d[5]), "+f"(d[6]), "+f"(d[7]),
      "+f"(d[8]), "+f"(d[9]), "+f"(d[10]), "+f"(d[11]), "+f"(d[12]), "+f"(d[13]), "+f"(d[14]), "+f"(d[15]),
      "+f"(d[16]), "+f"(d[17]), "+f"(d[18]), "+f"(d[19]), "+f"(d[20]), "+f"(d[21]), "+f"(d[22]), "+f"(d[23]),
      "+f"(d[24]), "+f"(d[25]), "+f"(d[26]), "+f"(d[27]), "+f"(d[28]), "+f"(d[29]), "+f"(d[30]), "+f"(d[31]),
      "+f"(d[32]), "+f"(d[33]), "+f"(d[34]), "+f"(d[35]), "+f"(d[36]), "+f"(d[37]), "+f"(d[38]), "+f"(d[39]),
      "+f"(d[40]), "+f"(d[41]), "+f"(d[42]), "+f"(d[43]), "+f"(d[44]), "+f"(d[45]), "+f"(d[46]), "+f"(d[47]),
      "+f"(d[48]), "+f"(d[49]), "+f"(d[50]), "+f"(d[51]), "+f"(d[52]), "+f"(d[53]), "+f"(d[54]), "+f"(d[55]),
      "+f"(d[56]), "+f"(d[57]), "+f"(d[58]), "+f"(d[59]), "+f"(d[60]), "+f"(d[61]), "+f"(d[62]), "+f"(d[63]),
      "+f"(d[64]), "+f"(d[65]), "+f"(d[66]), "+f"(d[67]), "+f"(d[68]), "+f"(d[69]), "+f"(d[70]), "+f"(d[71]),
      "+f"(d[72]), "+f"(d[73]), "+f"(d[74]), "+f"(d[75]), "+f"(d[76]), "+f"(d[77]), "+f"(d[78]), "+f"(d[79]),
      "+f"(d[80]), "+f"(d[81]), "+f"(d[82]), "+f"(d[83]), "+f"(d[84]), "+f"(d[85]), "+f"(d[86]), "+f"(d[87]),
      "+f"(d[88]), "+f"(d[89]), "+f"(d[90]), "+f"(d[91]), "+f"(d[92]), "+f"(d[93]), "+f"(d[94]), "+f"(d[95]),
      "+f"(d[96]), "+f"(d[97]), "+f"(d[98]), "+f"(d[99]), "+f"(d[100]), "+f"(d[101]), "+f"(d[102]), "+f"(d[103]),
      "+f"(d[104]), "+f"(d[105]), "+f"(d[106]), "+f"(d[107]), "+f"(d[108]), "+f"(d[109]), "+f"(d[110]), "+f"(d[111]),
      "+f"(d[112]), "+f"(d[113]), "+f"(d[114]), "+f"(d[115]), "+f"(d[116]), "+f"(d[117]), "+f"(d[118]), "+f"(d[119]),
      "+f"(d[120]), "+f"(d[121]), "+f"(d[122]), "+f"(d[123]), "+f"(d[124]), "+f"(d[125]), "+f"(d[126]), "+f"(d[127])
    : "l"(da), "l"(db), "r"(scale_d));
}

namespace {

constexpr int SEQ = 2048, DM = 1024, FF = 3584;
constexpr int NCTA = 128;

constexpr uint32_t STG_OFF = 196608;
constexpr uint32_t MISC_OFF = STG_OFF + 32768;
constexpr uint32_t SMEM_BYTES = MISC_OFF + 3072;
constexpr uint32_t MODB_OFF = MISC_OFF + 512;

enum { B_FQ = 0, B_EQ = 4, B_FW = 8, B_EW = 14, B_FG = 20, B_EG = 24, B_FD = 28, B_ED = 34,
       B_STGF = 40, B_MODB = 42, B_SPF = 43, B_WM = 44, B_RDY = 48, B_STGE = 56, B_COUNT = 58 };
enum { C_H = 0, C_O = 1, C_H2 = 3, C_ACT = 4, C_AL = 8 };

struct Params {
  CUtensorMap h, o_ld, o_st, h2, act, out, wqkv, wqkv32, wo, wg, wu, wd, act_st;
  const bf16* x;
  const bf16* c;
  const bf16* wmod;
  uint4* x1;
  uint4* modll;
  uint4* halo;
  uint4* stats1;
  uint4* stats2;
  unsigned* cnt;
  unsigned* epoch;
};

__device__ bf16 g_h[SEQ * DM];
__device__ bf16 g_o[SEQ * DM];
__device__ bf16 g_h2[SEQ * DM];
__device__ bf16 g_act[SEQ * FF];
__device__ uint4 g_x1[NCTA * 8 * 256];
__device__ uint4 g_modll[3072 / 2];
__device__ uint4 g_halo[16 * 8 * 2 * 2 * 8 * 32];
__device__ uint4 g_stats[2 * SEQ * 8];
__device__ unsigned g_cnt[16 * 32];
__device__ unsigned g_epoch;
#define TR(off)

__device__ __forceinline__ uint32_t smem_u32(const void* p) { return (uint32_t)__cvta_generic_to_shared(p); }
__device__ __forceinline__ void mbar_init(uint32_t bar, uint32_t count) {
  asm volatile("mbarrier.init.shared::cta.b64 [%0], %1;" ::"r"(bar), "r"(count));
}
__device__ __forceinline__ void mbar_expect_tx(uint32_t bar, uint32_t bytes) {
  asm volatile("mbarrier.arrive.expect_tx.shared::cta.b64 _, [%0], %1;" ::"r"(bar), "r"(bytes) : "memory");
}
__device__ __forceinline__ void mbar_arrive(uint32_t bar) {
  asm volatile("mbarrier.arrive.shared::cta.b64 _, [%0];" ::"r"(bar) : "memory");
}
__device__ __forceinline__ void mbar_arrive_cluster(uint32_t cluster_addr) {
  asm volatile("mbarrier.arrive.shared::cluster.b64 _, [%0];" ::"r"(cluster_addr) : "memory");
}
__device__ __forceinline__ uint32_t mapa(uint32_t addr, uint32_t cta) {
  uint32_t r;
  asm volatile("mapa.shared::cluster.u32 %0, %1, %2;" : "=r"(r) : "r"(addr), "r"(cta));
  return r;
}
__device__ __forceinline__ void mbar_wait(uint32_t bar, uint32_t parity) {
  asm volatile(
      "{\n.reg .pred p;\n.reg .u32 n;\nmov.u32 n, 0;\n"
      "WAIT_%=:\n"
      "mbarrier.try_wait.parity.shared::cta.b64 p, [%0], %1;\n"
      "@p bra DONE_%=;\n"
      "add.u32 n, n, 1;\n"
      "setp.lt.u32 p, n, 2097152;\n"
      "@p bra WAIT_%=;\n"
      "trap;\n"
      "DONE_%=:\n}\n" ::"r"(bar), "r"(parity) : "memory");
}
__device__ __forceinline__ void cnt_wait(const unsigned* p, unsigned target) {
  asm volatile(
      "{\n.reg .pred p;\n.reg .u32 n, v;\n.reg .s32 d;\nmov.u32 n, 0;\n"
      "WAIT_%=:\n"
      "ld.acquire.gpu.global.u32 v, [%0];\n"
      "sub.s32 d, v, %1;\n"
      "setp.ge.s32 p, d, 0;\n"
      "@p bra DONE_%=;\n"
      "add.u32 n, n, 1;\n"
      "setp.lt.u32 p, n, 4194304;\n"
      "@p bra WAIT_%=;\n"
      "trap;\n"
      "DONE_%=:\n"
#if !(CW & 2)
      "fence.proxy.async.global;\n"
#endif
      "}\n" ::"l"(p), "r"(target) : "memory");
}
__device__ __forceinline__ void cnt_signal(unsigned* p) {
  asm volatile("{\n.reg .pred p;\nelect.sync _|p, 0xffffffff;\n@p red.relaxed.gpu.global.add.u32 [%0], 1;\n}\n" ::"l"(p) : "memory");
}
__device__ __forceinline__ void ll_store(uint4* p, uint32_t a, uint32_t b, uint32_t tag) {
  asm volatile("st.relaxed.gpu.global.v2.b64 [%0], {%1, %2};" ::"l"(p), "l"((uint64_t)a | ((uint64_t)tag << 32)),
               "l"((uint64_t)b | ((uint64_t)tag << 32)) : "memory");
}
__device__ __forceinline__ uint4 ll_peek(const uint4* p) {
  uint4 v;
  asm volatile("ld.relaxed.gpu.global.v4.u32 {%0, %1, %2, %3}, [%4];" : "=r"(v.x), "=r"(v.y), "=r"(v.z), "=r"(v.w) : "l"(p) : "memory");
  return v;
}
template <int N, class F>
__device__ __forceinline__ void ll_poll(F addr, uint32_t tag, uint32_t (&out)[2 * N]) {
  for (int n = 0;; n++) {
    uint4 v[N];
#pragma unroll
    for (int i = 0; i < N; i++) v[i] = ll_peek(addr(i));
    bool ok = true;
#pragma unroll
    for (int i = 0; i < N; i++) {
      ok = ok && v[i].y == tag && v[i].w == tag;
      out[2 * i] = v[i].x;
      out[2 * i + 1] = v[i].z;
    }
    if (ok) break;
    if (n > 2000000) asm volatile("trap;");
  }
  __syncwarp();
}
constexpr uint64_t POLICY_EVICT_FIRST = 0x12F0000000000000ull;
__device__ __forceinline__ void expect_tx_elect(uint32_t bar, uint32_t bytes) {
  asm volatile("{\n.reg .pred p;\nelect.sync _|p, 0xffffffff;\n@p mbarrier.arrive.expect_tx.shared::cta.b64 _, [%0], %1;\n}\n" ::"r"(bar), "r"(bytes) : "memory");
}
__device__ __forceinline__ void arrive_elect(uint32_t bar) {
  asm volatile("{\n.reg .pred p;\nelect.sync _|p, 0xffffffff;\n@p mbarrier.arrive.shared::cta.b64 _, [%0];\n}\n" ::"r"(bar) : "memory");
}
__device__ __forceinline__ void tma_load(uint32_t dst, const CUtensorMap* m, uint32_t bar, int c0, int c1) {
  asm volatile("{\n.reg .pred p;\nelect.sync _|p, 0xffffffff;\n"
               "@p cp.async.bulk.tensor.2d.shared::cluster.global.mbarrier::complete_tx::bytes [%0], [%1, {%3, %4}], [%2];\n}\n"
               ::"r"(dst), "l"(m), "r"(bar), "r"(c0), "r"(c1) : "memory");
}
__device__ __forceinline__ void tma_load_mc(uint32_t dst, const CUtensorMap* m, uint32_t bar, int c0, int c1) {
  asm volatile("{\n.reg .pred p;\nelect.sync _|p, 0xffffffff;\n"
               "@p cp.async.bulk.tensor.2d.shared::cluster.global.mbarrier::complete_tx::bytes.multicast::cluster.L2::cache_hint [%0], [%1, {%3, %4}], [%2], %5, %6;\n}\n"
               ::"r"(dst), "l"(m), "r"(bar), "r"(c0), "r"(c1), "h"((uint16_t)3), "l"(POLICY_EVICT_FIRST) : "memory");
}
__device__ __forceinline__ void tma_load_ef(uint32_t dst, const CUtensorMap* m, uint32_t bar, int c0, int c1) {
  asm volatile("{\n.reg .pred p;\nelect.sync _|p, 0xffffffff;\n"
               "@p cp.async.bulk.tensor.2d.shared::cluster.global.mbarrier::complete_tx::bytes.L2::cache_hint [%0], [%1, {%3, %4}], [%2], %5;\n}\n"
               ::"r"(dst), "l"(m), "r"(bar), "r"(c0), "r"(c1), "l"(POLICY_EVICT_FIRST) : "memory");
}
__device__ __forceinline__ void tma_store2(const CUtensorMap* m, uint32_t src, int c0, int c1) {
  asm volatile("{\n.reg .pred p;\nelect.sync _|p, 0xffffffff;\n"
               "@p cp.async.bulk.tensor.2d.global.shared::cta.bulk_group [%0, {%2, %3}], [%1];\n}\n"
               ::"l"(m), "r"(src), "r"(c0), "r"(c1) : "memory");
}
__device__ __forceinline__ void tma_store3(const CUtensorMap* m, uint32_t src, int c0, int c1, int c2) {
  asm volatile("{\n.reg .pred p;\nelect.sync _|p, 0xffffffff;\n"
               "@p cp.async.bulk.tensor.3d.global.shared::cta.bulk_group [%0, {%2, %3, %4}], [%1];\n}\n"
               ::"l"(m), "r"(src), "r"(c0), "r"(c1), "r"(c2) : "memory");
}
__device__ __forceinline__ void store_pause() {
  asm volatile("cp.async.bulk.commit_group;" ::: "memory");
  asm volatile("cp.async.bulk.wait_group.read 0;" ::: "memory");
  if (PAUSE) __nanosleep(PAUSE);
}
__device__ __forceinline__ void l2_prefetch_tile(const CUtensorMap* m, int c0, int c1) {
  asm volatile("cp.async.bulk.prefetch.tensor.2d.L2.global [%0, {%1, %2}];" ::"l"(m), "r"(c0), "r"(c1) : "memory");
}
__device__ __forceinline__ void prefetch_map(const CUtensorMap* m) {
  asm volatile("prefetch.tensormap [%0];" ::"l"(m) : "memory");
}
__device__ __forceinline__ void wg_fence() { asm volatile("wgmma.fence.sync.aligned;" ::: "memory"); }
__device__ __forceinline__ void wg_commit() { asm volatile("wgmma.commit_group.sync.aligned;" ::: "memory"); }
template <int N>
__device__ __forceinline__ void wg_wait() { asm volatile("wgmma.wait_group.sync.aligned %0;" ::"n"(N) : "memory"); }
__device__ __forceinline__ void bar_sync(int id, int n) { asm volatile("bar.sync %0, %1;" ::"r"(id), "r"(n) : "memory"); }
__device__ __forceinline__ void cluster_arrive() { asm volatile("barrier.cluster.arrive.release.aligned;" ::: "memory"); }
__device__ __forceinline__ void cluster_arrive_relaxed() { asm volatile("barrier.cluster.arrive.relaxed.aligned;" ::: "memory"); }
__device__ __forceinline__ void cluster_wait() { asm volatile("barrier.cluster.wait.acquire.aligned;" ::: "memory"); }
__device__ __forceinline__ uint32_t load_epoch(const unsigned* p) {
  uint32_t e;
  asm volatile("ld.relaxed.gpu.global.u32 %0, [%1];" : "=r"(e) : "l"(p) : "memory");
  return e;
}
__device__ __forceinline__ uint32_t pack2(float lo, float hi) {
  uint32_t r;
  asm("cvt.rn.bf16x2.f32 %0, %1, %2;" : "=r"(r) : "f"(hi), "f"(lo));
  return r;
}
__device__ __forceinline__ float bf_lo(uint32_t v) { return __uint_as_float(v << 16); }
__device__ __forceinline__ float bf_hi(uint32_t v) { return __uint_as_float(v & 0xffff0000u); }
__device__ __forceinline__ float bf_round(float v) { return __bfloat162float(__float2bfloat16_rn(v)); }
__device__ __forceinline__ float silu_f(float v) { return __fdividef(v, 1.0f + __expf(-v)); }
__device__ __forceinline__ uint4 ldg_nc(const void* p) {
  uint4 v;
  asm volatile("ld.global.nc.L1::no_allocate.v4.u32 {%0, %1, %2, %3}, [%4];" : "=r"(v.x), "=r"(v.y), "=r"(v.z), "=r"(v.w) : "l"(p));
  return v;
}
__device__ __forceinline__ uint4 ldg_stream(const void* p) {
  uint4 v;
  asm volatile("ld.global.nc.L1::no_allocate.L2::cache_hint.v4.u32 {%0, %1, %2, %3}, [%4], %5;" : "=r"(v.x), "=r"(v.y), "=r"(v.z), "=r"(v.w) : "l"(p), "l"(POLICY_EVICT_FIRST));
  return v;
}
__device__ __forceinline__ void stmatrix4(uint32_t addr, uint32_t a, uint32_t b, uint32_t c, uint32_t d) {
  asm volatile("stmatrix.sync.aligned.m8n8.x4.shared.b16 [%0], {%1, %2, %3, %4};" ::"r"(addr), "r"(a), "r"(b), "r"(c), "r"(d) : "memory");
}
__device__ __forceinline__ uint32_t movmatrix(uint32_t a) {
  uint32_t d;
  asm volatile("movmatrix.sync.aligned.m8n8.trans.b16 %0, %1;" : "=r"(d) : "r"(a));
  return d;
}
__device__ __forceinline__ void mma16816(float (&d)[4], uint32_t a0, uint32_t a1, uint32_t a2, uint32_t a3, uint32_t b0, uint32_t b1) {
  asm volatile("mma.sync.aligned.m16n8k16.row.col.f32.bf16.bf16.f32 {%0, %1, %2, %3}, {%4, %5, %6, %7}, {%8, %9}, {%0, %1, %2, %3};"
               : "+f"(d[0]), "+f"(d[1]), "+f"(d[2]), "+f"(d[3]) : "r"(a0), "r"(a1), "r"(a2), "r"(a3), "r"(b0), "r"(b1));
}
__device__ __forceinline__ void mma1688(float (&d)[4], uint32_t a0, uint32_t a1, uint32_t b0) {
  asm volatile("mma.sync.aligned.m16n8k8.row.col.f32.bf16.bf16.f32 {%0, %1, %2, %3}, {%4, %5}, {%6}, {%0, %1, %2, %3};"
               : "+f"(d[0]), "+f"(d[1]), "+f"(d[2]), "+f"(d[3]) : "r"(a0), "r"(a1), "r"(b0));
}
__device__ __forceinline__ void sts128(uint32_t addr, uint32_t a, uint32_t b, uint32_t c, uint32_t d) {
  asm volatile("st.shared.v4.u32 [%0], {%1, %2, %3, %4};" ::"r"(addr), "r"(a), "r"(b), "r"(c), "r"(d) : "memory");
}
__device__ __forceinline__ uint4 lds128(uint32_t addr) {
  uint4 v;
  asm volatile("ld.shared.v4.u32 {%0, %1, %2, %3}, [%4];" : "=r"(v.x), "=r"(v.y), "=r"(v.z), "=r"(v.w) : "r"(addr) : "memory");
  return v;
}
__device__ __forceinline__ float2 lds64f(uint32_t addr) {
  float2 v;
  asm volatile("ld.shared.v2.f32 {%0, %1}, [%2];" : "=f"(v.x), "=f"(v.y) : "r"(addr) : "memory");
  return v;
}
__device__ __forceinline__ void sts32f(uint32_t addr, float v) {
  asm volatile("st.shared.f32 [%0], %1;" ::"r"(addr), "f"(v) : "memory");
}
__device__ __forceinline__ float lds32f(uint32_t addr) {
  float v;
  asm volatile("ld.shared.f32 %0, [%1];" : "=f"(v) : "r"(addr) : "memory");
  return v;
}
#define PROF_AT(cond, slot) do {} while (0)

constexpr uint64_t DESC_A = ((uint64_t)1 << 62) | ((uint64_t)(1024 >> 4) << 32) | ((uint64_t)1 << 16);
constexpr uint64_t DESC_B = ((uint64_t)1 << 62) | ((uint64_t)(1024 >> 4) << 32) | ((uint64_t)(8192 >> 4) << 16);

template <int BN> struct Wg;
template <> struct Wg<128> { static __device__ __forceinline__ void mma(float (&d)[64], uint64_t a, uint64_t b, int s) { wgmma_ss_n128(d, a, b, s); } };
template <> struct Wg<192> { static __device__ __forceinline__ void mma(float (&d)[96], uint64_t a, uint64_t b, int s) { wgmma_ss_n192(d, a, b, s); } };
template <> struct Wg<256> { static __device__ __forceinline__ void mma(float (&d)[128], uint64_t a, uint64_t b, int s) { wgmma_ss_n256(d, a, b, s); } };

struct Ring {
  uint32_t a_base, b_base;
  uint32_t full0, rel0;
  int s;
  uint32_t ph;
  bool releaser;
};

template <int BN, int NST, uint32_t STAGE>
__device__ __forceinline__ void kblock(float (&acc)[BN / 2], Ring& g, uint32_t a_addr, bool first, int& prev) {
  mbar_wait(g.full0 + 8 * g.s, g.ph);
  const uint64_t da = DESC_A | (uint64_t)(a_addr >> 4);
  const uint64_t db = DESC_B | (uint64_t)((g.b_base + g.s * STAGE) >> 4);
  wg_fence();
#pragma unroll
  for (int k = 0; k < 4; k++) Wg<BN>::mma(acc, da + k * 2, db + k * 128, !(first && k == 0));
  wg_commit();
  wg_wait<1>();
  if (!first && g.releaser) mbar_arrive_cluster(g.rel0 + 8 * prev);
  prev = g.s;
  if (++g.s == NST) { g.s = 0; g.ph ^= 1; }
}

template <int BN>
__device__ __forceinline__ void tile_end(Ring& g, int prev) {
  wg_wait<0>();
  if (g.releaser) mbar_arrive_cluster(g.rel0 + 8 * prev);
}

template <int BN, int NST, uint32_t STAGE>
__device__ __forceinline__ void mainloop(float (&acc)[BN / 2], Ring& g, uint32_t a_own, int nkb) {
  int prev = 0;
#pragma unroll 1
  for (int kb = 0; kb < nkb; kb++)
    kblock<BN, NST, STAGE>(acc, g, (a_own != 0 && kb < 2) ? a_own + kb * 16384 : g.a_base + g.s * STAGE, kb == 0, prev);
  tile_end<BN>(g, prev);
}

__device__ __forceinline__ int own_first(int it, int j) {
  return it >= 16 ? (it & 15) : (it < 2 ? 2 * j + it : (it - 2 < 2 * j ? it - 2 : it));
}
__device__ __forceinline__ int down_k(int it) {
  const int r = (it >> 4) - 1, idx = it & 15;
  return r < 0 ? idx * 64 : (r < 3 ? (idx >> 1) * 448 + r * 128 + (idx & 1) * 64 : idx * 448 + 384);
}
__device__ __forceinline__ void wait_p3_free(uint32_t empty3, int i) {
  mbar_wait(empty3 + 8 * ((i * 2) / 3), 1);
  mbar_wait(empty3 + 8 * ((i * 2 + 1) / 3), 1);
}
__device__ __forceinline__ void wait_p2_free(uint32_t empty2, int i) {
  const int w0 = (i * 3) / 2, w1 = (i * 3 + 2) / 2;
  mbar_wait(empty2 + 8 * w0, w0 < 4 ? 0 : 1);
  mbar_wait(empty2 + 8 * w1, w1 < 4 ? 0 : 1);
}

__device__ __forceinline__ void chan(float& m, float& q, float m2, float q2, float n) {
  const float d = m2 - m;
  m = 0.5f * (m + m2);
  q = q + q2 + d * d * (0.5f * n);
}

template <int N>
__device__ __forceinline__ void row_stats(const uint32_t (&ll)[N], float& mean, float& rstd) {
  float ma = __uint_as_float(ll[0]), qa = __uint_as_float(ll[1]), mb = __uint_as_float(ll[4]), qb = __uint_as_float(ll[5]);
  chan(ma, qa, __uint_as_float(ll[2]), __uint_as_float(ll[3]), 128.f);
  chan(mb, qb, __uint_as_float(ll[6]), __uint_as_float(ll[7]), 128.f);
  chan(ma, qa, mb, qb, 256.f);
  const float mo = __shfl_xor_sync(~0u, ma, 16), qo = __shfl_xor_sync(~0u, qa, 16);
  chan(ma, qa, mo, qo, 512.f);
  mean = ma;
  rstd = rsqrtf(qa * (1.0f / DM) + 1e-5f);
}

__device__ __forceinline__ void stage_slab(uint32_t chunk, int warp, int lane, const uint32_t (&lo)[8], const uint32_t (&hi)[8]) {
  const int row = warp * 16 + (lane & 7) + ((lane >> 3) & 1) * 8;
  const uint32_t rbase = chunk + row * 128;
#pragma unroll
  for (int q = 0; q < 4; q++) {
    const int grp = 2 * q + (lane >> 4);
    stmatrix4(rbase + ((grp ^ (row & 7)) << 4), lo[2 * q], hi[2 * q], lo[2 * q + 1], hi[2 * q + 1]);
  }
}
__device__ __forceinline__ float silu_mul(float g, float u) {
  float e, r;
  asm("ex2.approx.ftz.f32 %0, %1;" : "=f"(e) : "f"(g * -1.4426950408889634f));
  asm("rcp.approx.ftz.f32 %0, %1;" : "=f"(r) : "f"(1.0f + e));
  return g * r * u;
}
__device__ __forceinline__ uint32_t swiglu2(uint32_t g2, uint32_t u2) {
  asm volatile("" : "+r"(g2));
  uint32_t o = pack2(silu_mul(bf_lo(g2), bf_lo(u2)), silu_mul(bf_hi(g2), bf_hi(u2)));
  asm volatile("" : "+r"(o));
  return o;
}
__device__ __forceinline__ void stage_done(uint32_t bar, int lane) {
  asm volatile("fence.proxy.async.shared::cta;" ::: "memory");
  __syncwarp();
  if (lane == 0) mbar_arrive(bar);
}

__device__ __forceinline__ void stage_done2(uint32_t bar, int lane) {
  asm volatile("fence.proxy.async.shared::cta;" ::: "memory");
  __syncwarp();
  if (lane < 2) mbar_arrive(bar + 8 * lane);
}

__global__ void __launch_bounds__(384, 1) fused_kernel(const __grid_constant__ Params p) {
  extern __shared__ __align__(1024) uint8_t smem_raw[];
  const uint32_t sm = smem_u32(smem_raw);
  const uint32_t bars = sm + MISC_OFF;
  const uint32_t stg = sm + STG_OFF;
  const int rank = blockIdx.x & 1;
  const int cl = blockIdx.x >> 1;
  const int grp = cl < 4 ? 0 : (cl < 36 ? (cl - 4) & 7 : 1 + (cl - 36) % 7);
  const int j = cl < 4 ? 4 + cl : (cl < 36 ? (cl - 4) >> 3 : 4 + (cl - 36) / 7);
  const int rb = grp * 2 + rank;
  const int cta = rb * 8 + j;
  PROF_AT(threadIdx.x == 0, 0);

  if (threadIdx.x < 128) {
    asm volatile("setmaxnreg.dec.sync.aligned.u32 40;");
    const int warp = __shfl_sync(~0u, (int)(threadIdx.x >> 5), 0), lane = threadIdx.x & 31;
    if (threadIdx.x == 0) {
      if (sm & 1023) asm volatile("trap;");
      for (int i = 0; i < 4; i++) { mbar_init(bars + 8 * (B_FQ + i), 1); mbar_init(bars + 8 * (B_EQ + i), 16); }
      for (int i = 0; i < 6; i++) { mbar_init(bars + 8 * (B_FW + i), 1); mbar_init(bars + 8 * (B_EW + i), 16); }
      for (int i = 0; i < 4; i++) { mbar_init(bars + 8 * (B_FG + i), 1); mbar_init(bars + 8 * (B_EG + i), 16); }
      for (int i = 0; i < 6; i++) { mbar_init(bars + 8 * (B_FD + i), 1); mbar_init(bars + 8 * (B_ED + i), 16); }
      for (int i = 0; i < 2; i++) { mbar_init(bars + 8 * (B_STGF + i), 8); mbar_init(bars + 8 * (B_STGE + i), 1); }
      mbar_init(bars + 8 * B_MODB, 1);
      mbar_init(bars + 8 * B_SPF, 2);
      for (int i = 0; i < 8; i++) mbar_init(bars + 8 * (B_RDY + i), 1);
      asm volatile("fence.mbarrier_init.release.cluster;" ::: "memory");
    }
    __syncwarp();
    cluster_arrive();
    const uint32_t tag = load_epoch(p.epoch) + 1;
    const unsigned target = tag * 8;
    unsigned* cnt = p.cnt + rb * 32;
    cluster_wait();
    if (warp == 0) {
      const CUtensorMap* wgu = rank ? &p.wu : &p.wg;
      uint32_t st = sm + 16384, fb = bars + 8 * B_FQ, ph = 1;
#pragma unroll 1
      for (int it = 0; it < 32; it++) {
        const int kb = own_first(it, j), col = j * 128 + (it >> 4) * 64;
        mbar_wait(fb + 8 * (B_EQ - B_FQ), ph);
        expect_tx_elect(fb, it < 2 ? 24576 : 40960);
        tma_load_mc(st + rank * 8192, &p.wqkv, fb, col + rank * 1024, kb * 64);
        tma_load_mc(st + 16384 + rank * 4096, &p.wqkv32, fb, col + 2048, kb * 64 + rank * 32);
        st += 49152; fb += 8;
        if ((it & 3) == 3) { st -= 4 * 49152; fb -= 32; ph ^= 1; }
      }
      mbar_wait(bars + 8 * B_SPF, 0);
      fb = bars + 8 * B_FW; ph = 1;
#pragma unroll 1
      for (int it = 0, s = 0; it < 16; it++) {
        if (it < 6) wait_p3_free(bars + 8 * B_EQ, it);
        mbar_wait(fb + 8 * (B_EW - B_FW), ph);
        expect_tx_elect(fb, 32768);
        tma_load_mc(st + rank * 8192, &p.wo, fb, j * 128 + rank * 64, (it & 7) * 128 + (it >> 3) * 64);
        st += 32768; fb += 8;
        if (++s == 6) { s = 0; st -= 6 * 32768; fb -= 48; ph ^= 1; }
      }
      st = sm + 16384; fb = bars + 8 * B_FG; ph = 1;
#pragma unroll 1
      for (int it = 0; it < 48; it++) {
        const int kb = own_first(it, j), col = j * 448 + (it >> 4) * 128;
        if (it < 4) wait_p2_free(bars + 8 * B_EW, it);
        mbar_wait(fb + 8 * (B_EG - B_FG), ph);
        expect_tx_elect(fb, it < 2 ? 32768 : 49152);
        tma_load_mc(st + rank * 16384, wgu, fb, col, kb * 64);
        tma_load_mc(st + rank * 16384 + 8192, wgu, fb, col + 64, kb * 64);
        st += 49152; fb += 8;
        if ((it & 3) == 3) { st -= 4 * 49152; fb -= 32; ph ^= 1; }
      }
      fb = bars + 8 * B_FD; ph = 1;
#pragma unroll 1
      for (int it = 0, s = 0; it < 72; it++) {
        if (it < 6) wait_p3_free(bars + 8 * B_EG, it);
        mbar_wait(fb + 8 * (B_ED - B_FD), ph);
        expect_tx_elect(fb, 32768);
        tma_load_mc(st + rank * 8192, it < 16 ? wgu : &p.wd, fb, it < 16 ? j * 448 + 384 : j * 128 + rank * 64, down_k(it));
        st += 32768; fb += 8;
        if (++s == 6) { s = 0; st -= 6 * 32768; fb -= 48; ph ^= 1; }
      }
    } else if (warp == 1) {
      const int arow = rb * 128;
      uint32_t st = sm + 2 * 49152, fb = bars + 8 * (B_FQ + 2), ph = 1;
      cnt_wait(cnt + C_H, target);
      PROF_AT(lane == 0, 16);
#pragma unroll 1
      for (int it = 2; it < 32; it++) {
        mbar_wait(fb + 8 * (B_EQ - B_FQ), ph);
        tma_load(st, &p.h, fb, own_first(it, j) * 64, arow);
        if (it == 5) arrive_elect(bars + 8 * B_RDY);
        st += 49152; fb += 8;
        if ((it & 3) == 3) { st -= 4 * 49152; fb -= 32; ph ^= 1; }
      }
      mbar_wait(bars + 8 * B_SPF, 0);
      fb = bars + 8 * B_FW; ph = 1;
#pragma unroll 1
      for (int it = 0, s = 0; it < 16; it++) {
        if (it < 6) wait_p3_free(bars + 8 * B_EQ, it);
        mbar_wait(fb + 8 * (B_EW - B_FW), ph);
        if ((it & 7) == 0) { mbar_wait(bars + 8 * (B_RDY + C_O + (it >> 3)), 0); PROF_AT(lane == 0, 17 + (it >> 3)); }
        tma_load(st, &p.o_ld, fb, (it & 7) * 128 + (it >> 3) * 64, arow);
        st += 32768; fb += 8;
        if (++s == 6) { s = 0; st -= 6 * 32768; fb -= 48; ph ^= 1; }
      }
      st = sm + 2 * 49152; fb = bars + 8 * (B_FG + 2); ph = 1;
      mbar_wait(bars + 8 * (B_RDY + C_H2), 0);
      PROF_AT(lane == 0, 19);
#pragma unroll 1
      for (int it = 2; it < 48; it++) {
        mbar_wait(fb + 8 * (B_EG - B_FG), ph);
        tma_load(st, &p.h2, fb, own_first(it, j) * 64, arow);
        st += 49152; fb += 8;
        if ((it & 3) == 3) { st -= 4 * 49152; fb -= 32; ph ^= 1; }
      }
      fb = bars + 8 * B_FD; ph = 1;
#pragma unroll 1
      for (int it = 0, s = 0; it < 72; it++) {
        if (it < 6) wait_p3_free(bars + 8 * B_EG, it);
        mbar_wait(fb + 8 * (B_ED - B_FD), ph);
        if ((it & 15) == 0 && it > 0) { mbar_wait(bars + 8 * (B_RDY + C_ACT - 1 + (it >> 4)), 0); PROF_AT(lane == 0, 19 + (it >> 4)); }
        tma_load(st, it < 16 ? &p.h2 : &p.act, fb, down_k(it), arow);
        st += 32768; fb += 8;
        if (++s == 6) { s = 0; st -= 6 * 32768; fb -= 48; ph ^= 1; }
      }
    } else if (warp == 2) {
      if (lane < 13) prefetch_map(&p.h + lane);
      __syncwarp();
      uint32_t ph1 = 0;
#pragma unroll 1
      for (int n = 0; n < 9; n++) {
        const int nch = (n == 1 || n == 2 || n == 7) ? 1 : 2;
#pragma unroll 1
        for (int ch = 0; ch < nch; ch++) {
          mbar_wait(bars + 8 * (B_STGF + ch), ch ? ph1 : (n & 1));
          const uint32_t src = stg + ch * 16384;
          if (n == 1 || n == 2) {
#pragma unroll 1
            for (int q = 0; q < 4; q++) {
              tma_store3(&p.o_st, src + q * 4096, j * 128 + (n - 1) * 64, rb * 64 + (q & 1) * 32, q >> 1);
              if (n == 1) store_pause();
            }
          } else if (n >= 4 && n < 8) {
#pragma unroll 1
            for (int q = 0; q < 4; q++) {
              tma_store2(&p.act_st, src + q * 4096, j * 448 + (n - 4) * 128 + ch * 64, rb * 128 + q * 32);
              store_pause();
            }
          } else {
            tma_store2(n == 0 ? &p.h : (n == 3 ? &p.h2 : &p.out), src, j * 128 + ch * 64, rb * 128);
          }
          if (n >= 4 && n < 7 && ch == 0) arrive_elect(bars + 8 * B_STGE);
        }
        asm volatile("cp.async.bulk.commit_group;" ::: "memory");
        asm volatile("cp.async.bulk.wait_group 0;" ::: "memory");
        __syncwarp();
        if (n < 8) cnt_signal(cnt + n);
        if (!(n >= 4 && n < 7)) arrive_elect(bars + 8 * B_STGE);
        if (nch == 2) { arrive_elect(bars + 8 * (B_STGE + 1)); ph1 ^= 1; }
        PROF_AT(lane == 0, n == 0 ? 33 : 23 + n);
      }
    } else {
      if (lane < 8) ll_store(p.modll + 512 + cta * 8 + lane, 0u, 0u, 0u);
      __syncwarp();
#pragma unroll
      for (int hh = 0; hh < 4; hh++) {
        const uint4 c0 = ldg_nc(p.c + hh * 256 + lane * 8);
        sts128(sm + MODB_OFF + hh * 512 + lane * 16, pack2(silu_f(bf_lo(c0.x)), silu_f(bf_hi(c0.x))), pack2(silu_f(bf_lo(c0.y)), silu_f(bf_hi(c0.y))),
               pack2(silu_f(bf_lo(c0.z)), silu_f(bf_hi(c0.z))), pack2(silu_f(bf_lo(c0.w)), silu_f(bf_hi(c0.w))));
      }
      mbar_wait(bars + 8 * B_RDY, 0);
      __syncwarp();
      const bf16* wp = p.wmod + 2048 + cta * 32 + (lane & 3) * 8 + (size_t)(lane >> 2) * 6144;
      auto fetch = [&](int i) {
        const uint32_t buf = sm + (i & 3) * 49152 + 40960 + lane * 16;
#pragma unroll
        for (int e = 0; e < 8; e++)
          asm volatile("cp.async.cg.shared.global.L2::cache_hint [%0], [%1], 16, %2;" ::"r"(buf + e * 512), "l"(wp + (size_t)(i * 64 + e * 8) * 6144),
                       "l"(POLICY_EVICT_FIRST) : "memory");
      };
#pragma unroll
      for (int i = 0; i < WMD; i++) { fetch(i); asm volatile("cp.async.commit_group;" ::: "memory"); }
      float v[8];
#pragma unroll
      for (int q = 0; q < 8; q++) v[q] = 0.f;
#pragma unroll 1
      for (int i = 0; i < 16; i++) {
        asm volatile("cp.async.wait_group %0;" ::"n"(WMD - 1) : "memory");
        const uint32_t buf = sm + (i & 3) * 49152 + 40960 + lane * 16;
        if (i + WMD < 16) fetch(i + WMD);
        asm volatile("cp.async.commit_group;" ::: "memory");
#pragma unroll 4
        for (int e = 0; e < 8; e++) {
          const uint4 w = lds128(buf + e * 512);
          uint16_t sh;
          asm volatile("ld.shared.u16 %0, [%1];" : "=h"(sh) : "r"(sm + MODB_OFF + (i * 64 + e * 8 + (lane >> 2)) * 2));
          const float sv = bf_lo(sh);
          v[0] += sv * bf_lo(w.x); v[1] += sv * bf_hi(w.x); v[2] += sv * bf_lo(w.y); v[3] += sv * bf_hi(w.y);
          v[4] += sv * bf_lo(w.z); v[5] += sv * bf_hi(w.z); v[6] += sv * bf_lo(w.w); v[7] += sv * bf_hi(w.w);
        }
      }
      __syncwarp();
      if (lane < 2) mbar_arrive_cluster(mapa(bars + 8 * B_SPF, lane));
      __syncwarp();
      {
        const bool b4 = lane & 16, b3 = lane & 8;
#pragma unroll
        for (int q = 0; q < 4; q++) v[q] = (b4 ? v[q + 4] : v[q]) + __shfl_xor_sync(~0u, b4 ? v[q] : v[q + 4], 16);
#pragma unroll
        for (int q = 0; q < 4; q++) v[q] += __shfl_xor_sync(~0u, v[q], 8);
#pragma unroll
        for (int q = 0; q < 4; q++) v[q] += __shfl_xor_sync(~0u, v[q], 4);
        if (!b3 && !(lane & 4)) ll_store(p.modll + 512 + cta * 8 + (lane & 3) * 2 + (lane >> 4), pack2(v[0], v[1]), pack2(v[2], v[3]), tag);
        __syncwarp();
      }
      PROF_AT(lane == 0, 34);
      {
        uint32_t m[8];
        const uint4* src = p.modll + 512 + j * 32 + lane;
        ll_poll<4>([&](int i) { return src + i * 256; }, tag, m);
#pragma unroll
        for (int vec = 0; vec < 4; vec++) {
          const float add = vec == 2 ? 1.0f : 0.0f;
          sts128(sm + MODB_OFF + (vec * 128 + lane * 4) * 4, __float_as_uint(bf_round(bf_lo(m[2 * vec]) + add)), __float_as_uint(bf_round(bf_hi(m[2 * vec]) + add)),
                 __float_as_uint(bf_round(bf_lo(m[2 * vec + 1]) + add)), __float_as_uint(bf_round(bf_hi(m[2 * vec + 1]) + add)));
        }
        __syncwarp();
        if (lane == 0) mbar_arrive(bars + 8 * B_MODB);
        PROF_AT(lane == 0, 15);
      }
      __syncwarp();
#pragma unroll 1
      for (int n = C_O; n < 8; n++) {
        cnt_wait(cnt + n, target);
        arrive_elect(bars + 8 * (B_RDY + n));
      }
    }
    __syncwarp();
    cluster_arrive_relaxed();
    cluster_wait();
  } else {
    const int tid = threadIdx.x - 128;
    const int cw = __shfl_sync(~0u, tid >> 7, 0), warp = __shfl_sync(~0u, (tid >> 5) & 3, 0), lane = tid & 31;
    uint32_t tag;

    {
      const int l16 = lane & 15, half = lane >> 4;
      uint4 wv[8], xv[8];
      uint16_t cv[8];
      const bf16* wp = p.wmod + cta * 16 + (tid & 1) * 8;
#pragma unroll
      for (int i = 0; i < 8; i++) wv[i] = ldg_stream(wp + (size_t)(i * 128 + (tid >> 1)) * 6144);
      const int tok0 = rb * 128 + (warp * 16 + half) * 2 + cw;
#pragma unroll
      for (int i = 0; i < 8; i++) xv[i] = ldg_nc(p.x + (size_t)(tok0 + 4 * i) * DM + j * 128 + l16 * 8);
#pragma unroll
      for (int i = 0; i < 8; i++)
        asm volatile("ld.global.nc.u16 %0, [%1];" : "=h"(cv[i]) : "l"(p.c + i * 128 + (tid >> 1)));
      tag = load_epoch(p.epoch) + 1;
      uint4* st1 = p.stats1 + (rb * 8 + j) * 128 + cw * 64 + warp * 16 + (l16 >> 1) * 2 + half;
      if ((lane & 1) == 0) ll_store(st1, 0u, 0u, 0u);
      if (tid < 4) ll_store(p.modll + cta * 4 + tid, 0u, 0u, 0u);
      __syncwarp();
      cluster_arrive_relaxed();
      asm volatile("setmaxnreg.inc.sync.aligned.u32 232;");
      PROF_AT(tid == 0, 32);
      float v[8];
#pragma unroll
      for (int q = 0; q < 8; q++) v[q] = 0.f;
#pragma unroll
      for (int i = 0; i < 8; i++) {
        const float s = bf_round(silu_f(bf_lo(cv[i])));
        v[0] += s * bf_lo(wv[i].x); v[1] += s * bf_hi(wv[i].x); v[2] += s * bf_lo(wv[i].y); v[3] += s * bf_hi(wv[i].y);
        v[4] += s * bf_lo(wv[i].z); v[5] += s * bf_hi(wv[i].z); v[6] += s * bf_lo(wv[i].w); v[7] += s * bf_hi(wv[i].w);
      }
      {
        const bool b4 = lane & 16, b3 = lane & 8, b2 = lane & 4;
#pragma unroll
        for (int q = 0; q < 4; q++) v[q] = (b4 ? v[q + 4] : v[q]) + __shfl_xor_sync(~0u, b4 ? v[q] : v[q + 4], 16);
#pragma unroll
        for (int q = 0; q < 2; q++) v[q] = (b3 ? v[q + 2] : v[q]) + __shfl_xor_sync(~0u, b3 ? v[q] : v[q + 2], 8);
        v[0] = (b2 ? v[1] : v[0]) + __shfl_xor_sync(~0u, b2 ? v[0] : v[1], 4);
        v[0] += __shfl_xor_sync(~0u, v[0], 2);
      }
      const uint32_t red = sm;
      if ((lane & 2) == 0) {
        const int col = (lane & 1) * 8 + ((lane >> 4) & 1) * 4 + ((lane >> 3) & 1) * 2 + ((lane >> 2) & 1);
        sts32f(red + ((tid >> 5) * 16 + col) * 4, v[0]);
      }
      bar_sync(1, 256);
      if (tid < 4) {
        float a[4] = {0.f, 0.f, 0.f, 0.f};
#pragma unroll
        for (int w = 0; w < 8; w++) {
          const uint4 t4 = lds128(red + (w * 16 + tid * 4) * 4);
          a[0] += __uint_as_float(t4.x); a[1] += __uint_as_float(t4.y); a[2] += __uint_as_float(t4.z); a[3] += __uint_as_float(t4.w);
        }
        ll_store(p.modll + cta * 4 + tid, pack2(a[0], a[1]), pack2(a[2], a[3]), tag);
      }
      __syncwarp();
      PROF_AT(tid == 0, 1);
#pragma unroll
      for (int i = 0; i < 8; i++) asm volatile("" : "+r"(xv[i].x), "+r"(xv[i].y), "+r"(xv[i].z), "+r"(xv[i].w));
      float m[8], q[8];
#pragma unroll
      for (int i = 0; i < 8; i++) {
        const float e[8] = {bf_lo(xv[i].x), bf_hi(xv[i].x), bf_lo(xv[i].y), bf_hi(xv[i].y), bf_lo(xv[i].z), bf_hi(xv[i].z), bf_lo(xv[i].w), bf_hi(xv[i].w)};
        m[i] = (((e[0] + e[1]) + (e[2] + e[3])) + ((e[4] + e[5]) + (e[6] + e[7]))) * 0.125f;
        q[i] = 0.f;
#pragma unroll
        for (int k = 0; k < 8; k++) q[i] += (e[k] - m[i]) * (e[k] - m[i]);
      }
      {
        const bool b3 = lane & 8, b2 = lane & 4, b1 = lane & 2;
#pragma unroll
        for (int i = 0; i < 4; i++) {
          const float mo = __shfl_xor_sync(~0u, b3 ? m[i] : m[i + 4], 8), qo = __shfl_xor_sync(~0u, b3 ? q[i] : q[i + 4], 8);
          m[i] = b3 ? m[i + 4] : m[i]; q[i] = b3 ? q[i + 4] : q[i];
          chan(m[i], q[i], mo, qo, 8.f);
        }
#pragma unroll
        for (int i = 0; i < 2; i++) {
          const float mo = __shfl_xor_sync(~0u, b2 ? m[i] : m[i + 2], 4), qo = __shfl_xor_sync(~0u, b2 ? q[i] : q[i + 2], 4);
          m[i] = b2 ? m[i + 2] : m[i]; q[i] = b2 ? q[i + 2] : q[i];
          chan(m[i], q[i], mo, qo, 16.f);
        }
        {
          const float mo = __shfl_xor_sync(~0u, b1 ? m[0] : m[1], 2), qo = __shfl_xor_sync(~0u, b1 ? q[0] : q[1], 2);
          m[0] = b1 ? m[1] : m[0]; q[0] = b1 ? q[1] : q[0];
          chan(m[0], q[0], mo, qo, 32.f);
        }
        {
          const float mo = __shfl_xor_sync(~0u, m[0], 1), qo = __shfl_xor_sync(~0u, q[0], 1);
          chan(m[0], q[0], mo, qo, 64.f);
        }
      }
      if ((lane & 1) == 0) ll_store(st1, __float_as_uint(m[0]), __float_as_uint(q[0]), tag);
      __syncwarp();
      PROF_AT(tid == 0, 50);
      uint32_t ll[12];
      {
        const uint4* sp = p.stats1 + (rb * 8 + half * 4) * 128 + cw * 64 + warp * 16 + l16;
        const uint4* mp = p.modll + j * 32 + lane;
        ll_poll<6>([&](int i) { return i < 4 ? sp + i * 128 : mp + (i & 1) * 256; }, tag, ll);
      }
      PROF_AT(tid == 0, 2);
      float mean, rstd;
      row_stats(ll, mean, rstd);
      float sa[8], ca[8];
#pragma unroll
      for (int e = 0; e < 4; e++) {
        const uint32_t sv = __shfl_sync(~0u, ll[8 + (e & 1)], l16 * 2 + (e >> 1)), cv2 = __shfl_sync(~0u, ll[10 + (e & 1)], l16 * 2 + (e >> 1));
        sa[2 * e] = bf_lo(sv); sa[2 * e + 1] = bf_hi(sv);
        ca[2 * e] = bf_round(1.0f + bf_lo(cv2)); ca[2 * e + 1] = bf_round(1.0f + bf_hi(cv2));
      }
#pragma unroll
      for (int i = 0; i < 8; i++) {
        const float mu = __shfl_sync(~0u, mean, i * 2 + half), rs = __shfl_sync(~0u, rstd, i * 2 + half);
        const uint32_t u[4] = {xv[i].x, xv[i].y, xv[i].z, xv[i].w};
        uint32_t o[4];
#pragma unroll
        for (int e = 0; e < 4; e++)
          o[e] = pack2((bf_lo(u[e]) - mu) * rs * ca[2 * e] + sa[2 * e], (bf_hi(u[e]) - mu) * rs * ca[2 * e + 1] + sa[2 * e + 1]);
        const int row = cw * 64 + warp * 16 + i * 2 + half;
        sts128(stg + (l16 >> 3) * 16384 + row * 128 + (((l16 & 7) ^ (row & 7)) << 4), o[0], o[1], o[2], o[3]);
      }
      cluster_wait();
      stage_done2(bars + 8 * B_STGF, lane);
      bar_sync(2 + cw, 128);
      PROF_AT(tid == 0, 3);
    }

    const int r = lane >> 2, c = lane & 3;
    const bool releaser = lane < 2;
    const int srow = warp * 16 + (lane & 7) + ((lane >> 3) & 1) * 8;
    const uint32_t slab = stg + cw * 8192 + srow * 128;
    const uint32_t rbars = mapa(bars, lane & 1);
    const uint32_t a_base = (sm & 0x3FFFF) + cw * 8192, b_base = (sm & 0x3FFFF) + 16384;
    const uint32_t a_own = a_base + STG_OFF;
    uint4* st2 = p.stats2 + (rb * 8 + j) * 128 + cw * 64 + warp * 16 + r + (c & 1) * 8;
    if (c < 2) ll_store(st2, 0u, 0u, 0u);
    if (warp == 3) {
#pragma unroll
      for (int t = 0; t < 16; t++) ll_store(p.halo + ((cta * 2 + (t >> 3)) * 2 + cw) * 256 + (t & 7) * 32 + lane, 0u, 0u, 0u);
    }
    __syncwarp();

    {
      Ring g{a_base, b_base, bars + 8 * B_FQ, rbars + 8 * B_EQ, 0, 0u, releaser TR(0)};
#pragma unroll 1
      for (int rho = 0; rho < 2; rho++) {
        float acc[96];
        mainloop<192, 4, 49152>(acc, g, rho == 0 ? a_own : 0u, 16);
        PROF_AT(tid == 0, 4 + rho * 2);
        uint32_t ql[8], qh[8], k0[8], k1[8], v0[8], v1[8], hp[16];
#pragma unroll
        for (int t = 0; t < 8; t++) {
          k1[t] = pack2(acc[4 * (8 + t) + 2], acc[4 * (8 + t) + 3]);
          v1[t] = movmatrix(pack2(acc[4 * (16 + t) + 2], acc[4 * (16 + t) + 3]));
        }
        mbar_wait(bars + 8 * B_STGE, rho);
        mbar_wait(bars + 8 * (B_STGE + 1), 0);
        const uint32_t xch = stg + 16384 + (cw * 4 + warp) * 2048 + lane * 16;
        if (warp < 3) {
          sts128(xch, k1[0], k1[1], k1[2], k1[3]);
          sts128(xch + 512, k1[4], k1[5], k1[6], k1[7]);
          sts128(xch + 1024, v1[0], v1[1], v1[2], v1[3]);
          sts128(xch + 1536, v1[4], v1[5], v1[6], v1[7]);
        } else if (rb < 15) {
          uint4* dst = p.halo + ((cta * 2 + rho) * 2 + cw) * 256 + lane;
#pragma unroll
          for (int t = 0; t < 4; t++) {
            ll_store(dst + t * 32, k1[2 * t], k1[2 * t + 1], tag);
            ll_store(dst + (4 + t) * 32, v1[2 * t], v1[2 * t + 1], tag);
          }
        }
#pragma unroll
        for (int t = 0; t < 8; t++) {
          ql[t] = pack2(acc[4 * t], acc[4 * t + 1]);
          qh[t] = pack2(acc[4 * t + 2], acc[4 * t + 3]);
          k0[t] = pack2(acc[4 * (8 + t)], acc[4 * (8 + t) + 1]);
          v0[t] = movmatrix(pack2(acc[4 * (16 + t)], acc[4 * (16 + t) + 1]));
        }
        PROF_AT(tid == 0, 40 + rho * 4);
        bar_sync(2 + cw, 128);
        PROF_AT(tid == 0, 41 + rho * 4);
        if (warp > 0) {
#pragma unroll
          for (int t = 0; t < 4; t++) {
            const uint4 a = lds128(xch - 2048 + t * 512);
            hp[4 * t] = a.x; hp[4 * t + 1] = a.y; hp[4 * t + 2] = a.z; hp[4 * t + 3] = a.w;
          }
        } else if (rb > 0) {
          const uint4* src = p.halo + (((cta - 8) * 2 + rho) * 2 + cw) * 256 + lane;
          ll_poll<8>([&](int i) { return src + i * 32; }, tag, hp);
        } else {
#pragma unroll
          for (int t = 0; t < 16; t++) hp[t] = 0;
        }
        PROF_AT(tid == 0, 42 + rho * 4);
        const bool first = (rb == 0) && (warp == 0);
        const bool up0 = 2 * c > r, up1 = 2 * c + 1 > r;
        const float scale = 0.17677669529663687f;
        const float log2e = 1.4426950408889634f;
        uint32_t ol[8], oh[8];
#pragma unroll
        for (int h = 0; h < 2; h++) {
          float sp[4] = {0.f, 0.f, 0.f, 0.f}, s0[4] = {0.f, 0.f, 0.f, 0.f}, s1[4] = {0.f, 0.f, 0.f, 0.f};
#pragma unroll
          for (int ks = 0; ks < 2; ks++) {
            const int t = 4 * h + 2 * ks;
            mma16816(sp, ql[t], qh[t], ql[t + 1], qh[t + 1], hp[t], hp[t + 1]);
            mma16816(s0, ql[t], qh[t], ql[t + 1], qh[t + 1], k0[t], k0[t + 1]);
            mma16816(s1, ql[t], qh[t], ql[t + 1], qh[t + 1], k1[t], k1[t + 1]);
          }
          float l0 = (up0 ? sp[0] : s0[0]) * scale, l1 = (up1 ? sp[1] : s0[1]) * scale;
          const float h0 = (up0 ? s0[2] : s1[2]) * scale, h1 = (up1 ? s0[3] : s1[3]) * scale;
          if (first && up0) l0 = -1000000000.0f;
          if (first && up1) l1 = -1000000000.0f;
          float ml = fmaxf(l0, l1), mh = fmaxf(h0, h1);
          ml = fmaxf(ml, __shfl_xor_sync(~0u, ml, 1)); mh = fmaxf(mh, __shfl_xor_sync(~0u, mh, 1));
          ml = fmaxf(ml, __shfl_xor_sync(~0u, ml, 2)); mh = fmaxf(mh, __shfl_xor_sync(~0u, mh, 2));
          float pl0 = exp2f((l0 - ml) * log2e), pl1 = exp2f((l1 - ml) * log2e);
          float ph0 = exp2f((h0 - mh) * log2e), ph1 = exp2f((h1 - mh) * log2e);
          float sl = pl0 + pl1, sh = ph0 + ph1;
          sl += __shfl_xor_sync(~0u, sl, 1); sh += __shfl_xor_sync(~0u, sh, 1);
          sl += __shfl_xor_sync(~0u, sl, 2); sh += __shfl_xor_sync(~0u, sh, 2);
          const float il = __fdividef(1.0f, sl), ih = __fdividef(1.0f, sh);
          pl0 *= il; pl1 *= il; ph0 *= ih; ph1 *= ih;
          const uint32_t a0 = pack2(up0 ? pl0 : 0.f, up1 ? pl1 : 0.f);
          const uint32_t a2 = pack2(up0 ? 0.f : pl0, up1 ? 0.f : pl1);
          const uint32_t a3 = pack2(up0 ? ph0 : 0.f, up1 ? ph1 : 0.f);
          const uint32_t a5 = pack2(up0 ? 0.f : ph0, up1 ? 0.f : ph1);
#pragma unroll
          for (int t = 0; t < 4; t++) {
            float o[4] = {0.f, 0.f, 0.f, 0.f};
            mma16816(o, a0, 0u, a2, a3, hp[8 + 4 * h + t], v0[4 * h + t]);
            mma1688(o, 0u, a5, v1[4 * h + t]);
            ol[4 * h + t] = pack2(o[0], o[1]);
            oh[4 * h + t] = pack2(o[2], o[3]);
          }
        }
        stage_slab(stg + cw * 8192, warp, lane, ol, oh);
        stage_done(bars + 8 * B_STGF, lane);
        PROF_AT(tid == 0, 5 + rho * 2);
        PROF_AT(tid == 32, 43 + rho * 4);
      }
    }

    const int row0 = rb * 128 + cw * 64 + warp * 16 + r;
    {
      uint32_t xl[16], xh[16];
      const bf16* xp = p.x + (size_t)row0 * DM + j * 128 + 2 * c;
#pragma unroll
      for (int n = 0; n < 16; n++) {
        xl[n] = __ldg((const uint32_t*)(xp + 8 * n));
        xh[n] = __ldg((const uint32_t*)(xp + 8 * DM + 8 * n));
      }
      float acc[64];
      Ring g{a_base, b_base, bars + 8 * B_FW, rbars + 8 * B_EW, 0, 0u, releaser TR(32)};
      mainloop<128, 6, 32768>(acc, g, 0u, 16);
      PROF_AT(tid == 0, 8);
      mbar_wait(bars + 8 * B_MODB, 0);
      float sl = 0.f, sh = 0.f;
#pragma unroll
      for (int n = 0; n < 16; n++) {
        const float2 ga = lds64f(sm + MODB_OFF + (8 * n + 2 * c) * 4);
        xl[n] = pack2(bf_lo(xl[n]) + ga.x * acc[4 * n], bf_hi(xl[n]) + ga.y * acc[4 * n + 1]);
        xh[n] = pack2(bf_lo(xh[n]) + ga.x * acc[4 * n + 2], bf_hi(xh[n]) + ga.y * acc[4 * n + 3]);
        acc[4 * n] = bf_lo(xl[n]); acc[4 * n + 1] = bf_hi(xl[n]);
        acc[4 * n + 2] = bf_lo(xh[n]); acc[4 * n + 3] = bf_hi(xh[n]);
        sl += acc[4 * n] + acc[4 * n + 1];
        sh += acc[4 * n + 2] + acc[4 * n + 3];
      }
      sl += __shfl_xor_sync(~0u, sl, 1); sh += __shfl_xor_sync(~0u, sh, 1);
      sl += __shfl_xor_sync(~0u, sl, 2); sh += __shfl_xor_sync(~0u, sh, 2);
      const float ml = sl * (1.0f / 128), mh = sh * (1.0f / 128);
      float ql = 0.f, qh = 0.f;
#pragma unroll
      for (int n = 0; n < 16; n++) {
        const float d0 = acc[4 * n] - ml, d1 = acc[4 * n + 1] - ml, d2 = acc[4 * n + 2] - mh, d3 = acc[4 * n + 3] - mh;
        ql += d0 * d0 + d1 * d1;
        qh += d2 * d2 + d3 * d3;
      }
      ql += __shfl_xor_sync(~0u, ql, 1); qh += __shfl_xor_sync(~0u, qh, 1);
      ql += __shfl_xor_sync(~0u, ql, 2); qh += __shfl_xor_sync(~0u, qh, 2);
      if (c < 2) ll_store(st2, __float_as_uint(c ? mh : ml), __float_as_uint(c ? qh : ql), tag);
      __syncwarp();
      PROF_AT(tid == 0, 48);
      uint4* x1p = p.x1 + (size_t)cta * 2048 + tid;
#pragma unroll
      for (int q = 0; q < 4; q++) {
        x1p[q * 256] = make_uint4(xl[4 * q], xl[4 * q + 1], xl[4 * q + 2], xl[4 * q + 3]);
        x1p[(4 + q) * 256] = make_uint4(xh[4 * q], xh[4 * q + 1], xh[4 * q + 2], xh[4 * q + 3]);
      }
      mbar_wait(bars + 8 * B_STGE, 0);
      PROF_AT(tid == 0, 49);
      float mean[2], rstd[2];
      {
        uint32_t st[8];
        const uint4* sp = p.stats2 + (rb * 8 + (lane >> 4) * 4) * 128 + cw * 64 + warp * 16 + (lane & 15);
        ll_poll<4>([&](int i) { return sp + i * 128; }, tag, st);
        float mu, rs;
        row_stats(st, mu, rs);
        mean[0] = __shfl_sync(~0u, mu, r); rstd[0] = __shfl_sync(~0u, rs, r);
        mean[1] = __shfl_sync(~0u, mu, r + 8); rstd[1] = __shfl_sync(~0u, rs, r + 8);
      }
      PROF_AT(tid == 0, 9);
#pragma unroll
      for (int ch = 0; ch < 2; ch++) {
        uint32_t lo[8], hi[8];
#pragma unroll
        for (int t = 0; t < 8; t++) {
          const int n = ch * 8 + t;
          const float2 sb = lds64f(sm + MODB_OFF + (128 + 8 * n + 2 * c) * 4), cb = lds64f(sm + MODB_OFF + (256 + 8 * n + 2 * c) * 4);
          lo[t] = pack2((acc[4 * n] - mean[0]) * rstd[0] * cb.x + sb.x, (acc[4 * n + 1] - mean[0]) * rstd[0] * cb.y + sb.y);
          hi[t] = pack2((acc[4 * n + 2] - mean[1]) * rstd[1] * cb.x + sb.x, (acc[4 * n + 3] - mean[1]) * rstd[1] * cb.y + sb.y);
        }
        stage_slab(stg + ch * 16384 + cw * 8192, warp, lane, lo, hi);
        stage_done(bars + 8 * (B_STGF + ch), lane);
      }
      bar_sync(2 + cw, 128);
      PROF_AT(tid == 0, 10);
    }

    uint32_t pg[32], pu[32];
    const uint32_t sw0 = (lane >> 4) ^ (srow & 7);
    {
      Ring g{a_base, b_base, bars + 8 * B_FG, rbars + 8 * B_EG, 0, 0u, releaser TR(48)};
      float acc[128];
      mainloop<256, 4, 49152>(acc, g, a_own, 16);
      PROF_AT(tid == 0, 36);
#pragma unroll 1
      for (int t = 1; t < 3; t++) {
#pragma unroll
        for (int q = 0; q < 32; q++) {
          pg[q] = pack2(acc[2 * q], acc[2 * q + 1]);
          pu[q] = pack2(acc[64 + 2 * q], acc[64 + 2 * q + 1]);
        }
        int prev = 0;
#pragma unroll 1
        for (int blk = 0; blk < 4; blk++) {
          g.s = 0;
#pragma unroll
          for (int i = 0; i < 4; i++) {
            kblock<256, 4, 49152>(acc, g, a_base + i * 49152, blk == 0 && i == 0, prev);
            pg[2 * i] = swiglu2(pg[2 * i], pu[2 * i]);
            pg[2 * i + 1] = swiglu2(pg[2 * i + 1], pu[2 * i + 1]);
            if (i & 1) {
              if ((blk & 1) == 0 && i == 1) mbar_wait(bars + 8 * (B_STGE + (blk >> 1)), t & 1);
              stmatrix4(slab + (blk >> 1) * 16384 + ((sw0 ^ (((blk & 1) * 2 + (i >> 1)) * 2)) << 4), pg[2 * i - 2], pg[2 * i - 1], pg[2 * i], pg[2 * i + 1]);
            }
          }
#pragma unroll
          for (int q = 0; q < 24; q++) { pg[q] = pg[q + 8]; pu[q] = pu[q + 8]; }
          if (blk & 1) stage_done(bars + 8 * (B_STGF + (blk >> 1)), lane);
        }
        tile_end<256>(g, prev);
        PROF_AT(tid == 0, 36 + t);
      }
#pragma unroll
      for (int q = 0; q < 32; q++) {
        pg[q] = pack2(acc[2 * q], acc[2 * q + 1]);
        pu[q] = pack2(acc[64 + 2 * q], acc[64 + 2 * q + 1]);
      }
      PROF_AT(tid == 0, 11);
    }

    {
      Ring g{a_base, b_base, bars + 8 * B_FD, rbars + 8 * B_ED, 0, 0u, releaser TR(96)};
      float acc[64];
      int prev = 0;
#pragma unroll 1
      for (int blk = 0; blk < 6; blk++) {
#pragma unroll
        for (int i = 0; i < 8; i++) {
          kblock<128, 6, 32768>(acc, g, a_base + g.s * 32768, (blk & ~2) == 0 && i == 0, prev);
          pg[i] = swiglu2(pg[i], pu[i]);
          if ((i & 3) == 3) {
            if ((blk & 1) == 0 && i == 3) mbar_wait(bars + 8 * (B_STGE + ((blk >> 1) & 1)), blk < 4);
            stmatrix4(slab + ((blk >> 1) & 1) * 16384 + ((sw0 ^ (((blk & 1) * 2 + (i >> 2)) * 2)) << 4), pg[i - 3], pg[i - 2], pg[i - 1], pg[i]);
          }
        }
#pragma unroll
        for (int q = 0; q < 24; q++) { pg[q] = pg[q + 8]; pu[q] = pu[q + 8]; }
        if (blk & 1) stage_done(bars + 8 * (B_STGF + ((blk >> 1) & 1)), lane);
        if (blk == 1) {
          tile_end<128>(g, prev);
          PROF_AT(tid == 0, 39);
#pragma unroll
          for (int q = 0; q < 16; q++) {
            pg[16 + q] = pack2(acc[2 * q], acc[2 * q + 1]);
            pu[16 + q] = pack2(acc[32 + 2 * q], acc[32 + 2 * q + 1]);
          }
          PROF_AT(tid == 0, 12);
        }
      }
      uint4 x1[8];
      const uint4* x1p = p.x1 + (size_t)cta * 2048 + tid;
#pragma unroll
      for (int q = 0; q < 8; q++) {
        kblock<128, 6, 32768>(acc, g, a_base + g.s * 32768, false, prev);
        x1[q] = ll_peek(x1p + q * 256);
      }
#pragma unroll 1
      for (int kb = 56; kb < 72; kb++) kblock<128, 6, 32768>(acc, g, a_base + g.s * 32768, false, prev);
      tile_end<128>(g, prev);
      PROF_AT(tid == 0, 13);
      mbar_wait(bars + 8 * B_STGE, 1);
      mbar_wait(bars + 8 * (B_STGE + 1), 0);
#pragma unroll
      for (int ch = 0; ch < 2; ch++) {
        uint32_t lo[8], hi[8];
#pragma unroll
        for (int t = 0; t < 8; t++) {
          const int n = ch * 8 + t;
          const float2 gb = lds64f(sm + MODB_OFF + (384 + 8 * n + 2 * c) * 4);
          const uint4 a = x1[n >> 2], b = x1[4 + (n >> 2)];
          const uint32_t xl = (n & 3) == 0 ? a.x : (n & 3) == 1 ? a.y : (n & 3) == 2 ? a.z : a.w;
          const uint32_t xh = (n & 3) == 0 ? b.x : (n & 3) == 1 ? b.y : (n & 3) == 2 ? b.z : b.w;
          lo[t] = pack2(bf_lo(xl) + gb.x * acc[4 * n], bf_hi(xl) + gb.y * acc[4 * n + 1]);
          hi[t] = pack2(bf_lo(xh) + gb.x * acc[4 * n + 2], bf_hi(xh) + gb.y * acc[4 * n + 3]);
        }
        stage_slab(stg + ch * 16384 + cw * 8192, warp, lane, lo, hi);
        stage_done(bars + 8 * (B_STGF + ch), lane);
      }
      PROF_AT(tid == 0, 14);
    }
    if (blockIdx.x == 0 && tid == 0) asm volatile("st.relaxed.gpu.global.u32 [%0], %1;" ::"l"(p.epoch), "r"(tag) : "memory");
    __syncwarp();
    cluster_arrive_relaxed();
    cluster_wait();
  }
}

typedef CUresult (*EncodeFn)(CUtensorMap*, CUtensorMapDataType, cuuint32_t, void*, const cuuint64_t*, const cuuint64_t*,
                             const cuuint32_t*, const cuuint32_t*, CUtensorMapInterleave, CUtensorMapSwizzle,
                             CUtensorMapL2promotion, CUtensorMapFloatOOBfill);

void encode2d(EncodeFn fn, CUtensorMap* m, const void* ptr, uint64_t cols, uint64_t rows, uint32_t box_rows) {
  cuuint64_t dims[2] = {cols, rows};
  cuuint64_t strides[1] = {cols * 2};
  cuuint32_t box[2] = {64, box_rows};
  cuuint32_t es[2] = {1, 1};
  fn(m, CU_TENSOR_MAP_DATA_TYPE_BFLOAT16, 2, (void*)ptr, dims, strides, box, es, CU_TENSOR_MAP_INTERLEAVE_NONE,
     CU_TENSOR_MAP_SWIZZLE_128B, CU_TENSOR_MAP_L2_PROMOTION_L2_128B, CU_TENSOR_MAP_FLOAT_OOB_FILL_NONE);
}

}

extern "C" void kernel_launch(void* const* d_in, const int* in_sizes, int n_in, void* d_out, int out_size) {
  (void)in_sizes; (void)n_in; (void)out_size;
  void* fp = nullptr;
  cudaDriverEntryPointQueryResult qr;
  cudaGetDriverEntryPoint("cuTensorMapEncodeTiled", &fp, cudaEnableDefault, &qr);
  EncodeFn fn = (EncodeFn)fp;
  void *ph, *po, *ph2, *pact;
  cudaGetSymbolAddress(&ph, g_h);
  cudaGetSymbolAddress(&po, g_o);
  cudaGetSymbolAddress(&ph2, g_h2);
  cudaGetSymbolAddress(&pact, g_act);
  Params p;
  encode2d(fn, &p.h, ph, DM, SEQ, 128);
  encode2d(fn, &p.o_ld, po, DM, SEQ, 128);
  encode2d(fn, &p.h2, ph2, DM, SEQ, 128);
  encode2d(fn, &p.act, pact, FF, SEQ, 128);
  encode2d(fn, &p.act_st, pact, FF, SEQ, 32);
  encode2d(fn, &p.out, d_out, DM, SEQ, 128);
  encode2d(fn, &p.wqkv, d_in[1], 3 * DM, DM, 64);
  encode2d(fn, &p.wqkv32, d_in[1], 3 * DM, DM, 32);
  encode2d(fn, &p.wo, d_in[2], DM, DM, 64);
  encode2d(fn, &p.wg, d_in[4], FF, DM, 64);
  encode2d(fn, &p.wu, d_in[5], FF, DM, 64);
  encode2d(fn, &p.wd, d_in[6], DM, FF, 64);
  {
    cuuint64_t dims[3] = {DM, SEQ / 2, 2};
    cuuint64_t strides[2] = {DM * 4, DM * 2};
    cuuint32_t box[3] = {64, 32, 1};
    cuuint32_t es[3] = {1, 1, 1};
    fn(&p.o_st, CU_TENSOR_MAP_DATA_TYPE_BFLOAT16, 3, po, dims, strides, box, es, CU_TENSOR_MAP_INTERLEAVE_NONE,
       CU_TENSOR_MAP_SWIZZLE_128B, CU_TENSOR_MAP_L2_PROMOTION_L2_128B, CU_TENSOR_MAP_FLOAT_OOB_FILL_NONE);
  }
  p.x = (const bf16*)d_in[0];
  p.c = (const bf16*)d_in[7];
  p.wmod = (const bf16*)d_in[8];
  void* q;
  cudaGetSymbolAddress(&q, g_x1); p.x1 = (uint4*)q;
  cudaGetSymbolAddress(&q, g_modll); p.modll = (uint4*)q;
  cudaGetSymbolAddress(&q, g_halo); p.halo = (uint4*)q;
  cudaGetSymbolAddress(&q, g_stats); p.stats1 = (uint4*)q; p.stats2 = p.stats1 + SEQ * 8;
  cudaGetSymbolAddress(&q, g_cnt); p.cnt = (unsigned*)q;
  cudaGetSymbolAddress(&q, g_epoch); p.epoch = (unsigned*)q;

  cudaFuncSetAttribute(fused_kernel, cudaFuncAttributeMaxDynamicSharedMemorySize, SMEM_BYTES);
  cudaLaunchConfig_t cfg = {};
  cfg.gridDim = dim3(NCTA);
  cfg.blockDim = dim3(384);
  cfg.dynamicSmemBytes = SMEM_BYTES;
  cfg.stream = cudaStreamPerThread;
  cudaLaunchAttribute at[1];
  at[0].id = cudaLaunchAttributeClusterDimension;
  at[0].val.clusterDim.x = 2; at[0].val.clusterDim.y = 1; at[0].val.clusterDim.z = 1;
  cfg.attrs = at;
  cfg.numAttrs = 1;
  cudaLaunchKernelEx(&cfg, fused_kernel, p);
}
```

```cpp
#include <cuda_runtime.h>
#include <cuda_bf16.h>
#include <cuda.h>
#include <stdint.h>

typedef __nv_bfloat16 bf16;

#define MAPPING 2

#define ALIGN 0

#define PF 0

#define EF 1

#define ALIGNE 3

#define CW 1

#define PAUSE 200

#define WMD 2

#define WMDELAY 2000

#define WMPACE 0

#define NPRE0 4

#define NPRE1 2
#define GATE 0

#define WFIRST 1

#define BDELAY 0

#define ALIAS 1

__device__ __forceinline__ void wgmma_ss_n128(float (&d)[64], uint32_t da, uint32_t db, int scale_d) {
  asm volatile("{\n.reg .pred p;\n.reg .b64 da, db;\nsetp.ne.b32 p, %66, 0;\n"
    "mov.b64 da, {%64, 0x40000040};\nmov.b64 db, {%65, 0x40000040};\n"
    "wgmma.mma_async.sync.aligned.m64n128k16.f32.bf16.bf16 "
    "{%0, %1, %2, %3, %4, %5, %6, %7, %8, %9, %10, %11, %12, %13, %14, %15, "
    "%16, %17, %18, %19, %20, %21, %22, %23, %24, %25, %26, %27, %28, %29, %30, %31, "
    "%32, %33, %34, %35, %36, %37, %38, %39, %40, %41, %42, %43, %44, %45, %46, %47, "
    "%48, %49, %50, %51, %52, %53, %54, %55, %56, %57, %58, %59, %60, %61, %62, %63}, "
    "da, db, p, 1, 1, 0, 1;\n}\n"
    : "+f"(d[0]), "+f"(d[1]), "+f"(d[2]), "+f"(d[3]), "+f"(d[4]), "+f"(d[5]), "+f"(d[6]), "+f"(d[7]),
      "+f"(d[8]), "+f"(d[9]), "+f"(d[10]), "+f"(d[11]), "+f"(d[12]), "+f"(d[13]), "+f"(d[14]), "+f"(d[15]),
      "+f"(d[16]), "+f"(d[17]), "+f"(d[18]), "+f"(d[19]), "+f"(d[20]), "+f"(d[21]), "+f"(d[22]), "+f"(d[23]),
      "+f"(d[24]), "+f"(d[25]), "+f"(d[26]), "+f"(d[27]), "+f"(d[28]), "+f"(d[29]), "+f"(d[30]), "+f"(d[31]),
      "+f"(d[32]), "+f"(d[33]), "+f"(d[34]), "+f"(d[35]), "+f"(d[36]), "+f"(d[37]), "+f"(d[38]), "+f"(d[39]),
      "+f"(d[40]), "+f"(d[41]), "+f"(d[42]), "+f"(d[43]), "+f"(d[44]), "+f"(d[45]), "+f"(d[46]), "+f"(d[47]),
      "+f"(d[48]), "+f"(d[49]), "+f"(d[50]), "+f"(d[51]), "+f"(d[52]), "+f"(d[53]), "+f"(d[54]), "+f"(d[55]),
      "+f"(d[56]), "+f"(d[57]), "+f"(d[58]), "+f"(d[59]), "+f"(d[60]), "+f"(d[61]), "+f"(d[62]), "+f"(d[63])
    : "r"(da), "r"(db), "r"(scale_d));
}

__device__ __forceinline__ void wgmma_ss_n192(float (&d)[96], uint32_t da, uint32_t db, int scale_d) {
  asm volatile("{\n.reg .pred p;\n.reg .b64 da, db;\nsetp.ne.b32 p, %98, 0;\n"
    "mov.b64 da, {%96, 0x40000040};\nmov.b64 db, {%97, 0x40000040};\n"
    "wgmma.mma_async.sync.aligned.m64n192k16.f32.bf16.bf16 "
    "{%0, %1, %2, %3, %4, %5, %6, %7, %8, %9, %10, %11, %12, %13, %14, %15, "
    "%16, %17, %18, %19, %20, %21, %22, %23, %24, %25, %26, %27, %28, %29, %30, %31, "
    "%32, %33, %34, %35, %36, %37, %38, %39, %40, %41, %42, %43, %44, %45, %46, %47, "
    "%48, %49, %50, %51, %52, %53, %54, %55, %56, %57, %58, %59, %60, %61, %62, %63, "
    "%64, %65, %66, %67, %68, %69, %70, %71, %72, %73, %74, %75, %76, %77, %78, %79, "
    "%80, %81, %82, %83, %84, %85, %86, %87, %88, %89, %90, %91, %92, %93, %94, %95}, "
    "da, db, p, 1, 1, 0, 1;\n}\n"
    : "+f"(d[0]), "+f"(d[1]), "+f"(d[2]), "+f"(d[3]), "+f"(d[4]), "+f"(d[5]), "+f"(d[6]), "+f"(d[7]),
      "+f"(d[8]), "+f"(d[9]), "+f"(d[10]), "+f"(d[11]), "+f"(d[12]), "+f"(d[13]), "+f"(d[14]), "+f"(d[15]),
      "+f"(d[16]), "+f"(d[17]), "+f"(d[18]), "+f"(d[19]), "+f"(d[20]), "+f"(d[21]), "+f"(d[22]), "+f"(d[23]),
      "+f"(d[24]), "+f"(d[25]), "+f"(d[26]), "+f"(d[27]), "+f"(d[28]), "+f"(d[29]), "+f"(d[30]), "+f"(d[31]),
      "+f"(d[32]), "+f"(d[33]), "+f"(d[34]), "+f"(d[35]), "+f"(d[36]), "+f"(d[37]), "+f"(d[38]), "+f"(d[39]),
      "+f"(d[40]), "+f"(d[41]), "+f"(d[42]), "+f"(d[43]), "+f"(d[44]), "+f"(d[45]), "+f"(d[46]), "+f"(d[47]),
      "+f"(d[48]), "+f"(d[49]), "+f"(d[50]), "+f"(d[51]), "+f"(d[52]), "+f"(d[53]), "+f"(d[54]), "+f"(d[55]),
      "+f"(d[56]), "+f"(d[57]), "+f"(d[58]), "+f"(d[59]), "+f"(d[60]), "+f"(d[61]), "+f"(d[62]), "+f"(d[63]),
      "+f"(d[64]), "+f"(d[65]), "+f"(d[66]), "+f"(d[67]), "+f"(d[68]), "+f"(d[69]), "+f"(d[70]), "+f"(d[71]),
      "+f"(d[72]), "+f"(d[73]), "+f"(d[74]), "+f"(d[75]), "+f"(d[76]), "+f"(d[77]), "+f"(d[78]), "+f"(d[79]),
      "+f"(d[80]), "+f"(d[81]), "+f"(d[82]), "+f"(d[83]), "+f"(d[84]), "+f"(d[85]), "+f"(d[86]), "+f"(d[87]),
      "+f"(d[88]), "+f"(d[89]), "+f"(d[90]), "+f"(d[91]), "+f"(d[92]), "+f"(d[93]), "+f"(d[94]), "+f"(d[95])
    : "r"(da), "r"(db), "r"(scale_d));
}

__device__ __forceinline__ void wgmma_ss_n256(float (&d)[128], uint32_t da, uint32_t db, int scale_d) {
  asm volatile("{\n.reg .pred p;\n.reg .b64 da, db;\nsetp.ne.b32 p, %130, 0;\n"
    "mov.b64 da, {%128, 0x40000040};\nmov.b64 db, {%129, 0x40000040};\n"
    "wgmma.mma_async.sync.aligned.m64n256k16.f32.bf16.bf16 "
    "{%0, %1, %2, %3, %4, %5, %6, %7, %8, %9, %10, %11, %12, %13, %14, %15, "
    "%16, %17, %18, %19, %20, %21, %22, %23, %24, %25, %26, %27, %28, %29, %30, %31, "
    "%32, %33, %34, %35, %36, %37, %38, %39, %40, %41, %42, %43, %44, %45, %46, %47, "
    "%48, %49, %50, %51, %52, %53, %54, %55, %56, %57, %58, %59, %60, %61, %62, %63, "
    "%64, %65, %66, %67, %68, %69, %70, %71, %72, %73, %74, %75, %76, %77, %78, %79, "
    "%80, %81, %82, %83, %84, %85, %86, %87, %88, %89, %90, %91, %92, %93, %94, %95, "
    "%96, %97, %98, %99, %100, %101, %102, %103, %104, %105, %106, %107, %108, %109, %110, %111, "
    "%112, %113, %114, %115, %116, %117, %118, %119, %120, %121, %122, %123, %124, %125, %126, %127}, "
    "da, db, p, 1, 1, 0, 1;\n}\n"
    : "+f"(d[0]), "+f"(d[1]), "+f"(d[2]), "+f"(d[3]), "+f"(d[4]), "+f"(d[5]), "+f"(d[6]), "+f"(d[7]),
      "+f"(d[8]), "+f"(d[9]), "+f"(d[10]), "+f"(d[11]), "+f"(d[12]), "+f"(d[13]), "+f"(d[14]), "+f"(d[15]),
      "+f"(d[16]), "+f"(d[17]), "+f"(d[18]), "+f"(d[19]), "+f"(d[20]), "+f"(d[21]), "+f"(d[22]), "+f"(d[23]),
      "+f"(d[24]), "+f"(d[25]), "+f"(d[26]), "+f"(d[27]), "+f"(d[28]), "+f"(d[29]), "+f"(d[30]), "+f"(d[31]),
      "+f"(d[32]), "+f"(d[33]), "+f"(d[34]), "+f"(d[35]), "+f"(d[36]), "+f"(d[37]), "+f"(d[38]), "+f"(d[39]),
      "+f"(d[40]), "+f"(d[41]), "+f"(d[42]), "+f"(d[43]), "+f"(d[44]), "+f"(d[45]), "+f"(d[46]), "+f"(d[47]),
      "+f"(d[48]), "+f"(d[49]), "+f"(d[50]), "+f"(d[51]), "+f"(d[52]), "+f"(d[53]), "+f"(d[54]), "+f"(d[55]),
      "+f"(d[56]), "+f"(d[57]), "+f"(d[58]), "+f"(d[59]), "+f"(d[60]), "+f"(d[61]), "+f"(d[62]), "+f"(d[63]),
      "+f"(d[64]), "+f"(d[65]), "+f"(d[66]), "+f"(d[67]), "+f"(d[68]), "+f"(d[69]), "+f"(d[70]), "+f"(d[71]),
      "+f"(d[72]), "+f"(d[73]), "+f"(d[74]), "+f"(d[75]), "+f"(d[76]), "+f"(d[77]), "+f"(d[78]), "+f"(d[79]),
      "+f"(d[80]), "+f"(d[81]), "+f"(d[82]), "+f"(d[83]), "+f"(d[84]), "+f"(d[85]), "+f"(d[86]), "+f"(d[87]),
      "+f"(d[88]), "+f"(d[89]), "+f"(d[90]), "+f"(d[91]), "+f"(d[92]), "+f"(d[93]), "+f"(d[94]), "+f"(d[95]),
      "+f"(d[96]), "+f"(d[97]), "+f"(d[98]), "+f"(d[99]), "+f"(d[100]), "+f"(d[101]), "+f"(d[102]), "+f"(d[103]),
      "+f"(d[104]), "+f"(d[105]), "+f"(d[106]), "+f"(d[107]), "+f"(d[108]), "+f"(d[109]), "+f"(d[110]), "+f"(d[111]),
      "+f"(d[112]), "+f"(d[113]), "+f"(d[114]), "+f"(d[115]), "+f"(d[116]), "+f"(d[117]), "+f"(d[118]), "+f"(d[119]),
      "+f"(d[120]), "+f"(d[121]), "+f"(d[122]), "+f"(d[123]), "+f"(d[124]), "+f"(d[125]), "+f"(d[126]), "+f"(d[127])
    : "r"(da), "r"(db), "r"(scale_d));
}

namespace {

constexpr int SEQ = 2048, DM = 1024, FF = 3584;
constexpr int NCTA = 128;

constexpr uint32_t STG_OFF = 196608;
constexpr uint32_t MISC_OFF = STG_OFF + 32768;
constexpr uint32_t SMEM_BYTES = MISC_OFF + 3072;
constexpr uint32_t RED_OFF = 2 * 49152;
constexpr uint32_t MODB_OFF = MISC_OFF + 512;

enum { B_FQ = 0, B_EQ = 4, B_FW = 8, B_EW = 14, B_FG = 20, B_EG = 24, B_FD = 28, B_ED = 34,
       B_STGF = 40, B_MODB = 42, B_GATE = 44, B_RDY = 48, B_STGE = 56, B_COUNT = 58 };
enum { C_H = 0, C_O = 1, C_H2 = 3, C_ACT = 4, C_AL = 8 };

struct Params {
  CUtensorMap h, o_ld, o_st, h2, act, out, wqkv, wqkv32, wo, wg, wu, wd, act_st, wm;
  const bf16* x;
  const bf16* c;
  const bf16* wmod;
  uint4* x1;
  uint4* modll;
  uint4* halo;
  uint4* stats1;
  uint4* stats2;
  unsigned* cnt;
  unsigned* epoch;
  uint8_t slot[64];
};

__device__ bf16 g_h[SEQ * DM];
__device__ bf16 g_o[SEQ * DM];
__device__ bf16 g_h2[SEQ * DM];
__device__ bf16 g_act[SEQ * FF];
__device__ uint4 g_x1[NCTA * 8 * 256];
__device__ uint4 g_modll[3072 / 2];
__device__ uint4 g_halo[16 * 8 * 2 * 2 * 8 * 32];
__device__ uint4 g_stats[2 * SEQ * 8];
__device__ unsigned g_cnt[16 * 32];
__device__ unsigned g_epoch;
#define TR(off)

__device__ __forceinline__ uint32_t smem_u32(const void* p) { return (uint32_t)__cvta_generic_to_shared(p); }
__device__ __forceinline__ void mbar_init(uint32_t bar, uint32_t count) {
  asm volatile("mbarrier.init.shared::cta.b64 [%0], %1;" ::"r"(bar), "r"(count));
}
__device__ __forceinline__ void mbar_expect_tx(uint32_t bar, uint32_t bytes) {
  asm volatile("mbarrier.arrive.expect_tx.shared::cta.b64 _, [%0], %1;" ::"r"(bar), "r"(bytes) : "memory");
}
__device__ __forceinline__ void mbar_arrive(uint32_t bar) {
  asm volatile("mbarrier.arrive.shared::cta.b64 _, [%0];" ::"r"(bar) : "memory");
}
__device__ __forceinline__ void mbar_arrive_cluster(uint32_t cluster_addr) {
  asm volatile("mbarrier.arrive.shared::cluster.b64 _, [%0];" ::"r"(cluster_addr) : "memory");
}
__device__ __forceinline__ uint32_t mapa(uint32_t addr, uint32_t cta) {
  uint32_t r;
  asm volatile("mapa.shared::cluster.u32 %0, %1, %2;" : "=r"(r) : "r"(addr), "r"(cta));
  return r;
}
__device__ __forceinline__ void mbar_wait(uint32_t bar, uint32_t parity) {
  asm volatile(
      "{\n.reg .pred p;\n"
      "WAIT_%=:\n"
      "mbarrier.try_wait.parity.shared::cta.b64 p, [%0], %1;\n"
      "@!p bra WAIT_%=;\n}\n" ::"r"(bar), "r"(parity) : "memory");
}
__device__ __forceinline__ void mbar_wait_watchdog(uint32_t bar, uint32_t parity) {
  asm volatile(
      "{\n.reg .pred p;\n.reg .u64 t0, t1;\nmov.u64 t0, %%globaltimer;\n"
      "WAIT_%=:\n"
      "mbarrier.try_wait.parity.shared::cta.b64 p, [%0], %1;\n"
      "@p bra DONE_%=;\n"
      "mov.u64 t1, %%globaltimer;\n"
      "sub.u64 t1, t1, t0;\n"
      "setp.lt.u64 p, t1, 2000000000;\n"
      "@p bra WAIT_%=;\n"
      "trap;\n"
      "DONE_%=:\n}\n" ::"r"(bar), "r"(parity) : "memory");
}
__device__ __forceinline__ void cnt_wait(const unsigned* p, unsigned target) {
  asm volatile(
      "{\n.reg .pred p;\n.reg .u32 v;\n.reg .s32 d;\n"
      "WAIT_%=:\n"
      "ld.relaxed.gpu.global.u32 v, [%0];\n"
      "sub.s32 d, v, %1;\n"
      "setp.lt.s32 p, d, 0;\n"
      "@p bra WAIT_%=;\n"
      "fence.proxy.async.global;\n"
      "}\n" ::"l"(p), "r"(target) : "memory");
}
__device__ __forceinline__ void cnt_wait_lazy(const unsigned* p, unsigned target) {
  asm volatile(
      "{\n.reg .pred p;\n.reg .u32 v;\n.reg .s32 d;\n"
      "WAIT_%=:\n"
      "nanosleep.u32 400;\n"
      "ld.relaxed.gpu.global.u32 v, [%0];\n"
      "sub.s32 d, v, %1;\n"
      "setp.lt.s32 p, d, 0;\n"
      "@p bra WAIT_%=;\n"
      "fence.proxy.async.global;\n"
      "}\n" ::"l"(p), "r"(target) : "memory");
}
__device__ __forceinline__ void cnt_signal(unsigned* p) {
  asm volatile("{\n.reg .pred p;\nelect.sync _|p, 0xffffffff;\n@p red.relaxed.gpu.global.add.u32 [%0], 1;\n}\n" ::"l"(p) : "memory");
}
__device__ __forceinline__ void ll_store(uint4* p, uint32_t a, uint32_t b, uint32_t tag) {
  asm volatile("st.relaxed.gpu.global.v2.b64 [%0], {%1, %2};" ::"l"(p), "l"((uint64_t)a | ((uint64_t)tag << 32)),
               "l"((uint64_t)b | ((uint64_t)tag << 32)) : "memory");
}
__device__ __forceinline__ uint4 ll_peek(const uint4* p) {
  uint4 v;
  asm volatile("ld.relaxed.gpu.global.v4.u32 {%0, %1, %2, %3}, [%4];" : "=r"(v.x), "=r"(v.y), "=r"(v.z), "=r"(v.w) : "l"(p) : "memory");
  return v;
}
template <int N, class F>
__device__ __forceinline__ void ll_poll(F addr, uint32_t tag, uint32_t (&out)[2 * N]) {
  for (;;) {
    uint4 v[N];
#pragma unroll
    for (int i = 0; i < N; i++) v[i] = ll_peek(addr(i));
    uint32_t bad = 0;
#pragma unroll
    for (int i = 0; i < N; i++) {
      bad |= (v[i].y ^ tag) | (v[i].w ^ tag);
      out[2 * i] = v[i].x;
      out[2 * i + 1] = v[i].z;
    }
    if (__all_sync(~0u, bad == 0)) break;
  }
}
constexpr uint64_t POLICY_EVICT_FIRST = 0x12F0000000000000ull;
__device__ __forceinline__ void expect_tx_elect(uint32_t bar, uint32_t bytes) {
  asm volatile("{\n.reg .pred p;\nelect.sync _|p, 0xffffffff;\n@p mbarrier.arrive.expect_tx.shared::cta.b64 _, [%0], %1;\n}\n" ::"r"(bar), "r"(bytes) : "memory");
}
__device__ __forceinline__ void arrive_elect(uint32_t bar) {
  asm volatile("{\n.reg .pred p;\nelect.sync _|p, 0xffffffff;\n@p mbarrier.arrive.shared::cta.b64 _, [%0];\n}\n" ::"r"(bar) : "memory");
}
__device__ __forceinline__ void tma_load(uint32_t dst, const CUtensorMap* m, uint32_t bar, int c0, int c1) {
  asm volatile("{\n.reg .pred p;\nelect.sync _|p, 0xffffffff;\n"
               "@p cp.async.bulk.tensor.2d.shared::cluster.global.mbarrier::complete_tx::bytes [%0], [%1, {%3, %4}], [%2];\n}\n"
               ::"r"(dst), "l"(m), "r"(bar), "r"(c0), "r"(c1) : "memory");
}
__device__ __forceinline__ void tma_load_mc(uint32_t dst, const CUtensorMap* m, uint32_t bar, int c0, int c1) {
  asm volatile("{\n.reg .pred p;\nelect.sync _|p, 0xffffffff;\n"
               "@p cp.async.bulk.tensor.2d.shared::cluster.global.mbarrier::complete_tx::bytes.multicast::cluster.L2::cache_hint [%0], [%1, {%3, %4}], [%2], %5, %6;\n}\n"
               ::"r"(dst), "l"(m), "r"(bar), "r"(c0), "r"(c1), "h"((uint16_t)3), "l"(POLICY_EVICT_FIRST) : "memory");
}
__device__ __forceinline__ void tma_load_ef(uint32_t dst, const CUtensorMap* m, uint32_t bar, int c0, int c1) {
  asm volatile("{\n.reg .pred p;\nelect.sync _|p, 0xffffffff;\n"
               "@p cp.async.bulk.tensor.2d.shared::cluster.global.mbarrier::complete_tx::bytes.L2::cache_hint [%0], [%1, {%3, %4}], [%2], %5;\n}\n"
               ::"r"(dst), "l"(m), "r"(bar), "r"(c0), "r"(c1), "l"(POLICY_EVICT_FIRST) : "memory");
}
__device__ __forceinline__ void tma_store2(const CUtensorMap* m, uint32_t src, int c0, int c1) {
  asm volatile("{\n.reg .pred p;\nelect.sync _|p, 0xffffffff;\n"
               "@p cp.async.bulk.tensor.2d.global.shared::cta.bulk_group [%0, {%2, %3}], [%1];\n}\n"
               ::"l"(m), "r"(src), "r"(c0), "r"(c1) : "memory");
}
__device__ __forceinline__ void tma_store3(const CUtensorMap* m, uint32_t src, int c0, int c1, int c2) {
  asm volatile("{\n.reg .pred p;\nelect.sync _|p, 0xffffffff;\n"
               "@p cp.async.bulk.tensor.3d.global.shared::cta.bulk_group [%0, {%2, %3, %4}], [%1];\n}\n"
               ::"l"(m), "r"(src), "r"(c0), "r"(c1), "r"(c2) : "memory");
}
__device__ __forceinline__ void store_pause(bool sleep) {
  asm volatile("cp.async.bulk.commit_group;" ::: "memory");
  asm volatile("cp.async.bulk.wait_group.read 0;" ::: "memory");
  if (sleep) __nanosleep(PAUSE);
}
__device__ __forceinline__ void l2_prefetch_tile(const CUtensorMap* m, int c0, int c1) {
  asm volatile("{\n.reg .pred p;\nelect.sync _|p, 0xffffffff;\n@p cp.async.bulk.prefetch.tensor.2d.L2.global.L2::cache_hint [%0, {%1, %2}], %3;\n}\n"
               ::"l"(m), "r"(c0), "r"(c1), "l"(POLICY_EVICT_FIRST) : "memory");
}
__device__ __forceinline__ void prefetch_map(const CUtensorMap* m) {
  asm volatile("prefetch.tensormap [%0];" ::"l"(m) : "memory");
}
__device__ __forceinline__ void wg_fence() { asm volatile("wgmma.fence.sync.aligned;" ::: "memory"); }
__device__ __forceinline__ void wg_commit() { asm volatile("wgmma.commit_group.sync.aligned;" ::: "memory"); }
template <int N>
__device__ __forceinline__ void wg_wait() { asm volatile("wgmma.wait_group.sync.aligned %0;" ::"n"(N) : "memory"); }
__device__ __forceinline__ void bar_sync(int id, int n) { asm volatile("bar.sync %0, %1;" ::"r"(id), "r"(n) : "memory"); }
__device__ __forceinline__ void wg_bar(int cw) {
  asm volatile("{\n.reg .pred p;\nsetp.ne.s32 p, %0, 0;\n@p bar.sync 3, 128;\n@!p bar.sync 2, 128;\n}\n" ::"r"(cw) : "memory");
}
__device__ __forceinline__ void cluster_arrive() { asm volatile("barrier.cluster.arrive.release.aligned;" ::: "memory"); }
__device__ __forceinline__ void cluster_arrive_relaxed() { asm volatile("barrier.cluster.arrive.relaxed.aligned;" ::: "memory"); }
__device__ __forceinline__ void cluster_wait() { asm volatile("barrier.cluster.wait.acquire.aligned;" ::: "memory"); }
__device__ __forceinline__ uint32_t load_epoch(const unsigned* p) {
  uint32_t e;
  asm volatile("ld.relaxed.gpu.global.u32 %0, [%1];" : "=r"(e) : "l"(p) : "memory");
  return e;
}
__device__ __forceinline__ uint32_t pack2(float lo, float hi) {
  uint32_t r;
  asm("cvt.rn.bf16x2.f32 %0, %1, %2;" : "=r"(r) : "f"(hi), "f"(lo));
  return r;
}
__device__ __forceinline__ float bf_lo(uint32_t v) { return __uint_as_float(v << 16); }
__device__ __forceinline__ float bf_hi(uint32_t v) { return __uint_as_float(v & 0xffff0000u); }
__device__ __forceinline__ float bf_round(float v) { return __bfloat162float(__float2bfloat16_rn(v)); }
__device__ __forceinline__ float silu_f(float v) { return __fdividef(v, 1.0f + __expf(-v)); }
__device__ __forceinline__ uint4 ldg_nc(const void* p) {
  uint4 v;
  asm volatile("ld.global.nc.L1::no_allocate.v4.u32 {%0, %1, %2, %3}, [%4];" : "=r"(v.x), "=r"(v.y), "=r"(v.z), "=r"(v.w) : "l"(p));
  return v;
}
__device__ __forceinline__ uint4 ldg_stream(const void* p) {
  uint4 v;
  asm volatile("ld.global.nc.L1::no_allocate.L2::cache_hint.v4.u32 {%0, %1, %2, %3}, [%4], %5;" : "=r"(v.x), "=r"(v.y), "=r"(v.z), "=r"(v.w) : "l"(p), "l"(POLICY_EVICT_FIRST));
  return v;
}
__device__ __forceinline__ uint32_t ldg32(const void* p) {
  uint32_t v;
  asm volatile("ld.global.nc.u32 %0, [%1];" : "=r"(v) : "l"(p));
  return v;
}
__device__ __forceinline__ void stmatrix4(uint32_t addr, uint32_t a, uint32_t b, uint32_t c, uint32_t d) {
  asm volatile("stmatrix.sync.aligned.m8n8.x4.shared.b16 [%0], {%1, %2, %3, %4};" ::"r"(addr), "r"(a), "r"(b), "r"(c), "r"(d) : "memory");
}
__device__ __forceinline__ void stmatrix2(uint32_t addr, uint32_t a, uint32_t b) {
  asm volatile("stmatrix.sync.aligned.m8n8.x2.shared.b16 [%0], {%1, %2};" ::"r"(addr), "r"(a), "r"(b) : "memory");
}
__device__ __forceinline__ void stmatrix1(uint32_t addr, uint32_t a) {
  asm volatile("stmatrix.sync.aligned.m8n8.x1.shared.b16 [%0], {%1};" ::"r"(addr), "r"(a) : "memory");
}
__device__ __forceinline__ uint32_t movmatrix(uint32_t a) {
  uint32_t d;
  asm("movmatrix.sync.aligned.m8n8.trans.b16 %0, %1;" : "=r"(d) : "r"(a));
  return d;
}
__device__ __forceinline__ void mma16816(float (&d)[4], uint32_t a0, uint32_t a1, uint32_t a2, uint32_t a3, uint32_t b0, uint32_t b1) {
  asm("mma.sync.aligned.m16n8k16.row.col.f32.bf16.bf16.f32 {%0, %1, %2, %3}, {%4, %5, %6, %7}, {%8, %9}, {%0, %1, %2, %3};"
               : "+f"(d[0]), "+f"(d[1]), "+f"(d[2]), "+f"(d[3]) : "r"(a0), "r"(a1), "r"(a2), "r"(a3), "r"(b0), "r"(b1));
}
__device__ __forceinline__ void mma1688(float (&d)[4], uint32_t a0, uint32_t a1, uint32_t b0) {
  asm("mma.sync.aligned.m16n8k8.row.col.f32.bf16.bf16.f32 {%0, %1, %2, %3}, {%4, %5}, {%6}, {%0, %1, %2, %3};"
               : "+f"(d[0]), "+f"(d[1]), "+f"(d[2]), "+f"(d[3]) : "r"(a0), "r"(a1), "r"(b0));
}
__device__ __forceinline__ void ldmatrix4t(uint32_t (&b)[4], uint32_t addr) {
  asm volatile("ldmatrix.sync.aligned.m8n8.x4.trans.shared.b16 {%0, %1, %2, %3}, [%4];" : "=r"(b[0]), "=r"(b[1]), "=r"(b[2]), "=r"(b[3]) : "r"(addr) : "memory");
}
__device__ __forceinline__ void ldmatrix4(uint32_t& a, uint32_t& b, uint32_t& c, uint32_t& d, uint32_t addr) {
  asm volatile("ldmatrix.sync.aligned.m8n8.x4.shared.b16 {%0, %1, %2, %3}, [%4];" : "=r"(a), "=r"(b), "=r"(c), "=r"(d) : "r"(addr) : "memory");
}
__device__ __forceinline__ void cp_async16(uint32_t dst, const void* src) {
  asm volatile("cp.async.cg.shared.global.L2::cache_hint [%0], [%1], 16, %2;" ::"r"(dst), "l"(src), "l"(POLICY_EVICT_FIRST) : "memory");
}
__device__ __forceinline__ uint32_t lds32(uint32_t addr) {
  uint32_t v;
  asm volatile("ld.shared.u32 %0, [%1];" : "=r"(v) : "r"(addr) : "memory");
  return v;
}
__device__ __forceinline__ void sts64f(uint32_t addr, float a, float b) {
  asm volatile("st.shared.v2.f32 [%0], {%1, %2};" ::"r"(addr), "f"(a), "f"(b) : "memory");
}
constexpr float QK_SCALE = 0.17677669529663687f;
__device__ __forceinline__ void softmax8(float& p0, float& p1) {
  float m = fmaxf(p0, p1);
  m = fmaxf(m, __shfl_xor_sync(~0u, m, 1));
  m = fmaxf(m, __shfl_xor_sync(~0u, m, 2));
  asm("ex2.approx.ftz.f32 %0, %1;" : "=f"(p0) : "f"((p0 - m) * 1.4426950408889634f));
  asm("ex2.approx.ftz.f32 %0, %1;" : "=f"(p1) : "f"((p1 - m) * 1.4426950408889634f));
  float s = p0 + p1;
  s += __shfl_xor_sync(~0u, s, 1);
  s += __shfl_xor_sync(~0u, s, 2);
  float r;
  asm("rcp.approx.ftz.f32 %0, %1;" : "=f"(r) : "f"(s));
  p0 *= r;
  p1 *= r;
}
__device__ __forceinline__ void sts128(uint32_t addr, uint32_t a, uint32_t b, uint32_t c, uint32_t d) {
  asm volatile("st.shared.v4.u32 [%0], {%1, %2, %3, %4};" ::"r"(addr), "r"(a), "r"(b), "r"(c), "r"(d) : "memory");
}
__device__ __forceinline__ uint4 lds128(uint32_t addr) {
  uint4 v;
  asm volatile("ld.shared.v4.u32 {%0, %1, %2, %3}, [%4];" : "=r"(v.x), "=r"(v.y), "=r"(v.z), "=r"(v.w) : "r"(addr) : "memory");
  return v;
}
__device__ __forceinline__ float2 lds64f(uint32_t addr) {
  float2 v;
  asm volatile("ld.shared.v2.f32 {%0, %1}, [%2];" : "=f"(v.x), "=f"(v.y) : "r"(addr) : "memory");
  return v;
}
__device__ __forceinline__ void sts32f(uint32_t addr, float v) {
  asm volatile("st.shared.f32 [%0], %1;" ::"r"(addr), "f"(v) : "memory");
}
__device__ __forceinline__ float lds32f(uint32_t addr) {
  float v;
  asm volatile("ld.shared.f32 %0, [%1];" : "=f"(v) : "r"(addr) : "memory");
  return v;
}
#define PROF_AT(cond, slot) do {} while (0)

constexpr uint32_t SMEM_BASE = 1024;
constexpr uint32_t DESC_A = (1u << 16) | (SMEM_BASE >> 4);
constexpr uint32_t DESC_B = ((8192u >> 4) << 16) | ((SMEM_BASE + 16384) >> 4);

template <int BN> struct Wg;
template <> struct Wg<128> { static __device__ __forceinline__ void mma(float (&d)[64], uint32_t a, uint32_t b, int s) { wgmma_ss_n128(d, a, b, s); } };
template <> struct Wg<192> { static __device__ __forceinline__ void mma(float (&d)[96], uint32_t a, uint32_t b, int s) { wgmma_ss_n192(d, a, b, s); } };
template <> struct Wg<256> { static __device__ __forceinline__ void mma(float (&d)[128], uint32_t a, uint32_t b, int s) { wgmma_ss_n256(d, a, b, s); } };

struct Ring {
  uint32_t full0, rel0;
  int s;
  uint32_t ph;
  bool releaser;
};

template <int N>
__device__ __forceinline__ void fence_regs(float (&a)[N]) {
#pragma unroll
  for (int i = 0; i < N; i++) asm volatile("" : "+f"(a[i])::"memory");
}

template <int BN, int NST, uint32_t STAGE>
__device__ __forceinline__ void kblock(float (&acc)[BN / 2], Ring& g, uint32_t a_addr, bool zero, uint32_t& prev) {
  mbar_wait(g.full0 + 8 * g.s, g.ph);
  const uint32_t da = DESC_A + (a_addr >> 4);
  const uint32_t db = DESC_B + g.s * (STAGE >> 4);
  wg_fence();
#pragma unroll
  for (int k = 0; k < 4; k++) Wg<BN>::mma(acc, da + k * 2, db + k * 128, !(zero && k == 0));
  wg_commit();
  wg_wait<1>();
  if (prev != 0) mbar_arrive_cluster(prev);
  prev = g.releaser ? g.rel0 + 8 * g.s : 0u;
  if (++g.s == NST) { g.s = 0; g.ph ^= 1; }
}
template <int N>
__device__ __forceinline__ void tile_end(float (&acc)[N], uint32_t& prev) {
  wg_wait<0>();
  if (prev != 0) mbar_arrive_cluster(prev);
  prev = 0;
  fence_regs(acc);
}

__device__ __forceinline__ int own_first(int it, int j) {
  return it >= 16 ? (it & 15) : (it < 2 ? 2 * j + it : (it - 2 < 2 * j ? it - 2 : it));
}
__device__ __forceinline__ int qkv_kb(int it, int j) {
  const int q = it < 18 ? it - 4 : it - 18;
  return it < 4 ? 2 * j + (it & 1) : (q < 2 * j ? q : q + 2);
}
__device__ __forceinline__ int wo_k(int it, int j) {
  return it < 8 ? it * 128 : (it == 8 ? j : (it - 9 < j ? it - 9 : it - 8)) * 128 + 64;
}
__device__ __forceinline__ int down_k(int it) {
  const int r = (it >> 4) - 1, idx = it & 15;
  return r < 0 ? idx * 64 : (r < 3 ? (idx >> 1) * 448 + r * 128 + (idx & 1) * 64 : idx * 448 + 384);
}
__device__ __forceinline__ void wait_p3_free(uint32_t empty3, int i) {
  mbar_wait(empty3 + 8 * ((i * 2) / 3), 1);
  mbar_wait(empty3 + 8 * ((i * 2 + 1) / 3), 1);
}
__device__ __forceinline__ void wait_p2_free(uint32_t empty2, int i) {
  const int w0 = (i * 3) / 2, w1 = (i * 3 + 2) / 2;
  mbar_wait(empty2 + 8 * w0, w0 < 4 ? 0 : 1);
  mbar_wait(empty2 + 8 * w1, w1 < 4 ? 0 : 1);
}

__device__ __forceinline__ void chan(float& m, float& q, float m2, float q2, float n) {
  const float d = m2 - m;
  m = 0.5f * (m + m2);
  q = q + q2 + d * d * (0.5f * n);
}

template <int N>
__device__ __forceinline__ void row_stats(const uint32_t (&ll)[N], float& mean, float& rstd) {
  float ma = __uint_as_float(ll[0]), qa = __uint_as_float(ll[1]), mb = __uint_as_float(ll[4]), qb = __uint_as_float(ll[5]);
  chan(ma, qa, __uint_as_float(ll[2]), __uint_as_float(ll[3]), 128.f);
  chan(mb, qb, __uint_as_float(ll[6]), __uint_as_float(ll[7]), 128.f);
  chan(ma, qa, mb, qb, 256.f);
  const float mo = __shfl_xor_sync(~0u, ma, 16), qo = __shfl_xor_sync(~0u, qa, 16);
  chan(ma, qa, mo, qo, 512.f);
  mean = ma;
  rstd = rsqrtf(qa * (1.0f / DM) + 1e-5f);
}

__device__ __forceinline__ void stage_slab(uint32_t chunk, int warp, int lane, const uint32_t (&lo)[8], const uint32_t (&hi)[8]) {
  const int row = warp * 16 + (lane & 7) + ((lane >> 3) & 1) * 8;
  const uint32_t rbase = chunk + row * 128;
#pragma unroll
  for (int q = 0; q < 4; q++) {
    const int grp = 2 * q + (lane >> 4);
    stmatrix4(rbase + ((grp ^ (row & 7)) << 4), lo[2 * q], hi[2 * q], lo[2 * q + 1], hi[2 * q + 1]);
  }
}
__device__ __forceinline__ float silu_mul(float g, float u) {
  float e, r;
  asm("ex2.approx.ftz.f32 %0, %1;" : "=f"(e) : "f"(g * -1.4426950408889634f));
  asm("rcp.approx.ftz.f32 %0, %1;" : "=f"(r) : "f"(1.0f + e));
  return g * r * u;
}
__device__ __forceinline__ uint32_t swiglu2(uint32_t g2, uint32_t u2) {
  asm volatile("" : "+r"(g2));
  return pack2(silu_mul(bf_lo(g2), bf_lo(u2)), silu_mul(bf_hi(g2), bf_hi(u2)));
}
__device__ __forceinline__ void stage_done(uint32_t bar, int lane) {
  asm volatile("fence.proxy.async.shared::cta;" ::: "memory");
  __syncwarp();
  if (lane == 0) mbar_arrive(bar);
}

__device__ __forceinline__ void stage_done2(uint32_t bar, int lane) {
  asm volatile("fence.proxy.async.shared::cta;" ::: "memory");
  __syncwarp();
  if (lane < 2) mbar_arrive(bar + 8 * lane);
}

__device__ __forceinline__ int fresh_tid() {
  int t;
  asm volatile("mov.u32 %0, %%tid.x;" : "=r"(t));
  return t;
}
#define RING_IDS()                                                                                           \
  const int tid = fresh_tid() - 128;                                                                         \
  const int cw = __shfl_sync(~0u, tid >> 7, 0), warp = __shfl_sync(~0u, (tid >> 5) & 3, 0);                  \
  const bool releaser = (tid & 31) < 2;                                                                      \
  const uint32_t rbars = mapa(bars, tid & 1);                                                                \
  const uint32_t a_base = cw * 8192
#define LANE_IDS()                                                                                           \
  const int lane = fresh_tid() & 31, r = lane >> 2, c = lane & 3;                                            \
  const int srow = warp * 16 + (lane & 7) + ((lane >> 3) & 1) * 8;                                           \
  const uint32_t slab = stg + cw * 8192 + srow * 128, sw0 = (lane >> 4) ^ (srow & 7);                        \
  (void)r; (void)c; (void)slab; (void)sw0

template <int NPRE, class Step>
__device__ __forceinline__ void attention(float (&acc)[96], const Params& p, int rho, int rb, int cta, int cw, int warp, uint32_t tag,
                                          uint32_t stg, uint32_t bars, uint32_t& prev, Step step) {
  uint32_t ql[8], qh[8], k0[8], k1[8], v0[8], v1[8], hp[16];
  step();
  fence_regs(acc);
#pragma unroll
  for (int t = 0; t < 8; t++) {
    k0[t] = pack2(acc[4 * (8 + t)], acc[4 * (8 + t) + 1]);
    k1[t] = pack2(acc[4 * (8 + t) + 2], acc[4 * (8 + t) + 3]);
    v0[t] = pack2(acc[4 * (16 + t)], acc[4 * (16 + t) + 1]);
    v1[t] = pack2(acc[4 * (16 + t) + 2], acc[4 * (16 + t) + 3]);
    asm volatile("" : "+r"(k0[t]), "+r"(k1[t]), "+r"(v0[t]), "+r"(v1[t]));
  }
  const int lane = fresh_tid() & 31, r = lane >> 2, c = lane & 3;
#pragma unroll
  for (int t = 0; t < 8; t++) v1[t] = movmatrix(v1[t]);
  mbar_wait(bars + 8 * B_STGE, rho);
  mbar_wait(bars + 8 * (B_STGE + 1), 0);
  const uint32_t xch = stg + 16384 + (cw * 4 + warp) * 2048 + lane * 16;
  if (warp < 3) {
    sts128(xch, k1[0], k1[1], k1[2], k1[3]);
    sts128(xch + 512, k1[4], k1[5], k1[6], k1[7]);
    sts128(xch + 1024, v1[0], v1[1], v1[2], v1[3]);
    sts128(xch + 1536, v1[4], v1[5], v1[6], v1[7]);
  } else if (rb < 15) {
    uint4* dst = p.halo + ((cta * 2 + rho) * 2 + cw) * 256 + lane;
#pragma unroll
    for (int t = 0; t < 4; t++) {
      ll_store(dst + t * 32, k1[2 * t], k1[2 * t + 1], tag);
      ll_store(dst + (4 + t) * 32, v1[2 * t], v1[2 * t + 1], tag);
    }
  }
#pragma unroll
  for (int t = 0; t < 8; t++) {
    v0[t] = movmatrix(v0[t]);
    ql[t] = pack2(acc[4 * t], acc[4 * t + 1]);
    qh[t] = pack2(acc[4 * t + 2], acc[4 * t + 3]);
    asm volatile("" : "+r"(v0[t]), "+r"(ql[t]), "+r"(qh[t]));
  }
#pragma unroll 1
  for (int i = 0; i < NPRE; i++) step();
  const uint4* src = p.halo + (((cta - 8) * 2 + rho) * 2 + cw) * 256 + lane;
  uint4 early[8] = {};
  if (warp == 0 && rb > 0) {
#pragma unroll
    for (int i = 0; i < 8; i++) early[i] = ll_peek(src + i * 32);
  }
  step();
  wg_bar(cw);
  if (warp > 0) {
#pragma unroll
    for (int t = 0; t < 4; t++) {
      const uint4 a = lds128(xch - 2048 + t * 512);
      hp[4 * t] = a.x; hp[4 * t + 1] = a.y; hp[4 * t + 2] = a.z; hp[4 * t + 3] = a.w;
    }
  } else if (rb > 0) {
    uint32_t bad = 0;
#pragma unroll
    for (int i = 0; i < 8; i++) {
      bad |= (early[i].y ^ tag) | (early[i].w ^ tag);
      hp[2 * i] = early[i].x;
      hp[2 * i + 1] = early[i].z;
    }
    if (!__all_sync(~0u, bad == 0)) ll_poll<8>([&](int i) { return src + i * 32; }, tag, hp);
  } else {
#pragma unroll
    for (int t = 0; t < 16; t++) hp[t] = 0;
  }
  wg_wait<0>();
  if (prev != 0) mbar_arrive_cluster(prev);
  prev = 0;
#pragma unroll
  for (int t = 0; t < 8; t++) asm volatile("" : "+r"(ql[t])::"memory");
  const bool up0 = 2 * c > r, up1 = 2 * c + 1 > r;
  const bool first = (rb == 0) && (warp == 0);
  uint32_t a0[2], a2[2], a3[2], a5[2];
#pragma unroll
  for (int h = 0; h < 2; h++) {
    float sp[4] = {0.f, 0.f, 0.f, 0.f}, s0[4] = {0.f, 0.f, 0.f, 0.f}, s1[4] = {0.f, 0.f, 0.f, 0.f};
#pragma unroll
    for (int ks = 0; ks < 2; ks++) {
      const int t = 4 * h + 2 * ks;
      mma16816(sp, ql[t], qh[t], ql[t + 1], qh[t + 1], hp[t], hp[t + 1]);
      mma16816(s0, ql[t], qh[t], ql[t + 1], qh[t + 1], k0[t], k0[t + 1]);
      mma16816(s1, ql[t], qh[t], ql[t + 1], qh[t + 1], k1[t], k1[t + 1]);
    }
    float p0 = (up0 ? sp[0] : s0[0]) * QK_SCALE, p1 = (up1 ? sp[1] : s0[1]) * QK_SCALE;
    float p2 = (up0 ? s0[2] : s1[2]) * QK_SCALE, p3 = (up1 ? s0[3] : s1[3]) * QK_SCALE;
    if (first && up0) p0 = -1000000000.0f;
    if (first && up1) p1 = -1000000000.0f;
    softmax8(p0, p1);
    softmax8(p2, p3);
    a0[h] = pack2(up0 ? p0 : 0.f, up1 ? p1 : 0.f);
    a2[h] = pack2(up0 ? 0.f : p0, up1 ? 0.f : p1);
    a3[h] = pack2(up0 ? p2 : 0.f, up1 ? p3 : 0.f);
    a5[h] = pack2(up0 ? 0.f : p2, up1 ? 0.f : p3);
  }
  float o[8][4];
#pragma unroll
  for (int t = 0; t < 8; t++) {
#pragma unroll
    for (int q = 0; q < 4; q++) o[t][q] = 0.f;
    mma1688(o[t], 0u, a5[t >> 2], v1[t]);
    mma16816(o[t], a0[t >> 2], 0u, a2[t >> 2], a3[t >> 2], hp[8 + t], v0[t]);
  }
#pragma unroll
  for (int t = 0; t < 8; t++) fence_regs(o[t]);
  step();
  uint32_t ol[8], oh[8];
#pragma unroll
  for (int t = 0; t < 8; t++) {
    ol[t] = pack2(o[t][0], o[t][1]);
    oh[t] = pack2(o[t][2], o[t][3]);
  }
  stage_slab(stg + cw * 8192, warp, lane, ol, oh);
  stage_done(bars + 8 * B_STGF, lane);
}

__global__ void __launch_bounds__(384, 1) fused_kernel(const __grid_constant__ Params p) {
  extern __shared__ __align__(1024) uint8_t smem_raw[];
  const uint32_t sm = smem_u32(smem_raw);
  const uint32_t bars = sm + MISC_OFF;
  const uint32_t stg = sm + STG_OFF;
  const int rank = blockIdx.x & 1;
  const int cl = blockIdx.x >> 1;
  if (cl >= NCTA / 2) {
    const int e = blockIdx.x - NCTA, wid = __shfl_sync(~0u, (int)(threadIdx.x >> 5), 0), lane = threadIdx.x & 31;
    if (threadIdx.x == 0) {
      for (int i = 0; i < 6; i++) { mbar_init(bars + 8 * i, 1); mbar_init(bars + 8 * (6 + i), 8); }
      asm volatile("fence.mbarrier_init.release.cluster;" ::: "memory");
    }
    const uint32_t tag = load_epoch(p.epoch) + 1;
    if (threadIdx.x < 256) ll_store(p.modll + 512 + (threadIdx.x >> 6) * 256 + e * 64 + (threadIdx.x & 63), 0u, 0u, 0u);
    for (int i = threadIdx.x; i < 1536; i += 384) {
      uint4 o = make_uint4(0u, 0u, 0u, 0u);
      if (i < 1024 && (i & 63) < 8) {
        const uint4 cv = ldg_nc(p.c + (i >> 6) * 64 + (i & 7) * 8);
        o = make_uint4(pack2(silu_f(bf_lo(cv.x)), silu_f(bf_hi(cv.x))), pack2(silu_f(bf_lo(cv.y)), silu_f(bf_hi(cv.y))),
                       pack2(silu_f(bf_lo(cv.z)), silu_f(bf_hi(cv.z))), pack2(silu_f(bf_lo(cv.w)), silu_f(bf_hi(cv.w))));
      }
      sts128(stg + i * 16, o.x, o.y, o.z, o.w);
    }
    asm volatile("fence.proxy.async.shared::cta;" ::: "memory");
    __syncthreads();
    if (wid == 0) {
      __nanosleep(WMDELAY);
      uint32_t ph = 1;
#pragma unroll 1
      for (int it = 0, s = 0; it < 64; it++) {
        mbar_wait(bars + 8 * (6 + s), ph);
        expect_tx_elect(bars + 8 * s, 32768);
#pragma unroll
        for (int q = 0; q < 4; q++) tma_load_ef(sm + s * 32768 + q * 8192, &p.wm, bars + 8 * s, 2048 + (it >> 4) * 1024 + e * 256 + q * 64, (it & 15) * 64);
        if (++s == 6) { s = 0; ph ^= 1; }
      }
    } else if (wid >= 4) {
      const int hf = (wid >> 2) - 1;
      uint32_t ph = 0;
      int s = 0;
#pragma unroll 1
      for (int v = 0; v < 4; v++) {
        float acc[64];
#pragma unroll 1
        for (int kb = 0; kb < 16; kb++) {
          mbar_wait_watchdog(bars + 8 * s, ph);
          const uint32_t da = DESC_A + ((STG_OFF + kb * 1024) >> 4), db = DESC_B + ((s * 32768 + hf * 16384) >> 4) - 1024;
          wg_fence();
#pragma unroll
          for (int k = 0; k < 4; k++) wgmma_ss_n128(acc, da + k * 2, db + k * 128, (kb | k) != 0);
          wg_commit();
          wg_wait<0>();
          if (lane == 0) mbar_arrive(bars + 8 * (6 + s));
          if (++s == 6) { s = 0; ph ^= 1; }
        }
        if ((wid & 3) == 0) {
#pragma unroll
          for (int n = 0; n < 16; n++) {
            const uint32_t mine = pack2(acc[4 * n], acc[4 * n + 1]), next = __shfl_down_sync(~0u, mine, 1);
            if (lane < 4 && (lane & 1) == 0) ll_store(p.modll + 512 + v * 256 + e * 64 + hf * 32 + n * 2 + (lane >> 1), mine, next, tag);
          }
        }
      }
    }
    return;
  }
  const int slot = p.slot[cl];
  const int rb = (slot >> 3) * 2 + rank, j = slot & 7;
  const int cta = rb * 8 + j;
  PROF_AT(threadIdx.x == 0, 0);

  if (threadIdx.x < 128) {
    asm volatile("setmaxnreg.dec.sync.aligned.u32 40;");
    const int warp = __shfl_sync(~0u, (int)(threadIdx.x >> 5), 0), lane = threadIdx.x & 31;
    if (threadIdx.x == 0) {
      if ((sm & 0x3FFFF) != SMEM_BASE) asm volatile("trap;");
      for (int i = 0; i < 4; i++) { mbar_init(bars + 8 * (B_FQ + i), 1); mbar_init(bars + 8 * (B_EQ + i), 16); }
      for (int i = 0; i < 6; i++) { mbar_init(bars + 8 * (B_FW + i), 1); mbar_init(bars + 8 * (B_EW + i), 16); }
      for (int i = 0; i < 4; i++) { mbar_init(bars + 8 * (B_FG + i), 1); mbar_init(bars + 8 * (B_EG + i), 16); }
      for (int i = 0; i < 6; i++) { mbar_init(bars + 8 * (B_FD + i), 1); mbar_init(bars + 8 * (B_ED + i), 16); }
      for (int i = 0; i < 2; i++) { mbar_init(bars + 8 * (B_STGF + i), 8); mbar_init(bars + 8 * (B_STGE + i), 1); }
      mbar_init(bars + 8 * B_MODB, 1);
      mbar_init(bars + 8 * (B_MODB + 1), 1);
      mbar_init(bars + 8 * B_GATE, 1);
      for (int i = 0; i < 8; i++) mbar_init(bars + 8 * (B_RDY + i), 1);
      asm volatile("fence.mbarrier_init.release.cluster;" ::: "memory");
    }
    __syncwarp();
    cluster_arrive();
    const uint32_t tag = load_epoch(p.epoch) + 1;
    const unsigned target = tag * 8;
    unsigned* cnt = p.cnt + rb * 32;
    cluster_wait();
    if (warp == 0) {
      const CUtensorMap* wgu = rank ? &p.wu : &p.wg;
      uint32_t st = sm + 16384, fb = bars + 8 * B_FQ, ph = 1;
      if (BDELAY) __nanosleep(BDELAY);
#pragma unroll 1
      for (int it = 0; it < 32; it++) {
        const int kb = qkv_kb(it, j), col = j * 128 + ((it < 4 ? it >= 2 : it >= 18) ? 64 : 0);
        mbar_wait(fb + 8 * (B_EQ - B_FQ), ph);
        expect_tx_elect(fb, it < 4 ? 24576 : 40960);
        tma_load_mc(st + rank * 8192, &p.wqkv, fb, col + rank * 1024, kb * 64);
        tma_load_mc(st + 16384 + rank * 4096, &p.wqkv32, fb, col + 2048, kb * 64 + rank * 32);
        st += 49152; fb += 8;
        if ((it & 3) == 3) { st -= 4 * 49152; fb -= 32; ph ^= 1; }
      }
      fb = bars + 8 * B_FW; ph = 1;
#pragma unroll 1
      for (int it = 0, s = 0; it < 16; it++) {
        if (it < 6) wait_p3_free(bars + 8 * B_EQ, it);
        if (GATE && it == GATE) mbar_wait(bars + 8 * B_GATE, 0);
        mbar_wait(fb + 8 * (B_EW - B_FW), ph);
        expect_tx_elect(fb, it == 8 ? 16384 : 32768);
        tma_load_mc(st + rank * 8192, &p.wo, fb, j * 128 + rank * 64, wo_k(it, j));
        st += 32768; fb += 8;
        if (++s == 6) { s = 0; st -= 6 * 32768; fb -= 48; ph ^= 1; }
      }
      st = sm + 16384; fb = bars + 8 * B_FG; ph = 1;
#pragma unroll 1
      for (int it = 0; it < 48; it++) {
        const int kb = own_first(it, j), col = j * 448 + (it >> 4) * 128;
        if (it < 4) wait_p2_free(bars + 8 * B_EW, it);
        mbar_wait(fb + 8 * (B_EG - B_FG), ph);
        expect_tx_elect(fb, it < 2 ? 32768 : 49152);
        tma_load_mc(st + rank * 16384, wgu, fb, col, kb * 64);
        tma_load_mc(st + rank * 16384 + 8192, wgu, fb, col + 64, kb * 64);
        st += 49152; fb += 8;
        if ((it & 3) == 3) { st -= 4 * 49152; fb -= 32; ph ^= 1; }
      }
      fb = bars + 8 * B_FD; ph = 1;
#pragma unroll 1
      for (int it = 0, s = 0; it < 72; it++) {
        if (it < 6) wait_p3_free(bars + 8 * B_EG, it);
        mbar_wait(fb + 8 * (B_ED - B_FD), ph);
        expect_tx_elect(fb, 32768);
        tma_load_mc(st + rank * 8192, it < 16 ? wgu : &p.wd, fb, it < 16 ? j * 448 + 384 : j * 128 + rank * 64, down_k(it));
        st += 32768; fb += 8;
        if (++s == 6) { s = 0; st -= 6 * 32768; fb -= 48; ph ^= 1; }
      }
    } else if (warp == 1) {
      const int arow = rb * 128;
      uint32_t st = sm, fb = bars + 8 * B_FQ, ph = 0;
      cnt_wait(cnt + C_H, target);
      PROF_AT(lane == 0, 16);
#pragma unroll 1
      for (int it = 4; it < 32; it++) {
        mbar_wait(fb + 8 * (B_EQ - B_FQ), ph);
        tma_load(st, &p.h, fb, qkv_kb(it, j) * 64, arow);
        st += 49152; fb += 8;
        if ((it & 3) == 3) { st -= 4 * 49152; fb -= 32; ph ^= 1; }
      }
      fb = bars + 8 * B_FW; ph = 1;
#pragma unroll 1
      for (int it = 0, s = 0; it < 16; it++) {
        if (it < 6) wait_p3_free(bars + 8 * B_EQ, it);
        if (GATE && it == GATE) mbar_wait(bars + 8 * B_GATE, 0);
        mbar_wait(fb + 8 * (B_EW - B_FW), ph);
        if (it == 0 || it == 9) { mbar_wait(bars + 8 * (B_RDY + C_O + (it >> 3)), 0); PROF_AT(lane == 0, 17 + (it >> 3)); }
        if (it != 8) tma_load(st, &p.o_ld, fb, wo_k(it, j), arow);
        st += 32768; fb += 8;
        if (++s == 6) { s = 0; st -= 6 * 32768; fb -= 48; ph ^= 1; }
      }
      st = sm + 2 * 49152; fb = bars + 8 * (B_FG + 2); ph = 1;
      mbar_wait(bars + 8 * (B_RDY + C_H2), 0);
      PROF_AT(lane == 0, 19);
#pragma unroll 1
      for (int it = 2; it < 48; it++) {
        mbar_wait(fb + 8 * (B_EG - B_FG), ph);
        tma_load(st, &p.h2, fb, own_first(it, j) * 64, arow);
        st += 49152; fb += 8;
        if ((it & 3) == 3) { st -= 4 * 49152; fb -= 32; ph ^= 1; }
      }
      fb = bars + 8 * B_FD; ph = 1;
#pragma unroll 1
      for (int it = 0, s = 0; it < 72; it++) {
        if (it < 6) wait_p3_free(bars + 8 * B_EG, it);
        mbar_wait(fb + 8 * (B_ED - B_FD), ph);
        if ((it & 15) == 0 && it > 0) { mbar_wait(bars + 8 * (B_RDY + C_ACT - 1 + (it >> 4)), 0); PROF_AT(lane == 0, 19 + (it >> 4)); }
        tma_load(st, it < 16 ? &p.h2 : &p.act, fb, down_k(it), arow);
        st += 32768; fb += 8;
        if (++s == 6) { s = 0; st -= 6 * 32768; fb -= 48; ph ^= 1; }
      }
    } else if (warp == 2) {
      if (lane < 13) prefetch_map(&p.h + lane);
      __syncwarp();
      uint32_t ph1 = 0;
#pragma unroll 1
      for (int n = 0; n < 9; n++) {
        const int nch = (n == 1 || n == 2 || n == 7) ? 1 : 2;
#pragma unroll 1
        for (int ch = 0; ch < nch; ch++) {
          mbar_wait_watchdog(bars + 8 * (B_STGF + ch), ch ? ph1 : (n & 1));
          const uint32_t src = stg + ch * 16384;
          if (n == 1 || n == 2) {
#pragma unroll 1
            for (int q = 0; q < 4; q++) {
              tma_store2(&p.o_st, src + q * 4096, j * 128 + (n - 1) * 64, rb * 128 + q * 32);
              if (n == 1) store_pause(true);
            }
            if (n == 2) arrive_elect(bars + 8 * B_GATE);
          } else if (n >= 4 && n < 8) {
#pragma unroll 1
            for (int q = 0; q < 4; q++) {
              tma_store2(&p.act_st, src + q * 4096, j * 448 + (n - 4) * 128 + ch * 64, rb * 128 + q * 32);
              store_pause(true);
            }
          } else if (n == 8) {
            tma_store3(&p.out, src, j * 128 + ch * 64, rb * 64, 0);
          } else {
            tma_store2(n == 0 ? &p.h : &p.h2, src, j * 128 + ch * 64, rb * 128);
          }
          if (n >= 4 && n < 7 && ch == 0) arrive_elect(bars + 8 * B_STGE);
        }
        asm volatile("cp.async.bulk.commit_group;" ::: "memory");
        asm volatile("cp.async.bulk.wait_group 0;" ::: "memory");
        __syncwarp();
        if (n < 8) cnt_signal(cnt + n);
        if (!(n >= 4 && n < 7)) arrive_elect(bars + 8 * B_STGE);
        if (nch == 2) { arrive_elect(bars + 8 * (B_STGE + 1)); ph1 ^= 1; }
        PROF_AT(lane == 0, n == 0 ? 33 : 23 + n);
      }
    } else {
      if (lane < 4) ll_store(p.modll + cta * 4 + lane, 0u, 0u, 0u);
      bar_sync(1, 288);
      {
        const uint4 t4 = lds128(sm + RED_OFF + lane * 16);
        float a[4] = {__uint_as_float(t4.x), __uint_as_float(t4.y), __uint_as_float(t4.z), __uint_as_float(t4.w)};
#pragma unroll
        for (int o = 4; o < 32; o <<= 1)
#pragma unroll
          for (int q = 0; q < 4; q++) a[q] += __shfl_xor_sync(~0u, a[q], o);
        if (lane < 4) ll_store(p.modll + cta * 4 + lane, pack2(a[0], a[1]), pack2(a[2], a[3]), tag);
        PROF_AT(lane == 0, 1);
        uint32_t m[4];
        const uint4* mp = p.modll + j * 32 + lane;
        ll_poll<2>([&](int i) { return mp + i * 256; }, tag, m);
        const uint32_t c0 = pack2(1.0f + bf_lo(m[2]), 1.0f + bf_hi(m[2])), c1 = pack2(1.0f + bf_lo(m[3]), 1.0f + bf_hi(m[3]));
        sts128(sm + MODB_OFF + lane * 16, m[0] << 16, m[0] & 0xffff0000u, m[1] << 16, m[1] & 0xffff0000u);
        sts128(sm + MODB_OFF + 512 + lane * 16, c0 << 16, c0 & 0xffff0000u, c1 << 16, c1 & 0xffff0000u);
        asm volatile("bar.arrive 4, 288;" ::: "memory");
      }
#pragma unroll 1
      for (int n = C_O; n < C_H2; n++) {
        if (n == C_O) cnt_wait_lazy(cnt + n, target); else cnt_wait(cnt + n, target);
        arrive_elect(bars + 8 * (B_RDY + n));
      }
      {
        uint32_t m[6];
        const uint4* src = p.modll + 512 + j * 32 + lane;
        ll_poll<3>([&](int i) { return src + i * 256; }, tag, m);
#pragma unroll
        for (int vec = 0; vec < 3; vec++) {
          const float add = vec == 2 ? 1.0f : 0.0f;
          sts128(sm + MODB_OFF + (vec * 128 + lane * 4) * 4, __float_as_uint(bf_round(bf_lo(m[2 * vec]) + add)), __float_as_uint(bf_round(bf_hi(m[2 * vec]) + add)),
                 __float_as_uint(bf_round(bf_lo(m[2 * vec + 1]) + add)), __float_as_uint(bf_round(bf_hi(m[2 * vec + 1]) + add)));
        }
        __syncwarp();
        if (lane == 0) mbar_arrive(bars + 8 * B_MODB);
        PROF_AT(lane == 0, 15);
      }
      __syncwarp();
#pragma unroll 1
      for (int n = C_H2; n < 8; n++) {
        if (n == C_H2) cnt_wait(cnt + n, target); else cnt_wait_lazy(cnt + n, target);
        arrive_elect(bars + 8 * (B_RDY + n));
      }
      {
        uint32_t m[2];
        const uint4* src = p.modll + 512 + 768 + j * 32 + lane;
        ll_poll<1>([&](int) { return src; }, tag, m);
        sts128(sm + MODB_OFF + (384 + lane * 4) * 4, m[0] << 16, m[0] & 0xffff0000u, m[1] << 16, m[1] & 0xffff0000u);
        __syncwarp();
        if (lane == 0) mbar_arrive(bars + 8 * (B_MODB + 1));
      }
    }
    __syncwarp();
    cluster_arrive_relaxed();
    cluster_wait();
  } else {
    uint32_t tag;

    {
      const int tid = threadIdx.x - 128, cw = tid >> 7, warp = (tid >> 5) & 3, lane = tid & 31;
      const int l16 = lane & 15, half = lane >> 4, w8 = cw * 4 + warp;
      uint4 xv[8];
      const int tok0 = rb * 128 + (warp * 16 + half) * 2 + cw;
      uint32_t c0, c1;
      {
        const bf16* cp = p.c + w8 * 128 + (lane >> 2) * 16 + (lane & 3) * 2;
        asm volatile("ld.global.nc.u32 %0, [%1];" : "=r"(c0) : "l"(cp));
        asm volatile("ld.global.nc.u32 %0, [%1];" : "=r"(c1) : "l"(cp + 8));
      }
      tag = load_epoch(p.epoch);
      const uint32_t wbuf = sm + cw * 49152 + warp * 4096;
      {
        const bf16* wp = p.wmod + cta * 16 + (lane & 1) * 8 + (size_t)(w8 * 128 + (lane >> 1)) * 6144;
#pragma unroll
        for (int i = 0; i < 8; i++) cp_async16(wbuf + i * 512 + lane * 16, wp + (size_t)i * 16 * 6144);
      }
      asm volatile("cp.async.commit_group;" ::: "memory");
      const uint32_t xbuf = sm + 40960 + (cw * 2 + (l16 >> 3)) * 49152 + (warp * 16 + half) * 128;
#pragma unroll
      for (int i = 0; i < 8; i++)
        cp_async16(xbuf + i * 256 + (((l16 & 7) ^ ((i * 2 + half) & 7)) << 4), p.x + (size_t)(tok0 + 4 * i) * DM + j * 128 + l16 * 8);
      asm volatile("cp.async.commit_group;" ::: "memory");
      PROF_AT(tid == 0, 32);
      uint4* st1 = p.stats1 + (rb * 8 + j) * 128 + cw * 64 + warp * 16 + (l16 >> 1) * 2 + half;
      if ((lane & 1) == 0) ll_store(st1, 0u, 0u, 0u);
      __syncwarp();
      cluster_arrive_relaxed();
      asm volatile("setmaxnreg.inc.sync.aligned.u32 232;");
      asm volatile("" : "+r"(tag), "+r"(c0), "+r"(c1));
      tag += 1;
      uint32_t sa0[8], sa2[8];
      {
        c0 = pack2(silu_f(bf_lo(c0)), silu_f(bf_hi(c0)));
        c1 = pack2(silu_f(bf_lo(c1)), silu_f(bf_hi(c1)));
#pragma unroll
        for (int ks = 0; ks < 8; ks++) {
          sa0[ks] = __shfl_sync(~0u, c0, ks * 4 + (lane & 3));
          sa2[ks] = __shfl_sync(~0u, c1, ks * 4 + (lane & 3));
        }
      }
      asm volatile("cp.async.wait_group 1;" ::: "memory");
      __syncwarp();
      PROF_AT(tid == 0, 51);
      {
        float d0[4] = {0.f, 0.f, 0.f, 0.f}, d1[4] = {0.f, 0.f, 0.f, 0.f};
#pragma unroll
        for (int ks = 0; ks < 8; ks++) {
          uint32_t b[4];
          ldmatrix4t(b, wbuf + (ks * 16 + (lane & 15)) * 32 + (lane >> 4) * 16);
          mma16816(d0, sa0[ks], 0u, sa2[ks], 0u, b[0], b[1]);
          mma16816(d1, sa0[ks], 0u, sa2[ks], 0u, b[2], b[3]);
        }
        if (lane < 4) {
          sts64f(sm + RED_OFF + (w8 * 16 + lane * 2) * 4, d0[0], d0[1]);
          sts64f(sm + RED_OFF + (w8 * 16 + 8 + lane * 2) * 4, d1[0], d1[1]);
        }
        asm volatile("bar.arrive 1, 288;" ::: "memory");
      }
      asm volatile("cp.async.wait_group 0;" ::: "memory");
#pragma unroll
      for (int i = 0; i < 8; i++) xv[i] = lds128(xbuf + i * 256 + (((l16 & 7) ^ ((i * 2 + half) & 7)) << 4));
      float e[8][8], m[8], q[8];
#pragma unroll
      for (int i = 0; i < 8; i++) {
        e[i][0] = bf_lo(xv[i].x); e[i][1] = bf_hi(xv[i].x); e[i][2] = bf_lo(xv[i].y); e[i][3] = bf_hi(xv[i].y);
        e[i][4] = bf_lo(xv[i].z); e[i][5] = bf_hi(xv[i].z); e[i][6] = bf_lo(xv[i].w); e[i][7] = bf_hi(xv[i].w);
        m[i] = (((e[i][0] + e[i][1]) + (e[i][2] + e[i][3])) + ((e[i][4] + e[i][5]) + (e[i][6] + e[i][7]))) * 0.125f;
        q[i] = 0.f;
#pragma unroll
        for (int k = 0; k < 8; k++) q[i] += (e[i][k] - m[i]) * (e[i][k] - m[i]);
      }
      {
        const bool b3 = lane & 8, b2 = lane & 4, b1 = lane & 2;
#pragma unroll
        for (int i = 0; i < 4; i++) {
          const float mo = __shfl_xor_sync(~0u, b3 ? m[i] : m[i + 4], 8), qo = __shfl_xor_sync(~0u, b3 ? q[i] : q[i + 4], 8);
          m[i] = b3 ? m[i + 4] : m[i]; q[i] = b3 ? q[i + 4] : q[i];
          chan(m[i], q[i], mo, qo, 8.f);
        }
#pragma unroll
        for (int i = 0; i < 2; i++) {
          const float mo = __shfl_xor_sync(~0u, b2 ? m[i] : m[i + 2], 4), qo = __shfl_xor_sync(~0u, b2 ? q[i] : q[i + 2], 4);
          m[i] = b2 ? m[i + 2] : m[i]; q[i] = b2 ? q[i + 2] : q[i];
          chan(m[i], q[i], mo, qo, 16.f);
        }
        {
          const float mo = __shfl_xor_sync(~0u, b1 ? m[0] : m[1], 2), qo = __shfl_xor_sync(~0u, b1 ? q[0] : q[1], 2);
          m[0] = b1 ? m[1] : m[0]; q[0] = b1 ? q[1] : q[0];
          chan(m[0], q[0], mo, qo, 32.f);
        }
        {
          const float mo = __shfl_xor_sync(~0u, m[0], 1), qo = __shfl_xor_sync(~0u, q[0], 1);
          chan(m[0], q[0], mo, qo, 64.f);
        }
      }
      if ((lane & 1) == 0) ll_store(st1, __float_as_uint(m[0]), __float_as_uint(q[0]), tag);
      PROF_AT(tid == 0, 50);
      {
        uint32_t ll[8];
        const uint4* sp = p.stats1 + (rb * 8 + half * 4) * 128 + cw * 64 + warp * 16 + l16;
        ll_poll<4>([&](int i) { return sp + i * 128; }, tag, ll);
        float nmr, rstd;
        row_stats(ll, nmr, rstd);
        nmr *= -rstd;
#pragma unroll
        for (int i = 0; i < 8; i++) {
          const float rs = __shfl_sync(~0u, rstd, i * 2 + half), nb = __shfl_sync(~0u, nmr, i * 2 + half);
#pragma unroll
          for (int k = 0; k < 8; k++) { e[i][k] = e[i][k] * rs + nb; asm volatile("" : "+f"(e[i][k])); }
        }
      }
      PROF_AT(tid == 0, 52);
      bar_sync(4, 288);
      PROF_AT(tid == 0, 2);
      float sa[8], ca[8];
#pragma unroll
      for (int k = 0; k < 2; k++) {
        const uint4 sv = lds128(sm + MODB_OFF + (l16 * 8 + k * 4) * 4), cv = lds128(sm + MODB_OFF + (128 + l16 * 8 + k * 4) * 4);
        sa[4 * k] = __uint_as_float(sv.x); sa[4 * k + 1] = __uint_as_float(sv.y); sa[4 * k + 2] = __uint_as_float(sv.z); sa[4 * k + 3] = __uint_as_float(sv.w);
        ca[4 * k] = __uint_as_float(cv.x); ca[4 * k + 1] = __uint_as_float(cv.y); ca[4 * k + 2] = __uint_as_float(cv.z); ca[4 * k + 3] = __uint_as_float(cv.w);
      }
#pragma unroll
      for (int i = 0; i < 8; i++) {
        uint32_t o[4];
#pragma unroll
        for (int k = 0; k < 4; k++) o[k] = pack2(e[i][2 * k] * ca[2 * k] + sa[2 * k], e[i][2 * k + 1] * ca[2 * k + 1] + sa[2 * k + 1]);
        const int row = cw * 64 + warp * 16 + i * 2 + half;
        sts128(stg + (l16 >> 3) * 16384 + row * 128 + (((l16 & 7) ^ (row & 7)) << 4), o[0], o[1], o[2], o[3]);
      }
      cluster_wait();
      stage_done2(bars + 8 * B_STGF, lane);
      wg_bar(cw);
      PROF_AT(tid == 0, 3);
    }

    uint32_t xl[16], xh[16];
    {
      RING_IDS();
      uint32_t prev = 0;
      float acc1[96];
      {
        Ring g{bars + 8 * B_FQ, rbars + 8 * B_EQ, 0, 0u, releaser TR(0)};
        float acc0[96];
#pragma unroll 1
        for (int kb = 0; kb < 2; kb++) kblock<192, 4, 49152>(acc0, g, a_base + STG_OFF + kb * 16384, kb == 0, prev);
#pragma unroll 1
        for (int kb = 0; kb < 2; kb++) kblock<192, 4, 49152>(acc1, g, a_base + STG_OFF + kb * 16384, kb == 0, prev);
        {
          LANE_IDS();
          if (c < 2) ll_store(p.stats2 + (rb * 8 + j) * 128 + cw * 64 + warp * 16 + r + c * 8, 0u, 0u, 0u);
          if (warp == 3) {
#pragma unroll 1
            for (int t = 0; t < 16; t++) ll_store(p.halo + ((cta * 2 + (t >> 3)) * 2 + cw) * 256 + (t & 7) * 32 + lane, 0u, 0u, 0u);
          }
          __syncwarp();
        }
#pragma unroll 1
        for (int kb = 0; kb < 14; kb++) kblock<192, 4, 49152>(acc0, g, a_base + g.s * 49152, false, prev);
        PROF_AT(tid == 0, 4);
        attention<NPRE0>(acc0, p, 0, rb, cta, cw, warp, tag, stg, bars, prev, [&]() { kblock<192, 4, 49152>(acc1, g, a_base + g.s * 49152, false, prev); });
        PROF_AT(tid == 0, 5);
        {
          LANE_IDS();
#pragma unroll
          for (int q = 0; q < 8; q++)
            ldmatrix4(xl[2 * q], xh[2 * q], xl[2 * q + 1], xh[2 * q + 1], sm + 40960 + (cw * 2 + (q >> 2)) * 49152 + srow * 128 + ((sw0 ^ ((q & 3) * 2)) << 4));
#pragma unroll
          for (int q = 0; q < 16; q++) asm volatile("" : "+r"(xl[q]), "+r"(xh[q])::"memory");
        }
#pragma unroll 1
        for (int kb = 3 + NPRE0; kb < 14; kb++) kblock<192, 4, 49152>(acc1, g, a_base + g.s * 49152, false, prev);
        PROF_AT(tid == 0, 6);
      }
      float acc[64];
      Ring g{bars + 8 * B_FW, rbars + 8 * B_EW, 0, 0u, releaser TR(32)};
      attention<NPRE1>(acc1, p, 1, rb, cta, cw, warp, tag, stg, bars, prev, [&]() { kblock<128, 6, 32768>(acc, g, a_base + g.s * 32768, g.s == 0, prev); });
      PROF_AT(tid == 0, 7);
      LANE_IDS();
      uint4* st2 = p.stats2 + (rb * 8 + j) * 128 + cw * 64 + warp * 16 + r + (c & 1) * 8;
#pragma unroll 1
      for (int kb = 3 + NPRE1; kb < 16; kb++) {
        if (kb == 8) wg_bar(cw);
        kblock<128, 6, 32768>(acc, g, a_base + (kb == 8 ? STG_OFF : g.s * 32768), false, prev);
      }
      mbar_wait(bars + 8 * B_MODB, 0);
      float2 ga[16];
#pragma unroll
      for (int n = 0; n < 16; n++) ga[n] = lds64f(sm + MODB_OFF + (8 * n + 2 * c) * 4);
      tile_end(acc, prev);
      PROF_AT(tid == 0, 8);
      float sl[2] = {0.f, 0.f}, sh[2] = {0.f, 0.f}, ql[2] = {0.f, 0.f}, qh[2] = {0.f, 0.f};
#pragma unroll
      for (int n = 0; n < 16; n++) {
        acc[4 * n] = ga[n].x * acc[4 * n] + bf_lo(xl[n]); acc[4 * n + 1] = ga[n].y * acc[4 * n + 1] + bf_hi(xl[n]);
        acc[4 * n + 2] = ga[n].x * acc[4 * n + 2] + bf_lo(xh[n]); acc[4 * n + 3] = ga[n].y * acc[4 * n + 3] + bf_hi(xh[n]);
        sl[0] += acc[4 * n]; sl[1] += acc[4 * n + 1]; sh[0] += acc[4 * n + 2]; sh[1] += acc[4 * n + 3];
        ql[0] += acc[4 * n] * acc[4 * n]; ql[1] += acc[4 * n + 1] * acc[4 * n + 1];
        qh[0] += acc[4 * n + 2] * acc[4 * n + 2]; qh[1] += acc[4 * n + 3] * acc[4 * n + 3];
      }
      {
        const float ml = (sl[0] + sl[1]) * (1.0f / 32), mh = (sh[0] + sh[1]) * (1.0f / 32);
        const float vl = (ql[0] + ql[1]) - 32.0f * ml * ml, vh = (qh[0] + qh[1]) - 32.0f * mh * mh;
        const bool b0 = c & 1;
        float m = b0 ? mh : ml, q = b0 ? vh : vl;
        chan(m, q, __shfl_xor_sync(~0u, b0 ? ml : mh, 1), __shfl_xor_sync(~0u, b0 ? vl : vh, 1), 32.f);
        chan(m, q, __shfl_xor_sync(~0u, m, 2), __shfl_xor_sync(~0u, q, 2), 64.f);
        if (c < 2) ll_store(st2, __float_as_uint(m), __float_as_uint(fmaxf(q, 0.f)), tag);
        __syncwarp();
      }
      PROF_AT(tid == 0, 48);
      float2 sb[16], cb[16];
#pragma unroll
      for (int n = 0; n < 16; n++) {
        sb[n] = lds64f(sm + MODB_OFF + (128 + 8 * n + 2 * c) * 4);
        cb[n] = lds64f(sm + MODB_OFF + (256 + 8 * n + 2 * c) * 4);
        xl[n] = pack2(acc[4 * n], acc[4 * n + 1]);
        xh[n] = pack2(acc[4 * n + 2], acc[4 * n + 3]);
      }
      mbar_wait(bars + 8 * B_STGE, 0);
      PROF_AT(tid == 0, 49);
      float nb[2], rstd[2];
      {
        uint32_t st[8];
        const uint4* sp = p.stats2 + (rb * 8 + (lane >> 4) * 4) * 128 + cw * 64 + warp * 16 + (lane & 15);
        ll_poll<4>([&](int i) { return sp + i * 128; }, tag, st);
        float mu, rs;
        row_stats(st, mu, rs);
        mu *= -rs;
        nb[0] = __shfl_sync(~0u, mu, r); rstd[0] = __shfl_sync(~0u, rs, r);
        nb[1] = __shfl_sync(~0u, mu, r + 8); rstd[1] = __shfl_sync(~0u, rs, r + 8);
      }
      PROF_AT(tid == 0, 9);
#pragma unroll
      for (int ch = 0; ch < 2; ch++) {
        uint32_t lo[8], hi[8];
#pragma unroll
        for (int t = 0; t < 8; t++) {
          const int n = ch * 8 + t;
          lo[t] = pack2((acc[4 * n] * rstd[0] + nb[0]) * cb[n].x + sb[n].x, (acc[4 * n + 1] * rstd[0] + nb[0]) * cb[n].y + sb[n].y);
          hi[t] = pack2((acc[4 * n + 2] * rstd[1] + nb[1]) * cb[n].x + sb[n].x, (acc[4 * n + 3] * rstd[1] + nb[1]) * cb[n].y + sb[n].y);
        }
        stage_slab(stg + ch * 16384 + cw * 8192, warp, lane, lo, hi);
        stage_done(bars + 8 * (B_STGF + ch), lane);
      }
      wg_bar(cw);
      PROF_AT(tid == 0, 10);
    }

    uint32_t pg[32], pu[32];
    {
      RING_IDS();
      LANE_IDS();
      Ring g{bars + 8 * B_FG, rbars + 8 * B_EG, 0, 0u, releaser TR(48)};
      float acc[128];
      {
        uint32_t prev = 0;
        uint4* x1p = p.x1 + (size_t)(rb * 128 + (tid >> 4)) * 128 + j * 16 + (tid & 15);
#pragma unroll 1
        for (int kb = 0; kb < 16; kb++) {
          kblock<256, 4, 49152>(acc, g, a_base + (kb < 2 ? STG_OFF + kb * 16384 : g.s * 49152), kb == 0, prev);
          if (kb == 5) {
#pragma unroll
            for (int q = 0; q < 4; q++) x1p[q * 2048] = make_uint4(xl[4 * q], xl[4 * q + 1], xl[4 * q + 2], xl[4 * q + 3]);
          }
          if (kb == 8) {
#pragma unroll
            for (int q = 0; q < 4; q++) x1p[(4 + q) * 2048] = make_uint4(xh[4 * q], xh[4 * q + 1], xh[4 * q + 2], xh[4 * q + 3]);
          }
        }
        tile_end(acc, prev);
      }
      PROF_AT(tid == 0, 36);
#pragma unroll 1
      for (int t = 1; t < 3; t++) {
#pragma unroll
        for (int q = 0; q < 32; q++) {
          pg[q] = pack2(acc[2 * q], acc[2 * q + 1]);
          pu[q] = pack2(acc[64 + 2 * q], acc[64 + 2 * q + 1]);
        }
        uint32_t prev = 0;
#pragma unroll 1
        for (int blk = 0; blk < 4; blk++) {
          g.s = 0;
#pragma unroll
          for (int i = 0; i < 4; i++) {
            kblock<256, 4, 49152>(acc, g, a_base + i * 49152, blk == 0 && i == 0, prev);
            if ((blk & 1) == 0 && i == 0) mbar_wait(bars + 8 * (B_STGE + (blk >> 1)), t & 1);
            stmatrix2(slab + (blk >> 1) * 16384 + (((srow & 7) ^ ((blk & 1) * 4 + i)) << 4), swiglu2(pg[2 * i], pu[2 * i]), swiglu2(pg[2 * i + 1], pu[2 * i + 1]));
          }
#pragma unroll
          for (int q = 0; q < 24; q++) { pg[q] = pg[q + 8]; pu[q] = pu[q + 8]; }
          if (blk & 1) stage_done(bars + 8 * (B_STGF + (blk >> 1)), lane);
        }
        tile_end(acc, prev);
        PROF_AT(tid == 0, 36 + t);
      }
#pragma unroll
      for (int q = 0; q < 32; q++) {
        pg[q] = pack2(acc[2 * q], acc[2 * q + 1]);
        pu[q] = pack2(acc[64 + 2 * q], acc[64 + 2 * q + 1]);
      }
      PROF_AT(tid == 0, 11);
    }

    {
      RING_IDS();
      LANE_IDS();
      Ring g{bars + 8 * B_FD, rbars + 8 * B_ED, 0, 0u, releaser TR(96)};
      float acc[64];
      uint32_t prev = 0;
#pragma unroll 1
      for (int blk = 0; blk < 6; blk++) {
#pragma unroll
        for (int i = 0; i < 8; i++) {
          kblock<128, 6, 32768>(acc, g, a_base + g.s * 32768, (blk & ~2) == 0 && i == 0, prev);
          if ((blk & 1) == 0 && i == 0) mbar_wait(bars + 8 * (B_STGE + ((blk >> 1) & 1)), blk < 4);
          stmatrix1(slab + ((blk >> 1) & 1) * 16384 + (i & 1) * 1024 + (((srow & 7) ^ ((blk & 1) * 4 + (i >> 1))) << 4), swiglu2(pg[i], pu[i]));
        }
#pragma unroll
        for (int q = 0; q < 24; q++) { pg[q] = pg[q + 8]; pu[q] = pu[q + 8]; }
        if (blk & 1) stage_done(bars + 8 * (B_STGF + ((blk >> 1) & 1)), lane);
        if (blk == 1) {
          tile_end(acc, prev);
          PROF_AT(tid == 0, 39);
#pragma unroll
          for (int q = 0; q < 16; q++) {
            pg[16 + q] = pack2(acc[2 * q], acc[2 * q + 1]);
            pu[16 + q] = pack2(acc[32 + 2 * q], acc[32 + 2 * q + 1]);
          }
          PROF_AT(tid == 0, 12);
        }
      }
      uint4 x1[8];
      const int ft = fresh_tid() - 128;
      const uint4* x1p = p.x1 + (size_t)(rb * 128 + (ft >> 4)) * 128 + j * 16 + (ft & 15);
#pragma unroll
      for (int q = 0; q < 2; q++) {
#pragma unroll
        for (int e = 0; e < 4; e++) x1[4 * q + e] = ll_peek(x1p + (4 * q + e) * 2048);
#pragma unroll 1
        for (int kb = 0; kb < 12; kb++) kblock<128, 6, 32768>(acc, g, a_base + g.s * 32768, false, prev);
      }
      mbar_wait(bars + 8 * (B_MODB + 1), 0);
      mbar_wait(bars + 8 * B_STGE, 1);
      mbar_wait(bars + 8 * (B_STGE + 1), 0);
      float2 gbv[16];
#pragma unroll
      for (int n = 0; n < 16; n++) gbv[n] = lds64f(sm + MODB_OFF + (384 + 8 * n + 2 * c) * 4);
      tile_end(acc, prev);
      PROF_AT(tid == 0, 13);
#pragma unroll
      for (int ch = 0; ch < 2; ch++) {
        uint32_t lo[8], hi[8];
#pragma unroll
        for (int t = 0; t < 8; t++) {
          const int n = ch * 8 + t;
          const float2 gb = gbv[n];
          const uint4 a = x1[n >> 2], b = x1[4 + (n >> 2)];
          const uint32_t xl = (n & 3) == 0 ? a.x : (n & 3) == 1 ? a.y : (n & 3) == 2 ? a.z : a.w;
          const uint32_t xh = (n & 3) == 0 ? b.x : (n & 3) == 1 ? b.y : (n & 3) == 2 ? b.z : b.w;
          lo[t] = pack2(bf_lo(xl) + gb.x * acc[4 * n], bf_hi(xl) + gb.y * acc[4 * n + 1]);
          hi[t] = pack2(bf_lo(xh) + gb.x * acc[4 * n + 2], bf_hi(xh) + gb.y * acc[4 * n + 3]);
        }
        stage_slab(stg + ch * 16384 + cw * 8192, warp, lane, lo, hi);
        stage_done(bars + 8 * (B_STGF + ch), lane);
      }
      PROF_AT(tid == 0, 14);
    }
    if (blockIdx.x == 0 && threadIdx.x == 128) asm volatile("st.relaxed.gpu.global.u32 [%0], %1;" ::"l"(p.epoch), "r"(tag) : "memory");
    __syncwarp();
    cluster_arrive_relaxed();
    cluster_wait();
  }
}

typedef CUresult (*EncodeFn)(CUtensorMap*, CUtensorMapDataType, cuuint32_t, void*, const cuuint64_t*, const cuuint64_t*,
                             const cuuint32_t*, const cuuint32_t*, CUtensorMapInterleave, CUtensorMapSwizzle,
                             CUtensorMapL2promotion, CUtensorMapFloatOOBfill);

void encode2d(EncodeFn fn, CUtensorMap* m, const void* ptr, uint64_t cols, uint64_t rows, uint32_t box_rows) {
  cuuint64_t dims[2] = {cols, rows};
  cuuint64_t strides[1] = {cols * 2};
  cuuint32_t box[2] = {64, box_rows};
  cuuint32_t es[2] = {1, 1};
  fn(m, CU_TENSOR_MAP_DATA_TYPE_BFLOAT16, 2, (void*)ptr, dims, strides, box, es, CU_TENSOR_MAP_INTERLEAVE_NONE,
     CU_TENSOR_MAP_SWIZZLE_128B, CU_TENSOR_MAP_L2_PROMOTION_L2_128B, CU_TENSOR_MAP_FLOAT_OOB_FILL_NONE);
}

}

extern "C" void kernel_launch(void* const* d_in, const int* in_sizes, int n_in, void* d_out, int out_size) {
  (void)in_sizes; (void)n_in; (void)out_size;
  void* fp = nullptr;
  cudaDriverEntryPointQueryResult qr;
  cudaGetDriverEntryPoint("cuTensorMapEncodeTiled", &fp, cudaEnableDefault, &qr);
  EncodeFn fn = (EncodeFn)fp;
  void *ph, *po, *ph2, *pact;
  cudaGetSymbolAddress(&ph, g_h);
  cudaGetSymbolAddress(&po, g_o);
  ph2 = ph;
  cudaGetSymbolAddress(&pact, g_act);
  Params p;
  encode2d(fn, &p.h, ph, DM, SEQ, 128);
  encode2d(fn, &p.o_ld, po, DM, SEQ, 128);
  encode2d(fn, &p.h2, ph2, DM, SEQ, 128);
  encode2d(fn, &p.act, pact, FF, SEQ, 128);
  encode2d(fn, &p.act_st, pact, FF, SEQ, 32);
  encode2d(fn, &p.wm, d_in[8], 6 * DM, DM, 64);
  encode2d(fn, &p.o_st, po, DM, SEQ, 32);
  encode2d(fn, &p.wqkv, d_in[1], 3 * DM, DM, 64);
  encode2d(fn, &p.wqkv32, d_in[1], 3 * DM, DM, 32);
  encode2d(fn, &p.wo, d_in[2], DM, DM, 64);
  encode2d(fn, &p.wg, d_in[4], FF, DM, 64);
  encode2d(fn, &p.wu, d_in[5], FF, DM, 64);
  encode2d(fn, &p.wd, d_in[6], DM, FF, 64);
  {
    cuuint64_t dims[3] = {DM, SEQ / 2, 2};
    cuuint64_t strides[2] = {DM * 4, DM * 2};
    cuuint32_t box[3] = {64, 64, 2};
    cuuint32_t es[3] = {1, 1, 1};
    fn(&p.out, CU_TENSOR_MAP_DATA_TYPE_BFLOAT16, 3, d_out, dims, strides, box, es, CU_TENSOR_MAP_INTERLEAVE_NONE,
       CU_TENSOR_MAP_SWIZZLE_128B, CU_TENSOR_MAP_L2_PROMOTION_L2_128B, CU_TENSOR_MAP_FLOAT_OOB_FILL_NONE);
  }
  p.x = (const bf16*)d_in[0];
  p.c = (const bf16*)d_in[7];
  p.wmod = (const bf16*)d_in[8];
  for (int cl = 0; cl < 64; cl++) {
    const int grp = cl < 4 ? 0 : (cl < 36 ? (cl - 4) & 7 : 1 + (cl - 36) % 7);
    const int j = cl < 4 ? 4 + cl : (cl < 36 ? (cl - 4) >> 3 : 4 + (cl - 36) / 7);
    p.slot[cl] = (uint8_t)(grp * 8 + j);
  }
  void* q;
  p.x1 = (uint4*)d_out;
  cudaGetSymbolAddress(&q, g_modll); p.modll = (uint4*)q;
  cudaGetSymbolAddress(&q, g_halo); p.halo = (uint4*)q;
  cudaGetSymbolAddress(&q, g_stats); p.stats1 = (uint4*)q; p.stats2 = p.stats1 + SEQ * 8;
  cudaGetSymbolAddress(&q, g_cnt); p.cnt = (unsigned*)q;
  cudaGetSymbolAddress(&q, g_epoch); p.epoch = (unsigned*)q;

  cudaFuncSetAttribute(fused_kernel, cudaFuncAttributeMaxDynamicSharedMemorySize, SMEM_BYTES);
  cudaLaunchConfig_t cfg = {};
  cfg.gridDim = dim3(NCTA + 4);
  cfg.blockDim = dim3(384);
  cfg.dynamicSmemBytes = SMEM_BYTES;
  cfg.stream = cudaStreamPerThread;
  cudaLaunchAttribute at[1];
  at[0].id = cudaLaunchAttributeClusterDimension;
  at[0].val.clusterDim.x = 2; at[0].val.clusterDim.y = 1; at[0].val.clusterDim.z = 1;
  cfg.attrs = at;
  cfg.numAttrs = 1;
  cudaLaunchKernelEx(&cfg, fused_kernel, p);
}
```

```cpp
#include <cuda_runtime.h>
#include <cuda_bf16.h>
#include <cuda.h>
#include <stdint.h>

typedef __nv_bfloat16 bf16;

#define MAPPING 2

#define ALIGN 0

#define PF 0

#define EF 1

#define ALIGNE 3

#define CW 1

#define PAUSE 200

#define WMD 2

#define WMDELAY 2000

#define WMPACE 0

#define NPRE0 4

#define NPRE1 2
#define GATE 0

#define WFIRST 1

#define BDELAY 1500

#define ALIAS 1

#define PB1 0
#define PB2 0

__device__ __forceinline__ void wgmma_ss_n128(float (&d)[64], uint32_t da, uint32_t db, int scale_d) {
  asm volatile("{\n.reg .pred p;\n.reg .b64 da, db;\nsetp.ne.b32 p, %66, 0;\n"
    "mov.b64 da, {%64, 0x40000040};\nmov.b64 db, {%65, 0x40000040};\n"
    "wgmma.mma_async.sync.aligned.m64n128k16.f32.bf16.bf16 "
    "{%0, %1, %2, %3, %4, %5, %6, %7, %8, %9, %10, %11, %12, %13, %14, %15, "
    "%16, %17, %18, %19, %20, %21, %22, %23, %24, %25, %26, %27, %28, %29, %30, %31, "
    "%32, %33, %34, %35, %36, %37, %38, %39, %40, %41, %42, %43, %44, %45, %46, %47, "
    "%48, %49, %50, %51, %52, %53, %54, %55, %56, %57, %58, %59, %60, %61, %62, %63}, "
    "da, db, p, 1, 1, 0, 1;\n}\n"
    : "+f"(d[0]), "+f"(d[1]), "+f"(d[2]), "+f"(d[3]), "+f"(d[4]), "+f"(d[5]), "+f"(d[6]), "+f"(d[7]),
      "+f"(d[8]), "+f"(d[9]), "+f"(d[10]), "+f"(d[11]), "+f"(d[12]), "+f"(d[13]), "+f"(d[14]), "+f"(d[15]),
      "+f"(d[16]), "+f"(d[17]), "+f"(d[18]), "+f"(d[19]), "+f"(d[20]), "+f"(d[21]), "+f"(d[22]), "+f"(d[23]),
      "+f"(d[24]), "+f"(d[25]), "+f"(d[26]), "+f"(d[27]), "+f"(d[28]), "+f"(d[29]), "+f"(d[30]), "+f"(d[31]),
      "+f"(d[32]), "+f"(d[33]), "+f"(d[34]), "+f"(d[35]), "+f"(d[36]), "+f"(d[37]), "+f"(d[38]), "+f"(d[39]),
      "+f"(d[40]), "+f"(d[41]), "+f"(d[42]), "+f"(d[43]), "+f"(d[44]), "+f"(d[45]), "+f"(d[46]), "+f"(d[47]),
      "+f"(d[48]), "+f"(d[49]), "+f"(d[50]), "+f"(d[51]), "+f"(d[52]), "+f"(d[53]), "+f"(d[54]), "+f"(d[55]),
      "+f"(d[56]), "+f"(d[57]), "+f"(d[58]), "+f"(d[59]), "+f"(d[60]), "+f"(d[61]), "+f"(d[62]), "+f"(d[63])
    : "r"(da), "r"(db), "r"(scale_d));
}

__device__ __forceinline__ void wgmma_ss_n192(float (&d)[96], uint32_t da, uint32_t db, int scale_d) {
  asm volatile("{\n.reg .pred p;\n.reg .b64 da, db;\nsetp.ne.b32 p, %98, 0;\n"
    "mov.b64 da, {%96, 0x40000040};\nmov.b64 db, {%97, 0x40000040};\n"
    "wgmma.mma_async.sync.aligned.m64n192k16.f32.bf16.bf16 "
    "{%0, %1, %2, %3, %4, %5, %6, %7, %8, %9, %10, %11, %12, %13, %14, %15, "
    "%16, %17, %18, %19, %20, %21, %22, %23, %24, %25, %26, %27, %28, %29, %30, %31, "
    "%32, %33, %34, %35, %36, %37, %38, %39, %40, %41, %42, %43, %44, %45, %46, %47, "
    "%48, %49, %50, %51, %52, %53, %54, %55, %56, %57, %58, %59, %60, %61, %62, %63, "
    "%64, %65, %66, %67, %68, %69, %70, %71, %72, %73, %74, %75, %76, %77, %78, %79, "
    "%80, %81, %82, %83, %84, %85, %86, %87, %88, %89, %90, %91, %92, %93, %94, %95}, "
    "da, db, p, 1, 1, 0, 1;\n}\n"
    : "+f"(d[0]), "+f"(d[1]), "+f"(d[2]), "+f"(d[3]), "+f"(d[4]), "+f"(d[5]), "+f"(d[6]), "+f"(d[7]),
      "+f"(d[8]), "+f"(d[9]), "+f"(d[10]), "+f"(d[11]), "+f"(d[12]), "+f"(d[13]), "+f"(d[14]), "+f"(d[15]),
      "+f"(d[16]), "+f"(d[17]), "+f"(d[18]), "+f"(d[19]), "+f"(d[20]), "+f"(d[21]), "+f"(d[22]), "+f"(d[23]),
      "+f"(d[24]), "+f"(d[25]), "+f"(d[26]), "+f"(d[27]), "+f"(d[28]), "+f"(d[29]), "+f"(d[30]), "+f"(d[31]),
      "+f"(d[32]), "+f"(d[33]), "+f"(d[34]), "+f"(d[35]), "+f"(d[36]), "+f"(d[37]), "+f"(d[38]), "+f"(d[39]),
      "+f"(d[40]), "+f"(d[41]), "+f"(d[42]), "+f"(d[43]), "+f"(d[44]), "+f"(d[45]), "+f"(d[46]), "+f"(d[47]),
      "+f"(d[48]), "+f"(d[49]), "+f"(d[50]), "+f"(d[51]), "+f"(d[52]), "+f"(d[53]), "+f"(d[54]), "+f"(d[55]),
      "+f"(d[56]), "+f"(d[57]), "+f"(d[58]), "+f"(d[59]), "+f"(d[60]), "+f"(d[61]), "+f"(d[62]), "+f"(d[63]),
      "+f"(d[64]), "+f"(d[65]), "+f"(d[66]), "+f"(d[67]), "+f"(d[68]), "+f"(d[69]), "+f"(d[70]), "+f"(d[71]),
      "+f"(d[72]), "+f"(d[73]), "+f"(d[74]), "+f"(d[75]), "+f"(d[76]), "+f"(d[77]), "+f"(d[78]), "+f"(d[79]),
      "+f"(d[80]), "+f"(d[81]), "+f"(d[82]), "+f"(d[83]), "+f"(d[84]), "+f"(d[85]), "+f"(d[86]), "+f"(d[87]),
      "+f"(d[88]), "+f"(d[89]), "+f"(d[90]), "+f"(d[91]), "+f"(d[92]), "+f"(d[93]), "+f"(d[94]), "+f"(d[95])
    : "r"(da), "r"(db), "r"(scale_d));
}

__device__ __forceinline__ void wgmma_ss_n256(float (&d)[128], uint32_t da, uint32_t db, int scale_d) {
  asm volatile("{\n.reg .pred p;\n.reg .b64 da, db;\nsetp.ne.b32 p, %130, 0;\n"
    "mov.b64 da, {%128, 0x40000040};\nmov.b64 db, {%129, 0x40000040};\n"
    "wgmma.mma_async.sync.aligned.m64n256k16.f32.bf16.bf16 "
    "{%0, %1, %2, %3, %4, %5, %6, %7, %8, %9, %10, %11, %12, %13, %14, %15, "
    "%16, %17, %18, %19, %20, %21, %22, %23, %24, %25, %26, %27, %28, %29, %30, %31, "
    "%32, %33, %34, %35, %36, %37, %38, %39, %40, %41, %42, %43, %44, %45, %46, %47, "
    "%48, %49, %50, %51, %52, %53, %54, %55, %56, %57, %58, %59, %60, %61, %62, %63, "
    "%64, %65, %66, %67, %68, %69, %70, %71, %72, %73, %74, %75, %76, %77, %78, %79, "
    "%80, %81, %82, %83, %84, %85, %86, %87, %88, %89, %90, %91, %92, %93, %94, %95, "
    "%96, %97, %98, %99, %100, %101, %102, %103, %104, %105, %106, %107, %108, %109, %110, %111, "
    "%112, %113, %114, %115, %116, %117, %118, %119, %120, %121, %122, %123, %124, %125, %126, %127}, "
    "da, db, p, 1, 1, 0, 1;\n}\n"
    : "+f"(d[0]), "+f"(d[1]), "+f"(d[2]), "+f"(d[3]), "+f"(d[4]), "+f"(d[5]), "+f"(d[6]), "+f"(d[7]),
      "+f"(d[8]), "+f"(d[9]), "+f"(d[10]), "+f"(d[11]), "+f"(d[12]), "+f"(d[13]), "+f"(d[14]), "+f"(d[15]),
      "+f"(d[16]), "+f"(d[17]), "+f"(d[18]), "+f"(d[19]), "+f"(d[20]), "+f"(d[21]), "+f"(d[22]), "+f"(d[23]),
      "+f"(d[24]), "+f"(d[25]), "+f"(d[26]), "+f"(d[27]), "+f"(d[28]), "+f"(d[29]), "+f"(d[30]), "+f"(d[31]),
      "+f"(d[32]), "+f"(d[33]), "+f"(d[34]), "+f"(d[35]), "+f"(d[36]), "+f"(d[37]), "+f"(d[38]), "+f"(d[39]),
      "+f"(d[40]), "+f"(d[41]), "+f"(d[42]), "+f"(d[43]), "+f"(d[44]), "+f"(d[45]), "+f"(d[46]), "+f"(d[47]),
      "+f"(d[48]), "+f"(d[49]), "+f"(d[50]), "+f"(d[51]), "+f"(d[52]), "+f"(d[53]), "+f"(d[54]), "+f"(d[55]),
      "+f"(d[56]), "+f"(d[57]), "+f"(d[58]), "+f"(d[59]), "+f"(d[60]), "+f"(d[61]), "+f"(d[62]), "+f"(d[63]),
      "+f"(d[64]), "+f"(d[65]), "+f"(d[66]), "+f"(d[67]), "+f"(d[68]), "+f"(d[69]), "+f"(d[70]), "+f"(d[71]),
      "+f"(d[72]), "+f"(d[73]), "+f"(d[74]), "+f"(d[75]), "+f"(d[76]), "+f"(d[77]), "+f"(d[78]), "+f"(d[79]),
      "+f"(d[80]), "+f"(d[81]), "+f"(d[82]), "+f"(d[83]), "+f"(d[84]), "+f"(d[85]), "+f"(d[86]), "+f"(d[87]),
      "+f"(d[88]), "+f"(d[89]), "+f"(d[90]), "+f"(d[91]), "+f"(d[92]), "+f"(d[93]), "+f"(d[94]), "+f"(d[95]),
      "+f"(d[96]), "+f"(d[97]), "+f"(d[98]), "+f"(d[99]), "+f"(d[100]), "+f"(d[101]), "+f"(d[102]), "+f"(d[103]),
      "+f"(d[104]), "+f"(d[105]), "+f"(d[106]), "+f"(d[107]), "+f"(d[108]), "+f"(d[109]), "+f"(d[110]), "+f"(d[111]),
      "+f"(d[112]), "+f"(d[113]), "+f"(d[114]), "+f"(d[115]), "+f"(d[116]), "+f"(d[117]), "+f"(d[118]), "+f"(d[119]),
      "+f"(d[120]), "+f"(d[121]), "+f"(d[122]), "+f"(d[123]), "+f"(d[124]), "+f"(d[125]), "+f"(d[126]), "+f"(d[127])
    : "r"(da), "r"(db), "r"(scale_d));
}

namespace {

constexpr int SEQ = 2048, DM = 1024, FF = 3584;
constexpr int NCTA = 128;

constexpr uint32_t STG_OFF = 196608;
constexpr uint32_t MISC_OFF = STG_OFF + 32768;
constexpr uint32_t SMEM_BYTES = MISC_OFF + 3072;
constexpr uint32_t RED_OFF = 2 * 49152;
constexpr uint32_t MODB_OFF = MISC_OFF + 512;

enum { B_FQ = 0, B_EQ = 4, B_FW = 8, B_EW = 14, B_FG = 20, B_EG = 24, B_FD = 28, B_ED = 34,
       B_STGF = 40, B_MODB = 42, B_GATE = 44, B_MODA = 45, B_RDY = 48, B_STGE = 56, B_COUNT = 58 };
enum { C_H = 0, C_O = 1, C_H2 = 3, C_ACT = 4, C_AL = 8 };

struct Params {
  CUtensorMap h, o_ld, o_st, h2, act, out, wqkv, wqkv32, wo, wg, wu, wd, act_st, wm;
  const bf16* x;
  const bf16* c;
  const bf16* wmod;
  uint4* x1;
  uint4* modll;
  uint4* halo;
  uint4* stats1;
  uint4* stats2;
  unsigned* cnt;
  unsigned* epoch;
  uint8_t slot[64];
};

__device__ bf16 g_h[SEQ * DM];
__device__ bf16 g_o[SEQ * DM];
__device__ bf16 g_h2[SEQ * DM];
__device__ bf16 g_act[SEQ * FF];
__device__ uint4 g_x1[NCTA * 8 * 256];
__device__ uint4 g_modll[3072 / 2];
__device__ uint4 g_halo[16 * 8 * 2 * 2 * 8 * 32];
__device__ uint4 g_stats[2 * SEQ * 8];
__device__ unsigned g_cnt[16 * 32];
__device__ uint4 g_epoch;
#define TR(off)

__device__ __forceinline__ uint32_t smem_u32(const void* p) { return (uint32_t)__cvta_generic_to_shared(p); }
__device__ __forceinline__ void mbar_init(uint32_t bar, uint32_t count) {
  asm volatile("mbarrier.init.shared::cta.b64 [%0], %1;" ::"r"(bar), "r"(count));
}
__device__ __forceinline__ void mbar_expect_tx(uint32_t bar, uint32_t bytes) {
  asm volatile("mbarrier.arrive.expect_tx.shared::cta.b64 _, [%0], %1;" ::"r"(bar), "r"(bytes) : "memory");
}
__device__ __forceinline__ void mbar_arrive(uint32_t bar) {
  asm volatile("mbarrier.arrive.shared::cta.b64 _, [%0];" ::"r"(bar) : "memory");
}
__device__ __forceinline__ void mbar_arrive_cluster(uint32_t cluster_addr) {
  asm volatile("mbarrier.arrive.shared::cluster.b64 _, [%0];" ::"r"(cluster_addr) : "memory");
}
__device__ __forceinline__ uint32_t mapa(uint32_t addr, uint32_t cta) {
  uint32_t r;
  asm volatile("mapa.shared::cluster.u32 %0, %1, %2;" : "=r"(r) : "r"(addr), "r"(cta));
  return r;
}
__device__ __forceinline__ void mbar_wait(uint32_t bar, uint32_t parity) {
  asm volatile(
      "{\n.reg .pred p;\n"
      "WAIT_%=:\n"
      "mbarrier.try_wait.parity.shared::cta.b64 p, [%0], %1;\n"
      "@!p bra WAIT_%=;\n}\n" ::"r"(bar), "r"(parity) : "memory");
}
__device__ __forceinline__ void mbar_wait_watchdog(uint32_t bar, uint32_t parity) {
  asm volatile(
      "{\n.reg .pred p;\n.reg .u64 t0, t1;\nmov.u64 t0, %%globaltimer;\n"
      "WAIT_%=:\n"
      "mbarrier.try_wait.parity.shared::cta.b64 p, [%0], %1;\n"
      "@p bra DONE_%=;\n"
      "mov.u64 t1, %%globaltimer;\n"
      "sub.u64 t1, t1, t0;\n"
      "setp.lt.u64 p, t1, 2000000000;\n"
      "@p bra WAIT_%=;\n"
      "trap;\n"
      "DONE_%=:\n}\n" ::"r"(bar), "r"(parity) : "memory");
}
__device__ __forceinline__ void cnt_wait(const unsigned* p, unsigned target) {
  asm volatile(
      "{\n.reg .pred p;\n.reg .u32 v;\n.reg .s32 d;\n"
      "WAIT_%=:\n"
      "ld.relaxed.gpu.global.u32 v, [%0];\n"
      "sub.s32 d, v, %1;\n"
      "setp.lt.s32 p, d, 0;\n"
      "@p bra WAIT_%=;\n"
      "fence.proxy.async.global;\n"
      "}\n" ::"l"(p), "r"(target) : "memory");
}
__device__ __forceinline__ void cnt_wait_lazy(const unsigned* p, unsigned target) {
  asm volatile(
      "{\n.reg .pred p;\n.reg .u32 v;\n.reg .s32 d;\n"
      "WAIT_%=:\n"
      "nanosleep.u32 400;\n"
      "ld.relaxed.gpu.global.u32 v, [%0];\n"
      "sub.s32 d, v, %1;\n"
      "setp.lt.s32 p, d, 0;\n"
      "@p bra WAIT_%=;\n"
      "fence.proxy.async.global;\n"
      "}\n" ::"l"(p), "r"(target) : "memory");
}
__device__ __forceinline__ void cnt_signal(unsigned* p) {
  asm volatile("{\n.reg .pred p;\nelect.sync _|p, 0xffffffff;\n@p red.relaxed.gpu.global.add.u32 [%0], 1;\n}\n" ::"l"(p) : "memory");
}
__device__ __forceinline__ void ll_store(uint4* p, uint32_t a, uint32_t b, uint32_t tag) {
  asm volatile("st.relaxed.gpu.global.v2.b64 [%0], {%1, %2};" ::"l"(p), "l"((uint64_t)a | ((uint64_t)tag << 32)),
               "l"((uint64_t)b | ((uint64_t)tag << 32)) : "memory");
}
__device__ __forceinline__ uint4 ll_peek(const uint4* p) {
  uint4 v;
  asm volatile("ld.relaxed.gpu.global.v4.u32 {%0, %1, %2, %3}, [%4];" : "=r"(v.x), "=r"(v.y), "=r"(v.z), "=r"(v.w) : "l"(p) : "memory");
  return v;
}
template <int N, int SLEEP = 0, class F>
__device__ __forceinline__ void ll_poll(F addr, uint32_t tag, uint32_t (&out)[2 * N]) {
  for (;;) {
    uint4 v[N];
#pragma unroll
    for (int i = 0; i < N; i++) v[i] = ll_peek(addr(i));
    uint32_t bad = 0;
#pragma unroll
    for (int i = 0; i < N; i++) {
      bad |= (v[i].y ^ tag) | (v[i].w ^ tag);
      out[2 * i] = v[i].x;
      out[2 * i + 1] = v[i].z;
    }
    if (__all_sync(~0u, bad == 0)) break;
    if (SLEEP) __nanosleep(SLEEP);
  }
}
constexpr uint64_t POLICY_EVICT_FIRST = 0x12F0000000000000ull;
__device__ __forceinline__ void expect_tx_elect(uint32_t bar, uint32_t bytes) {
  asm volatile("{\n.reg .pred p;\nelect.sync _|p, 0xffffffff;\n@p mbarrier.arrive.expect_tx.shared::cta.b64 _, [%0], %1;\n}\n" ::"r"(bar), "r"(bytes) : "memory");
}
__device__ __forceinline__ void arrive_elect(uint32_t bar) {
  asm volatile("{\n.reg .pred p;\nelect.sync _|p, 0xffffffff;\n@p mbarrier.arrive.shared::cta.b64 _, [%0];\n}\n" ::"r"(bar) : "memory");
}
__device__ __forceinline__ void tma_load(uint32_t dst, const CUtensorMap* m, uint32_t bar, int c0, int c1) {
  asm volatile("{\n.reg .pred p;\nelect.sync _|p, 0xffffffff;\n"
               "@p cp.async.bulk.tensor.2d.shared::cluster.global.mbarrier::complete_tx::bytes [%0], [%1, {%3, %4}], [%2];\n}\n"
               ::"r"(dst), "l"(m), "r"(bar), "r"(c0), "r"(c1) : "memory");
}
__device__ __forceinline__ void tma_load_mc(uint32_t dst, const CUtensorMap* m, uint32_t bar, int c0, int c1) {
  asm volatile("{\n.reg .pred p;\nelect.sync _|p, 0xffffffff;\n"
               "@p cp.async.bulk.tensor.2d.shared::cluster.global.mbarrier::complete_tx::bytes.multicast::cluster.L2::cache_hint [%0], [%1, {%3, %4}], [%2], %5, %6;\n}\n"
               ::"r"(dst), "l"(m), "r"(bar), "r"(c0), "r"(c1), "h"((uint16_t)3), "l"(POLICY_EVICT_FIRST) : "memory");
}
__device__ __forceinline__ void tma_load_ef(uint32_t dst, const CUtensorMap* m, uint32_t bar, int c0, int c1) {
  asm volatile("{\n.reg .pred p;\nelect.sync _|p, 0xffffffff;\n"
               "@p cp.async.bulk.tensor.2d.shared::cluster.global.mbarrier::complete_tx::bytes.L2::cache_hint [%0], [%1, {%3, %4}], [%2], %5;\n}\n"
               ::"r"(dst), "l"(m), "r"(bar), "r"(c0), "r"(c1), "l"(POLICY_EVICT_FIRST) : "memory");
}
__device__ __forceinline__ void tma_store2(const CUtensorMap* m, uint32_t src, int c0, int c1) {
  asm volatile("{\n.reg .pred p;\nelect.sync _|p, 0xffffffff;\n"
               "@p cp.async.bulk.tensor.2d.global.shared::cta.bulk_group [%0, {%2, %3}], [%1];\n}\n"
               ::"l"(m), "r"(src), "r"(c0), "r"(c1) : "memory");
}
__device__ __forceinline__ void tma_store3(const CUtensorMap* m, uint32_t src, int c0, int c1, int c2) {
  asm volatile("{\n.reg .pred p;\nelect.sync _|p, 0xffffffff;\n"
               "@p cp.async.bulk.tensor.3d.global.shared::cta.bulk_group [%0, {%2, %3, %4}], [%1];\n}\n"
               ::"l"(m), "r"(src), "r"(c0), "r"(c1), "r"(c2) : "memory");
}
__device__ __forceinline__ void store_pause(bool sleep) {
  asm volatile("cp.async.bulk.commit_group;" ::: "memory");
  asm volatile("cp.async.bulk.wait_group.read 0;" ::: "memory");
  if (sleep) __nanosleep(PAUSE);
}
__device__ __forceinline__ void l2_prefetch_tile(const CUtensorMap* m, int c0, int c1) {
  asm volatile("{\n.reg .pred p;\nelect.sync _|p, 0xffffffff;\n@p cp.async.bulk.prefetch.tensor.2d.L2.global.L2::cache_hint [%0, {%1, %2}], %3;\n}\n"
               ::"l"(m), "r"(c0), "r"(c1), "l"(POLICY_EVICT_FIRST) : "memory");
}
__device__ __forceinline__ void prefetch_map(const CUtensorMap* m) {
  asm volatile("prefetch.tensormap [%0];" ::"l"(m) : "memory");
}
__device__ __forceinline__ void wg_fence() { asm volatile("wgmma.fence.sync.aligned;" ::: "memory"); }
__device__ __forceinline__ void wg_commit() { asm volatile("wgmma.commit_group.sync.aligned;" ::: "memory"); }
template <int N>
__device__ __forceinline__ void wg_wait() { asm volatile("wgmma.wait_group.sync.aligned %0;" ::"n"(N) : "memory"); }
__device__ __forceinline__ void bar_sync(int id, int n) { asm volatile("bar.sync %0, %1;" ::"r"(id), "r"(n) : "memory"); }
__device__ __forceinline__ void wg_bar(int cw) {
  asm volatile("{\n.reg .pred p;\nsetp.ne.s32 p, %0, 0;\n@p bar.sync 3, 128;\n@!p bar.sync 2, 128;\n}\n" ::"r"(cw) : "memory");
}
__device__ __forceinline__ void cluster_arrive() { asm volatile("barrier.cluster.arrive.release.aligned;" ::: "memory"); }
__device__ __forceinline__ void cluster_arrive_relaxed() { asm volatile("barrier.cluster.arrive.relaxed.aligned;" ::: "memory"); }
__device__ __forceinline__ void cluster_wait() { asm volatile("barrier.cluster.wait.acquire.aligned;" ::: "memory"); }
__device__ __forceinline__ uint32_t load_epoch(const unsigned* p) {
  uint32_t e;
  asm volatile("ld.relaxed.gpu.global.u32 %0, [%1];" : "=r"(e) : "l"(p) : "memory");
  return e;
}
__device__ __forceinline__ uint32_t pack2(float lo, float hi) {
  uint32_t r;
  asm("cvt.rn.bf16x2.f32 %0, %1, %2;" : "=r"(r) : "f"(hi), "f"(lo));
  return r;
}
__device__ __forceinline__ float bf_lo(uint32_t v) { return __uint_as_float(v << 16); }
__device__ __forceinline__ float bf_hi(uint32_t v) { return __uint_as_float(v & 0xffff0000u); }
__device__ __forceinline__ float bf_round(float v) { return __bfloat162float(__float2bfloat16_rn(v)); }
__device__ __forceinline__ float silu_f(float v) { return __fdividef(v, 1.0f + __expf(-v)); }
__device__ __forceinline__ uint4 ldg_nc(const void* p) {
  uint4 v;
  asm volatile("ld.global.nc.L1::no_allocate.v4.u32 {%0, %1, %2, %3}, [%4];" : "=r"(v.x), "=r"(v.y), "=r"(v.z), "=r"(v.w) : "l"(p));
  return v;
}
__device__ __forceinline__ uint4 ldg_stream(const void* p) {
  uint4 v;
  asm volatile("ld.global.nc.L1::no_allocate.L2::cache_hint.v4.u32 {%0, %1, %2, %3}, [%4], %5;" : "=r"(v.x), "=r"(v.y), "=r"(v.z), "=r"(v.w) : "l"(p), "l"(POLICY_EVICT_FIRST));
  return v;
}
__device__ __forceinline__ uint32_t ldg32(const void* p) {
  uint32_t v;
  asm volatile("ld.global.nc.u32 %0, [%1];" : "=r"(v) : "l"(p));
  return v;
}
__device__ __forceinline__ void stmatrix4(uint32_t addr, uint32_t a, uint32_t b, uint32_t c, uint32_t d) {
  asm volatile("stmatrix.sync.aligned.m8n8.x4.shared.b16 [%0], {%1, %2, %3, %4};" ::"r"(addr), "r"(a), "r"(b), "r"(c), "r"(d) : "memory");
}
__device__ __forceinline__ void stmatrix2(uint32_t addr, uint32_t a, uint32_t b) {
  asm volatile("stmatrix.sync.aligned.m8n8.x2.shared.b16 [%0], {%1, %2};" ::"r"(addr), "r"(a), "r"(b) : "memory");
}
__device__ __forceinline__ void stmatrix1(uint32_t addr, uint32_t a) {
  asm volatile("stmatrix.sync.aligned.m8n8.x1.shared.b16 [%0], {%1};" ::"r"(addr), "r"(a) : "memory");
}
__device__ __forceinline__ uint32_t movmatrix(uint32_t a) {
  uint32_t d;
  asm("movmatrix.sync.aligned.m8n8.trans.b16 %0, %1;" : "=r"(d) : "r"(a));
  return d;
}
__device__ __forceinline__ void mma16816(float (&d)[4], uint32_t a0, uint32_t a1, uint32_t a2, uint32_t a3, uint32_t b0, uint32_t b1) {
  asm("mma.sync.aligned.m16n8k16.row.col.f32.bf16.bf16.f32 {%0, %1, %2, %3}, {%4, %5, %6, %7}, {%8, %9}, {%0, %1, %2, %3};"
               : "+f"(d[0]), "+f"(d[1]), "+f"(d[2]), "+f"(d[3]) : "r"(a0), "r"(a1), "r"(a2), "r"(a3), "r"(b0), "r"(b1));
}
__device__ __forceinline__ void mma1688(float (&d)[4], uint32_t a0, uint32_t a1, uint32_t b0) {
  asm("mma.sync.aligned.m16n8k8.row.col.f32.bf16.bf16.f32 {%0, %1, %2, %3}, {%4, %5}, {%6}, {%0, %1, %2, %3};"
               : "+f"(d[0]), "+f"(d[1]), "+f"(d[2]), "+f"(d[3]) : "r"(a0), "r"(a1), "r"(b0));
}
__device__ __forceinline__ void ldmatrix4t(uint32_t (&b)[4], uint32_t addr) {
  asm volatile("ldmatrix.sync.aligned.m8n8.x4.trans.shared.b16 {%0, %1, %2, %3}, [%4];" : "=r"(b[0]), "=r"(b[1]), "=r"(b[2]), "=r"(b[3]) : "r"(addr) : "memory");
}
__device__ __forceinline__ void ldmatrix4(uint32_t& a, uint32_t& b, uint32_t& c, uint32_t& d, uint32_t addr) {
  asm volatile("ldmatrix.sync.aligned.m8n8.x4.shared.b16 {%0, %1, %2, %3}, [%4];" : "=r"(a), "=r"(b), "=r"(c), "=r"(d) : "r"(addr) : "memory");
}
__device__ __forceinline__ void cp_async16(uint32_t dst, const void* src) {
  asm volatile("cp.async.cg.shared.global.L2::cache_hint [%0], [%1], 16, %2;" ::"r"(dst), "l"(src), "l"(POLICY_EVICT_FIRST) : "memory");
}
__device__ __forceinline__ uint32_t lds32(uint32_t addr) {
  uint32_t v;
  asm volatile("ld.shared.u32 %0, [%1];" : "=r"(v) : "r"(addr) : "memory");
  return v;
}
__device__ __forceinline__ void sts64f(uint32_t addr, float a, float b) {
  asm volatile("st.shared.v2.f32 [%0], {%1, %2};" ::"r"(addr), "f"(a), "f"(b) : "memory");
}
constexpr float QK_SCALE = 0.17677669529663687f;
__device__ __forceinline__ void softmax8(float& p0, float& p1) {
  float m = fmaxf(p0, p1);
  m = fmaxf(m, __shfl_xor_sync(~0u, m, 1));
  m = fmaxf(m, __shfl_xor_sync(~0u, m, 2));
  asm("ex2.approx.ftz.f32 %0, %1;" : "=f"(p0) : "f"((p0 - m) * 1.4426950408889634f));
  asm("ex2.approx.ftz.f32 %0, %1;" : "=f"(p1) : "f"((p1 - m) * 1.4426950408889634f));
  float s = p0 + p1;
  s += __shfl_xor_sync(~0u, s, 1);
  s += __shfl_xor_sync(~0u, s, 2);
  float r;
  asm("rcp.approx.ftz.f32 %0, %1;" : "=f"(r) : "f"(s));
  p0 *= r;
  p1 *= r;
}
__device__ __forceinline__ void sts128(uint32_t addr, uint32_t a, uint32_t b, uint32_t c, uint32_t d) {
  asm volatile("st.shared.v4.u32 [%0], {%1, %2, %3, %4};" ::"r"(addr), "r"(a), "r"(b), "r"(c), "r"(d) : "memory");
}
__device__ __forceinline__ uint4 lds128(uint32_t addr) {
  uint4 v;
  asm volatile("ld.shared.v4.u32 {%0, %1, %2, %3}, [%4];" : "=r"(v.x), "=r"(v.y), "=r"(v.z), "=r"(v.w) : "r"(addr) : "memory");
  return v;
}
__device__ __forceinline__ float2 lds64f(uint32_t addr) {
  float2 v;
  asm volatile("ld.shared.v2.f32 {%0, %1}, [%2];" : "=f"(v.x), "=f"(v.y) : "r"(addr) : "memory");
  return v;
}
__device__ __forceinline__ void sts32f(uint32_t addr, float v) {
  asm volatile("st.shared.f32 [%0], %1;" ::"r"(addr), "f"(v) : "memory");
}
__device__ __forceinline__ float lds32f(uint32_t addr) {
  float v;
  asm volatile("ld.shared.f32 %0, [%1];" : "=f"(v) : "r"(addr) : "memory");
  return v;
}
#define PROF_AT(cond, slot) do {} while (0)

constexpr uint32_t SMEM_BASE = 1024;
constexpr uint32_t DESC_A = (1u << 16) | (SMEM_BASE >> 4);
constexpr uint32_t DESC_B = ((8192u >> 4) << 16) | ((SMEM_BASE + 16384) >> 4);

template <int BN> struct Wg;
template <> struct Wg<128> { static __device__ __forceinline__ void mma(float (&d)[64], uint32_t a, uint32_t b, int s) { wgmma_ss_n128(d, a, b, s); } };
template <> struct Wg<192> { static __device__ __forceinline__ void mma(float (&d)[96], uint32_t a, uint32_t b, int s) { wgmma_ss_n192(d, a, b, s); } };
template <> struct Wg<256> { static __device__ __forceinline__ void mma(float (&d)[128], uint32_t a, uint32_t b, int s) { wgmma_ss_n256(d, a, b, s); } };

struct Ring {
  uint32_t full0, rel0;
  int s;
  uint32_t ph;
  bool releaser;
};

template <int N>
__device__ __forceinline__ void fence_regs(float (&a)[N]) {
#pragma unroll
  for (int i = 0; i < N; i++) asm volatile("" : "+f"(a[i])::"memory");
}

template <int BN, int NST, uint32_t STAGE>
__device__ __forceinline__ void kblock(float (&acc)[BN / 2], Ring& g, uint32_t a_addr, bool zero, uint32_t& prev) {
  mbar_wait(g.full0 + 8 * g.s, g.ph);
  const uint32_t da = DESC_A + (a_addr >> 4);
  const uint32_t db = DESC_B + g.s * (STAGE >> 4);
  wg_fence();
#pragma unroll
  for (int k = 0; k < 4; k++) Wg<BN>::mma(acc, da + k * 2, db + k * 128, !(zero && k == 0));
  wg_commit();
  wg_wait<1>();
  if (prev != 0) mbar_arrive_cluster(prev);
  prev = g.releaser ? g.rel0 + 8 * g.s : 0u;
  if (++g.s == NST) { g.s = 0; g.ph ^= 1; }
}
template <int N>
__device__ __forceinline__ void tile_end(float (&acc)[N], uint32_t& prev) {
  wg_wait<0>();
  if (prev != 0) mbar_arrive_cluster(prev);
  prev = 0;
  fence_regs(acc);
}

__device__ __forceinline__ int own_first(int it, int j) {
  return it >= 16 ? (it & 15) : (it < 2 ? 2 * j + it : (it - 2 < 2 * j ? it - 2 : it));
}
__device__ __forceinline__ int qkv_kb(int it, int j) {
  const int q = it < 18 ? it - 4 : it - 18;
  return it < 4 ? 2 * j + (it & 1) : (q < 2 * j ? q : q + 2);
}
__device__ __forceinline__ int wo_k(int it, int j) {
  return it < 8 ? it * 128 : (it == 8 ? j : (it - 9 < j ? it - 9 : it - 8)) * 128 + 64;
}
__device__ __forceinline__ int down_k(int it) {
  const int r = (it >> 4) - 1, idx = it & 15;
  return r < 0 ? idx * 64 : (r < 3 ? (idx >> 1) * 448 + r * 128 + (idx & 1) * 64 : idx * 448 + 384);
}
__device__ __forceinline__ void wait_p3_free(uint32_t empty3, int i) {
  mbar_wait(empty3 + 8 * ((i * 2) / 3), 1);
  mbar_wait(empty3 + 8 * ((i * 2 + 1) / 3), 1);
}
__device__ __forceinline__ void wait_p2_free(uint32_t empty2, int i) {
  const int w0 = (i * 3) / 2, w1 = (i * 3 + 2) / 2;
  mbar_wait(empty2 + 8 * w0, w0 < 4 ? 0 : 1);
  mbar_wait(empty2 + 8 * w1, w1 < 4 ? 0 : 1);
}

__device__ __forceinline__ void chan(float& m, float& q, float m2, float q2, float n) {
  const float d = m2 - m;
  m = 0.5f * (m + m2);
  q = q + q2 + d * d * (0.5f * n);
}

template <int N>
__device__ __forceinline__ void row_stats(const uint32_t (&ll)[N], float& mean, float& rstd) {
  float ma = __uint_as_float(ll[0]), qa = __uint_as_float(ll[1]), mb = __uint_as_float(ll[4]), qb = __uint_as_float(ll[5]);
  chan(ma, qa, __uint_as_float(ll[2]), __uint_as_float(ll[3]), 128.f);
  chan(mb, qb, __uint_as_float(ll[6]), __uint_as_float(ll[7]), 128.f);
  chan(ma, qa, mb, qb, 256.f);
  const float mo = __shfl_xor_sync(~0u, ma, 16), qo = __shfl_xor_sync(~0u, qa, 16);
  chan(ma, qa, mo, qo, 512.f);
  mean = ma;
  rstd = rsqrtf(qa * (1.0f / DM) + 1e-5f);
}

__device__ __forceinline__ void stage_slab(uint32_t chunk, int warp, int lane, const uint32_t (&lo)[8], const uint32_t (&hi)[8]) {
  const int row = warp * 16 + (lane & 7) + ((lane >> 3) & 1) * 8;
  const uint32_t rbase = chunk + row * 128;
#pragma unroll
  for (int q = 0; q < 4; q++) {
    const int grp = 2 * q + (lane >> 4);
    stmatrix4(rbase + ((grp ^ (row & 7)) << 4), lo[2 * q], hi[2 * q], lo[2 * q + 1], hi[2 * q + 1]);
  }
}
__device__ __forceinline__ float silu_mul(float g, float u) {
  float e, r;
  asm("ex2.approx.ftz.f32 %0, %1;" : "=f"(e) : "f"(g * -1.4426950408889634f));
  asm("rcp.approx.ftz.f32 %0, %1;" : "=f"(r) : "f"(1.0f + e));
  return g * r * u;
}
__device__ __forceinline__ uint32_t swiglu2(uint32_t g2, uint32_t u2) {
  asm volatile("" : "+r"(g2));
  return pack2(silu_mul(bf_lo(g2), bf_lo(u2)), silu_mul(bf_hi(g2), bf_hi(u2)));
}
__device__ __forceinline__ void stage_done(uint32_t bar, int lane) {
  asm volatile("fence.proxy.async.shared::cta;" ::: "memory");
  __syncwarp();
  if (lane == 0) mbar_arrive(bar);
}

__device__ __forceinline__ void stage_done2(uint32_t bar, int lane) {
  asm volatile("fence.proxy.async.shared::cta;" ::: "memory");
  __syncwarp();
  if (lane < 2) mbar_arrive(bar + 8 * lane);
}

__device__ __forceinline__ int fresh_tid() {
  int t;
  asm volatile("mov.u32 %0, %%tid.x;" : "=r"(t));
  return t;
}
#define RING_IDS()                                                                                           \
  const int tid = fresh_tid() - 128;                                                                         \
  const int cw = __shfl_sync(~0u, tid >> 7, 0), warp = __shfl_sync(~0u, (tid >> 5) & 3, 0);                  \
  const bool releaser = (tid & 31) < 2;                                                                      \
  const uint32_t rbars = mapa(bars, tid & 1);                                                                \
  const uint32_t a_base = cw * 8192
#define LANE_IDS()                                                                                           \
  const int lane = fresh_tid() & 31, r = lane >> 2, c = lane & 3;                                            \
  const int srow = warp * 16 + (lane & 7) + ((lane >> 3) & 1) * 8;                                           \
  const uint32_t slab = stg + cw * 8192 + srow * 128, sw0 = (lane >> 4) ^ (srow & 7);                        \
  (void)r; (void)c; (void)slab; (void)sw0

template <int NPRE, class Step>
__device__ __forceinline__ void attention(float (&acc)[96], const Params& p, int rho, int rb, int cta, int cw, int warp, uint32_t tag,
                                          uint32_t stg, uint32_t bars, uint32_t& prev, Step step) {
  uint32_t ql[8], qh[8], k0[8], k1[8], v0[8], v1[8], hp[16];
  step();
  fence_regs(acc);
#pragma unroll
  for (int t = 0; t < 8; t++) {
    k0[t] = pack2(acc[4 * (8 + t)], acc[4 * (8 + t) + 1]);
    k1[t] = pack2(acc[4 * (8 + t) + 2], acc[4 * (8 + t) + 3]);
    v0[t] = pack2(acc[4 * (16 + t)], acc[4 * (16 + t) + 1]);
    v1[t] = pack2(acc[4 * (16 + t) + 2], acc[4 * (16 + t) + 3]);
    asm volatile("" : "+r"(k0[t]), "+r"(k1[t]), "+r"(v0[t]), "+r"(v1[t]));
  }
  const int lane = fresh_tid() & 31, r = lane >> 2, c = lane & 3;
#pragma unroll
  for (int t = 0; t < 8; t++) v1[t] = movmatrix(v1[t]);
  mbar_wait(bars + 8 * B_STGE, rho);
  mbar_wait(bars + 8 * (B_STGE + 1), 0);
  const uint32_t xch = stg + 16384 + (cw * 4 + warp) * 2048 + lane * 16;
  if (warp < 3) {
    sts128(xch, k1[0], k1[1], k1[2], k1[3]);
    sts128(xch + 512, k1[4], k1[5], k1[6], k1[7]);
    sts128(xch + 1024, v1[0], v1[1], v1[2], v1[3]);
    sts128(xch + 1536, v1[4], v1[5], v1[6], v1[7]);
  } else if (rb < 15) {
    uint4* dst = p.halo + ((cta * 2 + rho) * 2 + cw) * 256 + lane;
#pragma unroll
    for (int t = 0; t < 4; t++) {
      ll_store(dst + t * 32, k1[2 * t], k1[2 * t + 1], tag);
      ll_store(dst + (4 + t) * 32, v1[2 * t], v1[2 * t + 1], tag);
    }
  }
#pragma unroll
  for (int t = 0; t < 8; t++) {
    v0[t] = movmatrix(v0[t]);
    ql[t] = pack2(acc[4 * t], acc[4 * t + 1]);
    qh[t] = pack2(acc[4 * t + 2], acc[4 * t + 3]);
    asm volatile("" : "+r"(v0[t]), "+r"(ql[t]), "+r"(qh[t]));
  }
#pragma unroll 1
  for (int i = 0; i < NPRE; i++) step();
  const uint4* src = p.halo + (((cta - 8) * 2 + rho) * 2 + cw) * 256 + lane;
  uint4 early[8] = {};
  if (warp == 0 && rb > 0) {
#pragma unroll
    for (int i = 0; i < 8; i++) early[i] = ll_peek(src + i * 32);
  }
  step();
  wg_bar(cw);
  if (warp > 0) {
#pragma unroll
    for (int t = 0; t < 4; t++) {
      const uint4 a = lds128(xch - 2048 + t * 512);
      hp[4 * t] = a.x; hp[4 * t + 1] = a.y; hp[4 * t + 2] = a.z; hp[4 * t + 3] = a.w;
    }
  } else if (rb > 0) {
    uint32_t bad = 0;
#pragma unroll
    for (int i = 0; i < 8; i++) {
      bad |= (early[i].y ^ tag) | (early[i].w ^ tag);
      hp[2 * i] = early[i].x;
      hp[2 * i + 1] = early[i].z;
    }
    if (!__all_sync(~0u, bad == 0)) ll_poll<8>([&](int i) { return src + i * 32; }, tag, hp);
  } else {
#pragma unroll
    for (int t = 0; t < 16; t++) hp[t] = 0;
  }
  wg_wait<0>();
  if (prev != 0) mbar_arrive_cluster(prev);
  prev = 0;
#pragma unroll
  for (int t = 0; t < 8; t++) asm volatile("" : "+r"(ql[t])::"memory");
  const bool up0 = 2 * c > r, up1 = 2 * c + 1 > r;
  const bool first = (rb == 0) && (warp == 0);
  uint32_t a0[2], a2[2], a3[2], a5[2];
#pragma unroll
  for (int h = 0; h < 2; h++) {
    float sp[4] = {0.f, 0.f, 0.f, 0.f}, s0[4] = {0.f, 0.f, 0.f, 0.f}, s1[4] = {0.f, 0.f, 0.f, 0.f};
#pragma unroll
    for (int ks = 0; ks < 2; ks++) {
      const int t = 4 * h + 2 * ks;
      mma16816(sp, ql[t], qh[t], ql[t + 1], qh[t + 1], hp[t], hp[t + 1]);
      mma16816(s0, ql[t], qh[t], ql[t + 1], qh[t + 1], k0[t], k0[t + 1]);
      mma16816(s1, ql[t], qh[t], ql[t + 1], qh[t + 1], k1[t], k1[t + 1]);
    }
    float p0 = (up0 ? sp[0] : s0[0]) * QK_SCALE, p1 = (up1 ? sp[1] : s0[1]) * QK_SCALE;
    float p2 = (up0 ? s0[2] : s1[2]) * QK_SCALE, p3 = (up1 ? s0[3] : s1[3]) * QK_SCALE;
    if (first && up0) p0 = -1000000000.0f;
    if (first && up1) p1 = -1000000000.0f;
    softmax8(p0, p1);
    softmax8(p2, p3);
    a0[h] = pack2(up0 ? p0 : 0.f, up1 ? p1 : 0.f);
    a2[h] = pack2(up0 ? 0.f : p0, up1 ? 0.f : p1);
    a3[h] = pack2(up0 ? p2 : 0.f, up1 ? p3 : 0.f);
    a5[h] = pack2(up0 ? 0.f : p2, up1 ? 0.f : p3);
  }
  float o[8][4];
#pragma unroll
  for (int t = 0; t < 8; t++) {
#pragma unroll
    for (int q = 0; q < 4; q++) o[t][q] = 0.f;
    mma1688(o[t], 0u, a5[t >> 2], v1[t]);
    mma16816(o[t], a0[t >> 2], 0u, a2[t >> 2], a3[t >> 2], hp[8 + t], v0[t]);
  }
#pragma unroll
  for (int t = 0; t < 8; t++) fence_regs(o[t]);
  step();
  uint32_t ol[8], oh[8];
#pragma unroll
  for (int t = 0; t < 8; t++) {
    ol[t] = pack2(o[t][0], o[t][1]);
    oh[t] = pack2(o[t][2], o[t][3]);
  }
  stage_slab(stg + cw * 8192, warp, lane, ol, oh);
  stage_done(bars + 8 * B_STGF, lane);
}

__global__ void __launch_bounds__(384, 1) fused_kernel(const __grid_constant__ Params p) {
  extern __shared__ __align__(1024) uint8_t smem_raw[];
  const uint32_t sm = smem_u32(smem_raw);
  const uint32_t bars = sm + MISC_OFF;
  const uint32_t stg = sm + STG_OFF;
  const int rank = blockIdx.x & 1;
  const int cl = blockIdx.x >> 1;
  if (cl >= NCTA / 2) {
    const int e = blockIdx.x - NCTA, wid = __shfl_sync(~0u, (int)(threadIdx.x >> 5), 0), lane = threadIdx.x & 31;
    if (threadIdx.x == 0) {
      for (int i = 0; i < 6; i++) { mbar_init(bars + 8 * i, 1); mbar_init(bars + 8 * (6 + i), 8); }
      asm volatile("fence.mbarrier_init.release.cluster;" ::: "memory");
    }
    const uint32_t tag = load_epoch(p.epoch) + 1;
    if (threadIdx.x < 256) ll_store(p.modll + 512 + (threadIdx.x >> 6) * 256 + e * 64 + (threadIdx.x & 63), 0u, 0u, 0u);
    for (int i = threadIdx.x; i < 1536; i += 384) {
      uint4 o = make_uint4(0u, 0u, 0u, 0u);
      if (i < 1024 && (i & 63) < 8) {
        const uint4 cv = ldg_nc(p.c + (i >> 6) * 64 + (i & 7) * 8);
        o = make_uint4(pack2(silu_f(bf_lo(cv.x)), silu_f(bf_hi(cv.x))), pack2(silu_f(bf_lo(cv.y)), silu_f(bf_hi(cv.y))),
                       pack2(silu_f(bf_lo(cv.z)), silu_f(bf_hi(cv.z))), pack2(silu_f(bf_lo(cv.w)), silu_f(bf_hi(cv.w))));
      }
      sts128(stg + i * 16, o.x, o.y, o.z, o.w);
    }
    asm volatile("fence.proxy.async.shared::cta;" ::: "memory");
    __syncthreads();
    if (wid == 0) {
      __nanosleep(WMDELAY);
      uint32_t ph = 1;
#pragma unroll 1
      for (int it = 0, s = 0; it < 64; it++) {
        mbar_wait(bars + 8 * (6 + s), ph);
        expect_tx_elect(bars + 8 * s, 32768);
#pragma unroll
        for (int q = 0; q < 4; q++) tma_load_ef(sm + s * 32768 + q * 8192, &p.wm, bars + 8 * s, 2048 + (it >> 4) * 1024 + e * 256 + q * 64, (it & 15) * 64);
        if (++s == 6) { s = 0; ph ^= 1; }
      }
    } else if (wid >= 4) {
      const int hf = (wid >> 2) - 1;
      uint32_t ph = 0;
      int s = 0;
#pragma unroll 1
      for (int v = 0; v < 4; v++) {
        float acc[64];
#pragma unroll 1
        for (int kb = 0; kb < 16; kb++) {
          mbar_wait_watchdog(bars + 8 * s, ph);
          const uint32_t da = DESC_A + ((STG_OFF + kb * 1024) >> 4), db = DESC_B + ((s * 32768 + hf * 16384) >> 4) - 1024;
          wg_fence();
#pragma unroll
          for (int k = 0; k < 4; k++) wgmma_ss_n128(acc, da + k * 2, db + k * 128, (kb | k) != 0);
          wg_commit();
          wg_wait<0>();
          if (lane == 0) mbar_arrive(bars + 8 * (6 + s));
          if (++s == 6) { s = 0; ph ^= 1; }
        }
        if ((wid & 3) == 0) {
#pragma unroll
          for (int n = 0; n < 16; n++) {
            const uint32_t mine = pack2(acc[4 * n], acc[4 * n + 1]), next = __shfl_down_sync(~0u, mine, 1);
            if (lane < 4 && (lane & 1) == 0) ll_store(p.modll + 512 + v * 256 + e * 64 + hf * 32 + n * 2 + (lane >> 1), mine, next, tag);
          }
        }
      }
    }
    return;
  }
  const int slot = p.slot[cl];
  const int rb = (slot >> 3) * 2 + rank, j = slot & 7;
  const int cta = rb * 8 + j;
  PROF_AT(threadIdx.x == 0, 0);

  if (threadIdx.x < 128) {
    uint32_t tag = load_epoch(p.epoch);
    asm volatile("setmaxnreg.dec.sync.aligned.u32 40;");
    const int warp = __shfl_sync(~0u, (int)(threadIdx.x >> 5), 0), lane = threadIdx.x & 31;
    if (threadIdx.x == 0) {
      if ((sm & 0x3FFFF) != SMEM_BASE) asm volatile("trap;");
      for (int i = 0; i < 4; i++) { mbar_init(bars + 8 * (B_FQ + i), 1); mbar_init(bars + 8 * (B_EQ + i), 16); }
      for (int i = 0; i < 6; i++) { mbar_init(bars + 8 * (B_FW + i), 1); mbar_init(bars + 8 * (B_EW + i), 16); }
      for (int i = 0; i < 4; i++) { mbar_init(bars + 8 * (B_FG + i), 1); mbar_init(bars + 8 * (B_EG + i), 16); }
      for (int i = 0; i < 6; i++) { mbar_init(bars + 8 * (B_FD + i), 1); mbar_init(bars + 8 * (B_ED + i), 16); }
      for (int i = 0; i < 2; i++) { mbar_init(bars + 8 * (B_STGF + i), 8); mbar_init(bars + 8 * (B_STGE + i), 1); }
      mbar_init(bars + 8 * B_MODB, 1);
      mbar_init(bars + 8 * (B_MODB + 1), 1);
      mbar_init(bars + 8 * B_GATE, 1);
      mbar_init(bars + 8 * B_MODA, 1);
      for (int i = 0; i < 8; i++) mbar_init(bars + 8 * (B_RDY + i), 1);
      asm volatile("fence.mbarrier_init.release.cluster;" ::: "memory");
    }
    __syncwarp();
    cluster_arrive_relaxed();
    tag += 1;
    const unsigned target = tag * 8;
    unsigned* cnt = p.cnt + rb * 32;
    cluster_wait();
    if (warp == 0) {
      const CUtensorMap* wgu = rank ? &p.wu : &p.wg;
      uint32_t st = sm + 16384, fb = bars + 8 * B_FQ, ph = 1;
      if (BDELAY) __nanosleep(BDELAY);
#pragma unroll 1
      for (int it = 0; it < 32; it++) {
        const int kb = qkv_kb(it, j), col = j * 128 + ((it < 4 ? it >= 2 : it >= 18) ? 64 : 0);
        mbar_wait(fb + 8 * (B_EQ - B_FQ), ph);
        expect_tx_elect(fb, it < 4 ? 24576 : 40960);
        tma_load_mc(st + rank * 8192, &p.wqkv, fb, col + rank * 1024, kb * 64);
        tma_load_mc(st + 16384 + rank * 4096, &p.wqkv32, fb, col + 2048, kb * 64 + rank * 32);
        st += 49152; fb += 8;
        if ((it & 3) == 3) { st -= 4 * 49152; fb -= 32; ph ^= 1; }
      }
      fb = bars + 8 * B_FW; ph = 1;
#pragma unroll 1
      for (int it = 0, s = 0; it < 16; it++) {
        if (it < 6) wait_p3_free(bars + 8 * B_EQ, it);
        if (GATE && it == GATE) mbar_wait(bars + 8 * B_GATE, 0);
        mbar_wait(fb + 8 * (B_EW - B_FW), ph);
        expect_tx_elect(fb, it == 8 ? 16384 : 32768);
        tma_load_mc(st + rank * 8192, &p.wo, fb, j * 128 + rank * 64, wo_k(it, j));
        st += 32768; fb += 8;
        if (++s == 6) { s = 0; st -= 6 * 32768; fb -= 48; ph ^= 1; }
      }
      st = sm + 16384; fb = bars + 8 * B_FG; ph = 1;
#pragma unroll 1
      for (int it = 0; it < 48; it++) {
        const int kb = own_first(it, j), col = j * 448 + (it >> 4) * 128;
        if (it < 4) wait_p2_free(bars + 8 * B_EW, it);
        mbar_wait(fb + 8 * (B_EG - B_FG), ph);
        expect_tx_elect(fb, it < 2 ? 32768 : 49152);
        tma_load_mc(st + rank * 16384, wgu, fb, col, kb * 64);
        tma_load_mc(st + rank * 16384 + 8192, wgu, fb, col + 64, kb * 64);
        st += 49152; fb += 8;
        if ((it & 3) == 3) { st -= 4 * 49152; fb -= 32; ph ^= 1; }
      }
      fb = bars + 8 * B_FD; ph = 1;
#pragma unroll 1
      for (int it = 0, s = 0; it < 72; it++) {
        if (it < 6) wait_p3_free(bars + 8 * B_EG, it);
        mbar_wait(fb + 8 * (B_ED - B_FD), ph);
        expect_tx_elect(fb, 32768);
        tma_load_mc(st + rank * 8192, it < 16 ? wgu : &p.wd, fb, it < 16 ? j * 448 + 384 : j * 128 + rank * 64, down_k(it));
        st += 32768; fb += 8;
        if (++s == 6) { s = 0; st -= 6 * 32768; fb -= 48; ph ^= 1; }
      }
    } else if (warp == 1) {
      const int arow = rb * 128;
      uint32_t st = sm, fb = bars + 8 * B_FQ, ph = 0;
      cnt_wait(cnt + C_H, target);
      PROF_AT(lane == 0, 16);
#pragma unroll 1
      for (int it = 4; it < 32; it++) {
        mbar_wait(fb + 8 * (B_EQ - B_FQ), ph);
        tma_load(st, &p.h, fb, qkv_kb(it, j) * 64, arow);
        st += 49152; fb += 8;
        if ((it & 3) == 3) { st -= 4 * 49152; fb -= 32; ph ^= 1; }
      }
      fb = bars + 8 * B_FW; ph = 1;
#pragma unroll 1
      for (int it = 0, s = 0; it < 16; it++) {
        if (it < 6) wait_p3_free(bars + 8 * B_EQ, it);
        if (GATE && it == GATE) mbar_wait(bars + 8 * B_GATE, 0);
        mbar_wait(fb + 8 * (B_EW - B_FW), ph);
        if (it == 0 || it == 9) { mbar_wait(bars + 8 * (B_RDY + C_O + (it >> 3)), 0); PROF_AT(lane == 0, 17 + (it >> 3)); }
        if (it != 8) tma_load(st, &p.o_ld, fb, wo_k(it, j), arow);
        st += 32768; fb += 8;
        if (++s == 6) { s = 0; st -= 6 * 32768; fb -= 48; ph ^= 1; }
      }
      st = sm + 2 * 49152; fb = bars + 8 * (B_FG + 2); ph = 1;
      mbar_wait(bars + 8 * (B_RDY + C_H2), 0);
      PROF_AT(lane == 0, 19);
#pragma unroll 1
      for (int it = 2; it < 48; it++) {
        mbar_wait(fb + 8 * (B_EG - B_FG), ph);
        tma_load(st, &p.h2, fb, own_first(it, j) * 64, arow);
        st += 49152; fb += 8;
        if ((it & 3) == 3) { st -= 4 * 49152; fb -= 32; ph ^= 1; }
      }
      fb = bars + 8 * B_FD; ph = 1;
#pragma unroll 1
      for (int it = 0, s = 0; it < 72; it++) {
        if (it < 6) wait_p3_free(bars + 8 * B_EG, it);
        mbar_wait(fb + 8 * (B_ED - B_FD), ph);
        if ((it & 15) == 0 && it > 0) { mbar_wait(bars + 8 * (B_RDY + C_ACT - 1 + (it >> 4)), 0); PROF_AT(lane == 0, 19 + (it >> 4)); }
        tma_load(st, it < 16 ? &p.h2 : &p.act, fb, down_k(it), arow);
        st += 32768; fb += 8;
        if (++s == 6) { s = 0; st -= 6 * 32768; fb -= 48; ph ^= 1; }
      }
    } else if (warp == 2) {
      if (lane < 13) prefetch_map(&p.h + lane);
      __syncwarp();
      uint32_t ph1 = 0;
#pragma unroll 1
      for (int n = 0; n < 9; n++) {
        const int nch = (n == 1 || n == 2 || n == 7) ? 1 : 2;
#pragma unroll 1
        for (int ch = 0; ch < nch; ch++) {
          mbar_wait_watchdog(bars + 8 * (B_STGF + ch), ch ? ph1 : (n & 1));
          const uint32_t src = stg + ch * 16384;
          if (n == 1 || n == 2) {
#pragma unroll 1
            for (int q = 0; q < 4; q++) {
              tma_store2(&p.o_st, src + q * 4096, j * 128 + (n - 1) * 64, rb * 128 + q * 32);
              if (n == 1) store_pause(true);
            }
            if (n == 2) arrive_elect(bars + 8 * B_GATE);
          } else if (n >= 4 && n < 8) {
#pragma unroll 1
            for (int q = 0; q < 4; q++) {
              tma_store2(&p.act_st, src + q * 4096, j * 448 + (n - 4) * 128 + ch * 64, rb * 128 + q * 32);
              store_pause(true);
            }
          } else if (n == 8) {
            tma_store3(&p.out, src, j * 128 + ch * 64, rb * 64, 0);
          } else {
            tma_store2(n == 0 ? &p.h : &p.h2, src, j * 128 + ch * 64, rb * 128);
          }
          if (n >= 4 && n < 7 && ch == 0) arrive_elect(bars + 8 * B_STGE);
        }
        asm volatile("cp.async.bulk.commit_group;" ::: "memory");
        asm volatile("cp.async.bulk.wait_group 0;" ::: "memory");
        __syncwarp();
        if (n < 8) cnt_signal(cnt + n);
        if (!(n >= 4 && n < 7)) arrive_elect(bars + 8 * B_STGE);
        if (nch == 2) { arrive_elect(bars + 8 * (B_STGE + 1)); ph1 ^= 1; }
        PROF_AT(lane == 0, n == 0 ? 33 : 23 + n);
      }
    } else {
      if (lane < 4) ll_store(p.modll + cta * 4 + lane, 0u, 0u, 0u);
      bar_sync(1, 288);
      {
        const uint4 t4 = lds128(sm + RED_OFF + lane * 16);
        float a[4] = {__uint_as_float(t4.x), __uint_as_float(t4.y), __uint_as_float(t4.z), __uint_as_float(t4.w)};
#pragma unroll
        for (int o = 4; o < 32; o <<= 1)
#pragma unroll
          for (int q = 0; q < 4; q++) a[q] += __shfl_xor_sync(~0u, a[q], o);
        if (lane < 4) ll_store(p.modll + cta * 4 + lane, pack2(a[0], a[1]), pack2(a[2], a[3]), tag);
        PROF_AT(lane == 0, 1);
        uint32_t m[4];
        const uint4* mp = p.modll + j * 32 + lane;
        ll_poll<2>([&](int i) { return mp + i * 256; }, tag, m);
        const uint32_t c0 = pack2(1.0f + bf_lo(m[2]), 1.0f + bf_hi(m[2])), c1 = pack2(1.0f + bf_lo(m[3]), 1.0f + bf_hi(m[3]));
        sts128(sm + MODB_OFF + lane * 16, m[0] << 16, m[0] & 0xffff0000u, m[1] << 16, m[1] & 0xffff0000u);
        sts128(sm + MODB_OFF + 512 + lane * 16, c0 << 16, c0 & 0xffff0000u, c1 << 16, c1 & 0xffff0000u);
        __syncwarp();
        arrive_elect(bars + 8 * B_MODA);
      }
#pragma unroll 1
      for (int n = C_O; n < C_H2; n++) {
        if (n == C_O) cnt_wait_lazy(cnt + n, target); else cnt_wait(cnt + n, target);
        arrive_elect(bars + 8 * (B_RDY + n));
      }
      {
        uint32_t m[6];
        const uint4* src = p.modll + 512 + j * 32 + lane;
        ll_poll<3>([&](int i) { return src + i * 256; }, tag, m);
#pragma unroll
        for (int vec = 0; vec < 3; vec++) {
          const float add = vec == 2 ? 1.0f : 0.0f;
          sts128(sm + MODB_OFF + (vec * 128 + lane * 4) * 4, __float_as_uint(bf_round(bf_lo(m[2 * vec]) + add)), __float_as_uint(bf_round(bf_hi(m[2 * vec]) + add)),
                 __float_as_uint(bf_round(bf_lo(m[2 * vec + 1]) + add)), __float_as_uint(bf_round(bf_hi(m[2 * vec + 1]) + add)));
        }
        __syncwarp();
        if (lane == 0) mbar_arrive(bars + 8 * B_MODB);
        PROF_AT(lane == 0, 15);
      }
      __syncwarp();
#pragma unroll 1
      for (int n = C_H2; n < 8; n++) {
        if (n == C_H2) cnt_wait(cnt + n, target); else cnt_wait_lazy(cnt + n, target);
        arrive_elect(bars + 8 * (B_RDY + n));
      }
      {
        uint32_t m[2];
        const uint4* src = p.modll + 512 + 768 + j * 32 + lane;
        ll_poll<1>([&](int) { return src; }, tag, m);
        sts128(sm + MODB_OFF + (384 + lane * 4) * 4, m[0] << 16, m[0] & 0xffff0000u, m[1] << 16, m[1] & 0xffff0000u);
        __syncwarp();
        if (lane == 0) mbar_arrive(bars + 8 * (B_MODB + 1));
      }
    }
    __syncwarp();
    cluster_arrive_relaxed();
    cluster_wait();
  } else {
    uint32_t tag;

    {
      const int tid = threadIdx.x - 128, cw = tid >> 7, warp = (tid >> 5) & 3, lane = tid & 31;
      const int l16 = lane & 15, half = lane >> 4, w8 = cw * 4 + warp;
      uint4 xv[8];
      const uint32_t cbuf = sm + 3 * 49152 + w8 * 512;
      if (lane <= 16) cp_async16(cbuf + lane * 16, lane < 16 ? (const void*)(p.c + w8 * 128 + lane * 8) : (const void*)p.epoch);
      asm volatile("cp.async.commit_group;" ::: "memory");
      const uint32_t wbuf = sm + cw * 49152 + warp * 4096;
      {
        const char* wp = (const char*)p.wmod + (uint32_t)(cta * 32 + (lane & 1) * 16 + (w8 * 128 + (lane >> 1)) * 12288);
#pragma unroll
        for (int i = 0; i < 8; i++) cp_async16(wbuf + i * 512 + lane * 16, wp + i * 16 * 12288);
      }
      asm volatile("cp.async.commit_group;" ::: "memory");
      const uint32_t xbuf = sm + 40960 + (cw * 2 + (l16 >> 3)) * 49152 + (warp * 16 + half) * 128;
      {
        const char* xp = (const char*)p.x + (uint32_t)((rb * 128 + (warp * 16 + half) * 2 + cw) * 2048 + j * 256 + l16 * 16);
#pragma unroll
        for (int i = 0; i < 8; i++) cp_async16(xbuf + i * 256 + (((l16 & 7) ^ ((i * 2 + half) & 7)) << 4), xp + i * 8192);
      }
      asm volatile("cp.async.commit_group;" ::: "memory");
      PROF_AT(tid == 0, 32);
      uint4* st1 = p.stats1 + (rb * 8 + j) * 128 + cw * 64 + warp * 16 + (l16 >> 1) * 2 + half;
      if ((lane & 1) == 0) ll_store(st1, 0u, 0u, 0u);
      __syncwarp();
      cluster_arrive_relaxed();
      asm volatile("setmaxnreg.inc.sync.aligned.u32 232;");
      uint32_t sa[4][4];
      {
        asm volatile("cp.async.wait_group 2;" ::: "memory");
        __syncwarp();
        tag = lds32(cbuf + 256) + 1;
        const float2 cv = lds64f(cbuf + lane * 8);
        const uint32_t c0 = __float_as_uint(cv.x), c1 = __float_as_uint(cv.y);
        sts64f(cbuf + lane * 8, __uint_as_float(pack2(silu_f(bf_lo(c0)), silu_f(bf_hi(c0)))), __uint_as_float(pack2(silu_f(bf_lo(c1)), silu_f(bf_hi(c1)))));
        __syncwarp();
#pragma unroll
        for (int q = 0; q < 4; q++) ldmatrix4(sa[q][0], sa[q][1], sa[q][2], sa[q][3], cbuf + q * 64 + (lane >> 3) * 16);
      }
      cluster_wait();
      asm volatile("cp.async.wait_group 1;" ::: "memory");
      __syncwarp();
      PROF_AT(tid == 0, 51);
      {
        uint32_t b[8][4];
#pragma unroll
        for (int ks = 0; ks < 8; ks++) ldmatrix4t(b[ks], wbuf + (ks * 16 + (lane & 15)) * 32 + (lane >> 4) * 16);
        float d0[4] = {0.f, 0.f, 0.f, 0.f}, d1[4] = {0.f, 0.f, 0.f, 0.f}, d2[4] = {0.f, 0.f, 0.f, 0.f}, d3[4] = {0.f, 0.f, 0.f, 0.f};
#pragma unroll
        for (int q = 0; q < 4; q++) {
          mma16816(d0, sa[q][0], sa[q][0], sa[q][1], sa[q][1], b[2 * q][0], b[2 * q][1]);
          mma16816(d1, sa[q][0], sa[q][0], sa[q][1], sa[q][1], b[2 * q][2], b[2 * q][3]);
          mma16816(d2, sa[q][2], sa[q][2], sa[q][3], sa[q][3], b[2 * q + 1][0], b[2 * q + 1][1]);
          mma16816(d3, sa[q][2], sa[q][2], sa[q][3], sa[q][3], b[2 * q + 1][2], b[2 * q + 1][3]);
        }
        d0[0] += d2[0]; d0[1] += d2[1]; d1[0] += d3[0]; d1[1] += d3[1];
        if (lane < 4) {
          sts64f(sm + RED_OFF + (w8 * 16 + lane * 2) * 4, d0[0], d0[1]);
          sts64f(sm + RED_OFF + (w8 * 16 + 8 + lane * 2) * 4, d1[0], d1[1]);
        }
        asm volatile("bar.arrive 1, 288;" ::: "memory");
      }
      asm volatile("cp.async.wait_group 0;" ::: "memory");
#pragma unroll
      for (int i = 0; i < 8; i++) xv[i] = lds128(xbuf + i * 256 + (((l16 & 7) ^ ((i * 2 + half) & 7)) << 4));
      float e[8][8], m[8], q[8];
#pragma unroll
      for (int i = 0; i < 8; i++) {
        e[i][0] = bf_lo(xv[i].x); e[i][1] = bf_hi(xv[i].x); e[i][2] = bf_lo(xv[i].y); e[i][3] = bf_hi(xv[i].y);
        e[i][4] = bf_lo(xv[i].z); e[i][5] = bf_hi(xv[i].z); e[i][6] = bf_lo(xv[i].w); e[i][7] = bf_hi(xv[i].w);
        m[i] = (((e[i][0] + e[i][1]) + (e[i][2] + e[i][3])) + ((e[i][4] + e[i][5]) + (e[i][6] + e[i][7]))) * 0.125f;
        q[i] = 0.f;
#pragma unroll
        for (int k = 0; k < 8; k++) q[i] += (e[i][k] - m[i]) * (e[i][k] - m[i]);
      }
      {
        const bool b3 = lane & 8, b2 = lane & 4, b1 = lane & 2;
#pragma unroll
        for (int i = 0; i < 4; i++) {
          const float mo = __shfl_xor_sync(~0u, b3 ? m[i] : m[i + 4], 8), qo = __shfl_xor_sync(~0u, b3 ? q[i] : q[i + 4], 8);
          m[i] = b3 ? m[i + 4] : m[i]; q[i] = b3 ? q[i + 4] : q[i];
          chan(m[i], q[i], mo, qo, 8.f);
        }
#pragma unroll
        for (int i = 0; i < 2; i++) {
          const float mo = __shfl_xor_sync(~0u, b2 ? m[i] : m[i + 2], 4), qo = __shfl_xor_sync(~0u, b2 ? q[i] : q[i + 2], 4);
          m[i] = b2 ? m[i + 2] : m[i]; q[i] = b2 ? q[i + 2] : q[i];
          chan(m[i], q[i], mo, qo, 16.f);
        }
        {
          const float mo = __shfl_xor_sync(~0u, b1 ? m[0] : m[1], 2), qo = __shfl_xor_sync(~0u, b1 ? q[0] : q[1], 2);
          m[0] = b1 ? m[1] : m[0]; q[0] = b1 ? q[1] : q[0];
          chan(m[0], q[0], mo, qo, 32.f);
        }
        {
          const float mo = __shfl_xor_sync(~0u, m[0], 1), qo = __shfl_xor_sync(~0u, q[0], 1);
          chan(m[0], q[0], mo, qo, 64.f);
        }
      }
      if ((lane & 1) == 0) ll_store(st1, __float_as_uint(m[0]), __float_as_uint(q[0]), tag);
      PROF_AT(tid == 0, 50);
      {
        uint32_t ll[8];
        const uint4* sp = p.stats1 + (rb * 8 + half * 4) * 128 + cw * 64 + warp * 16 + l16;
        ll_poll<4, PB1>([&](int i) { return sp + i * 128; }, tag, ll);
        float nmr, rstd;
        row_stats(ll, nmr, rstd);
        nmr *= -rstd;
#pragma unroll
        for (int i = 0; i < 8; i++) {
          const float rs = __shfl_sync(~0u, rstd, i * 2 + half), nb = __shfl_sync(~0u, nmr, i * 2 + half);
#pragma unroll
          for (int k = 0; k < 8; k++) { e[i][k] = e[i][k] * rs + nb; asm volatile("" : "+f"(e[i][k])); }
        }
      }
      PROF_AT(tid == 0, 52);
      mbar_wait(bars + 8 * B_MODA, 0);
      PROF_AT(tid == 0, 2);
      float sh[8], ca[8];
#pragma unroll
      for (int k = 0; k < 2; k++) {
        const uint4 sv = lds128(sm + MODB_OFF + (l16 * 8 + k * 4) * 4), cv = lds128(sm + MODB_OFF + (128 + l16 * 8 + k * 4) * 4);
        sh[4 * k] = __uint_as_float(sv.x); sh[4 * k + 1] = __uint_as_float(sv.y); sh[4 * k + 2] = __uint_as_float(sv.z); sh[4 * k + 3] = __uint_as_float(sv.w);
        ca[4 * k] = __uint_as_float(cv.x); ca[4 * k + 1] = __uint_as_float(cv.y); ca[4 * k + 2] = __uint_as_float(cv.z); ca[4 * k + 3] = __uint_as_float(cv.w);
      }
#pragma unroll
      for (int i = 0; i < 8; i++) {
        uint32_t o[4];
#pragma unroll
        for (int k = 0; k < 4; k++) o[k] = pack2(e[i][2 * k] * ca[2 * k] + sh[2 * k], e[i][2 * k + 1] * ca[2 * k + 1] + sh[2 * k + 1]);
        const int row = cw * 64 + warp * 16 + i * 2 + half;
        sts128(stg + (l16 >> 3) * 16384 + row * 128 + (((l16 & 7) ^ (row & 7)) << 4), o[0], o[1], o[2], o[3]);
      }
      stage_done2(bars + 8 * B_STGF, lane);
      wg_bar(cw);
      PROF_AT(tid == 0, 3);
    }

    uint32_t xl[16], xh[16];
    {
      RING_IDS();
      uint32_t prev = 0;
      float acc1[96];
      {
        Ring g{bars + 8 * B_FQ, rbars + 8 * B_EQ, 0, 0u, releaser TR(0)};
        float acc0[96];
#pragma unroll 1
        for (int kb = 0; kb < 2; kb++) kblock<192, 4, 49152>(acc0, g, a_base + STG_OFF + kb * 16384, kb == 0, prev);
#pragma unroll 1
        for (int kb = 0; kb < 2; kb++) kblock<192, 4, 49152>(acc1, g, a_base + STG_OFF + kb * 16384, kb == 0, prev);
        {
          LANE_IDS();
          if (c < 2) ll_store(p.stats2 + (rb * 8 + j) * 128 + cw * 64 + warp * 16 + r + c * 8, 0u, 0u, 0u);
          if (warp == 3) {
#pragma unroll 1
            for (int t = 0; t < 16; t++) ll_store(p.halo + ((cta * 2 + (t >> 3)) * 2 + cw) * 256 + (t & 7) * 32 + lane, 0u, 0u, 0u);
          }
          __syncwarp();
        }
#pragma unroll 1
        for (int kb = 0; kb < 14; kb++) kblock<192, 4, 49152>(acc0, g, a_base + g.s * 49152, false, prev);
        PROF_AT(tid == 0, 4);
        attention<NPRE0>(acc0, p, 0, rb, cta, cw, warp, tag, stg, bars, prev, [&]() { kblock<192, 4, 49152>(acc1, g, a_base + g.s * 49152, false, prev); });
        PROF_AT(tid == 0, 5);
        {
          LANE_IDS();
#pragma unroll
          for (int q = 0; q < 8; q++)
            ldmatrix4(xl[2 * q], xh[2 * q], xl[2 * q + 1], xh[2 * q + 1], sm + 40960 + (cw * 2 + (q >> 2)) * 49152 + srow * 128 + ((sw0 ^ ((q & 3) * 2)) << 4));
#pragma unroll
          for (int q = 0; q < 16; q++) asm volatile("" : "+r"(xl[q]), "+r"(xh[q])::"memory");
        }
#pragma unroll 1
        for (int kb = 3 + NPRE0; kb < 14; kb++) kblock<192, 4, 49152>(acc1, g, a_base + g.s * 49152, false, prev);
        PROF_AT(tid == 0, 6);
      }
      float acc[64];
      Ring g{bars + 8 * B_FW, rbars + 8 * B_EW, 0, 0u, releaser TR(32)};
      attention<NPRE1>(acc1, p, 1, rb, cta, cw, warp, tag, stg, bars, prev, [&]() { kblock<128, 6, 32768>(acc, g, a_base + g.s * 32768, g.s == 0, prev); });
      PROF_AT(tid == 0, 7);
      LANE_IDS();
      uint4* st2 = p.stats2 + (rb * 8 + j) * 128 + cw * 64 + warp * 16 + r + (c & 1) * 8;
#pragma unroll 1
      for (int kb = 3 + NPRE1; kb < 16; kb++) {
        if (kb == 8) wg_bar(cw);
        kblock<128, 6, 32768>(acc, g, a_base + (kb == 8 ? STG_OFF : g.s * 32768), false, prev);
      }
      mbar_wait(bars + 8 * B_MODB, 0);
      float2 ga[16];
#pragma unroll
      for (int n = 0; n < 16; n++) ga[n] = lds64f(sm + MODB_OFF + (8 * n + 2 * c) * 4);
      tile_end(acc, prev);
      PROF_AT(tid == 0, 8);
      float sl[2] = {0.f, 0.f}, sh[2] = {0.f, 0.f}, ql[2] = {0.f, 0.f}, qh[2] = {0.f, 0.f};
#pragma unroll
      for (int n = 0; n < 16; n++) {
        acc[4 * n] = ga[n].x * acc[4 * n] + bf_lo(xl[n]); acc[4 * n + 1] = ga[n].y * acc[4 * n + 1] + bf_hi(xl[n]);
        acc[4 * n + 2] = ga[n].x * acc[4 * n + 2] + bf_lo(xh[n]); acc[4 * n + 3] = ga[n].y * acc[4 * n + 3] + bf_hi(xh[n]);
        sl[0] += acc[4 * n]; sl[1] += acc[4 * n + 1]; sh[0] += acc[4 * n + 2]; sh[1] += acc[4 * n + 3];
        ql[0] += acc[4 * n] * acc[4 * n]; ql[1] += acc[4 * n + 1] * acc[4 * n + 1];
        qh[0] += acc[4 * n + 2] * acc[4 * n + 2]; qh[1] += acc[4 * n + 3] * acc[4 * n + 3];
      }
      {
        const float ml = (sl[0] + sl[1]) * (1.0f / 32), mh = (sh[0] + sh[1]) * (1.0f / 32);
        const float vl = (ql[0] + ql[1]) - 32.0f * ml * ml, vh = (qh[0] + qh[1]) - 32.0f * mh * mh;
        const bool b0 = c & 1;
        float m = b0 ? mh : ml, q = b0 ? vh : vl;
        chan(m, q, __shfl_xor_sync(~0u, b0 ? ml : mh, 1), __shfl_xor_sync(~0u, b0 ? vl : vh, 1), 32.f);
        chan(m, q, __shfl_xor_sync(~0u, m, 2), __shfl_xor_sync(~0u, q, 2), 64.f);
        if (c < 2) ll_store(st2, __float_as_uint(m), __float_as_uint(fmaxf(q, 0.f)), tag);
        __syncwarp();
      }
      PROF_AT(tid == 0, 48);
      float2 sb[16], cb[16];
#pragma unroll
      for (int n = 0; n < 16; n++) {
        sb[n] = lds64f(sm + MODB_OFF + (128 + 8 * n + 2 * c) * 4);
        cb[n] = lds64f(sm + MODB_OFF + (256 + 8 * n + 2 * c) * 4);
        xl[n] = pack2(acc[4 * n], acc[4 * n + 1]);
        xh[n] = pack2(acc[4 * n + 2], acc[4 * n + 3]);
      }
      mbar_wait(bars + 8 * B_STGE, 0);
      PROF_AT(tid == 0, 49);
      float nb[2], rstd[2];
      {
        uint32_t st[8];
        const uint4* sp = p.stats2 + (rb * 8 + (lane >> 4) * 4) * 128 + cw * 64 + warp * 16 + (lane & 15);
        ll_poll<4, PB2>([&](int i) { return sp + i * 128; }, tag, st);
        float mu, rs;
        row_stats(st, mu, rs);
        mu *= -rs;
        nb[0] = __shfl_sync(~0u, mu, r); rstd[0] = __shfl_sync(~0u, rs, r);
        nb[1] = __shfl_sync(~0u, mu, r + 8); rstd[1] = __shfl_sync(~0u, rs, r + 8);
      }
      PROF_AT(tid == 0, 9);
#pragma unroll
      for (int ch = 0; ch < 2; ch++) {
        uint32_t lo[8], hi[8];
#pragma unroll
        for (int t = 0; t < 8; t++) {
          const int n = ch * 8 + t;
          lo[t] = pack2((acc[4 * n] * rstd[0] + nb[0]) * cb[n].x + sb[n].x, (acc[4 * n + 1] * rstd[0] + nb[0]) * cb[n].y + sb[n].y);
          hi[t] = pack2((acc[4 * n + 2] * rstd[1] + nb[1]) * cb[n].x + sb[n].x, (acc[4 * n + 3] * rstd[1] + nb[1]) * cb[n].y + sb[n].y);
        }
        stage_slab(stg + ch * 16384 + cw * 8192, warp, lane, lo, hi);
        stage_done(bars + 8 * (B_STGF + ch), lane);
      }
      wg_bar(cw);
      PROF_AT(tid == 0, 10);
    }

    uint32_t pg[32], pu[32];
    {
      RING_IDS();
      LANE_IDS();
      Ring g{bars + 8 * B_FG, rbars + 8 * B_EG, 0, 0u, releaser TR(48)};
      float acc[128];
      {
        uint32_t prev = 0;
        uint4* x1p = p.x1 + (size_t)(rb * 128 + (tid >> 4)) * 128 + j * 16 + (tid & 15);
#pragma unroll 1
        for (int kb = 0; kb < 16; kb++) {
          kblock<256, 4, 49152>(acc, g, a_base + (kb < 2 ? STG_OFF + kb * 16384 : g.s * 49152), kb == 0, prev);
          if (kb == 5) {
#pragma unroll
            for (int q = 0; q < 4; q++) x1p[q * 2048] = make_uint4(xl[4 * q], xl[4 * q + 1], xl[4 * q + 2], xl[4 * q + 3]);
          }
          if (kb == 8) {
#pragma unroll
            for (int q = 0; q < 4; q++) x1p[(4 + q) * 2048] = make_uint4(xh[4 * q], xh[4 * q + 1], xh[4 * q + 2], xh[4 * q + 3]);
          }
        }
        tile_end(acc, prev);
      }
      PROF_AT(tid == 0, 36);
#pragma unroll 1
      for (int t = 1; t < 3; t++) {
#pragma unroll
        for (int q = 0; q < 32; q++) {
          pg[q] = pack2(acc[2 * q], acc[2 * q + 1]);
          pu[q] = pack2(acc[64 + 2 * q], acc[64 + 2 * q + 1]);
        }
        uint32_t prev = 0;
#pragma unroll 1
        for (int blk = 0; blk < 4; blk++) {
          g.s = 0;
#pragma unroll
          for (int i = 0; i < 4; i++) {
            kblock<256, 4, 49152>(acc, g, a_base + i * 49152, blk == 0 && i == 0, prev);
            if ((blk & 1) == 0 && i == 0) mbar_wait(bars + 8 * (B_STGE + (blk >> 1)), t & 1);
            stmatrix2(slab + (blk >> 1) * 16384 + (((srow & 7) ^ ((blk & 1) * 4 + i)) << 4), swiglu2(pg[2 * i], pu[2 * i]), swiglu2(pg[2 * i + 1], pu[2 * i + 1]));
          }
#pragma unroll
          for (int q = 0; q < 24; q++) { pg[q] = pg[q + 8]; pu[q] = pu[q + 8]; }
          if (blk & 1) stage_done(bars + 8 * (B_STGF + (blk >> 1)), lane);
        }
        tile_end(acc, prev);
        PROF_AT(tid == 0, 36 + t);
      }
#pragma unroll
      for (int q = 0; q < 32; q++) {
        pg[q] = pack2(acc[2 * q], acc[2 * q + 1]);
        pu[q] = pack2(acc[64 + 2 * q], acc[64 + 2 * q + 1]);
      }
      PROF_AT(tid == 0, 11);
    }

    {
      RING_IDS();
      LANE_IDS();
      Ring g{bars + 8 * B_FD, rbars + 8 * B_ED, 0, 0u, releaser TR(96)};
      float acc[64];
      uint32_t prev = 0;
#pragma unroll 1
      for (int blk = 0; blk < 6; blk++) {
#pragma unroll
        for (int i = 0; i < 8; i++) {
          kblock<128, 6, 32768>(acc, g, a_base + g.s * 32768, (blk & ~2) == 0 && i == 0, prev);
          if ((blk & 1) == 0 && i == 0) mbar_wait(bars + 8 * (B_STGE + ((blk >> 1) & 1)), blk < 4);
          stmatrix1(slab + ((blk >> 1) & 1) * 16384 + (i & 1) * 1024 + (((srow & 7) ^ ((blk & 1) * 4 + (i >> 1))) << 4), swiglu2(pg[i], pu[i]));
        }
#pragma unroll
        for (int q = 0; q < 24; q++) { pg[q] = pg[q + 8]; pu[q] = pu[q + 8]; }
        if (blk & 1) stage_done(bars + 8 * (B_STGF + ((blk >> 1) & 1)), lane);
        if (blk == 1) {
          tile_end(acc, prev);
          PROF_AT(tid == 0, 39);
#pragma unroll
          for (int q = 0; q < 16; q++) {
            pg[16 + q] = pack2(acc[2 * q], acc[2 * q + 1]);
            pu[16 + q] = pack2(acc[32 + 2 * q], acc[32 + 2 * q + 1]);
          }
          PROF_AT(tid == 0, 12);
        }
      }
      uint4 x1[8];
      const int ft = fresh_tid() - 128;
      const uint4* x1p = p.x1 + (size_t)(rb * 128 + (ft >> 4)) * 128 + j * 16 + (ft & 15);
#pragma unroll
      for (int q = 0; q < 2; q++) {
#pragma unroll
        for (int e = 0; e < 4; e++) x1[4 * q + e] = ll_peek(x1p + (4 * q + e) * 2048);
#pragma unroll 1
        for (int kb = 0; kb < 12; kb++) kblock<128, 6, 32768>(acc, g, a_base + g.s * 32768, false, prev);
      }
      mbar_wait(bars + 8 * (B_MODB + 1), 0);
      mbar_wait(bars + 8 * B_STGE, 1);
      mbar_wait(bars + 8 * (B_STGE + 1), 0);
      float2 gbv[16];
#pragma unroll
      for (int n = 0; n < 16; n++) gbv[n] = lds64f(sm + MODB_OFF + (384 + 8 * n + 2 * c) * 4);
      tile_end(acc, prev);
      PROF_AT(tid == 0, 13);
#pragma unroll
      for (int ch = 0; ch < 2; ch++) {
        uint32_t lo[8], hi[8];
#pragma unroll
        for (int t = 0; t < 8; t++) {
          const int n = ch * 8 + t;
          const float2 gb = gbv[n];
          const uint4 a = x1[n >> 2], b = x1[4 + (n >> 2)];
          const uint32_t xl = (n & 3) == 0 ? a.x : (n & 3) == 1 ? a.y : (n & 3) == 2 ? a.z : a.w;
          const uint32_t xh = (n & 3) == 0 ? b.x : (n & 3) == 1 ? b.y : (n & 3) == 2 ? b.z : b.w;
          lo[t] = pack2(bf_lo(xl) + gb.x * acc[4 * n], bf_hi(xl) + gb.y * acc[4 * n + 1]);
          hi[t] = pack2(bf_lo(xh) + gb.x * acc[4 * n + 2], bf_hi(xh) + gb.y * acc[4 * n + 3]);
        }
        stage_slab(stg + ch * 16384 + cw * 8192, warp, lane, lo, hi);
        stage_done(bars + 8 * (B_STGF + ch), lane);
      }
      PROF_AT(tid == 0, 14);
    }
    if (blockIdx.x == 0 && threadIdx.x == 128) asm volatile("st.relaxed.gpu.global.u32 [%0], %1;" ::"l"(p.epoch), "r"(tag) : "memory");
    __syncwarp();
    cluster_arrive_relaxed();
    cluster_wait();
  }
}

typedef CUresult (*EncodeFn)(CUtensorMap*, CUtensorMapDataType, cuuint32_t, void*, const cuuint64_t*, const cuuint64_t*,
                             const cuuint32_t*, const cuuint32_t*, CUtensorMapInterleave, CUtensorMapSwizzle,
                             CUtensorMapL2promotion, CUtensorMapFloatOOBfill);

void encode2d(EncodeFn fn, CUtensorMap* m, const void* ptr, uint64_t cols, uint64_t rows, uint32_t box_rows) {
  cuuint64_t dims[2] = {cols, rows};
  cuuint64_t strides[1] = {cols * 2};
  cuuint32_t box[2] = {64, box_rows};
  cuuint32_t es[2] = {1, 1};
  fn(m, CU_TENSOR_MAP_DATA_TYPE_BFLOAT16, 2, (void*)ptr, dims, strides, box, es, CU_TENSOR_MAP_INTERLEAVE_NONE,
     CU_TENSOR_MAP_SWIZZLE_128B, CU_TENSOR_MAP_L2_PROMOTION_L2_128B, CU_TENSOR_MAP_FLOAT_OOB_FILL_NONE);
}

}

extern "C" void kernel_launch(void* const* d_in, const int* in_sizes, int n_in, void* d_out, int out_size) {
  (void)in_sizes; (void)n_in; (void)out_size;
  void* fp = nullptr;
  cudaDriverEntryPointQueryResult qr;
  cudaGetDriverEntryPoint("cuTensorMapEncodeTiled", &fp, cudaEnableDefault, &qr);
  EncodeFn fn = (EncodeFn)fp;
  void *ph, *po, *ph2, *pact;
  cudaGetSymbolAddress(&ph, g_h);
  cudaGetSymbolAddress(&po, g_o);
  ph2 = ph;
  cudaGetSymbolAddress(&pact, g_act);
  Params p;
  encode2d(fn, &p.h, ph, DM, SEQ, 128);
  encode2d(fn, &p.o_ld, po, DM, SEQ, 128);
  encode2d(fn, &p.h2, ph2, DM, SEQ, 128);
  encode2d(fn, &p.act, pact, FF, SEQ, 128);
  encode2d(fn, &p.act_st, pact, FF, SEQ, 32);
  encode2d(fn, &p.wm, d_in[8], 6 * DM, DM, 64);
  encode2d(fn, &p.o_st, po, DM, SEQ, 32);
  encode2d(fn, &p.wqkv, d_in[1], 3 * DM, DM, 64);
  encode2d(fn, &p.wqkv32, d_in[1], 3 * DM, DM, 32);
  encode2d(fn, &p.wo, d_in[2], DM, DM, 64);
  encode2d(fn, &p.wg, d_in[4], FF, DM, 64);
  encode2d(fn, &p.wu, d_in[5], FF, DM, 64);
  encode2d(fn, &p.wd, d_in[6], DM, FF, 64);
  {
    cuuint64_t dims[3] = {DM, SEQ / 2, 2};
    cuuint64_t strides[2] = {DM * 4, DM * 2};
    cuuint32_t box[3] = {64, 64, 2};
    cuuint32_t es[3] = {1, 1, 1};
    fn(&p.out, CU_TENSOR_MAP_DATA_TYPE_BFLOAT16, 3, d_out, dims, strides, box, es, CU_TENSOR_MAP_INTERLEAVE_NONE,
       CU_TENSOR_MAP_SWIZZLE_128B, CU_TENSOR_MAP_L2_PROMOTION_L2_128B, CU_TENSOR_MAP_FLOAT_OOB_FILL_NONE);
  }
  p.x = (const bf16*)d_in[0];
  p.c = (const bf16*)d_in[7];
  p.wmod = (const bf16*)d_in[8];
  for (int cl = 0; cl < 64; cl++) {
    const int grp = cl < 4 ? 0 : (cl < 36 ? (cl - 4) & 7 : 1 + (cl - 36) % 7);
    const int j = cl < 4 ? 4 + cl : (cl < 36 ? (cl - 4) >> 3 : 4 + (cl - 36) / 7);
    p.slot[cl] = (uint8_t)(grp * 8 + j);
  }
  void* q;
  p.x1 = (uint4*)d_out;
  cudaGetSymbolAddress(&q, g_modll); p.modll = (uint4*)q;
  cudaGetSymbolAddress(&q, g_halo); p.halo = (uint4*)q;
  cudaGetSymbolAddress(&q, g_stats); p.stats1 = (uint4*)q; p.stats2 = p.stats1 + SEQ * 8;
  cudaGetSymbolAddress(&q, g_cnt); p.cnt = (unsigned*)q;
  cudaGetSymbolAddress(&q, g_epoch); p.epoch = (unsigned*)q;

  cudaFuncSetAttribute(fused_kernel, cudaFuncAttributeMaxDynamicSharedMemorySize, SMEM_BYTES);
  cudaLaunchConfig_t cfg = {};
  cfg.gridDim = dim3(NCTA + 4);
  cfg.blockDim = dim3(384);
  cfg.dynamicSmemBytes = SMEM_BYTES;
  cfg.stream = cudaStreamPerThread;
  cudaLaunchAttribute at[1];
  at[0].id = cudaLaunchAttributeClusterDimension;
  at[0].val.clusterDim.x = 2; at[0].val.clusterDim.y = 1; at[0].val.clusterDim.z = 1;
  cfg.attrs = at;
  cfg.numAttrs = 1;
  cudaLaunchKernelEx(&cfg, fused_kernel, p);
}
```

```cpp
#include <cuda_runtime.h>
#include <cuda_bf16.h>
#include <cuda.h>
#include <stdint.h>

typedef __nv_bfloat16 bf16;

#define MAPPING 2

#define ALIGN 0

#define PF 0

#define EF 1

#define ALIGNE 3

#define CW 1

#define PAUSE 200

#define WMD 2

#define WMDELAY 2000

#define WMPACE 0

#define NPRE0 4

#define NPRE1 2
#define GATE 0

#define WFIRST 1

#define BDELAY 1500

#define ALIAS 1

#define PB1 0
#define PB2 0

#define LN2D 0

#define PIPEPOLL 0

__device__ __forceinline__ void wgmma_ss_n128(float (&d)[64], uint32_t da, uint32_t db, int scale_d) {
  asm volatile("{\n.reg .pred p;\n.reg .b64 da, db;\nsetp.ne.b32 p, %66, 0;\n"
    "mov.b64 da, {%64, 0x40000040};\nmov.b64 db, {%65, 0x40000040};\n"
    "wgmma.mma_async.sync.aligned.m64n128k16.f32.bf16.bf16 "
    "{%0, %1, %2, %3, %4, %5, %6, %7, %8, %9, %10, %11, %12, %13, %14, %15, "
    "%16, %17, %18, %19, %20, %21, %22, %23, %24, %25, %26, %27, %28, %29, %30, %31, "
    "%32, %33, %34, %35, %36, %37, %38, %39, %40, %41, %42, %43, %44, %45, %46, %47, "
    "%48, %49, %50, %51, %52, %53, %54, %55, %56, %57, %58, %59, %60, %61, %62, %63}, "
    "da, db, p, 1, 1, 0, 1;\n}\n"
    : "+f"(d[0]), "+f"(d[1]), "+f"(d[2]), "+f"(d[3]), "+f"(d[4]), "+f"(d[5]), "+f"(d[6]), "+f"(d[7]),
      "+f"(d[8]), "+f"(d[9]), "+f"(d[10]), "+f"(d[11]), "+f"(d[12]), "+f"(d[13]), "+f"(d[14]), "+f"(d[15]),
      "+f"(d[16]), "+f"(d[17]), "+f"(d[18]), "+f"(d[19]), "+f"(d[20]), "+f"(d[21]), "+f"(d[22]), "+f"(d[23]),
      "+f"(d[24]), "+f"(d[25]), "+f"(d[26]), "+f"(d[27]), "+f"(d[28]), "+f"(d[29]), "+f"(d[30]), "+f"(d[31]),
      "+f"(d[32]), "+f"(d[33]), "+f"(d[34]), "+f"(d[35]), "+f"(d[36]), "+f"(d[37]), "+f"(d[38]), "+f"(d[39]),
      "+f"(d[40]), "+f"(d[41]), "+f"(d[42]), "+f"(d[43]), "+f"(d[44]), "+f"(d[45]), "+f"(d[46]), "+f"(d[47]),
      "+f"(d[48]), "+f"(d[49]), "+f"(d[50]), "+f"(d[51]), "+f"(d[52]), "+f"(d[53]), "+f"(d[54]), "+f"(d[55]),
      "+f"(d[56]), "+f"(d[57]), "+f"(d[58]), "+f"(d[59]), "+f"(d[60]), "+f"(d[61]), "+f"(d[62]), "+f"(d[63])
    : "r"(da), "r"(db), "r"(scale_d));
}

__device__ __forceinline__ void wgmma_ss_n192(float (&d)[96], uint32_t da, uint32_t db, int scale_d) {
  asm volatile("{\n.reg .pred p;\n.reg .b64 da, db;\nsetp.ne.b32 p, %98, 0;\n"
    "mov.b64 da, {%96, 0x40000040};\nmov.b64 db, {%97, 0x40000040};\n"
    "wgmma.mma_async.sync.aligned.m64n192k16.f32.bf16.bf16 "
    "{%0, %1, %2, %3, %4, %5, %6, %7, %8, %9, %10, %11, %12, %13, %14, %15, "
    "%16, %17, %18, %19, %20, %21, %22, %23, %24, %25, %26, %27, %28, %29, %30, %31, "
    "%32, %33, %34, %35, %36, %37, %38, %39, %40, %41, %42, %43, %44, %45, %46, %47, "
    "%48, %49, %50, %51, %52, %53, %54, %55, %56, %57, %58, %59, %60, %61, %62, %63, "
    "%64, %65, %66, %67, %68, %69, %70, %71, %72, %73, %74, %75, %76, %77, %78, %79, "
    "%80, %81, %82, %83, %84, %85, %86, %87, %88, %89, %90, %91, %92, %93, %94, %95}, "
    "da, db, p, 1, 1, 0, 1;\n}\n"
    : "+f"(d[0]), "+f"(d[1]), "+f"(d[2]), "+f"(d[3]), "+f"(d[4]), "+f"(d[5]), "+f"(d[6]), "+f"(d[7]),
      "+f"(d[8]), "+f"(d[9]), "+f"(d[10]), "+f"(d[11]), "+f"(d[12]), "+f"(d[13]), "+f"(d[14]), "+f"(d[15]),
      "+f"(d[16]), "+f"(d[17]), "+f"(d[18]), "+f"(d[19]), "+f"(d[20]), "+f"(d[21]), "+f"(d[22]), "+f"(d[23]),
      "+f"(d[24]), "+f"(d[25]), "+f"(d[26]), "+f"(d[27]), "+f"(d[28]), "+f"(d[29]), "+f"(d[30]), "+f"(d[31]),
      "+f"(d[32]), "+f"(d[33]), "+f"(d[34]), "+f"(d[35]), "+f"(d[36]), "+f"(d[37]), "+f"(d[38]), "+f"(d[39]),
      "+f"(d[40]), "+f"(d[41]), "+f"(d[42]), "+f"(d[43]), "+f"(d[44]), "+f"(d[45]), "+f"(d[46]), "+f"(d[47]),
      "+f"(d[48]), "+f"(d[49]), "+f"(d[50]), "+f"(d[51]), "+f"(d[52]), "+f"(d[53]), "+f"(d[54]), "+f"(d[55]),
      "+f"(d[56]), "+f"(d[57]), "+f"(d[58]), "+f"(d[59]), "+f"(d[60]), "+f"(d[61]), "+f"(d[62]), "+f"(d[63]),
      "+f"(d[64]), "+f"(d[65]), "+f"(d[66]), "+f"(d[67]), "+f"(d[68]), "+f"(d[69]), "+f"(d[70]), "+f"(d[71]),
      "+f"(d[72]), "+f"(d[73]), "+f"(d[74]), "+f"(d[75]), "+f"(d[76]), "+f"(d[77]), "+f"(d[78]), "+f"(d[79]),
      "+f"(d[80]), "+f"(d[81]), "+f"(d[82]), "+f"(d[83]), "+f"(d[84]), "+f"(d[85]), "+f"(d[86]), "+f"(d[87]),
      "+f"(d[88]), "+f"(d[89]), "+f"(d[90]), "+f"(d[91]), "+f"(d[92]), "+f"(d[93]), "+f"(d[94]), "+f"(d[95])
    : "r"(da), "r"(db), "r"(scale_d));
}

__device__ __forceinline__ void wgmma_ss_n256(float (&d)[128], uint32_t da, uint32_t db, int scale_d) {
  asm volatile("{\n.reg .pred p;\n.reg .b64 da, db;\nsetp.ne.b32 p, %130, 0;\n"
    "mov.b64 da, {%128, 0x40000040};\nmov.b64 db, {%129, 0x40000040};\n"
    "wgmma.mma_async.sync.aligned.m64n256k16.f32.bf16.bf16 "
    "{%0, %1, %2, %3, %4, %5, %6, %7, %8, %9, %10, %11, %12, %13, %14, %15, "
    "%16, %17, %18, %19, %20, %21, %22, %23, %24, %25, %26, %27, %28, %29, %30, %31, "
    "%32, %33, %34, %35, %36, %37, %38, %39, %40, %41, %42, %43, %44, %45, %46, %47, "
    "%48, %49, %50, %51, %52, %53, %54, %55, %56, %57, %58, %59, %60, %61, %62, %63, "
    "%64, %65, %66, %67, %68, %69, %70, %71, %72, %73, %74, %75, %76, %77, %78, %79, "
    "%80, %81, %82, %83, %84, %85, %86, %87, %88, %89, %90, %91, %92, %93, %94, %95, "
    "%96, %97, %98, %99, %100, %101, %102, %103, %104, %105, %106, %107, %108, %109, %110, %111, "
    "%112, %113, %114, %115, %116, %117, %118, %119, %120, %121, %122, %123, %124, %125, %126, %127}, "
    "da, db, p, 1, 1, 0, 1;\n}\n"
    : "+f"(d[0]), "+f"(d[1]), "+f"(d[2]), "+f"(d[3]), "+f"(d[4]), "+f"(d[5]), "+f"(d[6]), "+f"(d[7]),
      "+f"(d[8]), "+f"(d[9]), "+f"(d[10]), "+f"(d[11]), "+f"(d[12]), "+f"(d[13]), "+f"(d[14]), "+f"(d[15]),
      "+f"(d[16]), "+f"(d[17]), "+f"(d[18]), "+f"(d[19]), "+f"(d[20]), "+f"(d[21]), "+f"(d[22]), "+f"(d[23]),
      "+f"(d[24]), "+f"(d[25]), "+f"(d[26]), "+f"(d[27]), "+f"(d[28]), "+f"(d[29]), "+f"(d[30]), "+f"(d[31]),
      "+f"(d[32]), "+f"(d[33]), "+f"(d[34]), "+f"(d[35]), "+f"(d[36]), "+f"(d[37]), "+f"(d[38]), "+f"(d[39]),
      "+f"(d[40]), "+f"(d[41]), "+f"(d[42]), "+f"(d[43]), "+f"(d[44]), "+f"(d[45]), "+f"(d[46]), "+f"(d[47]),
      "+f"(d[48]), "+f"(d[49]), "+f"(d[50]), "+f"(d[51]), "+f"(d[52]), "+f"(d[53]), "+f"(d[54]), "+f"(d[55]),
      "+f"(d[56]), "+f"(d[57]), "+f"(d[58]), "+f"(d[59]), "+f"(d[60]), "+f"(d[61]), "+f"(d[62]), "+f"(d[63]),
      "+f"(d[64]), "+f"(d[65]), "+f"(d[66]), "+f"(d[67]), "+f"(d[68]), "+f"(d[69]), "+f"(d[70]), "+f"(d[71]),
      "+f"(d[72]), "+f"(d[73]), "+f"(d[74]), "+f"(d[75]), "+f"(d[76]), "+f"(d[77]), "+f"(d[78]), "+f"(d[79]),
      "+f"(d[80]), "+f"(d[81]), "+f"(d[82]), "+f"(d[83]), "+f"(d[84]), "+f"(d[85]), "+f"(d[86]), "+f"(d[87]),
      "+f"(d[88]), "+f"(d[89]), "+f"(d[90]), "+f"(d[91]), "+f"(d[92]), "+f"(d[93]), "+f"(d[94]), "+f"(d[95]),
      "+f"(d[96]), "+f"(d[97]), "+f"(d[98]), "+f"(d[99]), "+f"(d[100]), "+f"(d[101]), "+f"(d[102]), "+f"(d[103]),
      "+f"(d[104]), "+f"(d[105]), "+f"(d[106]), "+f"(d[107]), "+f"(d[108]), "+f"(d[109]), "+f"(d[110]), "+f"(d[111]),
      "+f"(d[112]), "+f"(d[113]), "+f"(d[114]), "+f"(d[115]), "+f"(d[116]), "+f"(d[117]), "+f"(d[118]), "+f"(d[119]),
      "+f"(d[120]), "+f"(d[121]), "+f"(d[122]), "+f"(d[123]), "+f"(d[124]), "+f"(d[125]), "+f"(d[126]), "+f"(d[127])
    : "r"(da), "r"(db), "r"(scale_d));
}

namespace {

constexpr int SEQ = 2048, DM = 1024, FF = 3584;
constexpr int NCTA = 128;

constexpr uint32_t STG_OFF = 196608;
constexpr uint32_t MISC_OFF = STG_OFF + 32768;
constexpr uint32_t SMEM_BYTES = MISC_OFF + 3072;
constexpr uint32_t RED_OFF = 2 * 49152;
constexpr uint32_t MODB_OFF = MISC_OFF + 512;

enum { B_FQ = 0, B_EQ = 4, B_FW = 8, B_EW = 14, B_FG = 20, B_EG = 24, B_FD = 28, B_ED = 34,
       B_STGF = 40, B_MODB = 42, B_GATE = 44, B_MODA = 45, B_RDY = 48, B_STGE = 56, B_COUNT = 58 };
enum { C_H = 0, C_O = 1, C_H2 = 3, C_ACT = 4, C_HA = 8, C_H2A = 9 };

struct Params {
  CUtensorMap h, o_ld, o_st, h2, act, out, wqkv, wqkv32, wo, wg, wu, wd, act_st, wm;
  const bf16* x;
  const bf16* c;
  const bf16* wmod;
  uint4* x1;
  uint4* modll;
  uint4* halo;
  uint4* stats1;
  uint4* stats2;
  unsigned* cnt;
  unsigned* epoch;
  uint8_t slot[64];
};

__device__ bf16 g_h[SEQ * DM];
__device__ bf16 g_o[SEQ * DM];
__device__ bf16 g_h2[SEQ * DM];
__device__ bf16 g_act[SEQ * FF];
__device__ uint4 g_x1[NCTA * 8 * 256];
__device__ uint4 g_modll[3072 / 2];
__device__ uint4 g_halo[16 * 8 * 2 * 2 * 8 * 32];
__device__ uint4 g_stats[2 * SEQ * 8];
__device__ unsigned g_cnt[16 * 32];
__device__ uint4 g_epoch;
#define TR(off)

__device__ __forceinline__ uint32_t smem_u32(const void* p) { return (uint32_t)__cvta_generic_to_shared(p); }
__device__ __forceinline__ void mbar_init(uint32_t bar, uint32_t count) {
  asm volatile("mbarrier.init.shared::cta.b64 [%0], %1;" ::"r"(bar), "r"(count));
}
__device__ __forceinline__ void mbar_expect_tx(uint32_t bar, uint32_t bytes) {
  asm volatile("mbarrier.arrive.expect_tx.shared::cta.b64 _, [%0], %1;" ::"r"(bar), "r"(bytes) : "memory");
}
__device__ __forceinline__ void mbar_arrive(uint32_t bar) {
  asm volatile("mbarrier.arrive.shared::cta.b64 _, [%0];" ::"r"(bar) : "memory");
}
__device__ __forceinline__ void mbar_arrive_cluster(uint32_t cluster_addr) {
  asm volatile("mbarrier.arrive.shared::cluster.b64 _, [%0];" ::"r"(cluster_addr) : "memory");
}
__device__ __forceinline__ uint32_t mapa(uint32_t addr, uint32_t cta) {
  uint32_t r;
  asm volatile("mapa.shared::cluster.u32 %0, %1, %2;" : "=r"(r) : "r"(addr), "r"(cta));
  return r;
}
__device__ __forceinline__ void mbar_wait(uint32_t bar, uint32_t parity) {
  asm volatile(
      "{\n.reg .pred p;\n"
      "WAIT_%=:\n"
      "mbarrier.try_wait.parity.shared::cta.b64 p, [%0], %1;\n"
      "@!p bra WAIT_%=;\n}\n" ::"r"(bar), "r"(parity) : "memory");
}
__device__ __forceinline__ void mbar_wait_watchdog(uint32_t bar, uint32_t parity) {
  asm volatile(
      "{\n.reg .pred p;\n.reg .u64 t0, t1;\nmov.u64 t0, %%globaltimer;\n"
      "WAIT_%=:\n"
      "mbarrier.try_wait.parity.shared::cta.b64 p, [%0], %1;\n"
      "@p bra DONE_%=;\n"
      "mov.u64 t1, %%globaltimer;\n"
      "sub.u64 t1, t1, t0;\n"
      "setp.lt.u64 p, t1, 2000000000;\n"
      "@p bra WAIT_%=;\n"
      "trap;\n"
      "DONE_%=:\n}\n" ::"r"(bar), "r"(parity) : "memory");
}
__device__ __forceinline__ void cnt_wait(const unsigned* p, unsigned target) {
  asm volatile(
      "{\n.reg .pred p;\n.reg .u32 v;\n.reg .s32 d;\n"
      "WAIT_%=:\n"
      "ld.relaxed.gpu.global.u32 v, [%0];\n"
      "sub.s32 d, v, %1;\n"
      "setp.lt.s32 p, d, 0;\n"
      "@p bra WAIT_%=;\n"
      "fence.proxy.async.global;\n"
      "}\n" ::"l"(p), "r"(target) : "memory");
}
__device__ __forceinline__ void cnt_wait_lazy(const unsigned* p, unsigned target) {
  asm volatile(
      "{\n.reg .pred p;\n.reg .u32 v;\n.reg .s32 d;\n"
      "WAIT_%=:\n"
      "nanosleep.u32 400;\n"
      "ld.relaxed.gpu.global.u32 v, [%0];\n"
      "sub.s32 d, v, %1;\n"
      "setp.lt.s32 p, d, 0;\n"
      "@p bra WAIT_%=;\n"
      "fence.proxy.async.global;\n"
      "}\n" ::"l"(p), "r"(target) : "memory");
}
__device__ __forceinline__ void cnt_signal(unsigned* p) {
  asm volatile("{\n.reg .pred p;\nelect.sync _|p, 0xffffffff;\n@p red.relaxed.gpu.global.add.u32 [%0], 1;\n}\n" ::"l"(p) : "memory");
}
__device__ __forceinline__ void ll_store(uint4* p, uint32_t a, uint32_t b, uint32_t tag) {
  asm volatile("st.relaxed.gpu.global.v2.b64 [%0], {%1, %2};" ::"l"(p), "l"((uint64_t)a | ((uint64_t)tag << 32)),
               "l"((uint64_t)b | ((uint64_t)tag << 32)) : "memory");
}
__device__ __forceinline__ uint4 ll_peek(const uint4* p) {
  uint4 v;
  asm volatile("ld.relaxed.gpu.global.v4.u32 {%0, %1, %2, %3}, [%4];" : "=r"(v.x), "=r"(v.y), "=r"(v.z), "=r"(v.w) : "l"(p) : "memory");
  return v;
}
template <int N, int SLEEP = 0, class F>
__device__ __forceinline__ void ll_poll(F addr, uint32_t tag, uint32_t (&out)[2 * N]) {
  for (;;) {
    uint4 v[N];
#pragma unroll
    for (int i = 0; i < N; i++) v[i] = ll_peek(addr(i));
    uint32_t bad = 0;
#pragma unroll
    for (int i = 0; i < N; i++) {
      bad |= (v[i].y ^ tag) | (v[i].w ^ tag);
      out[2 * i] = v[i].x;
      out[2 * i + 1] = v[i].z;
    }
    if (__all_sync(~0u, bad == 0)) break;
    if (SLEEP) __nanosleep(SLEEP);
  }
}
constexpr uint64_t POLICY_EVICT_FIRST = 0x12F0000000000000ull;
__device__ __forceinline__ void expect_tx_elect(uint32_t bar, uint32_t bytes) {
  asm volatile("{\n.reg .pred p;\nelect.sync _|p, 0xffffffff;\n@p mbarrier.arrive.expect_tx.shared::cta.b64 _, [%0], %1;\n}\n" ::"r"(bar), "r"(bytes) : "memory");
}
__device__ __forceinline__ void arrive_elect(uint32_t bar) {
  asm volatile("{\n.reg .pred p;\nelect.sync _|p, 0xffffffff;\n@p mbarrier.arrive.shared::cta.b64 _, [%0];\n}\n" ::"r"(bar) : "memory");
}
__device__ __forceinline__ void tma_load(uint32_t dst, const CUtensorMap* m, uint32_t bar, int c0, int c1) {
  asm volatile("{\n.reg .pred p;\nelect.sync _|p, 0xffffffff;\n"
               "@p cp.async.bulk.tensor.2d.shared::cluster.global.mbarrier::complete_tx::bytes [%0], [%1, {%3, %4}], [%2];\n}\n"
               ::"r"(dst), "l"(m), "r"(bar), "r"(c0), "r"(c1) : "memory");
}
__device__ __forceinline__ void tma_load_mc(uint32_t dst, const CUtensorMap* m, uint32_t bar, int c0, int c1) {
  asm volatile("{\n.reg .pred p;\nelect.sync _|p, 0xffffffff;\n"
               "@p cp.async.bulk.tensor.2d.shared::cluster.global.mbarrier::complete_tx::bytes.multicast::cluster.L2::cache_hint [%0], [%1, {%3, %4}], [%2], %5, %6;\n}\n"
               ::"r"(dst), "l"(m), "r"(bar), "r"(c0), "r"(c1), "h"((uint16_t)3), "l"(POLICY_EVICT_FIRST) : "memory");
}
__device__ __forceinline__ void tma_load_ef(uint32_t dst, const CUtensorMap* m, uint32_t bar, int c0, int c1) {
  asm volatile("{\n.reg .pred p;\nelect.sync _|p, 0xffffffff;\n"
               "@p cp.async.bulk.tensor.2d.shared::cluster.global.mbarrier::complete_tx::bytes.L2::cache_hint [%0], [%1, {%3, %4}], [%2], %5;\n}\n"
               ::"r"(dst), "l"(m), "r"(bar), "r"(c0), "r"(c1), "l"(POLICY_EVICT_FIRST) : "memory");
}
__device__ __forceinline__ void tma_store2(const CUtensorMap* m, uint32_t src, int c0, int c1) {
  asm volatile("{\n.reg .pred p;\nelect.sync _|p, 0xffffffff;\n"
               "@p cp.async.bulk.tensor.2d.global.shared::cta.bulk_group [%0, {%2, %3}], [%1];\n}\n"
               ::"l"(m), "r"(src), "r"(c0), "r"(c1) : "memory");
}
__device__ __forceinline__ void tma_store3(const CUtensorMap* m, uint32_t src, int c0, int c1, int c2) {
  asm volatile("{\n.reg .pred p;\nelect.sync _|p, 0xffffffff;\n"
               "@p cp.async.bulk.tensor.3d.global.shared::cta.bulk_group [%0, {%2, %3, %4}], [%1];\n}\n"
               ::"l"(m), "r"(src), "r"(c0), "r"(c1), "r"(c2) : "memory");
}
__device__ __forceinline__ void store_pause(bool sleep) {
  asm volatile("cp.async.bulk.commit_group;" ::: "memory");
  asm volatile("cp.async.bulk.wait_group.read 0;" ::: "memory");
  if (sleep) __nanosleep(PAUSE);
}
__device__ __forceinline__ void l2_prefetch_tile(const CUtensorMap* m, int c0, int c1) {
  asm volatile("{\n.reg .pred p;\nelect.sync _|p, 0xffffffff;\n@p cp.async.bulk.prefetch.tensor.2d.L2.global.L2::cache_hint [%0, {%1, %2}], %3;\n}\n"
               ::"l"(m), "r"(c0), "r"(c1), "l"(POLICY_EVICT_FIRST) : "memory");
}
__device__ __forceinline__ void prefetch_map(const CUtensorMap* m) {
  asm volatile("prefetch.tensormap [%0];" ::"l"(m) : "memory");
}
__device__ __forceinline__ void wg_fence() { asm volatile("wgmma.fence.sync.aligned;" ::: "memory"); }
__device__ __forceinline__ void wg_commit() { asm volatile("wgmma.commit_group.sync.aligned;" ::: "memory"); }
template <int N>
__device__ __forceinline__ void wg_wait() { asm volatile("wgmma.wait_group.sync.aligned %0;" ::"n"(N) : "memory"); }
__device__ __forceinline__ void bar_sync(int id, int n) { asm volatile("bar.sync %0, %1;" ::"r"(id), "r"(n) : "memory"); }
__device__ __forceinline__ void wg_bar(int cw) {
  asm volatile("{\n.reg .pred p;\nsetp.ne.s32 p, %0, 0;\n@p bar.sync 3, 128;\n@!p bar.sync 2, 128;\n}\n" ::"r"(cw) : "memory");
}
__device__ __forceinline__ void cluster_arrive() { asm volatile("barrier.cluster.arrive.release.aligned;" ::: "memory"); }
__device__ __forceinline__ void cluster_arrive_relaxed() { asm volatile("barrier.cluster.arrive.relaxed.aligned;" ::: "memory"); }
__device__ __forceinline__ void cluster_wait() { asm volatile("barrier.cluster.wait.acquire.aligned;" ::: "memory"); }
__device__ __forceinline__ uint32_t load_epoch(const unsigned* p) {
  uint32_t e;
  asm volatile("ld.relaxed.gpu.global.u32 %0, [%1];" : "=r"(e) : "l"(p) : "memory");
  return e;
}
__device__ __forceinline__ uint32_t pack2(float lo, float hi) {
  uint32_t r;
  asm("cvt.rn.bf16x2.f32 %0, %1, %2;" : "=r"(r) : "f"(hi), "f"(lo));
  return r;
}
__device__ __forceinline__ float bf_lo(uint32_t v) { return __uint_as_float(v << 16); }
__device__ __forceinline__ float bf_hi(uint32_t v) { return __uint_as_float(v & 0xffff0000u); }
__device__ __forceinline__ float bf_round(float v) { return __bfloat162float(__float2bfloat16_rn(v)); }
__device__ __forceinline__ float silu_f(float v) { return __fdividef(v, 1.0f + __expf(-v)); }
__device__ __forceinline__ uint4 ldg_nc(const void* p) {
  uint4 v;
  asm volatile("ld.global.nc.L1::no_allocate.v4.u32 {%0, %1, %2, %3}, [%4];" : "=r"(v.x), "=r"(v.y), "=r"(v.z), "=r"(v.w) : "l"(p));
  return v;
}
__device__ __forceinline__ uint4 ldg_stream(const void* p) {
  uint4 v;
  asm volatile("ld.global.nc.L1::no_allocate.L2::cache_hint.v4.u32 {%0, %1, %2, %3}, [%4], %5;" : "=r"(v.x), "=r"(v.y), "=r"(v.z), "=r"(v.w) : "l"(p), "l"(POLICY_EVICT_FIRST));
  return v;
}
__device__ __forceinline__ uint32_t ldg32(const void* p) {
  uint32_t v;
  asm volatile("ld.global.nc.u32 %0, [%1];" : "=r"(v) : "l"(p));
  return v;
}
__device__ __forceinline__ void stmatrix4(uint32_t addr, uint32_t a, uint32_t b, uint32_t c, uint32_t d) {
  asm volatile("stmatrix.sync.aligned.m8n8.x4.shared.b16 [%0], {%1, %2, %3, %4};" ::"r"(addr), "r"(a), "r"(b), "r"(c), "r"(d) : "memory");
}
__device__ __forceinline__ void stmatrix2(uint32_t addr, uint32_t a, uint32_t b) {
  asm volatile("stmatrix.sync.aligned.m8n8.x2.shared.b16 [%0], {%1, %2};" ::"r"(addr), "r"(a), "r"(b) : "memory");
}
__device__ __forceinline__ void stmatrix1(uint32_t addr, uint32_t a) {
  asm volatile("stmatrix.sync.aligned.m8n8.x1.shared.b16 [%0], {%1};" ::"r"(addr), "r"(a) : "memory");
}
__device__ __forceinline__ uint32_t movmatrix(uint32_t a) {
  uint32_t d;
  asm("movmatrix.sync.aligned.m8n8.trans.b16 %0, %1;" : "=r"(d) : "r"(a));
  return d;
}
__device__ __forceinline__ void mma16816(float (&d)[4], uint32_t a0, uint32_t a1, uint32_t a2, uint32_t a3, uint32_t b0, uint32_t b1) {
  asm("mma.sync.aligned.m16n8k16.row.col.f32.bf16.bf16.f32 {%0, %1, %2, %3}, {%4, %5, %6, %7}, {%8, %9}, {%0, %1, %2, %3};"
               : "+f"(d[0]), "+f"(d[1]), "+f"(d[2]), "+f"(d[3]) : "r"(a0), "r"(a1), "r"(a2), "r"(a3), "r"(b0), "r"(b1));
}
__device__ __forceinline__ void mma1688(float (&d)[4], uint32_t a0, uint32_t a1, uint32_t b0) {
  asm("mma.sync.aligned.m16n8k8.row.col.f32.bf16.bf16.f32 {%0, %1, %2, %3}, {%4, %5}, {%6}, {%0, %1, %2, %3};"
               : "+f"(d[0]), "+f"(d[1]), "+f"(d[2]), "+f"(d[3]) : "r"(a0), "r"(a1), "r"(b0));
}
__device__ __forceinline__ void ldmatrix4t(uint32_t (&b)[4], uint32_t addr) {
  asm volatile("ldmatrix.sync.aligned.m8n8.x4.trans.shared.b16 {%0, %1, %2, %3}, [%4];" : "=r"(b[0]), "=r"(b[1]), "=r"(b[2]), "=r"(b[3]) : "r"(addr) : "memory");
}
__device__ __forceinline__ void ldmatrix4(uint32_t& a, uint32_t& b, uint32_t& c, uint32_t& d, uint32_t addr) {
  asm volatile("ldmatrix.sync.aligned.m8n8.x4.shared.b16 {%0, %1, %2, %3}, [%4];" : "=r"(a), "=r"(b), "=r"(c), "=r"(d) : "r"(addr) : "memory");
}
__device__ __forceinline__ void cp_async16(uint32_t dst, const void* src) {
  asm volatile("cp.async.cg.shared.global.L2::cache_hint [%0], [%1], 16, %2;" ::"r"(dst), "l"(src), "l"(POLICY_EVICT_FIRST) : "memory");
}
__device__ __forceinline__ uint32_t lds32(uint32_t addr) {
  uint32_t v;
  asm volatile("ld.shared.u32 %0, [%1];" : "=r"(v) : "r"(addr) : "memory");
  return v;
}
__device__ __forceinline__ void sts64f(uint32_t addr, float a, float b) {
  asm volatile("st.shared.v2.f32 [%0], {%1, %2};" ::"r"(addr), "f"(a), "f"(b) : "memory");
}
constexpr float QK_SCALE = 0.17677669529663687f;
__device__ __forceinline__ void softmax8(float& p0, float& p1) {
  float m = fmaxf(p0, p1);
  m = fmaxf(m, __shfl_xor_sync(~0u, m, 1));
  m = fmaxf(m, __shfl_xor_sync(~0u, m, 2));
  asm("ex2.approx.ftz.f32 %0, %1;" : "=f"(p0) : "f"((p0 - m) * 1.4426950408889634f));
  asm("ex2.approx.ftz.f32 %0, %1;" : "=f"(p1) : "f"((p1 - m) * 1.4426950408889634f));
  float s = p0 + p1;
  s += __shfl_xor_sync(~0u, s, 1);
  s += __shfl_xor_sync(~0u, s, 2);
  float r;
  asm("rcp.approx.ftz.f32 %0, %1;" : "=f"(r) : "f"(s));
  p0 *= r;
  p1 *= r;
}
__device__ __forceinline__ void sts128(uint32_t addr, uint32_t a, uint32_t b, uint32_t c, uint32_t d) {
  asm volatile("st.shared.v4.u32 [%0], {%1, %2, %3, %4};" ::"r"(addr), "r"(a), "r"(b), "r"(c), "r"(d) : "memory");
}
__device__ __forceinline__ uint4 lds128(uint32_t addr) {
  uint4 v;
  asm volatile("ld.shared.v4.u32 {%0, %1, %2, %3}, [%4];" : "=r"(v.x), "=r"(v.y), "=r"(v.z), "=r"(v.w) : "r"(addr) : "memory");
  return v;
}
__device__ __forceinline__ float2 lds64f(uint32_t addr) {
  float2 v;
  asm volatile("ld.shared.v2.f32 {%0, %1}, [%2];" : "=f"(v.x), "=f"(v.y) : "r"(addr) : "memory");
  return v;
}
__device__ __forceinline__ void sts32f(uint32_t addr, float v) {
  asm volatile("st.shared.f32 [%0], %1;" ::"r"(addr), "f"(v) : "memory");
}
__device__ __forceinline__ float lds32f(uint32_t addr) {
  float v;
  asm volatile("ld.shared.f32 %0, [%1];" : "=f"(v) : "r"(addr) : "memory");
  return v;
}
#define PROF_AT(cond, slot) do {} while (0)

constexpr uint32_t SMEM_BASE = 1024;
constexpr uint32_t DESC_A = (1u << 16) | (SMEM_BASE >> 4);
constexpr uint32_t DESC_B = ((8192u >> 4) << 16) | ((SMEM_BASE + 16384) >> 4);

template <int BN> struct Wg;
template <> struct Wg<128> { static __device__ __forceinline__ void mma(float (&d)[64], uint32_t a, uint32_t b, int s) { wgmma_ss_n128(d, a, b, s); } };
template <> struct Wg<192> { static __device__ __forceinline__ void mma(float (&d)[96], uint32_t a, uint32_t b, int s) { wgmma_ss_n192(d, a, b, s); } };
template <> struct Wg<256> { static __device__ __forceinline__ void mma(float (&d)[128], uint32_t a, uint32_t b, int s) { wgmma_ss_n256(d, a, b, s); } };

struct Ring {
  uint32_t full0, rel0;
  int s;
  uint32_t ph;
  bool releaser;
};

template <int N>
__device__ __forceinline__ void fence_regs(float (&a)[N]) {
#pragma unroll
  for (int i = 0; i < N; i++) asm volatile("" : "+f"(a[i])::"memory");
}

template <int BN, int NST, uint32_t STAGE>
__device__ __forceinline__ void kblock(float (&acc)[BN / 2], Ring& g, uint32_t a_addr, bool zero, uint32_t& prev) {
  mbar_wait(g.full0 + 8 * g.s, g.ph);
  const uint32_t da = DESC_A + (a_addr >> 4);
  const uint32_t db = DESC_B + g.s * (STAGE >> 4);
  wg_fence();
#pragma unroll
  for (int k = 0; k < 4; k++) Wg<BN>::mma(acc, da + k * 2, db + k * 128, !(zero && k == 0));
  wg_commit();
  wg_wait<1>();
  if (prev != 0) mbar_arrive_cluster(prev);
  prev = g.releaser ? g.rel0 + 8 * g.s : 0u;
  if (++g.s == NST) { g.s = 0; g.ph ^= 1; }
}
template <int N>
__device__ __forceinline__ void tile_end(float (&acc)[N], uint32_t& prev) {
  wg_wait<0>();
  if (prev != 0) mbar_arrive_cluster(prev);
  prev = 0;
  fence_regs(acc);
}

__device__ __forceinline__ int other_kb(int q, int j) {
  const int ch = q >= 7, jj = q - 7 * ch;
  return 2 * (jj < j ? jj : jj + 1) + ch;
}
__device__ __forceinline__ int own_first(int it, int j) {
  return it >= 16 ? (it & 15) : (it < 2 ? 2 * j + it : other_kb(it - 2, j));
}
__device__ __forceinline__ int qkv_kb(int it, int j) {
  return it < 4 ? 2 * j + (it & 1) : other_kb(it < 18 ? it - 4 : it - 18, j);
}
__device__ __forceinline__ int wo_k(int it, int j) {
  return it < 8 ? it * 128 : (it == 8 ? j : (it - 9 < j ? it - 9 : it - 8)) * 128 + 64;
}
__device__ __forceinline__ int down_k(int it) {
  const int r = (it >> 4) - 1, idx = it & 15;
  return r < 0 ? idx * 64 : (r < 3 ? (idx >> 1) * 448 + r * 128 + (idx & 1) * 64 : idx * 448 + 384);
}
__device__ __forceinline__ void wait_p3_free(uint32_t empty3, int i) {
  mbar_wait(empty3 + 8 * ((i * 2) / 3), 1);
  mbar_wait(empty3 + 8 * ((i * 2 + 1) / 3), 1);
}
__device__ __forceinline__ void wait_p2_free(uint32_t empty2, int i) {
  const int w0 = (i * 3) / 2, w1 = (i * 3 + 2) / 2;
  mbar_wait(empty2 + 8 * w0, w0 < 4 ? 0 : 1);
  mbar_wait(empty2 + 8 * w1, w1 < 4 ? 0 : 1);
}

__device__ __forceinline__ void chan(float& m, float& q, float m2, float q2, float n) {
  const float d = m2 - m;
  m = 0.5f * (m + m2);
  q = q + q2 + d * d * (0.5f * n);
}

template <int N>
__device__ __forceinline__ void row_stats(const uint32_t (&ll)[N], float& mean, float& rstd) {
  float ma = __uint_as_float(ll[0]), qa = __uint_as_float(ll[1]), mb = __uint_as_float(ll[4]), qb = __uint_as_float(ll[5]);
  chan(ma, qa, __uint_as_float(ll[2]), __uint_as_float(ll[3]), 128.f);
  chan(mb, qb, __uint_as_float(ll[6]), __uint_as_float(ll[7]), 128.f);
  chan(ma, qa, mb, qb, 256.f);
  const float mo = __shfl_xor_sync(~0u, ma, 16), qo = __shfl_xor_sync(~0u, qa, 16);
  chan(ma, qa, mo, qo, 512.f);
  mean = ma;
  rstd = rsqrtf(qa * (1.0f / DM) + 1e-5f);
}

__device__ __forceinline__ void publish_stats(const uint32_t (&xl)[16], const uint32_t (&xh)[16], uint4* slot, int lane, uint32_t tag) {
  float ds[4] = {0.f, 0.f, 0.f, 0.f}, dl[4] = {0.f, 0.f, 0.f, 0.f}, dh[4] = {0.f, 0.f, 0.f, 0.f};
#pragma unroll
  for (int q = 0; q < 8; q++) {
    mma16816(ds, xl[2 * q], xh[2 * q], xl[2 * q + 1], xh[2 * q + 1], 0x3f803f80u, 0x3f803f80u);
    mma16816(dl, xl[2 * q], xh[2 * q], xl[2 * q + 1], xh[2 * q + 1], xl[2 * q], xl[2 * q + 1]);
    mma16816(dh, xl[2 * q], xh[2 * q], xl[2 * q + 1], xh[2 * q + 1], xh[2 * q], xh[2 * q + 1]);
  }
  const int r = lane >> 2;
  if ((lane & 3) == (r >> 1)) {
    const float ml = ds[0] * (1.0f / 128), mh = ds[2] * (1.0f / 128);
    const float ql = fmaxf(((r & 1) ? dl[1] : dl[0]) - ds[0] * ml, 0.f), qh = fmaxf(((r & 1) ? dh[3] : dh[2]) - ds[2] * mh, 0.f);
    ll_store(slot + r, __float_as_uint(ml), __float_as_uint(ql), tag);
    ll_store(slot + r + 8, __float_as_uint(mh), __float_as_uint(qh), tag);
  }
  __syncwarp();
}

__device__ __forceinline__ void stage_slab(uint32_t chunk, int warp, int lane, const uint32_t (&lo)[8], const uint32_t (&hi)[8]) {
  const int row = warp * 16 + (lane & 7) + ((lane >> 3) & 1) * 8;
  const uint32_t rbase = chunk + row * 128;
#pragma unroll
  for (int q = 0; q < 4; q++) {
    const int grp = 2 * q + (lane >> 4);
    stmatrix4(rbase + ((grp ^ (row & 7)) << 4), lo[2 * q], hi[2 * q], lo[2 * q + 1], hi[2 * q + 1]);
  }
}
__device__ __forceinline__ float silu_mul(float g, float u) {
  float e, r;
  asm("ex2.approx.ftz.f32 %0, %1;" : "=f"(e) : "f"(g * -1.4426950408889634f));
  asm("rcp.approx.ftz.f32 %0, %1;" : "=f"(r) : "f"(1.0f + e));
  return g * r * u;
}
__device__ __forceinline__ uint32_t swiglu2(uint32_t g2, uint32_t u2) {
  asm volatile("" : "+r"(g2));
  return pack2(silu_mul(bf_lo(g2), bf_lo(u2)), silu_mul(bf_hi(g2), bf_hi(u2)));
}
__device__ __forceinline__ void stage_done(uint32_t bar, int lane) {
  asm volatile("fence.proxy.async.shared::cta;" ::: "memory");
  __syncwarp();
  if (lane == 0) mbar_arrive(bar);
}

__device__ __forceinline__ int fresh_tid() {
  int t;
  asm volatile("mov.u32 %0, %%tid.x;" : "=r"(t));
  return t;
}
#define RING_IDS()                                                                                           \
  const int tid = fresh_tid() - 128;                                                                         \
  const int cw = __shfl_sync(~0u, tid >> 7, 0), warp = __shfl_sync(~0u, (tid >> 5) & 3, 0);                  \
  const bool releaser = (tid & 31) < 2;                                                                      \
  const uint32_t rbars = mapa(bars, tid & 1);                                                                \
  const uint32_t a_base = cw * 8192
#define LANE_IDS()                                                                                           \
  const int lane = fresh_tid() & 31, r = lane >> 2, c = lane & 3;                                            \
  const int srow = warp * 16 + (lane & 7) + ((lane >> 3) & 1) * 8;                                           \
  const uint32_t slab = stg + cw * 8192 + srow * 128, sw0 = (lane >> 4) ^ (srow & 7);                        \
  (void)r; (void)c; (void)slab; (void)sw0

template <int NPRE, class Step>
__device__ __forceinline__ void attention(float (&acc)[96], const Params& p, int rho, int rb, int cta, int cw, int warp, uint32_t tag,
                                          uint32_t stg, uint32_t bars, uint32_t& prev, Step step) {
  uint32_t ql[8], qh[8], k0[8], k1[8], v0[8], v1[8], hp[16];
  step();
  fence_regs(acc);
#pragma unroll
  for (int t = 0; t < 8; t++) {
    k0[t] = pack2(acc[4 * (8 + t)], acc[4 * (8 + t) + 1]);
    k1[t] = pack2(acc[4 * (8 + t) + 2], acc[4 * (8 + t) + 3]);
    v0[t] = pack2(acc[4 * (16 + t)], acc[4 * (16 + t) + 1]);
    v1[t] = pack2(acc[4 * (16 + t) + 2], acc[4 * (16 + t) + 3]);
    asm volatile("" : "+r"(k0[t]), "+r"(k1[t]), "+r"(v0[t]), "+r"(v1[t]));
  }
  const int lane = fresh_tid() & 31, r = lane >> 2, c = lane & 3;
#pragma unroll
  for (int t = 0; t < 8; t++) v1[t] = movmatrix(v1[t]);
  mbar_wait(bars + 8 * B_STGE, rho);
  mbar_wait(bars + 8 * (B_STGE + 1), 0);
  const uint32_t xch = stg + 16384 + (cw * 4 + warp) * 2048 + lane * 16;
  if (warp < 3) {
    sts128(xch, k1[0], k1[1], k1[2], k1[3]);
    sts128(xch + 512, k1[4], k1[5], k1[6], k1[7]);
    sts128(xch + 1024, v1[0], v1[1], v1[2], v1[3]);
    sts128(xch + 1536, v1[4], v1[5], v1[6], v1[7]);
  } else if (rb < 15) {
    uint4* dst = p.halo + ((cta * 2 + rho) * 2 + cw) * 256 + lane;
#pragma unroll
    for (int t = 0; t < 4; t++) {
      ll_store(dst + t * 32, k1[2 * t], k1[2 * t + 1], tag);
      ll_store(dst + (4 + t) * 32, v1[2 * t], v1[2 * t + 1], tag);
    }
  }
#pragma unroll
  for (int t = 0; t < 8; t++) {
    v0[t] = movmatrix(v0[t]);
    ql[t] = pack2(acc[4 * t], acc[4 * t + 1]);
    qh[t] = pack2(acc[4 * t + 2], acc[4 * t + 3]);
    asm volatile("" : "+r"(v0[t]), "+r"(ql[t]), "+r"(qh[t]));
  }
#pragma unroll 1
  for (int i = 0; i < NPRE; i++) step();
  const uint4* src = p.halo + (((cta - 8) * 2 + rho) * 2 + cw) * 256 + lane;
  uint4 early[8] = {};
  if (warp == 0 && rb > 0) {
#pragma unroll
    for (int i = 0; i < 8; i++) early[i] = ll_peek(src + i * 32);
  }
  step();
  wg_bar(cw);
  if (warp > 0) {
#pragma unroll
    for (int t = 0; t < 4; t++) {
      const uint4 a = lds128(xch - 2048 + t * 512);
      hp[4 * t] = a.x; hp[4 * t + 1] = a.y; hp[4 * t + 2] = a.z; hp[4 * t + 3] = a.w;
    }
  } else if (rb > 0) {
    uint32_t bad = 0;
#pragma unroll
    for (int i = 0; i < 8; i++) {
      bad |= (early[i].y ^ tag) | (early[i].w ^ tag);
      hp[2 * i] = early[i].x;
      hp[2 * i + 1] = early[i].z;
    }
    if (!__all_sync(~0u, bad == 0)) ll_poll<8>([&](int i) { return src + i * 32; }, tag, hp);
  } else {
#pragma unroll
    for (int t = 0; t < 16; t++) hp[t] = 0;
  }
  wg_wait<0>();
  if (prev != 0) mbar_arrive_cluster(prev);
  prev = 0;
#pragma unroll
  for (int t = 0; t < 8; t++) asm volatile("" : "+r"(ql[t])::"memory");
  const bool up0 = 2 * c > r, up1 = 2 * c + 1 > r;
  const bool first = (rb == 0) && (warp == 0);
  uint32_t a0[2], a2[2], a3[2], a5[2];
#pragma unroll
  for (int h = 0; h < 2; h++) {
    float sp[4] = {0.f, 0.f, 0.f, 0.f}, s0[4] = {0.f, 0.f, 0.f, 0.f}, s1[4] = {0.f, 0.f, 0.f, 0.f};
#pragma unroll
    for (int ks = 0; ks < 2; ks++) {
      const int t = 4 * h + 2 * ks;
      mma16816(sp, ql[t], qh[t], ql[t + 1], qh[t + 1], hp[t], hp[t + 1]);
      mma16816(s0, ql[t], qh[t], ql[t + 1], qh[t + 1], k0[t], k0[t + 1]);
      mma16816(s1, ql[t], qh[t], ql[t + 1], qh[t + 1], k1[t], k1[t + 1]);
    }
    float p0 = (up0 ? sp[0] : s0[0]) * QK_SCALE, p1 = (up1 ? sp[1] : s0[1]) * QK_SCALE;
    float p2 = (up0 ? s0[2] : s1[2]) * QK_SCALE, p3 = (up1 ? s0[3] : s1[3]) * QK_SCALE;
    if (first && up0) p0 = -1000000000.0f;
    if (first && up1) p1 = -1000000000.0f;
    softmax8(p0, p1);
    softmax8(p2, p3);
    a0[h] = pack2(up0 ? p0 : 0.f, up1 ? p1 : 0.f);
    a2[h] = pack2(up0 ? 0.f : p0, up1 ? 0.f : p1);
    a3[h] = pack2(up0 ? p2 : 0.f, up1 ? p3 : 0.f);
    a5[h] = pack2(up0 ? 0.f : p2, up1 ? 0.f : p3);
  }
  float o[8][4];
#pragma unroll
  for (int t = 0; t < 8; t++) {
#pragma unroll
    for (int q = 0; q < 4; q++) o[t][q] = 0.f;
    mma1688(o[t], 0u, a5[t >> 2], v1[t]);
    mma16816(o[t], a0[t >> 2], 0u, a2[t >> 2], a3[t >> 2], hp[8 + t], v0[t]);
  }
#pragma unroll
  for (int t = 0; t < 8; t++) fence_regs(o[t]);
  step();
  uint32_t ol[8], oh[8];
#pragma unroll
  for (int t = 0; t < 8; t++) {
    ol[t] = pack2(o[t][0], o[t][1]);
    oh[t] = pack2(o[t][2], o[t][3]);
  }
  stage_slab(stg + cw * 8192, warp, lane, ol, oh);
  stage_done(bars + 8 * B_STGF, lane);
}

template <class Ready>
__device__ __forceinline__ void normalize_stage(const uint32_t (&xl)[16], const uint32_t (&xh)[16], const uint4* stats, uint32_t tag, uint32_t shift,
                                                uint32_t scale, uint32_t stg, uint32_t bars, int cw, int warp, int lane, Ready ready) {
  const int r = lane >> 2, c = lane & 3;
  float nb[2], rs[2];
  {
    uint32_t st[8];
    const uint4* sp = stats + (lane >> 4) * 512 + cw * 64 + warp * 16 + (lane & 15);
    ll_poll<4>([&](int i) { return sp + i * 128; }, tag, st);
    float mu, rstd;
    row_stats(st, mu, rstd);
    mu *= -rstd;
    nb[0] = __shfl_sync(~0u, mu, r); rs[0] = __shfl_sync(~0u, rstd, r);
    nb[1] = __shfl_sync(~0u, mu, r + 8); rs[1] = __shfl_sync(~0u, rstd, r + 8);
  }
  ready();
#pragma unroll
  for (int ch = 0; ch < 2; ch++) {
    uint32_t lo[8], hi[8];
#pragma unroll
    for (int t = 0; t < 8; t++) {
      const int n = ch * 8 + t;
      const float2 sb = lds64f(shift + (8 * n + 2 * c) * 4), cb = lds64f(scale + (8 * n + 2 * c) * 4);
      lo[t] = pack2((bf_lo(xl[n]) * rs[0] + nb[0]) * cb.x + sb.x, (bf_hi(xl[n]) * rs[0] + nb[0]) * cb.y + sb.y);
      hi[t] = pack2((bf_lo(xh[n]) * rs[1] + nb[1]) * cb.x + sb.x, (bf_hi(xh[n]) * rs[1] + nb[1]) * cb.y + sb.y);
    }
    stage_slab(stg + ch * 16384 + cw * 8192, warp, lane, lo, hi);
    stage_done(bars + 8 * (B_STGF + ch), lane);
  }
  wg_bar(cw);
}

__global__ void __launch_bounds__(384, 1) fused_kernel(const __grid_constant__ Params p) {
  extern __shared__ __align__(1024) uint8_t smem_raw[];
  const uint32_t sm = smem_u32(smem_raw);
  const uint32_t bars = sm + MISC_OFF;
  const uint32_t stg = sm + STG_OFF;
  const int rank = blockIdx.x & 1;
  const int cl = blockIdx.x >> 1;
  if (cl >= NCTA / 2) {
    const int e = blockIdx.x - NCTA, wid = __shfl_sync(~0u, (int)(threadIdx.x >> 5), 0), lane = threadIdx.x & 31;
    if (threadIdx.x == 0) {
      for (int i = 0; i < 6; i++) { mbar_init(bars + 8 * i, 1); mbar_init(bars + 8 * (6 + i), 8); }
      asm volatile("fence.mbarrier_init.release.cluster;" ::: "memory");
    }
    const uint32_t tag = load_epoch(p.epoch) + 1;
    if (threadIdx.x < 256) ll_store(p.modll + 512 + (threadIdx.x >> 6) * 256 + e * 64 + (threadIdx.x & 63), 0u, 0u, 0u);
    for (int i = threadIdx.x; i < 1536; i += 384) {
      uint4 o = make_uint4(0u, 0u, 0u, 0u);
      if (i < 1024 && (i & 63) < 8) {
        const uint4 cv = ldg_nc(p.c + (i >> 6) * 64 + (i & 7) * 8);
        o = make_uint4(pack2(silu_f(bf_lo(cv.x)), silu_f(bf_hi(cv.x))), pack2(silu_f(bf_lo(cv.y)), silu_f(bf_hi(cv.y))),
                       pack2(silu_f(bf_lo(cv.z)), silu_f(bf_hi(cv.z))), pack2(silu_f(bf_lo(cv.w)), silu_f(bf_hi(cv.w))));
      }
      sts128(stg + i * 16, o.x, o.y, o.z, o.w);
    }
    asm volatile("fence.proxy.async.shared::cta;" ::: "memory");
    __syncthreads();
    if (wid == 0) {
      __nanosleep(WMDELAY);
      uint32_t ph = 1;
#pragma unroll 1
      for (int it = 0, s = 0; it < 64; it++) {
        mbar_wait(bars + 8 * (6 + s), ph);
        expect_tx_elect(bars + 8 * s, 32768);
#pragma unroll
        for (int q = 0; q < 4; q++) tma_load_ef(sm + s * 32768 + q * 8192, &p.wm, bars + 8 * s, 2048 + (it >> 4) * 1024 + e * 256 + q * 64, (it & 15) * 64);
        if (++s == 6) { s = 0; ph ^= 1; }
      }
    } else if (wid >= 4) {
      const int hf = (wid >> 2) - 1;
      uint32_t ph = 0;
      int s = 0;
#pragma unroll 1
      for (int v = 0; v < 4; v++) {
        float acc[64];
#pragma unroll 1
        for (int kb = 0; kb < 16; kb++) {
          mbar_wait_watchdog(bars + 8 * s, ph);
          const uint32_t da = DESC_A + ((STG_OFF + kb * 1024) >> 4), db = DESC_B + ((s * 32768 + hf * 16384) >> 4) - 1024;
          wg_fence();
#pragma unroll
          for (int k = 0; k < 4; k++) wgmma_ss_n128(acc, da + k * 2, db + k * 128, (kb | k) != 0);
          wg_commit();
          wg_wait<0>();
          if (lane == 0) mbar_arrive(bars + 8 * (6 + s));
          if (++s == 6) { s = 0; ph ^= 1; }
        }
        if ((wid & 3) == 0) {
#pragma unroll
          for (int n = 0; n < 16; n++) {
            const uint32_t mine = pack2(acc[4 * n], acc[4 * n + 1]), next = __shfl_down_sync(~0u, mine, 1);
            if (lane < 4 && (lane & 1) == 0) ll_store(p.modll + 512 + v * 256 + e * 64 + hf * 32 + n * 2 + (lane >> 1), mine, next, tag);
          }
        }
      }
    }
    return;
  }
  const int slot = p.slot[cl];
  const int rb = (slot >> 3) * 2 + rank, j = slot & 7;
  const int cta = rb * 8 + j;
  PROF_AT(threadIdx.x == 0, 0);

  if (threadIdx.x < 128) {
    uint32_t tag = load_epoch(p.epoch);
    asm volatile("setmaxnreg.dec.sync.aligned.u32 40;");
    const int warp = __shfl_sync(~0u, (int)(threadIdx.x >> 5), 0), lane = threadIdx.x & 31;
    if (threadIdx.x == 0) {
      if ((sm & 0x3FFFF) != SMEM_BASE) asm volatile("trap;");
      for (int i = 0; i < 4; i++) { mbar_init(bars + 8 * (B_FQ + i), 1); mbar_init(bars + 8 * (B_EQ + i), 16); }
      for (int i = 0; i < 6; i++) { mbar_init(bars + 8 * (B_FW + i), 1); mbar_init(bars + 8 * (B_EW + i), 16); }
      for (int i = 0; i < 4; i++) { mbar_init(bars + 8 * (B_FG + i), 1); mbar_init(bars + 8 * (B_EG + i), 16); }
      for (int i = 0; i < 6; i++) { mbar_init(bars + 8 * (B_FD + i), 1); mbar_init(bars + 8 * (B_ED + i), 16); }
      for (int i = 0; i < 2; i++) { mbar_init(bars + 8 * (B_STGF + i), 8); mbar_init(bars + 8 * (B_STGE + i), 1); }
      mbar_init(bars + 8 * B_MODB, 1);
      mbar_init(bars + 8 * (B_MODB + 1), 1);
      mbar_init(bars + 8 * B_GATE, 1);
      mbar_init(bars + 8 * B_MODA, 1);
      for (int i = 0; i < 8; i++) mbar_init(bars + 8 * (B_RDY + i), 1);
      asm volatile("fence.mbarrier_init.release.cluster;" ::: "memory");
    }
    __syncwarp();
    cluster_arrive_relaxed();
    tag += 1;
    const unsigned target = tag * 8;
    unsigned* cnt = p.cnt + rb * 32;
    cluster_wait();
    if (warp == 0) {
      const CUtensorMap* wgu = rank ? &p.wu : &p.wg;
      uint32_t st = sm + 16384, fb = bars + 8 * B_FQ, ph = 1;
      if (BDELAY) __nanosleep(BDELAY);
#pragma unroll 1
      for (int it = 0; it < 32; it++) {
        const int kb = qkv_kb(it, j), col = j * 128 + ((it < 4 ? it >= 2 : it >= 18) ? 64 : 0);
        mbar_wait(fb + 8 * (B_EQ - B_FQ), ph);
        expect_tx_elect(fb, it < 4 ? 24576 : 40960);
        tma_load_mc(st + rank * 8192, &p.wqkv, fb, col + rank * 1024, kb * 64);
        tma_load_mc(st + 16384 + rank * 4096, &p.wqkv32, fb, col + 2048, kb * 64 + rank * 32);
        st += 49152; fb += 8;
        if ((it & 3) == 3) { st -= 4 * 49152; fb -= 32; ph ^= 1; }
      }
      fb = bars + 8 * B_FW; ph = 1;
#pragma unroll 1
      for (int it = 0, s = 0; it < 16; it++) {
        if (it < 6) wait_p3_free(bars + 8 * B_EQ, it);
        if (GATE && it == GATE) mbar_wait(bars + 8 * B_GATE, 0);
        mbar_wait(fb + 8 * (B_EW - B_FW), ph);
        expect_tx_elect(fb, it == 8 ? 16384 : 32768);
        tma_load_mc(st + rank * 8192, &p.wo, fb, j * 128 + rank * 64, wo_k(it, j));
        st += 32768; fb += 8;
        if (++s == 6) { s = 0; st -= 6 * 32768; fb -= 48; ph ^= 1; }
      }
      st = sm + 16384; fb = bars + 8 * B_FG; ph = 1;
#pragma unroll 1
      for (int it = 0; it < 48; it++) {
        const int kb = own_first(it, j), col = j * 448 + (it >> 4) * 128;
        if (it < 4) wait_p2_free(bars + 8 * B_EW, it);
        mbar_wait(fb + 8 * (B_EG - B_FG), ph);
        expect_tx_elect(fb, it < 2 ? 32768 : 49152);
        tma_load_mc(st + rank * 16384, wgu, fb, col, kb * 64);
        tma_load_mc(st + rank * 16384 + 8192, wgu, fb, col + 64, kb * 64);
        st += 49152; fb += 8;
        if ((it & 3) == 3) { st -= 4 * 49152; fb -= 32; ph ^= 1; }
      }
      fb = bars + 8 * B_FD; ph = 1;
#pragma unroll 1
      for (int it = 0, s = 0; it < 72; it++) {
        if (it < 6) wait_p3_free(bars + 8 * B_EG, it);
        mbar_wait(fb + 8 * (B_ED - B_FD), ph);
        expect_tx_elect(fb, 32768);
        tma_load_mc(st + rank * 8192, it < 16 ? wgu : &p.wd, fb, it < 16 ? j * 448 + 384 : j * 128 + rank * 64, down_k(it));
        st += 32768; fb += 8;
        if (++s == 6) { s = 0; st -= 6 * 32768; fb -= 48; ph ^= 1; }
      }
    } else if (warp == 1) {
      const int arow = rb * 128;
      uint32_t st = sm, fb = bars + 8 * B_FQ, ph = 0;
      cnt_wait(cnt + C_HA, target);
      PROF_AT(lane == 0, 16);
#pragma unroll 1
      for (int it = 4; it < 32; it++) {
        if (it == 11) mbar_wait(bars + 8 * (B_RDY + C_H), 0);
        mbar_wait(fb + 8 * (B_EQ - B_FQ), ph);
        tma_load(st, &p.h, fb, qkv_kb(it, j) * 64, arow);
        st += 49152; fb += 8;
        if ((it & 3) == 3) { st -= 4 * 49152; fb -= 32; ph ^= 1; }
      }
      fb = bars + 8 * B_FW; ph = 1;
#pragma unroll 1
      for (int it = 0, s = 0; it < 16; it++) {
        if (it < 6) wait_p3_free(bars + 8 * B_EQ, it);
        if (GATE && it == GATE) mbar_wait(bars + 8 * B_GATE, 0);
        mbar_wait(fb + 8 * (B_EW - B_FW), ph);
        if (it == 0) mbar_wait(bars + 8 * (B_RDY + C_O), 0);
        if (it == 9) cnt_wait(cnt + C_O + 1, target);
        PROF_AT(lane == 0 && (it == 0 || it == 9), 17 + (it >> 3));
        if (it != 8) tma_load(st, &p.o_ld, fb, wo_k(it, j), arow);
        st += 32768; fb += 8;
        if (++s == 6) { s = 0; st -= 6 * 32768; fb -= 48; ph ^= 1; }
      }
      st = sm + 2 * 49152; fb = bars + 8 * (B_FG + 2); ph = 1;
      cnt_wait(cnt + C_H2A, target);
      PROF_AT(lane == 0, 19);
#pragma unroll 1
      for (int it = 2; it < 48; it++) {
        if (it == 9) mbar_wait(bars + 8 * (B_RDY + C_H2), 0);
        mbar_wait(fb + 8 * (B_EG - B_FG), ph);
        tma_load(st, &p.h2, fb, own_first(it, j) * 64, arow);
        st += 49152; fb += 8;
        if ((it & 3) == 3) { st -= 4 * 49152; fb -= 32; ph ^= 1; }
      }
      fb = bars + 8 * B_FD; ph = 1;
#pragma unroll 1
      for (int it = 0, s = 0; it < 72; it++) {
        if (it < 6) wait_p3_free(bars + 8 * B_EG, it);
        mbar_wait(fb + 8 * (B_ED - B_FD), ph);
        if ((it & 15) == 0 && it > 0) { mbar_wait(bars + 8 * (B_RDY + C_ACT - 1 + (it >> 4)), 0); PROF_AT(lane == 0, 19 + (it >> 4)); }
        tma_load(st, it < 16 ? &p.h2 : &p.act, fb, down_k(it), arow);
        st += 32768; fb += 8;
        if (++s == 6) { s = 0; st -= 6 * 32768; fb -= 48; ph ^= 1; }
      }
    } else if (warp == 2) {
      if (lane < 13) prefetch_map(&p.h + lane);
      __syncwarp();
      uint32_t ph1 = 0;
#pragma unroll 1
      for (int n = 0; n < 9; n++) {
        const int nch = (n == 1 || n == 2 || n == 7) ? 1 : 2;
#pragma unroll 1
        for (int ch = 0; ch < nch; ch++) {
          mbar_wait_watchdog(bars + 8 * (B_STGF + ch), ch ? ph1 : (n & 1));
          const uint32_t src = stg + ch * 16384;
          if (n == 1 || n == 2) {
#pragma unroll 1
            for (int q = 0; q < 4; q++) {
              tma_store2(&p.o_st, src + q * 4096, j * 128 + (n - 1) * 64, rb * 128 + q * 32);
              if (n == 1) store_pause(true);
            }
            if (n == 2) arrive_elect(bars + 8 * B_GATE);
          } else if (n >= 4 && n < 8) {
#pragma unroll 1
            for (int q = 0; q < 4; q++) {
              tma_store2(&p.act_st, src + q * 4096, j * 448 + (n - 4) * 128 + ch * 64, rb * 128 + q * 32);
              store_pause(true);
            }
          } else if (n == 8) {
            tma_store3(&p.out, src, j * 128 + ch * 64, rb * 64, 0);
          } else {
            tma_store2(n == 0 ? &p.h : &p.h2, src, j * 128 + ch * 64, rb * 128);
            asm volatile("cp.async.bulk.commit_group;" ::: "memory");
            if (ch == 1) {
              asm volatile("cp.async.bulk.wait_group 1;" ::: "memory");
              __syncwarp();
              cnt_signal(cnt + (n == 0 ? C_HA : C_H2A));
            }
          }
          if (n >= 4 && n < 7 && ch == 0) arrive_elect(bars + 8 * B_STGE);
        }
        asm volatile("cp.async.bulk.commit_group;" ::: "memory");
        asm volatile("cp.async.bulk.wait_group 0;" ::: "memory");
        __syncwarp();
        if (n < 8) cnt_signal(cnt + n);
        if (!(n >= 4 && n < 7)) arrive_elect(bars + 8 * B_STGE);
        if (nch == 2) { arrive_elect(bars + 8 * (B_STGE + 1)); ph1 ^= 1; }
        PROF_AT(lane == 0, n == 0 ? 33 : 23 + n);
      }
    } else {
      if (lane < 4) ll_store(p.modll + cta * 4 + lane, 0u, 0u, 0u);
      bar_sync(1, 288);
      {
        const uint4 t4 = lds128(sm + RED_OFF + lane * 16);
        float a[4] = {__uint_as_float(t4.x), __uint_as_float(t4.y), __uint_as_float(t4.z), __uint_as_float(t4.w)};
#pragma unroll
        for (int o = 4; o < 32; o <<= 1)
#pragma unroll
          for (int q = 0; q < 4; q++) a[q] += __shfl_xor_sync(~0u, a[q], o);
        if (lane < 4) ll_store(p.modll + cta * 4 + lane, pack2(a[0], a[1]), pack2(a[2], a[3]), tag);
        PROF_AT(lane == 0, 1);
        uint32_t m[4];
        const uint4* mp = p.modll + j * 32 + lane;
        ll_poll<2>([&](int i) { return mp + i * 256; }, tag, m);
        const uint32_t c0 = pack2(1.0f + bf_lo(m[2]), 1.0f + bf_hi(m[2])), c1 = pack2(1.0f + bf_lo(m[3]), 1.0f + bf_hi(m[3]));
        sts128(sm + MODB_OFF + lane * 16, m[0] << 16, m[0] & 0xffff0000u, m[1] << 16, m[1] & 0xffff0000u);
        sts128(sm + MODB_OFF + 512 + lane * 16, c0 << 16, c0 & 0xffff0000u, c1 << 16, c1 & 0xffff0000u);
        __syncwarp();
        arrive_elect(bars + 8 * B_MODA);
      }
#pragma unroll 1
      for (int n = C_H; n <= C_O; n++) {
        cnt_wait_lazy(cnt + n, target);
        arrive_elect(bars + 8 * (B_RDY + n));
      }
      {
        uint32_t m[6];
        const uint4* src = p.modll + 512 + j * 32 + lane;
        ll_poll<3, 500>([&](int i) { return src + i * 256; }, tag, m);
#pragma unroll
        for (int vec = 0; vec < 3; vec++) {
          const float add = vec == 2 ? 1.0f : 0.0f;
          sts128(sm + MODB_OFF + (vec * 128 + lane * 4) * 4, __float_as_uint(bf_round(bf_lo(m[2 * vec]) + add)), __float_as_uint(bf_round(bf_hi(m[2 * vec]) + add)),
                 __float_as_uint(bf_round(bf_lo(m[2 * vec + 1]) + add)), __float_as_uint(bf_round(bf_hi(m[2 * vec + 1]) + add)));
        }
        __syncwarp();
        if (lane == 0) mbar_arrive(bars + 8 * B_MODB);
        PROF_AT(lane == 0, 15);
      }
      __syncwarp();
#pragma unroll 1
      for (int n = C_H2; n < 8; n++) {
        cnt_wait_lazy(cnt + n, target);
        arrive_elect(bars + 8 * (B_RDY + n));
      }
      {
        uint32_t m[2];
        const uint4* src = p.modll + 512 + 768 + j * 32 + lane;
        ll_poll<1>([&](int) { return src; }, tag, m);
        sts128(sm + MODB_OFF + (384 + lane * 4) * 4, m[0] << 16, m[0] & 0xffff0000u, m[1] << 16, m[1] & 0xffff0000u);
        __syncwarp();
        if (lane == 0) mbar_arrive(bars + 8 * (B_MODB + 1));
      }
    }
    __syncwarp();
    cluster_arrive_relaxed();
    cluster_wait();
  } else {
    uint32_t tag;

    {
      const int tid = threadIdx.x - 128, cw = tid >> 7, warp = (tid >> 5) & 3, lane = tid & 31;
      const int l16 = lane & 15, half = lane >> 4, w8 = cw * 4 + warp;
      const uint32_t cbuf = sm + 3 * 49152 + w8 * 512;
      if (lane <= 16) cp_async16(cbuf + lane * 16, lane < 16 ? (const void*)(p.c + w8 * 128 + lane * 8) : (const void*)p.epoch);
      asm volatile("cp.async.commit_group;" ::: "memory");
      const uint32_t wbuf = sm + cw * 49152 + warp * 4096;
      {
        const char* wp = (const char*)p.wmod + (uint32_t)(cta * 32 + (lane & 1) * 16 + (w8 * 128 + (lane >> 1)) * 12288);
#pragma unroll
        for (int i = 0; i < 8; i++) cp_async16(wbuf + i * 512 + lane * 16, wp + i * 16 * 12288);
      }
      asm volatile("cp.async.commit_group;" ::: "memory");
      const uint32_t xbuf = sm + 40960 + (cw * 2 + (l16 >> 3)) * 49152 + (warp * 16 + half) * 128;
      {
        const char* xp = (const char*)p.x + (uint32_t)((rb * 128 + (warp * 16 + half) * 2 + cw) * 2048 + j * 256 + l16 * 16);
#pragma unroll
        for (int i = 0; i < 8; i++) cp_async16(xbuf + i * 256 + (((l16 & 7) ^ ((i * 2 + half) & 7)) << 4), xp + i * 8192);
      }
      asm volatile("cp.async.commit_group;" ::: "memory");
      PROF_AT(tid == 0, 32);
      uint4* st1 = p.stats1 + (rb * 8 + j) * 128 + cw * 64 + warp * 16;
      if (lane < 16) ll_store(st1 + lane, 0u, 0u, 0u);
      __syncwarp();
      cluster_arrive_relaxed();
      asm volatile("setmaxnreg.inc.sync.aligned.u32 232;");
      uint32_t sa[4][4];
      {
        asm volatile("cp.async.wait_group 2;" ::: "memory");
        __syncwarp();
        tag = lds32(cbuf + 256) + 1;
        const float2 cv = lds64f(cbuf + lane * 8);
        const uint32_t c0 = __float_as_uint(cv.x), c1 = __float_as_uint(cv.y);
        sts64f(cbuf + lane * 8, __uint_as_float(pack2(silu_f(bf_lo(c0)), silu_f(bf_hi(c0)))), __uint_as_float(pack2(silu_f(bf_lo(c1)), silu_f(bf_hi(c1)))));
        __syncwarp();
#pragma unroll
        for (int q = 0; q < 4; q++) ldmatrix4(sa[q][0], sa[q][1], sa[q][2], sa[q][3], cbuf + q * 64 + (lane >> 3) * 16);
      }
      cluster_wait();
      asm volatile("cp.async.wait_group 1;" ::: "memory");
      __syncwarp();
      PROF_AT(tid == 0, 51);
      {
        uint32_t b[8][4];
#pragma unroll
        for (int ks = 0; ks < 8; ks++) ldmatrix4t(b[ks], wbuf + (ks * 16 + (lane & 15)) * 32 + (lane >> 4) * 16);
        float d0[4] = {0.f, 0.f, 0.f, 0.f}, d1[4] = {0.f, 0.f, 0.f, 0.f}, d2[4] = {0.f, 0.f, 0.f, 0.f}, d3[4] = {0.f, 0.f, 0.f, 0.f};
#pragma unroll
        for (int q = 0; q < 4; q++) {
          mma16816(d0, sa[q][0], sa[q][0], sa[q][1], sa[q][1], b[2 * q][0], b[2 * q][1]);
          mma16816(d1, sa[q][0], sa[q][0], sa[q][1], sa[q][1], b[2 * q][2], b[2 * q][3]);
          mma16816(d2, sa[q][2], sa[q][2], sa[q][3], sa[q][3], b[2 * q + 1][0], b[2 * q + 1][1]);
          mma16816(d3, sa[q][2], sa[q][2], sa[q][3], sa[q][3], b[2 * q + 1][2], b[2 * q + 1][3]);
        }
        d0[0] += d2[0]; d0[1] += d2[1]; d1[0] += d3[0]; d1[1] += d3[1];
        if (lane < 4) {
          sts64f(sm + RED_OFF + (w8 * 16 + lane * 2) * 4, d0[0], d0[1]);
          sts64f(sm + RED_OFF + (w8 * 16 + 8 + lane * 2) * 4, d1[0], d1[1]);
        }
        asm volatile("bar.arrive 1, 288;" ::: "memory");
      }
      asm volatile("cp.async.wait_group 0;" ::: "memory");
      __syncwarp();
      uint32_t xl[16], xh[16];
      {
        const int srow = warp * 16 + (lane & 15);
#pragma unroll
        for (int q = 0; q < 8; q++)
          ldmatrix4(xl[2 * q], xh[2 * q], xl[2 * q + 1], xh[2 * q + 1],
                    sm + 40960 + (cw * 2 + (q >> 2)) * 49152 + srow * 128 + (((half + (q & 3) * 2) ^ (srow & 7)) << 4));
      }
      publish_stats(xl, xh, st1, lane, tag);
      PROF_AT(tid == 0, 50);
      normalize_stage(xl, xh, p.stats1 + rb * 1024, tag, sm + MODB_OFF, sm + MODB_OFF + 512, stg, bars, cw, warp, lane,
                      [&]() { mbar_wait(bars + 8 * B_MODA, 0); });
      PROF_AT(tid == 0, 3);
    }

    uint32_t xl[16], xh[16];
    {
      RING_IDS();
      uint32_t prev = 0;
      float acc1[96];
      {
        Ring g{bars + 8 * B_FQ, rbars + 8 * B_EQ, 0, 0u, releaser TR(0)};
        float acc0[96];
#pragma unroll 1
        for (int kb = 0; kb < 2; kb++) kblock<192, 4, 49152>(acc0, g, a_base + STG_OFF + kb * 16384, kb == 0, prev);
#pragma unroll 1
        for (int kb = 0; kb < 2; kb++) kblock<192, 4, 49152>(acc1, g, a_base + STG_OFF + kb * 16384, kb == 0, prev);
        {
          LANE_IDS();
          if (c < 2) ll_store(p.stats2 + (rb * 8 + j) * 128 + cw * 64 + warp * 16 + r + c * 8, 0u, 0u, 0u);
          if (warp == 3) {
#pragma unroll 1
            for (int t = 0; t < 16; t++) ll_store(p.halo + ((cta * 2 + (t >> 3)) * 2 + cw) * 256 + (t & 7) * 32 + lane, 0u, 0u, 0u);
          }
          __syncwarp();
        }
#pragma unroll 1
        for (int kb = 0; kb < 14; kb++) kblock<192, 4, 49152>(acc0, g, a_base + g.s * 49152, false, prev);
        PROF_AT(tid == 0, 4);
        attention<NPRE0>(acc0, p, 0, rb, cta, cw, warp, tag, stg, bars, prev, [&]() { kblock<192, 4, 49152>(acc1, g, a_base + g.s * 49152, false, prev); });
        PROF_AT(tid == 0, 5);
        {
          LANE_IDS();
#pragma unroll
          for (int q = 0; q < 8; q++)
            ldmatrix4(xl[2 * q], xh[2 * q], xl[2 * q + 1], xh[2 * q + 1], sm + 40960 + (cw * 2 + (q >> 2)) * 49152 + srow * 128 + ((sw0 ^ ((q & 3) * 2)) << 4));
#pragma unroll
          for (int q = 0; q < 16; q++) asm volatile("" : "+r"(xl[q]), "+r"(xh[q])::"memory");
        }
#pragma unroll 1
        for (int kb = 3 + NPRE0; kb < 14; kb++) kblock<192, 4, 49152>(acc1, g, a_base + g.s * 49152, false, prev);
        PROF_AT(tid == 0, 6);
      }
      float acc[64];
      Ring g{bars + 8 * B_FW, rbars + 8 * B_EW, 0, 0u, releaser TR(32)};
      attention<NPRE1>(acc1, p, 1, rb, cta, cw, warp, tag, stg, bars, prev, [&]() { kblock<128, 6, 32768>(acc, g, a_base + g.s * 32768, g.s == 0, prev); });
      PROF_AT(tid == 0, 7);
      LANE_IDS();
#pragma unroll 1
      for (int kb = 3 + NPRE1; kb < 16; kb++) {
        if (kb == 8) wg_bar(cw);
        kblock<128, 6, 32768>(acc, g, a_base + (kb == 8 ? STG_OFF : g.s * 32768), false, prev);
      }
      mbar_wait(bars + 8 * B_MODB, 0);
      float2 ga[16];
#pragma unroll
      for (int n = 0; n < 16; n++) ga[n] = lds64f(sm + MODB_OFF + (8 * n + 2 * c) * 4);
      tile_end(acc, prev);
      PROF_AT(tid == 0, 8);
      uint4* st2 = p.stats2 + (rb * 8 + j) * 128 + cw * 64 + warp * 16 + r + (c & 1) * 8;
      float sl[2] = {0.f, 0.f}, sh[2] = {0.f, 0.f}, ql[2] = {0.f, 0.f}, qh[2] = {0.f, 0.f};
#pragma unroll
      for (int n = 0; n < 16; n++) {
        acc[4 * n] = ga[n].x * acc[4 * n] + bf_lo(xl[n]); acc[4 * n + 1] = ga[n].y * acc[4 * n + 1] + bf_hi(xl[n]);
        acc[4 * n + 2] = ga[n].x * acc[4 * n + 2] + bf_lo(xh[n]); acc[4 * n + 3] = ga[n].y * acc[4 * n + 3] + bf_hi(xh[n]);
        sl[0] += acc[4 * n]; sl[1] += acc[4 * n + 1]; sh[0] += acc[4 * n + 2]; sh[1] += acc[4 * n + 3];
        ql[0] += acc[4 * n] * acc[4 * n]; ql[1] += acc[4 * n + 1] * acc[4 * n + 1];
        qh[0] += acc[4 * n + 2] * acc[4 * n + 2]; qh[1] += acc[4 * n + 3] * acc[4 * n + 3];
      }
      {
        const float ml = (sl[0] + sl[1]) * (1.0f / 32), mh = (sh[0] + sh[1]) * (1.0f / 32);
        const float vl = (ql[0] + ql[1]) - 32.0f * ml * ml, vh = (qh[0] + qh[1]) - 32.0f * mh * mh;
        const bool b0 = c & 1;
        float m = b0 ? mh : ml, q = b0 ? vh : vl;
        chan(m, q, __shfl_xor_sync(~0u, b0 ? ml : mh, 1), __shfl_xor_sync(~0u, b0 ? vl : vh, 1), 32.f);
        chan(m, q, __shfl_xor_sync(~0u, m, 2), __shfl_xor_sync(~0u, q, 2), 64.f);
        if (c < 2) ll_store(st2, __float_as_uint(m), __float_as_uint(fmaxf(q, 0.f)), tag);
        __syncwarp();
      }
      PROF_AT(tid == 0, 48);
      float2 sb[16], cb[16];
#pragma unroll
      for (int n = 0; n < 16; n++) {
        sb[n] = lds64f(sm + MODB_OFF + (128 + 8 * n + 2 * c) * 4);
        cb[n] = lds64f(sm + MODB_OFF + (256 + 8 * n + 2 * c) * 4);
        xl[n] = pack2(acc[4 * n], acc[4 * n + 1]);
        xh[n] = pack2(acc[4 * n + 2], acc[4 * n + 3]);
      }
      mbar_wait(bars + 8 * B_STGE, 0);
      PROF_AT(tid == 0, 49);
      float nb[2], rstd[2];
      {
        uint32_t st[8];
        const uint4* sp = p.stats2 + (rb * 8 + (lane >> 4) * 4) * 128 + cw * 64 + warp * 16 + (lane & 15);
        ll_poll<4, PB2>([&](int i) { return sp + i * 128; }, tag, st);
        float mu, rs;
        row_stats(st, mu, rs);
        mu *= -rs;
        nb[0] = __shfl_sync(~0u, mu, r); rstd[0] = __shfl_sync(~0u, rs, r);
        nb[1] = __shfl_sync(~0u, mu, r + 8); rstd[1] = __shfl_sync(~0u, rs, r + 8);
      }
      PROF_AT(tid == 0, 9);
#pragma unroll
      for (int ch = 0; ch < 2; ch++) {
        uint32_t lo[8], hi[8];
#pragma unroll
        for (int t = 0; t < 8; t++) {
          const int n = ch * 8 + t;
          lo[t] = pack2((acc[4 * n] * rstd[0] + nb[0]) * cb[n].x + sb[n].x, (acc[4 * n + 1] * rstd[0] + nb[0]) * cb[n].y + sb[n].y);
          hi[t] = pack2((acc[4 * n + 2] * rstd[1] + nb[1]) * cb[n].x + sb[n].x, (acc[4 * n + 3] * rstd[1] + nb[1]) * cb[n].y + sb[n].y);
        }
        stage_slab(stg + ch * 16384 + cw * 8192, warp, lane, lo, hi);
        stage_done(bars + 8 * (B_STGF + ch), lane);
      }
      wg_bar(cw);
      PROF_AT(tid == 0, 10);
    }

    uint32_t pg[32], pu[32];
    {
      RING_IDS();
      LANE_IDS();
      Ring g{bars + 8 * B_FG, rbars + 8 * B_EG, 0, 0u, releaser TR(48)};
      float acc[128];
      {
        uint32_t prev = 0;
        uint4* x1p = p.x1 + (size_t)(rb * 128 + (tid >> 4)) * 128 + j * 16 + (tid & 15);
#pragma unroll 1
        for (int kb = 0; kb < 16; kb++) {
          kblock<256, 4, 49152>(acc, g, a_base + (kb < 2 ? STG_OFF + kb * 16384 : g.s * 49152), kb == 0, prev);
          if (kb == 5) {
#pragma unroll
            for (int q = 0; q < 4; q++) x1p[q * 2048] = make_uint4(xl[4 * q], xl[4 * q + 1], xl[4 * q + 2], xl[4 * q + 3]);
          }
          if (kb == 8) {
#pragma unroll
            for (int q = 0; q < 4; q++) x1p[(4 + q) * 2048] = make_uint4(xh[4 * q], xh[4 * q + 1], xh[4 * q + 2], xh[4 * q + 3]);
          }
        }
        tile_end(acc, prev);
      }
      PROF_AT(tid == 0, 36);
#pragma unroll 1
      for (int t = 1; t < 3; t++) {
#pragma unroll
        for (int q = 0; q < 32; q++) {
          pg[q] = pack2(acc[2 * q], acc[2 * q + 1]);
          pu[q] = pack2(acc[64 + 2 * q], acc[64 + 2 * q + 1]);
        }
        uint32_t prev = 0;
#pragma unroll 1
        for (int blk = 0; blk < 4; blk++) {
          g.s = 0;
#pragma unroll
          for (int i = 0; i < 4; i++) {
            kblock<256, 4, 49152>(acc, g, a_base + i * 49152, blk == 0 && i == 0, prev);
            if ((blk & 1) == 0 && i == 0) mbar_wait(bars + 8 * (B_STGE + (blk >> 1)), t & 1);
            stmatrix2(slab + (blk >> 1) * 16384 + (((srow & 7) ^ ((blk & 1) * 4 + i)) << 4), swiglu2(pg[2 * i], pu[2 * i]), swiglu2(pg[2 * i + 1], pu[2 * i + 1]));
          }
#pragma unroll
          for (int q = 0; q < 24; q++) { pg[q] = pg[q + 8]; pu[q] = pu[q + 8]; }
          if (blk & 1) stage_done(bars + 8 * (B_STGF + (blk >> 1)), lane);
        }
        tile_end(acc, prev);
        PROF_AT(tid == 0, 36 + t);
      }
#pragma unroll
      for (int q = 0; q < 32; q++) {
        pg[q] = pack2(acc[2 * q], acc[2 * q + 1]);
        pu[q] = pack2(acc[64 + 2 * q], acc[64 + 2 * q + 1]);
      }
      PROF_AT(tid == 0, 11);
    }

    {
      RING_IDS();
      LANE_IDS();
      Ring g{bars + 8 * B_FD, rbars + 8 * B_ED, 0, 0u, releaser TR(96)};
      float acc[64];
      uint32_t prev = 0;
#pragma unroll 1
      for (int blk = 0; blk < 6; blk++) {
#pragma unroll
        for (int i = 0; i < 8; i++) {
          kblock<128, 6, 32768>(acc, g, a_base + g.s * 32768, (blk & ~2) == 0 && i == 0, prev);
          if ((blk & 1) == 0 && i == 0) mbar_wait(bars + 8 * (B_STGE + ((blk >> 1) & 1)), blk < 4);
          stmatrix1(slab + ((blk >> 1) & 1) * 16384 + (i & 1) * 1024 + (((srow & 7) ^ ((blk & 1) * 4 + (i >> 1))) << 4), swiglu2(pg[i], pu[i]));
        }
#pragma unroll
        for (int q = 0; q < 24; q++) { pg[q] = pg[q + 8]; pu[q] = pu[q + 8]; }
        if (blk & 1) stage_done(bars + 8 * (B_STGF + ((blk >> 1) & 1)), lane);
        if (blk == 1) {
          tile_end(acc, prev);
          PROF_AT(tid == 0, 39);
#pragma unroll
          for (int q = 0; q < 16; q++) {
            pg[16 + q] = pack2(acc[2 * q], acc[2 * q + 1]);
            pu[16 + q] = pack2(acc[32 + 2 * q], acc[32 + 2 * q + 1]);
          }
          PROF_AT(tid == 0, 12);
        }
      }
      uint4 x1[8];
      const int ft = fresh_tid() - 128;
      const uint4* x1p = p.x1 + (size_t)(rb * 128 + (ft >> 4)) * 128 + j * 16 + (ft & 15);
#pragma unroll
      for (int q = 0; q < 2; q++) {
#pragma unroll
        for (int e = 0; e < 4; e++) x1[4 * q + e] = ll_peek(x1p + (4 * q + e) * 2048);
#pragma unroll 1
        for (int kb = 0; kb < 12; kb++) kblock<128, 6, 32768>(acc, g, a_base + g.s * 32768, false, prev);
      }
      mbar_wait(bars + 8 * (B_MODB + 1), 0);
      mbar_wait(bars + 8 * B_STGE, 1);
      mbar_wait(bars + 8 * (B_STGE + 1), 0);
      float2 gbv[16];
#pragma unroll
      for (int n = 0; n < 16; n++) gbv[n] = lds64f(sm + MODB_OFF + (384 + 8 * n + 2 * c) * 4);
      tile_end(acc, prev);
      PROF_AT(tid == 0, 13);
#pragma unroll
      for (int ch = 0; ch < 2; ch++) {
        uint32_t lo[8], hi[8];
#pragma unroll
        for (int t = 0; t < 8; t++) {
          const int n = ch * 8 + t;
          const float2 gb = gbv[n];
          const uint4 a = x1[n >> 2], b = x1[4 + (n >> 2)];
          const uint32_t xl = (n & 3) == 0 ? a.x : (n & 3) == 1 ? a.y : (n & 3) == 2 ? a.z : a.w;
          const uint32_t xh = (n & 3) == 0 ? b.x : (n & 3) == 1 ? b.y : (n & 3) == 2 ? b.z : b.w;
          lo[t] = pack2(bf_lo(xl) + gb.x * acc[4 * n], bf_hi(xl) + gb.y * acc[4 * n + 1]);
          hi[t] = pack2(bf_lo(xh) + gb.x * acc[4 * n + 2], bf_hi(xh) + gb.y * acc[4 * n + 3]);
        }
        stage_slab(stg + ch * 16384 + cw * 8192, warp, lane, lo, hi);
        stage_done(bars + 8 * (B_STGF + ch), lane);
      }
      PROF_AT(tid == 0, 14);
    }
    if (blockIdx.x == 0 && threadIdx.x == 128) asm volatile("st.relaxed.gpu.global.u32 [%0], %1;" ::"l"(p.epoch), "r"(tag) : "memory");
    __syncwarp();
    cluster_arrive_relaxed();
    cluster_wait();
  }
}

typedef CUresult (*EncodeFn)(CUtensorMap*, CUtensorMapDataType, cuuint32_t, void*, const cuuint64_t*, const cuuint64_t*,
                             const cuuint32_t*, const cuuint32_t*, CUtensorMapInterleave, CUtensorMapSwizzle,
                             CUtensorMapL2promotion, CUtensorMapFloatOOBfill);

void encode2d(EncodeFn fn, CUtensorMap* m, const void* ptr, uint64_t cols, uint64_t rows, uint32_t box_rows) {
  cuuint64_t dims[2] = {cols, rows};
  cuuint64_t strides[1] = {cols * 2};
  cuuint32_t box[2] = {64, box_rows};
  cuuint32_t es[2] = {1, 1};
  fn(m, CU_TENSOR_MAP_DATA_TYPE_BFLOAT16, 2, (void*)ptr, dims, strides, box, es, CU_TENSOR_MAP_INTERLEAVE_NONE,
     CU_TENSOR_MAP_SWIZZLE_128B, CU_TENSOR_MAP_L2_PROMOTION_L2_128B, CU_TENSOR_MAP_FLOAT_OOB_FILL_NONE);
}

}

extern "C" void kernel_launch(void* const* d_in, const int* in_sizes, int n_in, void* d_out, int out_size) {
  (void)in_sizes; (void)n_in; (void)out_size;
  void* fp = nullptr;
  cudaDriverEntryPointQueryResult qr;
  cudaGetDriverEntryPoint("cuTensorMapEncodeTiled", &fp, cudaEnableDefault, &qr);
  EncodeFn fn = (EncodeFn)fp;
  void *ph, *po, *ph2, *pact;
  cudaGetSymbolAddress(&ph, g_h);
  cudaGetSymbolAddress(&po, g_o);
  ph2 = ph;
  cudaGetSymbolAddress(&pact, g_act);
  Params p;
  encode2d(fn, &p.h, ph, DM, SEQ, 128);
  encode2d(fn, &p.o_ld, po, DM, SEQ, 128);
  encode2d(fn, &p.h2, ph2, DM, SEQ, 128);
  encode2d(fn, &p.act, pact, FF, SEQ, 128);
  encode2d(fn, &p.act_st, pact, FF, SEQ, 32);
  encode2d(fn, &p.wm, d_in[8], 6 * DM, DM, 64);
  encode2d(fn, &p.o_st, po, DM, SEQ, 32);
  encode2d(fn, &p.wqkv, d_in[1], 3 * DM, DM, 64);
  encode2d(fn, &p.wqkv32, d_in[1], 3 * DM, DM, 32);
  encode2d(fn, &p.wo, d_in[2], DM, DM, 64);
  encode2d(fn, &p.wg, d_in[4], FF, DM, 64);
  encode2d(fn, &p.wu, d_in[5], FF, DM, 64);
  encode2d(fn, &p.wd, d_in[6], DM, FF, 64);
  {
    cuuint64_t dims[3] = {DM, SEQ / 2, 2};
    cuuint64_t strides[2] = {DM * 4, DM * 2};
    cuuint32_t box[3] = {64, 64, 2};
    cuuint32_t es[3] = {1, 1, 1};
    fn(&p.out, CU_TENSOR_MAP_DATA_TYPE_BFLOAT16, 3, d_out, dims, strides, box, es, CU_TENSOR_MAP_INTERLEAVE_NONE,
       CU_TENSOR_MAP_SWIZZLE_128B, CU_TENSOR_MAP_L2_PROMOTION_L2_128B, CU_TENSOR_MAP_FLOAT_OOB_FILL_NONE);
  }
  p.x = (const bf16*)d_in[0];
  p.c = (const bf16*)d_in[7];
  p.wmod = (const bf16*)d_in[8];
  for (int cl = 0; cl < 64; cl++) {
    const int grp = cl < 4 ? 0 : (cl < 36 ? (cl - 4) & 7 : 1 + (cl - 36) % 7);
    const int j = cl < 4 ? 4 + cl : (cl < 36 ? (cl - 4) >> 3 : 4 + (cl - 36) / 7);
    p.slot[cl] = (uint8_t)(grp * 8 + j);
  }
  void* q;
  p.x1 = (uint4*)d_out;
  cudaGetSymbolAddress(&q, g_modll); p.modll = (uint4*)q;
  cudaGetSymbolAddress(&q, g_halo); p.halo = (uint4*)q;
  cudaGetSymbolAddress(&q, g_stats); p.stats1 = (uint4*)q; p.stats2 = p.stats1 + SEQ * 8;
  cudaGetSymbolAddress(&q, g_cnt); p.cnt = (unsigned*)q;
  cudaGetSymbolAddress(&q, g_epoch); p.epoch = (unsigned*)q;

  cudaFuncSetAttribute(fused_kernel, cudaFuncAttributeMaxDynamicSharedMemorySize, SMEM_BYTES);
  cudaLaunchConfig_t cfg = {};
  cfg.gridDim = dim3(NCTA + 4);
  cfg.blockDim = dim3(384);
  cfg.dynamicSmemBytes = SMEM_BYTES;
  cfg.stream = cudaStreamPerThread;
  cudaLaunchAttribute at[1];
  at[0].id = cudaLaunchAttributeClusterDimension;
  at[0].val.clusterDim.x = 2; at[0].val.clusterDim.y = 1; at[0].val.clusterDim.z = 1;
  cfg.attrs = at;
  cfg.numAttrs = 1;
  cudaLaunchKernelEx(&cfg, fused_kernel, p);
}
```

```cpp
#include <cuda_runtime.h>
#include <cuda_bf16.h>
#include <cuda.h>
#include <stdint.h>

typedef __nv_bfloat16 bf16;

#define MAPPING 2

#define ALIGN 0

#define PF 0

#define EF 1

#define ALIGNE 3

#define CW 1

#define PAUSE 200

#define WMD 2

#define WMDELAY 2000

#define WMPACE 0

#define NPRE0 4

#define NPRE1 1
#define GATE 0

#define WFIRST 1

#define BDELAY 1500

#define ALIAS 1

#define PB1 0
#define PB2 0

#define LN2D 0

#define PIPEPOLL 0

#define TAIL 1

#define EAGER1 1

__device__ __forceinline__ void wgmma_ss_n128(float (&d)[64], uint32_t da, uint32_t db, int scale_d) {
  asm volatile("{\n.reg .pred p;\n.reg .b64 da, db;\nsetp.ne.b32 p, %66, 0;\n"
    "mov.b64 da, {%64, 0x40000040};\nmov.b64 db, {%65, 0x40000040};\n"
    "wgmma.mma_async.sync.aligned.m64n128k16.f32.bf16.bf16 "
    "{%0, %1, %2, %3, %4, %5, %6, %7, %8, %9, %10, %11, %12, %13, %14, %15, "
    "%16, %17, %18, %19, %20, %21, %22, %23, %24, %25, %26, %27, %28, %29, %30, %31, "
    "%32, %33, %34, %35, %36, %37, %38, %39, %40, %41, %42, %43, %44, %45, %46, %47, "
    "%48, %49, %50, %51, %52, %53, %54, %55, %56, %57, %58, %59, %60, %61, %62, %63}, "
    "da, db, p, 1, 1, 0, 1;\n}\n"
    : "+f"(d[0]), "+f"(d[1]), "+f"(d[2]), "+f"(d[3]), "+f"(d[4]), "+f"(d[5]), "+f"(d[6]), "+f"(d[7]),
      "+f"(d[8]), "+f"(d[9]), "+f"(d[10]), "+f"(d[11]), "+f"(d[12]), "+f"(d[13]), "+f"(d[14]), "+f"(d[15]),
      "+f"(d[16]), "+f"(d[17]), "+f"(d[18]), "+f"(d[19]), "+f"(d[20]), "+f"(d[21]), "+f"(d[22]), "+f"(d[23]),
      "+f"(d[24]), "+f"(d[25]), "+f"(d[26]), "+f"(d[27]), "+f"(d[28]), "+f"(d[29]), "+f"(d[30]), "+f"(d[31]),
      "+f"(d[32]), "+f"(d[33]), "+f"(d[34]), "+f"(d[35]), "+f"(d[36]), "+f"(d[37]), "+f"(d[38]), "+f"(d[39]),
      "+f"(d[40]), "+f"(d[41]), "+f"(d[42]), "+f"(d[43]), "+f"(d[44]), "+f"(d[45]), "+f"(d[46]), "+f"(d[47]),
      "+f"(d[48]), "+f"(d[49]), "+f"(d[50]), "+f"(d[51]), "+f"(d[52]), "+f"(d[53]), "+f"(d[54]), "+f"(d[55]),
      "+f"(d[56]), "+f"(d[57]), "+f"(d[58]), "+f"(d[59]), "+f"(d[60]), "+f"(d[61]), "+f"(d[62]), "+f"(d[63])
    : "r"(da), "r"(db), "r"(scale_d));
}

__device__ __forceinline__ void wgmma_ss_n192(float (&d)[96], uint32_t da, uint32_t db, int scale_d) {
  asm volatile("{\n.reg .pred p;\n.reg .b64 da, db;\nsetp.ne.b32 p, %98, 0;\n"
    "mov.b64 da, {%96, 0x40000040};\nmov.b64 db, {%97, 0x40000040};\n"
    "wgmma.mma_async.sync.aligned.m64n192k16.f32.bf16.bf16 "
    "{%0, %1, %2, %3, %4, %5, %6, %7, %8, %9, %10, %11, %12, %13, %14, %15, "
    "%16, %17, %18, %19, %20, %21, %22, %23, %24, %25, %26, %27, %28, %29, %30, %31, "
    "%32, %33, %34, %35, %36, %37, %38, %39, %40, %41, %42, %43, %44, %45, %46, %47, "
    "%48, %49, %50, %51, %52, %53, %54, %55, %56, %57, %58, %59, %60, %61, %62, %63, "
    "%64, %65, %66, %67, %68, %69, %70, %71, %72, %73, %74, %75, %76, %77, %78, %79, "
    "%80, %81, %82, %83, %84, %85, %86, %87, %88, %89, %90, %91, %92, %93, %94, %95}, "
    "da, db, p, 1, 1, 0, 1;\n}\n"
    : "+f"(d[0]), "+f"(d[1]), "+f"(d[2]), "+f"(d[3]), "+f"(d[4]), "+f"(d[5]), "+f"(d[6]), "+f"(d[7]),
      "+f"(d[8]), "+f"(d[9]), "+f"(d[10]), "+f"(d[11]), "+f"(d[12]), "+f"(d[13]), "+f"(d[14]), "+f"(d[15]),
      "+f"(d[16]), "+f"(d[17]), "+f"(d[18]), "+f"(d[19]), "+f"(d[20]), "+f"(d[21]), "+f"(d[22]), "+f"(d[23]),
      "+f"(d[24]), "+f"(d[25]), "+f"(d[26]), "+f"(d[27]), "+f"(d[28]), "+f"(d[29]), "+f"(d[30]), "+f"(d[31]),
      "+f"(d[32]), "+f"(d[33]), "+f"(d[34]), "+f"(d[35]), "+f"(d[36]), "+f"(d[37]), "+f"(d[38]), "+f"(d[39]),
      "+f"(d[40]), "+f"(d[41]), "+f"(d[42]), "+f"(d[43]), "+f"(d[44]), "+f"(d[45]), "+f"(d[46]), "+f"(d[47]),
      "+f"(d[48]), "+f"(d[49]), "+f"(d[50]), "+f"(d[51]), "+f"(d[52]), "+f"(d[53]), "+f"(d[54]), "+f"(d[55]),
      "+f"(d[56]), "+f"(d[57]), "+f"(d[58]), "+f"(d[59]), "+f"(d[60]), "+f"(d[61]), "+f"(d[62]), "+f"(d[63]),
      "+f"(d[64]), "+f"(d[65]), "+f"(d[66]), "+f"(d[67]), "+f"(d[68]), "+f"(d[69]), "+f"(d[70]), "+f"(d[71]),
      "+f"(d[72]), "+f"(d[73]), "+f"(d[74]), "+f"(d[75]), "+f"(d[76]), "+f"(d[77]), "+f"(d[78]), "+f"(d[79]),
      "+f"(d[80]), "+f"(d[81]), "+f"(d[82]), "+f"(d[83]), "+f"(d[84]), "+f"(d[85]), "+f"(d[86]), "+f"(d[87]),
      "+f"(d[88]), "+f"(d[89]), "+f"(d[90]), "+f"(d[91]), "+f"(d[92]), "+f"(d[93]), "+f"(d[94]), "+f"(d[95])
    : "r"(da), "r"(db), "r"(scale_d));
}

__device__ __forceinline__ void wgmma_ss_n256(float (&d)[128], uint32_t da, uint32_t db, int scale_d) {
  asm volatile("{\n.reg .pred p;\n.reg .b64 da, db;\nsetp.ne.b32 p, %130, 0;\n"
    "mov.b64 da, {%128, 0x40000040};\nmov.b64 db, {%129, 0x40000040};\n"
    "wgmma.mma_async.sync.aligned.m64n256k16.f32.bf16.bf16 "
    "{%0, %1, %2, %3, %4, %5, %6, %7, %8, %9, %10, %11, %12, %13, %14, %15, "
    "%16, %17, %18, %19, %20, %21, %22, %23, %24, %25, %26, %27, %28, %29, %30, %31, "
    "%32, %33, %34, %35, %36, %37, %38, %39, %40, %41, %42, %43, %44, %45, %46, %47, "
    "%48, %49, %50, %51, %52, %53, %54, %55, %56, %57, %58, %59, %60, %61, %62, %63, "
    "%64, %65, %66, %67, %68, %69, %70, %71, %72, %73, %74, %75, %76, %77, %78, %79, "
    "%80, %81, %82, %83, %84, %85, %86, %87, %88, %89, %90, %91, %92, %93, %94, %95, "
    "%96, %97, %98, %99, %100, %101, %102, %103, %104, %105, %106, %107, %108, %109, %110, %111, "
    "%112, %113, %114, %115, %116, %117, %118, %119, %120, %121, %122, %123, %124, %125, %126, %127}, "
    "da, db, p, 1, 1, 0, 1;\n}\n"
    : "+f"(d[0]), "+f"(d[1]), "+f"(d[2]), "+f"(d[3]), "+f"(d[4]), "+f"(d[5]), "+f"(d[6]), "+f"(d[7]),
      "+f"(d[8]), "+f"(d[9]), "+f"(d[10]), "+f"(d[11]), "+f"(d[12]), "+f"(d[13]), "+f"(d[14]), "+f"(d[15]),
      "+f"(d[16]), "+f"(d[17]), "+f"(d[18]), "+f"(d[19]), "+f"(d[20]), "+f"(d[21]), "+f"(d[22]), "+f"(d[23]),
      "+f"(d[24]), "+f"(d[25]), "+f"(d[26]), "+f"(d[27]), "+f"(d[28]), "+f"(d[29]), "+f"(d[30]), "+f"(d[31]),
      "+f"(d[32]), "+f"(d[33]), "+f"(d[34]), "+f"(d[35]), "+f"(d[36]), "+f"(d[37]), "+f"(d[38]), "+f"(d[39]),
      "+f"(d[40]), "+f"(d[41]), "+f"(d[42]), "+f"(d[43]), "+f"(d[44]), "+f"(d[45]), "+f"(d[46]), "+f"(d[47]),
      "+f"(d[48]), "+f"(d[49]), "+f"(d[50]), "+f"(d[51]), "+f"(d[52]), "+f"(d[53]), "+f"(d[54]), "+f"(d[55]),
      "+f"(d[56]), "+f"(d[57]), "+f"(d[58]), "+f"(d[59]), "+f"(d[60]), "+f"(d[61]), "+f"(d[62]), "+f"(d[63]),
      "+f"(d[64]), "+f"(d[65]), "+f"(d[66]), "+f"(d[67]), "+f"(d[68]), "+f"(d[69]), "+f"(d[70]), "+f"(d[71]),
      "+f"(d[72]), "+f"(d[73]), "+f"(d[74]), "+f"(d[75]), "+f"(d[76]), "+f"(d[77]), "+f"(d[78]), "+f"(d[79]),
      "+f"(d[80]), "+f"(d[81]), "+f"(d[82]), "+f"(d[83]), "+f"(d[84]), "+f"(d[85]), "+f"(d[86]), "+f"(d[87]),
      "+f"(d[88]), "+f"(d[89]), "+f"(d[90]), "+f"(d[91]), "+f"(d[92]), "+f"(d[93]), "+f"(d[94]), "+f"(d[95]),
      "+f"(d[96]), "+f"(d[97]), "+f"(d[98]), "+f"(d[99]), "+f"(d[100]), "+f"(d[101]), "+f"(d[102]), "+f"(d[103]),
      "+f"(d[104]), "+f"(d[105]), "+f"(d[106]), "+f"(d[107]), "+f"(d[108]), "+f"(d[109]), "+f"(d[110]), "+f"(d[111]),
      "+f"(d[112]), "+f"(d[113]), "+f"(d[114]), "+f"(d[115]), "+f"(d[116]), "+f"(d[117]), "+f"(d[118]), "+f"(d[119]),
      "+f"(d[120]), "+f"(d[121]), "+f"(d[122]), "+f"(d[123]), "+f"(d[124]), "+f"(d[125]), "+f"(d[126]), "+f"(d[127])
    : "r"(da), "r"(db), "r"(scale_d));
}

namespace {

constexpr int SEQ = 2048, DM = 1024, FF = 3584;
constexpr int NCTA = 128;

constexpr uint32_t STG_OFF = 196608;
constexpr uint32_t MISC_OFF = STG_OFF + 32768;
constexpr uint32_t SMEM_BYTES = MISC_OFF + 3072;
constexpr uint32_t RED_OFF = 2 * 49152;
constexpr uint32_t MODB_OFF = MISC_OFF + 512;

enum { B_FQ = 0, B_EQ = 4, B_FW = 8, B_EW = 14, B_FG = 20, B_EG = 24, B_FD = 28, B_ED = 34,
       B_STGF = 40, B_MODB = 42, B_MODA = 45, B_RDY = 48, B_STGE = 56, B_COUNT = 58 };
enum { C_H = 0, C_O = 1, C_H2 = 3, C_ACT = 4, C_HA = 8, C_H2A = 9 };

struct Params {
  CUtensorMap h, o_ld, o_st, h2, act, out, wqkv, wqkv32, wo, wg, wu, wd, act_st, wm;
  const bf16* x;
  const bf16* c;
  const bf16* wmod;
  uint4* x1;
  uint4* modll;
  uint4* halo;
  uint4* stats1;
  uint4* stats2;
  unsigned* cnt;
  unsigned* epoch;
  uint8_t slot[64];
};

__device__ bf16 g_h[SEQ * DM];
__device__ bf16 g_o[SEQ * DM];
__device__ bf16 g_h2[SEQ * DM];
__device__ bf16 g_act[SEQ * FF];
__device__ uint4 g_x1[NCTA * 8 * 256];
__device__ uint4 g_modll[3072 / 2];
__device__ uint4 g_halo[16 * 8 * 2 * 2 * 8 * 32];
__device__ uint4 g_stats[2 * SEQ * 8];
__device__ unsigned g_cnt[16 * 32];
__device__ uint4 g_epoch;
#define TR(off)

__device__ __forceinline__ uint32_t smem_u32(const void* p) { return (uint32_t)__cvta_generic_to_shared(p); }
__device__ __forceinline__ void mbar_init(uint32_t bar, uint32_t count) {
  asm volatile("mbarrier.init.shared::cta.b64 [%0], %1;" ::"r"(bar), "r"(count));
}
__device__ __forceinline__ void mbar_expect_tx(uint32_t bar, uint32_t bytes) {
  asm volatile("mbarrier.arrive.expect_tx.shared::cta.b64 _, [%0], %1;" ::"r"(bar), "r"(bytes) : "memory");
}
__device__ __forceinline__ void mbar_arrive(uint32_t bar) {
  asm volatile("mbarrier.arrive.shared::cta.b64 _, [%0];" ::"r"(bar) : "memory");
}
__device__ __forceinline__ void mbar_arrive_cluster(uint32_t cluster_addr) {
  asm volatile("mbarrier.arrive.shared::cluster.b64 _, [%0];" ::"r"(cluster_addr) : "memory");
}
__device__ __forceinline__ uint32_t mapa(uint32_t addr, uint32_t cta) {
  uint32_t r;
  asm volatile("mapa.shared::cluster.u32 %0, %1, %2;" : "=r"(r) : "r"(addr), "r"(cta));
  return r;
}
__device__ __forceinline__ void mbar_wait(uint32_t bar, uint32_t parity) {
  asm volatile(
      "{\n.reg .pred p;\n"
      "WAIT_%=:\n"
      "mbarrier.try_wait.parity.shared::cta.b64 p, [%0], %1;\n"
      "@!p bra WAIT_%=;\n}\n" ::"r"(bar), "r"(parity) : "memory");
}
__device__ __forceinline__ void mbar_wait_watchdog(uint32_t bar, uint32_t parity) {
  asm volatile(
      "{\n.reg .pred p;\n.reg .u64 t0, t1;\nmov.u64 t0, %%globaltimer;\n"
      "WAIT_%=:\n"
      "mbarrier.try_wait.parity.shared::cta.b64 p, [%0], %1;\n"
      "@p bra DONE_%=;\n"
      "mov.u64 t1, %%globaltimer;\n"
      "sub.u64 t1, t1, t0;\n"
      "setp.lt.u64 p, t1, 2000000000;\n"
      "@p bra WAIT_%=;\n"
      "trap;\n"
      "DONE_%=:\n}\n" ::"r"(bar), "r"(parity) : "memory");
}
__device__ __forceinline__ void cnt_wait(const unsigned* p, unsigned target) {
  asm volatile(
      "{\n.reg .pred p;\n.reg .u32 v;\n.reg .s32 d;\n"
      "WAIT_%=:\n"
      "ld.relaxed.gpu.global.u32 v, [%0];\n"
      "sub.s32 d, v, %1;\n"
      "setp.lt.s32 p, d, 0;\n"
      "@p bra WAIT_%=;\n"
      "fence.proxy.async.global;\n"
      "}\n" ::"l"(p), "r"(target) : "memory");
}
__device__ __forceinline__ void cnt_wait_lazy(const unsigned* p, unsigned target) {
  asm volatile(
      "{\n.reg .pred p;\n.reg .u32 v;\n.reg .s32 d;\n"
      "WAIT_%=:\n"
      "nanosleep.u32 400;\n"
      "ld.relaxed.gpu.global.u32 v, [%0];\n"
      "sub.s32 d, v, %1;\n"
      "setp.lt.s32 p, d, 0;\n"
      "@p bra WAIT_%=;\n"
      "fence.proxy.async.global;\n"
      "}\n" ::"l"(p), "r"(target) : "memory");
}
__device__ __forceinline__ void cnt_signal(unsigned* p) {
  asm volatile("{\n.reg .pred p;\nelect.sync _|p, 0xffffffff;\n@p red.relaxed.gpu.global.add.u32 [%0], 1;\n}\n" ::"l"(p) : "memory");
}
__device__ __forceinline__ void ll_store(uint4* p, uint32_t a, uint32_t b, uint32_t tag) {
  asm volatile("st.relaxed.gpu.global.v2.b64 [%0], {%1, %2};" ::"l"(p), "l"((uint64_t)a | ((uint64_t)tag << 32)),
               "l"((uint64_t)b | ((uint64_t)tag << 32)) : "memory");
}
__device__ __forceinline__ uint4 ll_peek(const uint4* p) {
  uint4 v;
  asm volatile("ld.relaxed.gpu.global.v4.u32 {%0, %1, %2, %3}, [%4];" : "=r"(v.x), "=r"(v.y), "=r"(v.z), "=r"(v.w) : "l"(p) : "memory");
  return v;
}
template <int N, int SLEEP = 0, class F>
__device__ __forceinline__ void ll_poll(F addr, uint32_t tag, uint32_t (&out)[2 * N]) {
  for (;;) {
    uint4 v[N];
#pragma unroll
    for (int i = 0; i < N; i++) v[i] = ll_peek(addr(i));
    uint32_t bad = 0;
#pragma unroll
    for (int i = 0; i < N; i++) {
      bad |= (v[i].y ^ tag) | (v[i].w ^ tag);
      out[2 * i] = v[i].x;
      out[2 * i + 1] = v[i].z;
    }
    if (__all_sync(~0u, bad == 0)) break;
    if (SLEEP) __nanosleep(SLEEP);
  }
}
constexpr uint64_t POLICY_EVICT_FIRST = 0x12F0000000000000ull;
__device__ __forceinline__ void expect_tx_elect(uint32_t bar, uint32_t bytes) {
  asm volatile("{\n.reg .pred p;\nelect.sync _|p, 0xffffffff;\n@p mbarrier.arrive.expect_tx.shared::cta.b64 _, [%0], %1;\n}\n" ::"r"(bar), "r"(bytes) : "memory");
}
__device__ __forceinline__ void arrive_elect(uint32_t bar) {
  asm volatile("{\n.reg .pred p;\nelect.sync _|p, 0xffffffff;\n@p mbarrier.arrive.shared::cta.b64 _, [%0];\n}\n" ::"r"(bar) : "memory");
}
__device__ __forceinline__ void tma_load(uint32_t dst, const CUtensorMap* m, uint32_t bar, int c0, int c1) {
  asm volatile("{\n.reg .pred p;\nelect.sync _|p, 0xffffffff;\n"
               "@p cp.async.bulk.tensor.2d.shared::cluster.global.mbarrier::complete_tx::bytes [%0], [%1, {%3, %4}], [%2];\n}\n"
               ::"r"(dst), "l"(m), "r"(bar), "r"(c0), "r"(c1) : "memory");
}
__device__ __forceinline__ void tma_load_mc(uint32_t dst, const CUtensorMap* m, uint32_t bar, int c0, int c1) {
  asm volatile("{\n.reg .pred p;\nelect.sync _|p, 0xffffffff;\n"
               "@p cp.async.bulk.tensor.2d.shared::cluster.global.mbarrier::complete_tx::bytes.multicast::cluster.L2::cache_hint [%0], [%1, {%3, %4}], [%2], %5, %6;\n}\n"
               ::"r"(dst), "l"(m), "r"(bar), "r"(c0), "r"(c1), "h"((uint16_t)3), "l"(POLICY_EVICT_FIRST) : "memory");
}
__device__ __forceinline__ void tma_load_ef(uint32_t dst, const CUtensorMap* m, uint32_t bar, int c0, int c1) {
  asm volatile("{\n.reg .pred p;\nelect.sync _|p, 0xffffffff;\n"
               "@p cp.async.bulk.tensor.2d.shared::cluster.global.mbarrier::complete_tx::bytes.L2::cache_hint [%0], [%1, {%3, %4}], [%2], %5;\n}\n"
               ::"r"(dst), "l"(m), "r"(bar), "r"(c0), "r"(c1), "l"(POLICY_EVICT_FIRST) : "memory");
}
__device__ __forceinline__ void tma_store2(const CUtensorMap* m, uint32_t src, int c0, int c1) {
  asm volatile("{\n.reg .pred p;\nelect.sync _|p, 0xffffffff;\n"
               "@p cp.async.bulk.tensor.2d.global.shared::cta.bulk_group [%0, {%2, %3}], [%1];\n}\n"
               ::"l"(m), "r"(src), "r"(c0), "r"(c1) : "memory");
}
__device__ __forceinline__ void tma_store3(const CUtensorMap* m, uint32_t src, int c0, int c1, int c2) {
  asm volatile("{\n.reg .pred p;\nelect.sync _|p, 0xffffffff;\n"
               "@p cp.async.bulk.tensor.3d.global.shared::cta.bulk_group [%0, {%2, %3, %4}], [%1];\n}\n"
               ::"l"(m), "r"(src), "r"(c0), "r"(c1), "r"(c2) : "memory");
}
__device__ __forceinline__ void store_pause(bool sleep) {
  asm volatile("cp.async.bulk.commit_group;" ::: "memory");
  asm volatile("cp.async.bulk.wait_group.read 0;" ::: "memory");
  if (sleep) __nanosleep(PAUSE);
}
__device__ __forceinline__ void l2_prefetch_tile(const CUtensorMap* m, int c0, int c1) {
  asm volatile("{\n.reg .pred p;\nelect.sync _|p, 0xffffffff;\n@p cp.async.bulk.prefetch.tensor.2d.L2.global.L2::cache_hint [%0, {%1, %2}], %3;\n}\n"
               ::"l"(m), "r"(c0), "r"(c1), "l"(POLICY_EVICT_FIRST) : "memory");
}
__device__ __forceinline__ void prefetch_map(const CUtensorMap* m) {
  asm volatile("prefetch.tensormap [%0];" ::"l"(m) : "memory");
}
__device__ __forceinline__ void wg_fence() { asm volatile("wgmma.fence.sync.aligned;" ::: "memory"); }
__device__ __forceinline__ void wg_commit() { asm volatile("wgmma.commit_group.sync.aligned;" ::: "memory"); }
template <int N>
__device__ __forceinline__ void wg_wait() { asm volatile("wgmma.wait_group.sync.aligned %0;" ::"n"(N) : "memory"); }
__device__ __forceinline__ void bar_sync(int id, int n) { asm volatile("bar.sync %0, %1;" ::"r"(id), "r"(n) : "memory"); }
__device__ __forceinline__ void wg_bar(int cw) {
  asm volatile("{\n.reg .pred p;\nsetp.ne.s32 p, %0, 0;\n@p bar.sync 3, 128;\n@!p bar.sync 2, 128;\n}\n" ::"r"(cw) : "memory");
}
__device__ __forceinline__ void cluster_arrive() { asm volatile("barrier.cluster.arrive.release.aligned;" ::: "memory"); }
__device__ __forceinline__ void cluster_arrive_relaxed() { asm volatile("barrier.cluster.arrive.relaxed.aligned;" ::: "memory"); }
__device__ __forceinline__ void cluster_wait() { asm volatile("barrier.cluster.wait.acquire.aligned;" ::: "memory"); }
__device__ __forceinline__ uint32_t load_epoch(const unsigned* p) {
  uint32_t e;
  asm volatile("ld.relaxed.gpu.global.u32 %0, [%1];" : "=r"(e) : "l"(p) : "memory");
  return e;
}
__device__ __forceinline__ uint32_t pack2(float lo, float hi) {
  uint32_t r;
  asm("cvt.rn.bf16x2.f32 %0, %1, %2;" : "=r"(r) : "f"(hi), "f"(lo));
  return r;
}
__device__ __forceinline__ float bf_lo(uint32_t v) { return __uint_as_float(v << 16); }
__device__ __forceinline__ float bf_hi(uint32_t v) { return __uint_as_float(v & 0xffff0000u); }
__device__ __forceinline__ float bf_round(float v) { return __bfloat162float(__float2bfloat16_rn(v)); }
__device__ __forceinline__ float silu_f(float v) { return __fdividef(v, 1.0f + __expf(-v)); }
__device__ __forceinline__ uint4 ldg_nc(const void* p) {
  uint4 v;
  asm volatile("ld.global.nc.L1::no_allocate.v4.u32 {%0, %1, %2, %3}, [%4];" : "=r"(v.x), "=r"(v.y), "=r"(v.z), "=r"(v.w) : "l"(p));
  return v;
}
__device__ __forceinline__ uint4 ldg_stream(const void* p) {
  uint4 v;
  asm volatile("ld.global.nc.L1::no_allocate.L2::cache_hint.v4.u32 {%0, %1, %2, %3}, [%4], %5;" : "=r"(v.x), "=r"(v.y), "=r"(v.z), "=r"(v.w) : "l"(p), "l"(POLICY_EVICT_FIRST));
  return v;
}
__device__ __forceinline__ uint32_t ldg32(const void* p) {
  uint32_t v;
  asm volatile("ld.global.nc.u32 %0, [%1];" : "=r"(v) : "l"(p));
  return v;
}
__device__ __forceinline__ void stmatrix4(uint32_t addr, uint32_t a, uint32_t b, uint32_t c, uint32_t d) {
  asm volatile("stmatrix.sync.aligned.m8n8.x4.shared.b16 [%0], {%1, %2, %3, %4};" ::"r"(addr), "r"(a), "r"(b), "r"(c), "r"(d) : "memory");
}
__device__ __forceinline__ void stmatrix2(uint32_t addr, uint32_t a, uint32_t b) {
  asm volatile("stmatrix.sync.aligned.m8n8.x2.shared.b16 [%0], {%1, %2};" ::"r"(addr), "r"(a), "r"(b) : "memory");
}
__device__ __forceinline__ void stmatrix1(uint32_t addr, uint32_t a) {
  asm volatile("stmatrix.sync.aligned.m8n8.x1.shared.b16 [%0], {%1};" ::"r"(addr), "r"(a) : "memory");
}
__device__ __forceinline__ uint32_t movmatrix(uint32_t a) {
  uint32_t d;
  asm("movmatrix.sync.aligned.m8n8.trans.b16 %0, %1;" : "=r"(d) : "r"(a));
  return d;
}
__device__ __forceinline__ void mma16816(float (&d)[4], uint32_t a0, uint32_t a1, uint32_t a2, uint32_t a3, uint32_t b0, uint32_t b1) {
  asm("mma.sync.aligned.m16n8k16.row.col.f32.bf16.bf16.f32 {%0, %1, %2, %3}, {%4, %5, %6, %7}, {%8, %9}, {%0, %1, %2, %3};"
               : "+f"(d[0]), "+f"(d[1]), "+f"(d[2]), "+f"(d[3]) : "r"(a0), "r"(a1), "r"(a2), "r"(a3), "r"(b0), "r"(b1));
}
__device__ __forceinline__ void mma1688(float (&d)[4], uint32_t a0, uint32_t a1, uint32_t b0) {
  asm("mma.sync.aligned.m16n8k8.row.col.f32.bf16.bf16.f32 {%0, %1, %2, %3}, {%4, %5}, {%6}, {%0, %1, %2, %3};"
               : "+f"(d[0]), "+f"(d[1]), "+f"(d[2]), "+f"(d[3]) : "r"(a0), "r"(a1), "r"(b0));
}
__device__ __forceinline__ void ldmatrix4t(uint32_t (&b)[4], uint32_t addr) {
  asm volatile("ldmatrix.sync.aligned.m8n8.x4.trans.shared.b16 {%0, %1, %2, %3}, [%4];" : "=r"(b[0]), "=r"(b[1]), "=r"(b[2]), "=r"(b[3]) : "r"(addr) : "memory");
}
__device__ __forceinline__ void ldmatrix4(uint32_t& a, uint32_t& b, uint32_t& c, uint32_t& d, uint32_t addr) {
  asm volatile("ldmatrix.sync.aligned.m8n8.x4.shared.b16 {%0, %1, %2, %3}, [%4];" : "=r"(a), "=r"(b), "=r"(c), "=r"(d) : "r"(addr) : "memory");
}
__device__ __forceinline__ void cp_async16(uint32_t dst, const void* src) {
  asm volatile("cp.async.cg.shared.global.L2::cache_hint [%0], [%1], 16, %2;" ::"r"(dst), "l"(src), "l"(POLICY_EVICT_FIRST) : "memory");
}
__device__ __forceinline__ uint32_t lds32(uint32_t addr) {
  uint32_t v;
  asm volatile("ld.shared.u32 %0, [%1];" : "=r"(v) : "r"(addr) : "memory");
  return v;
}
__device__ __forceinline__ void sts64f(uint32_t addr, float a, float b) {
  asm volatile("st.shared.v2.f32 [%0], {%1, %2};" ::"r"(addr), "f"(a), "f"(b) : "memory");
}
constexpr float QK_SCALE = 0.17677669529663687f;
__device__ __forceinline__ void softmax8(float& p0, float& p1) {
  float m = fmaxf(p0, p1);
  m = fmaxf(m, __shfl_xor_sync(~0u, m, 1));
  m = fmaxf(m, __shfl_xor_sync(~0u, m, 2));
  asm("ex2.approx.ftz.f32 %0, %1;" : "=f"(p0) : "f"((p0 - m) * 1.4426950408889634f));
  asm("ex2.approx.ftz.f32 %0, %1;" : "=f"(p1) : "f"((p1 - m) * 1.4426950408889634f));
  float s = p0 + p1;
  s += __shfl_xor_sync(~0u, s, 1);
  s += __shfl_xor_sync(~0u, s, 2);
  float r;
  asm("rcp.approx.ftz.f32 %0, %1;" : "=f"(r) : "f"(s));
  p0 *= r;
  p1 *= r;
}
__device__ __forceinline__ void sts128(uint32_t addr, uint32_t a, uint32_t b, uint32_t c, uint32_t d) {
  asm volatile("st.shared.v4.u32 [%0], {%1, %2, %3, %4};" ::"r"(addr), "r"(a), "r"(b), "r"(c), "r"(d) : "memory");
}
__device__ __forceinline__ uint4 lds128(uint32_t addr) {
  uint4 v;
  asm volatile("ld.shared.v4.u32 {%0, %1, %2, %3}, [%4];" : "=r"(v.x), "=r"(v.y), "=r"(v.z), "=r"(v.w) : "r"(addr) : "memory");
  return v;
}
__device__ __forceinline__ float2 lds64f(uint32_t addr) {
  float2 v;
  asm volatile("ld.shared.v2.f32 {%0, %1}, [%2];" : "=f"(v.x), "=f"(v.y) : "r"(addr) : "memory");
  return v;
}
__device__ __forceinline__ void sts32f(uint32_t addr, float v) {
  asm volatile("st.shared.f32 [%0], %1;" ::"r"(addr), "f"(v) : "memory");
}
__device__ __forceinline__ float lds32f(uint32_t addr) {
  float v;
  asm volatile("ld.shared.f32 %0, [%1];" : "=f"(v) : "r"(addr) : "memory");
  return v;
}
#define PROF_AT(cond, slot) do {} while (0)

constexpr uint32_t SMEM_BASE = 1024;
constexpr uint32_t DESC_A = (1u << 16) | (SMEM_BASE >> 4);
constexpr uint32_t DESC_B = ((8192u >> 4) << 16) | ((SMEM_BASE + 16384) >> 4);

template <int BN> struct Wg;
template <> struct Wg<128> { static __device__ __forceinline__ void mma(float (&d)[64], uint32_t a, uint32_t b, int s) { wgmma_ss_n128(d, a, b, s); } };
template <> struct Wg<192> { static __device__ __forceinline__ void mma(float (&d)[96], uint32_t a, uint32_t b, int s) { wgmma_ss_n192(d, a, b, s); } };
template <> struct Wg<256> { static __device__ __forceinline__ void mma(float (&d)[128], uint32_t a, uint32_t b, int s) { wgmma_ss_n256(d, a, b, s); } };

struct Ring {
  uint32_t full0, rel0;
  int s;
  uint32_t ph;
  bool releaser;
};

template <int N>
__device__ __forceinline__ void fence_regs(float (&a)[N]) {
#pragma unroll
  for (int i = 0; i < N; i++) asm volatile("" : "+f"(a[i])::"memory");
}

template <int BN, int NST, uint32_t STAGE>
__device__ __forceinline__ void kblock(float (&acc)[BN / 2], Ring& g, uint32_t a_addr, bool zero, uint32_t& prev) {
  mbar_wait(g.full0 + 8 * g.s, g.ph);
  const uint32_t da = DESC_A + (a_addr >> 4);
  const uint32_t db = DESC_B + g.s * (STAGE >> 4);
  wg_fence();
#pragma unroll
  for (int k = 0; k < 4; k++) Wg<BN>::mma(acc, da + k * 2, db + k * 128, !(zero && k == 0));
  wg_commit();
  wg_wait<1>();
  if (prev != 0) mbar_arrive_cluster(prev);
  prev = g.releaser ? g.rel0 + 8 * g.s : 0u;
  if (++g.s == NST) { g.s = 0; g.ph ^= 1; }
}
template <int N>
__device__ __forceinline__ void tile_end(float (&acc)[N], uint32_t& prev) {
  wg_wait<0>();
  if (prev != 0) mbar_arrive_cluster(prev);
  prev = 0;
  fence_regs(acc);
}

__device__ __forceinline__ int other_kb(int q, int j) {
  const int ch = q >= 7, jj = q - 7 * ch;
  return 2 * (jj < j ? jj : jj + 1) + ch;
}
__device__ __forceinline__ int own_first(int it, int j) {
  return it >= 16 ? (it & 15) : (it < 2 ? 2 * j + it : other_kb(it - 2, j));
}
__device__ __forceinline__ int qkv_kb(int it, int j) {
  return it < 4 ? 2 * j + (it & 1) : other_kb(it < 18 ? it - 4 : it - 18, j);
}
__device__ __forceinline__ int wo_k(int it, int j) {
  return it < 8 ? it * 128 : (it == 8 ? j : (it - 9 < j ? it - 9 : it - 8)) * 128 + 64;
}
__device__ __forceinline__ int down_k(int it) {
  const int r = (it >> 4) - 1, idx = it & 15;
  return r < 0 ? idx * 64 : (r < 3 ? (idx >> 1) * 448 + r * 128 + (idx & 1) * 64 : idx * 448 + 384);
}
__device__ __forceinline__ void wait_p3_free(uint32_t empty3, int i) {
  mbar_wait(empty3 + 8 * ((i * 2) / 3), 1);
  mbar_wait(empty3 + 8 * ((i * 2 + 1) / 3), 1);
}
__device__ __forceinline__ void wait_p2_free(uint32_t empty2, int i) {
  const int w0 = (i * 3) / 2, w1 = (i * 3 + 2) / 2;
  mbar_wait(empty2 + 8 * w0, w0 < 4 ? 0 : 1);
  mbar_wait(empty2 + 8 * w1, w1 < 4 ? 0 : 1);
}

__device__ __forceinline__ void chan(float& m, float& q, float m2, float q2, float n) {
  const float d = m2 - m;
  m = 0.5f * (m + m2);
  q = q + q2 + d * d * (0.5f * n);
}

template <int N>
__device__ __forceinline__ void row_stats(const uint32_t (&ll)[N], float& mean, float& rstd) {
  float ma = __uint_as_float(ll[0]), qa = __uint_as_float(ll[1]), mb = __uint_as_float(ll[4]), qb = __uint_as_float(ll[5]);
  chan(ma, qa, __uint_as_float(ll[2]), __uint_as_float(ll[3]), 128.f);
  chan(mb, qb, __uint_as_float(ll[6]), __uint_as_float(ll[7]), 128.f);
  chan(ma, qa, mb, qb, 256.f);
  const float mo = __shfl_xor_sync(~0u, ma, 16), qo = __shfl_xor_sync(~0u, qa, 16);
  chan(ma, qa, mo, qo, 512.f);
  mean = ma;
  rstd = rsqrtf(qa * (1.0f / DM) + 1e-5f);
}

__device__ __forceinline__ void publish_stats(const uint32_t (&xl)[16], const uint32_t (&xh)[16], uint4* slot, int lane, uint32_t tag) {
  float ds[4] = {0.f, 0.f, 0.f, 0.f}, dl[4] = {0.f, 0.f, 0.f, 0.f}, dh[4] = {0.f, 0.f, 0.f, 0.f};
#pragma unroll
  for (int q = 0; q < 8; q++) {
    mma16816(ds, xl[2 * q], xh[2 * q], xl[2 * q + 1], xh[2 * q + 1], 0x3f803f80u, 0x3f803f80u);
    mma16816(dl, xl[2 * q], xh[2 * q], xl[2 * q + 1], xh[2 * q + 1], xl[2 * q], xl[2 * q + 1]);
    mma16816(dh, xl[2 * q], xh[2 * q], xl[2 * q + 1], xh[2 * q + 1], xh[2 * q], xh[2 * q + 1]);
  }
  const int r = lane >> 2;
  if ((lane & 3) == (r >> 1)) {
    const float ml = ds[0] * (1.0f / 128), mh = ds[2] * (1.0f / 128);
    const float ql = fmaxf(((r & 1) ? dl[1] : dl[0]) - ds[0] * ml, 0.f), qh = fmaxf(((r & 1) ? dh[3] : dh[2]) - ds[2] * mh, 0.f);
    ll_store(slot + r, __float_as_uint(ml), __float_as_uint(ql), tag);
    ll_store(slot + r + 8, __float_as_uint(mh), __float_as_uint(qh), tag);
  }
  __syncwarp();
}

__device__ __forceinline__ void stage_slab(uint32_t chunk, int warp, int lane, const uint32_t (&lo)[8], const uint32_t (&hi)[8]) {
  const int row = warp * 16 + (lane & 7) + ((lane >> 3) & 1) * 8;
  const uint32_t rbase = chunk + row * 128;
#pragma unroll
  for (int q = 0; q < 4; q++) {
    const int grp = 2 * q + (lane >> 4);
    stmatrix4(rbase + ((grp ^ (row & 7)) << 4), lo[2 * q], hi[2 * q], lo[2 * q + 1], hi[2 * q + 1]);
  }
}
__device__ __forceinline__ float silu_mul(float g, float u) {
  float e, r;
  asm("ex2.approx.ftz.f32 %0, %1;" : "=f"(e) : "f"(g * -1.4426950408889634f));
  asm("rcp.approx.ftz.f32 %0, %1;" : "=f"(r) : "f"(1.0f + e));
  return g * r * u;
}
__device__ __forceinline__ uint32_t swiglu2(uint32_t g2, uint32_t u2) {
  asm volatile("" : "+r"(g2));
  return pack2(silu_mul(bf_lo(g2), bf_lo(u2)), silu_mul(bf_hi(g2), bf_hi(u2)));
}
__device__ __forceinline__ void stage_done(uint32_t bar, int lane) {
  asm volatile("fence.proxy.async.shared::cta;" ::: "memory");
  __syncwarp();
  if (lane == 0) mbar_arrive(bar);
}

__device__ __forceinline__ int fresh_tid() {
  int t;
  asm volatile("mov.u32 %0, %%tid.x;" : "=r"(t));
  return t;
}
#define RING_IDS()                                                                                           \
  const int tid = fresh_tid() - 128;                                                                         \
  const int cw = __shfl_sync(~0u, tid >> 7, 0), warp = __shfl_sync(~0u, (tid >> 5) & 3, 0);                  \
  const bool releaser = (tid & 31) < 2;                                                                      \
  const uint32_t rbars = mapa(bars, tid & 1);                                                                \
  const uint32_t a_base = cw * 8192
#define LANE_IDS()                                                                                           \
  const int lane = fresh_tid() & 31, r = lane >> 2, c = lane & 3;                                            \
  const int srow = warp * 16 + (lane & 7) + ((lane >> 3) & 1) * 8;                                           \
  const uint32_t slab = stg + cw * 8192 + srow * 128, sw0 = (lane >> 4) ^ (srow & 7);                        \
  (void)r; (void)c; (void)slab; (void)sw0

template <int NPRE, bool EAGER, class Step>
__device__ __forceinline__ void attention(float (&acc)[96], const Params& p, int rho, int rb, int cta, int cw, int warp, uint32_t tag,
                                          uint32_t stg, uint32_t bars, uint32_t& prev, Step step) {
  uint32_t ql[8], qh[8], k0[8], k1[8], v0[8], v1[8], hp[16];
  if (EAGER) {
    tile_end(acc, prev);
  } else {
    step();
    fence_regs(acc);
  }
#pragma unroll
  for (int t = 0; t < 8; t++) {
    k0[t] = pack2(acc[4 * (8 + t)], acc[4 * (8 + t) + 1]);
    k1[t] = pack2(acc[4 * (8 + t) + 2], acc[4 * (8 + t) + 3]);
    v0[t] = pack2(acc[4 * (16 + t)], acc[4 * (16 + t) + 1]);
    v1[t] = pack2(acc[4 * (16 + t) + 2], acc[4 * (16 + t) + 3]);
    asm volatile("" : "+r"(k0[t]), "+r"(k1[t]), "+r"(v0[t]), "+r"(v1[t]));
  }
  const int lane = fresh_tid() & 31, r = lane >> 2, c = lane & 3;
#pragma unroll
  for (int t = 0; t < 8; t++) v1[t] = movmatrix(v1[t]);
  mbar_wait(bars + 8 * B_STGE, rho);
  mbar_wait(bars + 8 * (B_STGE + 1), 0);
  const uint32_t xch = stg + 16384 + (cw * 4 + warp) * 2048 + lane * 16;
  if (warp < 3) {
    sts128(xch, k1[0], k1[1], k1[2], k1[3]);
    sts128(xch + 512, k1[4], k1[5], k1[6], k1[7]);
    sts128(xch + 1024, v1[0], v1[1], v1[2], v1[3]);
    sts128(xch + 1536, v1[4], v1[5], v1[6], v1[7]);
  } else if (rb < 15) {
    uint4* dst = p.halo + ((cta * 2 + rho) * 2 + cw) * 256 + lane;
#pragma unroll
    for (int t = 0; t < 4; t++) {
      ll_store(dst + t * 32, k1[2 * t], k1[2 * t + 1], tag);
      ll_store(dst + (4 + t) * 32, v1[2 * t], v1[2 * t + 1], tag);
    }
  }
#pragma unroll
  for (int t = 0; t < 8; t++) {
    v0[t] = movmatrix(v0[t]);
    ql[t] = pack2(acc[4 * t], acc[4 * t + 1]);
    qh[t] = pack2(acc[4 * t + 2], acc[4 * t + 3]);
    asm volatile("" : "+r"(v0[t]), "+r"(ql[t]), "+r"(qh[t]));
  }
#pragma unroll 1
  for (int i = 0; i < NPRE; i++) step();
  const uint4* src = p.halo + (((cta - 8) * 2 + rho) * 2 + cw) * 256 + lane;
  uint4 early[8] = {};
  if (warp == 0 && rb > 0) {
#pragma unroll
    for (int i = 0; i < 8; i++) early[i] = ll_peek(src + i * 32);
  }
  step();
  wg_bar(cw);
  if (warp > 0) {
#pragma unroll
    for (int t = 0; t < 4; t++) {
      const uint4 a = lds128(xch - 2048 + t * 512);
      hp[4 * t] = a.x; hp[4 * t + 1] = a.y; hp[4 * t + 2] = a.z; hp[4 * t + 3] = a.w;
    }
  } else if (rb > 0) {
    uint32_t bad = 0;
#pragma unroll
    for (int i = 0; i < 8; i++) {
      bad |= (early[i].y ^ tag) | (early[i].w ^ tag);
      hp[2 * i] = early[i].x;
      hp[2 * i + 1] = early[i].z;
    }
    if (!__all_sync(~0u, bad == 0)) ll_poll<8>([&](int i) { return src + i * 32; }, tag, hp);
  } else {
#pragma unroll
    for (int t = 0; t < 16; t++) hp[t] = 0;
  }
  wg_wait<0>();
  if (prev != 0) mbar_arrive_cluster(prev);
  prev = 0;
#pragma unroll
  for (int t = 0; t < 8; t++) asm volatile("" : "+r"(ql[t])::"memory");
  const bool up0 = 2 * c > r, up1 = 2 * c + 1 > r;
  const bool first = (rb == 0) && (warp == 0);
  uint32_t a0[2], a2[2], a3[2], a5[2];
#pragma unroll
  for (int h = 0; h < 2; h++) {
    float sp[4] = {0.f, 0.f, 0.f, 0.f}, s0[4] = {0.f, 0.f, 0.f, 0.f}, s1[4] = {0.f, 0.f, 0.f, 0.f};
#pragma unroll
    for (int ks = 0; ks < 2; ks++) {
      const int t = 4 * h + 2 * ks;
      mma16816(sp, ql[t], qh[t], ql[t + 1], qh[t + 1], hp[t], hp[t + 1]);
      mma16816(s0, ql[t], qh[t], ql[t + 1], qh[t + 1], k0[t], k0[t + 1]);
      mma16816(s1, ql[t], qh[t], ql[t + 1], qh[t + 1], k1[t], k1[t + 1]);
    }
    float p0 = (up0 ? sp[0] : s0[0]) * QK_SCALE, p1 = (up1 ? sp[1] : s0[1]) * QK_SCALE;
    float p2 = (up0 ? s0[2] : s1[2]) * QK_SCALE, p3 = (up1 ? s0[3] : s1[3]) * QK_SCALE;
    if (first && up0) p0 = -1000000000.0f;
    if (first && up1) p1 = -1000000000.0f;
    softmax8(p0, p1);
    softmax8(p2, p3);
    a0[h] = pack2(up0 ? p0 : 0.f, up1 ? p1 : 0.f);
    a2[h] = pack2(up0 ? 0.f : p0, up1 ? 0.f : p1);
    a3[h] = pack2(up0 ? p2 : 0.f, up1 ? p3 : 0.f);
    a5[h] = pack2(up0 ? 0.f : p2, up1 ? 0.f : p3);
  }
  float o[8][4];
#pragma unroll
  for (int t = 0; t < 8; t++) {
#pragma unroll
    for (int q = 0; q < 4; q++) o[t][q] = 0.f;
    mma1688(o[t], 0u, a5[t >> 2], v1[t]);
    mma16816(o[t], a0[t >> 2], 0u, a2[t >> 2], a3[t >> 2], hp[8 + t], v0[t]);
  }
#pragma unroll
  for (int t = 0; t < 8; t++) fence_regs(o[t]);
  if (!EAGER) step();
  uint32_t ol[8], oh[8];
#pragma unroll
  for (int t = 0; t < 8; t++) {
    ol[t] = pack2(o[t][0], o[t][1]);
    oh[t] = pack2(o[t][2], o[t][3]);
  }
  stage_slab(stg + cw * 8192, warp, lane, ol, oh);
  stage_done(bars + 8 * B_STGF, lane);
}

template <class Ready>
__device__ __forceinline__ void normalize_stage(const uint32_t (&xl)[16], const uint32_t (&xh)[16], const uint4* stats, uint32_t tag, uint32_t shift,
                                                uint32_t scale, uint32_t stg, uint32_t bars, int cw, int warp, int lane, Ready ready) {
  const int r = lane >> 2, c = lane & 3;
  float nb[2], rs[2];
  {
    uint32_t st[8];
    const uint4* sp = stats + (lane >> 4) * 512 + cw * 64 + warp * 16 + (lane & 15);
    ll_poll<4>([&](int i) { return sp + i * 128; }, tag, st);
    float mu, rstd;
    row_stats(st, mu, rstd);
    mu *= -rstd;
    nb[0] = __shfl_sync(~0u, mu, r); rs[0] = __shfl_sync(~0u, rstd, r);
    nb[1] = __shfl_sync(~0u, mu, r + 8); rs[1] = __shfl_sync(~0u, rstd, r + 8);
  }
  ready();
#pragma unroll
  for (int ch = 0; ch < 2; ch++) {
    uint32_t lo[8], hi[8];
#pragma unroll
    for (int t = 0; t < 8; t++) {
      const int n = ch * 8 + t;
      const float2 sb = lds64f(shift + (8 * n + 2 * c) * 4), cb = lds64f(scale + (8 * n + 2 * c) * 4);
      lo[t] = pack2((bf_lo(xl[n]) * rs[0] + nb[0]) * cb.x + sb.x, (bf_hi(xl[n]) * rs[0] + nb[0]) * cb.y + sb.y);
      hi[t] = pack2((bf_lo(xh[n]) * rs[1] + nb[1]) * cb.x + sb.x, (bf_hi(xh[n]) * rs[1] + nb[1]) * cb.y + sb.y);
    }
    stage_slab(stg + ch * 16384 + cw * 8192, warp, lane, lo, hi);
    stage_done(bars + 8 * (B_STGF + ch), lane);
  }
  wg_bar(cw);
}

__global__ void __launch_bounds__(384, 1) fused_kernel(const __grid_constant__ Params p) {
  extern __shared__ __align__(1024) uint8_t smem_raw[];
  const uint32_t sm = smem_u32(smem_raw);
  const uint32_t bars = sm + MISC_OFF;
  const uint32_t stg = sm + STG_OFF;
  const int rank = blockIdx.x & 1;
  const int cl = blockIdx.x >> 1;
  if (cl >= NCTA / 2) {
    const int e = blockIdx.x - NCTA, wid = __shfl_sync(~0u, (int)(threadIdx.x >> 5), 0), lane = threadIdx.x & 31;
    if (threadIdx.x == 0) {
      for (int i = 0; i < 6; i++) { mbar_init(bars + 8 * i, 1); mbar_init(bars + 8 * (6 + i), 8); }
      asm volatile("fence.mbarrier_init.release.cluster;" ::: "memory");
    }
    const uint32_t tag = load_epoch(p.epoch) + 1;
    if (threadIdx.x < 256) ll_store(p.modll + 512 + (threadIdx.x >> 6) * 256 + e * 64 + (threadIdx.x & 63), 0u, 0u, 0u);
    for (int i = threadIdx.x; i < 1536; i += 384) {
      uint4 o = make_uint4(0u, 0u, 0u, 0u);
      if (i < 1024 && (i & 63) < 8) {
        const uint4 cv = ldg_nc(p.c + (i >> 6) * 64 + (i & 7) * 8);
        o = make_uint4(pack2(silu_f(bf_lo(cv.x)), silu_f(bf_hi(cv.x))), pack2(silu_f(bf_lo(cv.y)), silu_f(bf_hi(cv.y))),
                       pack2(silu_f(bf_lo(cv.z)), silu_f(bf_hi(cv.z))), pack2(silu_f(bf_lo(cv.w)), silu_f(bf_hi(cv.w))));
      }
      sts128(stg + i * 16, o.x, o.y, o.z, o.w);
    }
    asm volatile("fence.proxy.async.shared::cta;" ::: "memory");
    __syncthreads();
    if (wid == 0) {
      __nanosleep(WMDELAY);
      uint32_t ph = 1;
#pragma unroll 1
      for (int it = 0, s = 0; it < 64; it++) {
        mbar_wait(bars + 8 * (6 + s), ph);
        expect_tx_elect(bars + 8 * s, 32768);
#pragma unroll
        for (int q = 0; q < 4; q++) tma_load_ef(sm + s * 32768 + q * 8192, &p.wm, bars + 8 * s, 2048 + (it >> 4) * 1024 + e * 256 + q * 64, (it & 15) * 64);
        if (++s == 6) { s = 0; ph ^= 1; }
      }
    } else if (wid >= 4) {
      const int hf = (wid >> 2) - 1;
      uint32_t ph = 0;
      int s = 0;
#pragma unroll 1
      for (int v = 0; v < 4; v++) {
        float acc[64];
#pragma unroll 1
        for (int kb = 0; kb < 16; kb++) {
          mbar_wait_watchdog(bars + 8 * s, ph);
          const uint32_t da = DESC_A + ((STG_OFF + kb * 1024) >> 4), db = DESC_B + ((s * 32768 + hf * 16384) >> 4) - 1024;
          wg_fence();
#pragma unroll
          for (int k = 0; k < 4; k++) wgmma_ss_n128(acc, da + k * 2, db + k * 128, (kb | k) != 0);
          wg_commit();
          wg_wait<0>();
          if (lane == 0) mbar_arrive(bars + 8 * (6 + s));
          if (++s == 6) { s = 0; ph ^= 1; }
        }
        if ((wid & 3) == 0) {
#pragma unroll
          for (int n = 0; n < 16; n++) {
            const uint32_t mine = pack2(acc[4 * n], acc[4 * n + 1]), next = __shfl_down_sync(~0u, mine, 1);
            if (lane < 4 && (lane & 1) == 0) ll_store(p.modll + 512 + v * 256 + e * 64 + hf * 32 + n * 2 + (lane >> 1), mine, next, tag);
          }
        }
      }
    }
    return;
  }
  const int slot = p.slot[cl];
  const int rb = (slot >> 3) * 2 + rank, j = slot & 7;
  const int cta = rb * 8 + j;
  PROF_AT(threadIdx.x == 0, 0);

  if (threadIdx.x < 128) {
    uint32_t tag = load_epoch(p.epoch);
    asm volatile("setmaxnreg.dec.sync.aligned.u32 40;");
    const int warp = __shfl_sync(~0u, (int)(threadIdx.x >> 5), 0), lane = threadIdx.x & 31;
    if (threadIdx.x == 0) {
      if ((sm & 0x3FFFF) != SMEM_BASE) asm volatile("trap;");
      for (int i = 0; i < 4; i++) { mbar_init(bars + 8 * (B_FQ + i), 1); mbar_init(bars + 8 * (B_EQ + i), 16); }
      for (int i = 0; i < 6; i++) { mbar_init(bars + 8 * (B_FW + i), 1); mbar_init(bars + 8 * (B_EW + i), 16); }
      for (int i = 0; i < 4; i++) { mbar_init(bars + 8 * (B_FG + i), 1); mbar_init(bars + 8 * (B_EG + i), 16); }
      for (int i = 0; i < 6; i++) { mbar_init(bars + 8 * (B_FD + i), 1); mbar_init(bars + 8 * (B_ED + i), 16); }
      for (int i = 0; i < 2; i++) { mbar_init(bars + 8 * (B_STGF + i), 8); mbar_init(bars + 8 * (B_STGE + i), 1); }
      mbar_init(bars + 8 * B_MODB, 1);
      mbar_init(bars + 8 * (B_MODB + 1), 1);
      mbar_init(bars + 8 * B_MODA, 1);
      for (int i = 0; i < 8; i++) mbar_init(bars + 8 * (B_RDY + i), 1);
      asm volatile("fence.mbarrier_init.release.cluster;" ::: "memory");
    }
    __syncwarp();
    cluster_arrive_relaxed();
    tag += 1;
    const unsigned target = tag * 8;
    unsigned* cnt = p.cnt + rb * 32;
    cluster_wait();
    if (warp == 0) {
      const CUtensorMap* wgu = rank ? &p.wu : &p.wg;
      uint32_t st = sm + 16384, fb = bars + 8 * B_FQ, ph = 1;
      if (BDELAY) __nanosleep(BDELAY);
#pragma unroll 1
      for (int it = 0; it < 32; it++) {
        const int kb = qkv_kb(it, j), col = j * 128 + ((it < 4 ? it >= 2 : it >= 18) ? 64 : 0);
        mbar_wait(fb + 8 * (B_EQ - B_FQ), ph);
        expect_tx_elect(fb, it < 4 ? 24576 : 40960);
        tma_load_mc(st + rank * 8192, &p.wqkv, fb, col + rank * 1024, kb * 64);
        tma_load_mc(st + 16384 + rank * 4096, &p.wqkv32, fb, col + 2048, kb * 64 + rank * 32);
        st += 49152; fb += 8;
        if ((it & 3) == 3) { st -= 4 * 49152; fb -= 32; ph ^= 1; }
      }
      fb = bars + 8 * B_FW; ph = 1;
#pragma unroll 1
      for (int it = 0, s = 0; it < 16; it++) {
        if (it < 6) wait_p3_free(bars + 8 * B_EQ, it);
        mbar_wait(fb + 8 * (B_EW - B_FW), ph);
        expect_tx_elect(fb, it == 8 ? 16384 : 32768);
        tma_load_mc(st + rank * 8192, &p.wo, fb, j * 128 + rank * 64, wo_k(it, j));
        st += 32768; fb += 8;
        if (++s == 6) { s = 0; st -= 6 * 32768; fb -= 48; ph ^= 1; }
      }
      st = sm + 16384; fb = bars + 8 * B_FG; ph = 1;
#pragma unroll 1
      for (int it = 0; it < 48; it++) {
        const int kb = own_first(it, j), col = j * 448 + (it >> 4) * 128;
        if (it < 4) wait_p2_free(bars + 8 * B_EW, it);
        mbar_wait(fb + 8 * (B_EG - B_FG), ph);
        expect_tx_elect(fb, it < 2 ? 32768 : 49152);
        tma_load_mc(st + rank * 16384, wgu, fb, col, kb * 64);
        tma_load_mc(st + rank * 16384 + 8192, wgu, fb, col + 64, kb * 64);
        st += 49152; fb += 8;
        if ((it & 3) == 3) { st -= 4 * 49152; fb -= 32; ph ^= 1; }
      }
      fb = bars + 8 * B_FD; ph = 1;
#pragma unroll 1
      for (int it = 0, s = 0; it < 72; it++) {
        if (it < 6) wait_p3_free(bars + 8 * B_EG, it);
        mbar_wait(fb + 8 * (B_ED - B_FD), ph);
        expect_tx_elect(fb, 32768);
        tma_load_mc(st + rank * 8192, it < 16 ? wgu : &p.wd, fb, it < 16 ? j * 448 + 384 : j * 128 + rank * 64, down_k(it));
        st += 32768; fb += 8;
        if (++s == 6) { s = 0; st -= 6 * 32768; fb -= 48; ph ^= 1; }
      }
    } else if (warp == 1) {
      const int arow = rb * 128;
      uint32_t st = sm, fb = bars + 8 * B_FQ, ph = 0;
      cnt_wait(cnt + C_HA, target);
      PROF_AT(lane == 0, 16);
#pragma unroll 1
      for (int it = 4; it < 32; it++) {
        if (it == 11) mbar_wait(bars + 8 * (B_RDY + C_H), 0);
        mbar_wait(fb + 8 * (B_EQ - B_FQ), ph);
        tma_load(st, &p.h, fb, qkv_kb(it, j) * 64, arow);
        st += 49152; fb += 8;
        if ((it & 3) == 3) { st -= 4 * 49152; fb -= 32; ph ^= 1; }
      }
      fb = bars + 8 * B_FW; ph = 1;
#pragma unroll 1
      for (int it = 0, s = 0; it < 16; it++) {
        if (it < 6) wait_p3_free(bars + 8 * B_EQ, it);
        mbar_wait(fb + 8 * (B_EW - B_FW), ph);
        if (it == 0) mbar_wait(bars + 8 * (B_RDY + C_O), 0);
        if (it == 9) cnt_wait(cnt + C_O + 1, target);
        PROF_AT(lane == 0 && (it == 0 || it == 9), 17 + (it >> 3));
        if (it != 8) tma_load(st, &p.o_ld, fb, wo_k(it, j), arow);
        st += 32768; fb += 8;
        if (++s == 6) { s = 0; st -= 6 * 32768; fb -= 48; ph ^= 1; }
      }
      st = sm + 2 * 49152; fb = bars + 8 * (B_FG + 2); ph = 1;
      cnt_wait(cnt + C_H2A, target);
      PROF_AT(lane == 0, 19);
#pragma unroll 1
      for (int it = 2; it < 48; it++) {
        if (it == 9) mbar_wait(bars + 8 * (B_RDY + C_H2), 0);
        mbar_wait(fb + 8 * (B_EG - B_FG), ph);
        tma_load(st, &p.h2, fb, own_first(it, j) * 64, arow);
        st += 49152; fb += 8;
        if ((it & 3) == 3) { st -= 4 * 49152; fb -= 32; ph ^= 1; }
      }
      fb = bars + 8 * B_FD; ph = 1;
#pragma unroll 1
      for (int it = 0, s = 0; it < 72; it++) {
        if (it < 6) wait_p3_free(bars + 8 * B_EG, it);
        mbar_wait(fb + 8 * (B_ED - B_FD), ph);
        if ((it & 15) == 0 && it > 0) { mbar_wait(bars + 8 * (B_RDY + C_ACT - 1 + (it >> 4)), 0); PROF_AT(lane == 0, 19 + (it >> 4)); }
        tma_load(st, it < 16 ? &p.h2 : &p.act, fb, down_k(it), arow);
        st += 32768; fb += 8;
        if (++s == 6) { s = 0; st -= 6 * 32768; fb -= 48; ph ^= 1; }
      }
    } else if (warp == 2) {
      if (lane < 13) prefetch_map(&p.h + lane);
      __syncwarp();
      uint32_t ph1 = 0;
#pragma unroll 1
      for (int n = 0; n < 8; n++) {
        const int nch = (n == 1 || n == 2 || n == 7) ? 1 : 2;
#pragma unroll 1
        for (int ch = 0; ch < nch; ch++) {
          mbar_wait_watchdog(bars + 8 * (B_STGF + ch), ch ? ph1 : (n & 1));
          const uint32_t src = stg + ch * 16384;
          if (n == 1 || n == 2) {
#pragma unroll 1
            for (int q = 0; q < 4; q++) {
              tma_store2(&p.o_st, src + q * 4096, j * 128 + (n - 1) * 64, rb * 128 + q * 32);
              if (n == 1) store_pause(true);
            }
          } else if (n >= 4 && n < 8) {
#pragma unroll 1
            for (int q = 0; q < 4; q++) {
              tma_store2(&p.act_st, src + q * 4096, j * 448 + (n - 4) * 128 + ch * 64, rb * 128 + q * 32);
              store_pause(true);
            }
          } else {
            tma_store2(n == 0 ? &p.h : &p.h2, src, j * 128 + ch * 64, rb * 128);
            asm volatile("cp.async.bulk.commit_group;" ::: "memory");
            if (ch == 1) {
              asm volatile("cp.async.bulk.wait_group 1;" ::: "memory");
              __syncwarp();
              cnt_signal(cnt + (n == 0 ? C_HA : C_H2A));
            }
          }
          if (n >= 4 && n < 7 && ch == 0) arrive_elect(bars + 8 * B_STGE);
        }
        asm volatile("cp.async.bulk.commit_group;" ::: "memory");
        asm volatile("cp.async.bulk.wait_group 0;" ::: "memory");
        __syncwarp();
        cnt_signal(cnt + n);
        PROF_AT(lane == 0, n == 0 ? 33 : 23 + n);
        if (n == 0) {
#pragma unroll 1
          for (int t = 0; t < 36; t++) {
            ll_store(t < 32 ? p.halo + cta * 1024 + t * 32 + lane : p.stats2 + cta * 128 + (t - 32) * 32 + lane, 0u, 0u, 0u);
            __nanosleep(40);
          }
          __syncwarp();
        }
        if (!(n >= 4 && n < 7)) arrive_elect(bars + 8 * B_STGE);
        if (nch == 2) { arrive_elect(bars + 8 * (B_STGE + 1)); ph1 ^= 1; }
      }
      mbar_wait_watchdog(bars + 8 * B_STGF, 0);
      PROF_AT(lane == 0, 31);
    } else {
      if (lane < 4) ll_store(p.modll + cta * 4 + lane, 0u, 0u, 0u);
      bar_sync(1, 288);
      {
        const uint4 t4 = lds128(sm + RED_OFF + lane * 16);
        float a[4] = {__uint_as_float(t4.x), __uint_as_float(t4.y), __uint_as_float(t4.z), __uint_as_float(t4.w)};
#pragma unroll
        for (int o = 4; o < 32; o <<= 1)
#pragma unroll
          for (int q = 0; q < 4; q++) a[q] += __shfl_xor_sync(~0u, a[q], o);
        if (lane < 4) ll_store(p.modll + cta * 4 + lane, pack2(a[0], a[1]), pack2(a[2], a[3]), tag);
        PROF_AT(lane == 0, 1);
        uint32_t m[4];
        const uint4* mp = p.modll + j * 32 + lane;
        ll_poll<2>([&](int i) { return mp + i * 256; }, tag, m);
        const uint32_t c0 = pack2(1.0f + bf_lo(m[2]), 1.0f + bf_hi(m[2])), c1 = pack2(1.0f + bf_lo(m[3]), 1.0f + bf_hi(m[3]));
        sts128(sm + MODB_OFF + lane * 16, m[0] << 16, m[0] & 0xffff0000u, m[1] << 16, m[1] & 0xffff0000u);
        sts128(sm + MODB_OFF + 512 + lane * 16, c0 << 16, c0 & 0xffff0000u, c1 << 16, c1 & 0xffff0000u);
        __syncwarp();
        arrive_elect(bars + 8 * B_MODA);
      }
#pragma unroll 1
      for (int n = C_H; n <= C_O; n++) {
        cnt_wait_lazy(cnt + n, target);
        arrive_elect(bars + 8 * (B_RDY + n));
      }
      {
        uint32_t m[6];
        const uint4* src = p.modll + 512 + j * 32 + lane;
        ll_poll<3, 500>([&](int i) { return src + i * 256; }, tag, m);
#pragma unroll
        for (int vec = 0; vec < 3; vec++) {
          const float add = vec == 2 ? 1.0f : 0.0f;
          sts128(sm + MODB_OFF + (vec * 128 + lane * 4) * 4, __float_as_uint(bf_round(bf_lo(m[2 * vec]) + add)), __float_as_uint(bf_round(bf_hi(m[2 * vec]) + add)),
                 __float_as_uint(bf_round(bf_lo(m[2 * vec + 1]) + add)), __float_as_uint(bf_round(bf_hi(m[2 * vec + 1]) + add)));
        }
        __syncwarp();
        if (lane == 0) mbar_arrive(bars + 8 * B_MODB);
        PROF_AT(lane == 0, 15);
      }
      __syncwarp();
#pragma unroll 1
      for (int n = C_H2; n < 8; n++) {
        cnt_wait_lazy(cnt + n, target);
        arrive_elect(bars + 8 * (B_RDY + n));
      }
      {
        uint32_t m[2];
        const uint4* src = p.modll + 512 + 768 + j * 32 + lane;
        ll_poll<1>([&](int) { return src; }, tag, m);
        sts128(sm + MODB_OFF + (384 + lane * 4) * 4, m[0] << 16, m[0] & 0xffff0000u, m[1] << 16, m[1] & 0xffff0000u);
        __syncwarp();
        if (lane == 0) mbar_arrive(bars + 8 * (B_MODB + 1));
      }
    }
    if (!TAIL) {
      __syncwarp();
      cluster_arrive_relaxed();
      cluster_wait();
    }
  } else {
    uint32_t tag;

    {
      const int tid = threadIdx.x - 128, cw = tid >> 7, warp = (tid >> 5) & 3, lane = tid & 31;
      const int l16 = lane & 15, half = lane >> 4, w8 = cw * 4 + warp;
      const uint32_t cbuf = sm + 3 * 49152 + w8 * 512;
      if (lane <= 16) cp_async16(cbuf + lane * 16, lane < 16 ? (const void*)(p.c + w8 * 128 + lane * 8) : (const void*)p.epoch);
      asm volatile("cp.async.commit_group;" ::: "memory");
      const uint32_t wbuf = sm + cw * 49152 + warp * 4096;
      {
        const char* wp = (const char*)p.wmod + (uint32_t)(cta * 32 + (lane & 1) * 16 + (w8 * 128 + (lane >> 1)) * 12288);
#pragma unroll
        for (int i = 0; i < 8; i++) cp_async16(wbuf + i * 512 + lane * 16, wp + i * 16 * 12288);
      }
      asm volatile("cp.async.commit_group;" ::: "memory");
      const uint32_t xbuf = sm + 40960 + (cw * 2 + (l16 >> 3)) * 49152 + (warp * 16 + half) * 128;
      {
        const char* xp = (const char*)p.x + (uint32_t)((rb * 128 + (warp * 16 + half) * 2 + cw) * 2048 + j * 256 + l16 * 16);
#pragma unroll
        for (int i = 0; i < 8; i++) cp_async16(xbuf + i * 256 + (((l16 & 7) ^ ((i * 2 + half) & 7)) << 4), xp + i * 8192);
      }
      asm volatile("cp.async.commit_group;" ::: "memory");
      PROF_AT(tid == 0, 32);
      uint4* st1 = p.stats1 + (rb * 8 + j) * 128 + cw * 64 + warp * 16;
      if (lane < 16) ll_store(st1 + lane, 0u, 0u, 0u);
      __syncwarp();
      cluster_arrive_relaxed();
      asm volatile("setmaxnreg.inc.sync.aligned.u32 232;");
      uint32_t sa[4][4];
      {
        asm volatile("cp.async.wait_group 2;" ::: "memory");
        __syncwarp();
        tag = lds32(cbuf + 256) + 1;
        const float2 cv = lds64f(cbuf + lane * 8);
        const uint32_t c0 = __float_as_uint(cv.x), c1 = __float_as_uint(cv.y);
        sts64f(cbuf + lane * 8, __uint_as_float(pack2(silu_f(bf_lo(c0)), silu_f(bf_hi(c0)))), __uint_as_float(pack2(silu_f(bf_lo(c1)), silu_f(bf_hi(c1)))));
        __syncwarp();
#pragma unroll
        for (int q = 0; q < 4; q++) ldmatrix4(sa[q][0], sa[q][1], sa[q][2], sa[q][3], cbuf + q * 64 + (lane >> 3) * 16);
      }
      cluster_wait();
      asm volatile("cp.async.wait_group 1;" ::: "memory");
      __syncwarp();
      PROF_AT(tid == 0, 51);
      {
        uint32_t b[8][4];
#pragma unroll
        for (int ks = 0; ks < 8; ks++) ldmatrix4t(b[ks], wbuf + (ks * 16 + (lane & 15)) * 32 + (lane >> 4) * 16);
        float d0[4] = {0.f, 0.f, 0.f, 0.f}, d1[4] = {0.f, 0.f, 0.f, 0.f}, d2[4] = {0.f, 0.f, 0.f, 0.f}, d3[4] = {0.f, 0.f, 0.f, 0.f};
#pragma unroll
        for (int q = 0; q < 4; q++) {
          mma16816(d0, sa[q][0], sa[q][0], sa[q][1], sa[q][1], b[2 * q][0], b[2 * q][1]);
          mma16816(d1, sa[q][0], sa[q][0], sa[q][1], sa[q][1], b[2 * q][2], b[2 * q][3]);
          mma16816(d2, sa[q][2], sa[q][2], sa[q][3], sa[q][3], b[2 * q + 1][0], b[2 * q + 1][1]);
          mma16816(d3, sa[q][2], sa[q][2], sa[q][3], sa[q][3], b[2 * q + 1][2], b[2 * q + 1][3]);
        }
        d0[0] += d2[0]; d0[1] += d2[1]; d1[0] += d3[0]; d1[1] += d3[1];
        if (lane < 4) {
          sts64f(sm + RED_OFF + (w8 * 16 + lane * 2) * 4, d0[0], d0[1]);
          sts64f(sm + RED_OFF + (w8 * 16 + 8 + lane * 2) * 4, d1[0], d1[1]);
        }
        asm volatile("bar.arrive 1, 288;" ::: "memory");
      }
      asm volatile("cp.async.wait_group 0;" ::: "memory");
      __syncwarp();
      uint32_t xl[16], xh[16];
      {
        const int srow = warp * 16 + (lane & 15);
#pragma unroll
        for (int q = 0; q < 8; q++)
          ldmatrix4(xl[2 * q], xh[2 * q], xl[2 * q + 1], xh[2 * q + 1],
                    sm + 40960 + (cw * 2 + (q >> 2)) * 49152 + srow * 128 + (((half + (q & 3) * 2) ^ (srow & 7)) << 4));
      }
      publish_stats(xl, xh, st1, lane, tag);
      PROF_AT(tid == 0, 50);
      normalize_stage(xl, xh, p.stats1 + rb * 1024, tag, sm + MODB_OFF, sm + MODB_OFF + 512, stg, bars, cw, warp, lane,
                      [&]() { mbar_wait(bars + 8 * B_MODA, 0); });
      PROF_AT(tid == 0, 3);
    }

    uint32_t xl[16], xh[16];
    {
      RING_IDS();
      uint32_t prev = 0;
      float acc1[96];
      {
        Ring g{bars + 8 * B_FQ, rbars + 8 * B_EQ, 0, 0u, releaser TR(0)};
        float acc0[96];
#pragma unroll 1
        for (int kb = 0; kb < 2; kb++) kblock<192, 4, 49152>(acc0, g, a_base + STG_OFF + kb * 16384, kb == 0, prev);
#pragma unroll 1
        for (int kb = 0; kb < 2; kb++) kblock<192, 4, 49152>(acc1, g, a_base + STG_OFF + kb * 16384, kb == 0, prev);
#pragma unroll 1
        for (int kb = 0; kb < 14; kb++) kblock<192, 4, 49152>(acc0, g, a_base + g.s * 49152, false, prev);
        PROF_AT(tid == 0, 4);
        attention<NPRE0, false>(acc0, p, 0, rb, cta, cw, warp, tag, stg, bars, prev, [&]() { kblock<192, 4, 49152>(acc1, g, a_base + g.s * 49152, false, prev); });
        PROF_AT(tid == 0, 5);
        {
          LANE_IDS();
#pragma unroll
          for (int q = 0; q < 8; q++)
            ldmatrix4(xl[2 * q], xh[2 * q], xl[2 * q + 1], xh[2 * q + 1], sm + 40960 + (cw * 2 + (q >> 2)) * 49152 + srow * 128 + ((sw0 ^ ((q & 3) * 2)) << 4));
#pragma unroll
          for (int q = 0; q < 16; q++) asm volatile("" : "+r"(xl[q]), "+r"(xh[q])::"memory");
        }
#pragma unroll 1
        for (int kb = 3 + NPRE0; kb < 14; kb++) kblock<192, 4, 49152>(acc1, g, a_base + g.s * 49152, false, prev);
        PROF_AT(tid == 0, 6);
      }
      float acc[64];
      Ring g{bars + 8 * B_FW, rbars + 8 * B_EW, 0, 0u, releaser TR(32)};
      attention<NPRE1, EAGER1>(acc1, p, 1, rb, cta, cw, warp, tag, stg, bars, prev, [&]() { kblock<128, 6, 32768>(acc, g, a_base + g.s * 32768, g.s == 0, prev); });
      PROF_AT(tid == 0, 7);
      LANE_IDS();
#pragma unroll 1
      for (int kb = (EAGER1 ? 1 : 3) + NPRE1; kb < 16; kb++) {
        if (kb == 8) wg_bar(cw);
        kblock<128, 6, 32768>(acc, g, a_base + (kb == 8 ? STG_OFF : g.s * 32768), false, prev);
      }
      mbar_wait(bars + 8 * B_MODB, 0);
      float2 ga[16];
#pragma unroll
      for (int n = 0; n < 16; n++) ga[n] = lds64f(sm + MODB_OFF + (8 * n + 2 * c) * 4);
      tile_end(acc, prev);
      PROF_AT(tid == 0, 8);
      uint4* st2 = p.stats2 + (rb * 8 + j) * 128 + cw * 64 + warp * 16 + r + (c & 1) * 8;
      float sl[2] = {0.f, 0.f}, sh[2] = {0.f, 0.f}, ql[2] = {0.f, 0.f}, qh[2] = {0.f, 0.f};
#pragma unroll
      for (int n = 0; n < 16; n++) {
        acc[4 * n] = ga[n].x * acc[4 * n] + bf_lo(xl[n]); acc[4 * n + 1] = ga[n].y * acc[4 * n + 1] + bf_hi(xl[n]);
        acc[4 * n + 2] = ga[n].x * acc[4 * n + 2] + bf_lo(xh[n]); acc[4 * n + 3] = ga[n].y * acc[4 * n + 3] + bf_hi(xh[n]);
        sl[0] += acc[4 * n]; sl[1] += acc[4 * n + 1]; sh[0] += acc[4 * n + 2]; sh[1] += acc[4 * n + 3];
        ql[0] += acc[4 * n] * acc[4 * n]; ql[1] += acc[4 * n + 1] * acc[4 * n + 1];
        qh[0] += acc[4 * n + 2] * acc[4 * n + 2]; qh[1] += acc[4 * n + 3] * acc[4 * n + 3];
      }
      {
        const float ml = (sl[0] + sl[1]) * (1.0f / 32), mh = (sh[0] + sh[1]) * (1.0f / 32);
        const float vl = (ql[0] + ql[1]) - 32.0f * ml * ml, vh = (qh[0] + qh[1]) - 32.0f * mh * mh;
        const bool b0 = c & 1;
        float m = b0 ? mh : ml, q = b0 ? vh : vl;
        chan(m, q, __shfl_xor_sync(~0u, b0 ? ml : mh, 1), __shfl_xor_sync(~0u, b0 ? vl : vh, 1), 32.f);
        chan(m, q, __shfl_xor_sync(~0u, m, 2), __shfl_xor_sync(~0u, q, 2), 64.f);
        if (c < 2) ll_store(st2, __float_as_uint(m), __float_as_uint(fmaxf(q, 0.f)), tag);
        __syncwarp();
      }
      PROF_AT(tid == 0, 48);
      float2 sb[16], cb[16];
#pragma unroll
      for (int n = 0; n < 16; n++) {
        sb[n] = lds64f(sm + MODB_OFF + (128 + 8 * n + 2 * c) * 4);
        cb[n] = lds64f(sm + MODB_OFF + (256 + 8 * n + 2 * c) * 4);
        xl[n] = pack2(acc[4 * n], acc[4 * n + 1]);
        xh[n] = pack2(acc[4 * n + 2], acc[4 * n + 3]);
      }
      mbar_wait(bars + 8 * B_STGE, 0);
      PROF_AT(tid == 0, 49);
      float nb[2], rstd[2];
      {
        uint32_t st[8];
        const uint4* sp = p.stats2 + (rb * 8 + (lane >> 4) * 4) * 128 + cw * 64 + warp * 16 + (lane & 15);
        ll_poll<4, PB2>([&](int i) { return sp + i * 128; }, tag, st);
        float mu, rs;
        row_stats(st, mu, rs);
        mu *= -rs;
        nb[0] = __shfl_sync(~0u, mu, r); rstd[0] = __shfl_sync(~0u, rs, r);
        nb[1] = __shfl_sync(~0u, mu, r + 8); rstd[1] = __shfl_sync(~0u, rs, r + 8);
      }
      PROF_AT(tid == 0, 9);
#pragma unroll
      for (int ch = 0; ch < 2; ch++) {
        uint32_t lo[8], hi[8];
#pragma unroll
        for (int t = 0; t < 8; t++) {
          const int n = ch * 8 + t;
          lo[t] = pack2((acc[4 * n] * rstd[0] + nb[0]) * cb[n].x + sb[n].x, (acc[4 * n + 1] * rstd[0] + nb[0]) * cb[n].y + sb[n].y);
          hi[t] = pack2((acc[4 * n + 2] * rstd[1] + nb[1]) * cb[n].x + sb[n].x, (acc[4 * n + 3] * rstd[1] + nb[1]) * cb[n].y + sb[n].y);
        }
        stage_slab(stg + ch * 16384 + cw * 8192, warp, lane, lo, hi);
        stage_done(bars + 8 * (B_STGF + ch), lane);
      }
      wg_bar(cw);
      PROF_AT(tid == 0, 10);
    }

    uint32_t pg[32], pu[32];
    {
      RING_IDS();
      LANE_IDS();
      Ring g{bars + 8 * B_FG, rbars + 8 * B_EG, 0, 0u, releaser TR(48)};
      float acc[128];
      {
        uint32_t prev = 0;
        uint4* x1p = p.x1 + (size_t)(rb * 128 + (warp * 16 + (lane >> 4)) * 2 + cw) * 128 + j * 16 + (lane & 15);
#pragma unroll 1
        for (int kb = 0; kb < 16; kb++) {
          kblock<256, 4, 49152>(acc, g, a_base + (kb < 2 ? STG_OFF + kb * 16384 : g.s * 49152), kb == 0, prev);
          if (kb == 5) {
#pragma unroll
            for (int q = 0; q < 4; q++) x1p[q * 512] = make_uint4(xl[4 * q], xl[4 * q + 1], xl[4 * q + 2], xl[4 * q + 3]);
          }
          if (kb == 8) {
#pragma unroll
            for (int q = 0; q < 4; q++) x1p[(4 + q) * 512] = make_uint4(xh[4 * q], xh[4 * q + 1], xh[4 * q + 2], xh[4 * q + 3]);
          }
        }
        tile_end(acc, prev);
      }
      PROF_AT(tid == 0, 36);
#pragma unroll 1
      for (int t = 1; t < 3; t++) {
#pragma unroll
        for (int q = 0; q < 32; q++) {
          pg[q] = pack2(acc[2 * q], acc[2 * q + 1]);
          pu[q] = pack2(acc[64 + 2 * q], acc[64 + 2 * q + 1]);
        }
        uint32_t prev = 0;
#pragma unroll 1
        for (int blk = 0; blk < 4; blk++) {
          g.s = 0;
#pragma unroll
          for (int i = 0; i < 4; i++) {
            kblock<256, 4, 49152>(acc, g, a_base + i * 49152, blk == 0 && i == 0, prev);
            if ((blk & 1) == 0 && i == 0) mbar_wait(bars + 8 * (B_STGE + (blk >> 1)), t & 1);
            stmatrix2(slab + (blk >> 1) * 16384 + (((srow & 7) ^ ((blk & 1) * 4 + i)) << 4), swiglu2(pg[2 * i], pu[2 * i]), swiglu2(pg[2 * i + 1], pu[2 * i + 1]));
          }
#pragma unroll
          for (int q = 0; q < 24; q++) { pg[q] = pg[q + 8]; pu[q] = pu[q + 8]; }
          if (blk & 1) stage_done(bars + 8 * (B_STGF + (blk >> 1)), lane);
        }
        tile_end(acc, prev);
        PROF_AT(tid == 0, 36 + t);
      }
#pragma unroll
      for (int q = 0; q < 32; q++) {
        pg[q] = pack2(acc[2 * q], acc[2 * q + 1]);
        pu[q] = pack2(acc[64 + 2 * q], acc[64 + 2 * q + 1]);
      }
      PROF_AT(tid == 0, 11);
    }

    {
      RING_IDS();
      LANE_IDS();
      Ring g{bars + 8 * B_FD, rbars + 8 * B_ED, 0, 0u, releaser TR(96)};
      float acc[64];
      uint32_t prev = 0;
#pragma unroll 1
      for (int blk = 0; blk < 6; blk++) {
#pragma unroll
        for (int i = 0; i < 8; i++) {
          kblock<128, 6, 32768>(acc, g, a_base + g.s * 32768, (blk & ~2) == 0 && i == 0, prev);
          if ((blk & 1) == 0 && i == 0) mbar_wait(bars + 8 * (B_STGE + ((blk >> 1) & 1)), blk < 4);
          stmatrix1(slab + ((blk >> 1) & 1) * 16384 + (i & 1) * 1024 + (((srow & 7) ^ ((blk & 1) * 4 + (i >> 1))) << 4), swiglu2(pg[i], pu[i]));
        }
#pragma unroll
        for (int q = 0; q < 24; q++) { pg[q] = pg[q + 8]; pu[q] = pu[q + 8]; }
        if (blk & 1) stage_done(bars + 8 * (B_STGF + ((blk >> 1) & 1)), lane);
        if (blk == 1) {
          tile_end(acc, prev);
          PROF_AT(tid == 0, 39);
#pragma unroll
          for (int q = 0; q < 16; q++) {
            pg[16 + q] = pack2(acc[2 * q], acc[2 * q + 1]);
            pu[16 + q] = pack2(acc[32 + 2 * q], acc[32 + 2 * q + 1]);
          }
          PROF_AT(tid == 0, 12);
        }
      }
      uint4 x1[8];
      const int fl = fresh_tid() & 31;
      const uint4* x1p = p.x1 + (size_t)(rb * 128 + (warp * 16 + (fl >> 4)) * 2 + cw) * 128 + j * 16 + (fl & 15);
#pragma unroll
      for (int q = 0; q < 2; q++) {
#pragma unroll
        for (int e = 0; e < 4; e++) x1[4 * q + e] = ll_peek(x1p + (4 * q + e) * 512);
#pragma unroll 1
        for (int kb = 0; kb < 12; kb++) {
          if (TAIL && q == 1 && kb == 6) g.releaser = false;
          kblock<128, 6, 32768>(acc, g, a_base + g.s * 32768, false, prev);
        }
      }
      mbar_wait(bars + 8 * (B_MODB + 1), 0);
      mbar_wait(bars + 8 * B_STGE, 1);
      mbar_wait(bars + 8 * (B_STGE + 1), 0);
      float2 gbv[16];
#pragma unroll
      for (int n = 0; n < 16; n++) gbv[n] = lds64f(sm + MODB_OFF + (384 + 8 * n + 2 * c) * 4);
      tile_end(acc, prev);
      PROF_AT(tid == 0, 13);
#pragma unroll
      for (int ch = 0; ch < 2; ch++) {
        uint32_t lo[8], hi[8];
#pragma unroll
        for (int t = 0; t < 8; t++) {
          const int n = ch * 8 + t;
          const float2 gb = gbv[n];
          const uint4 a = x1[n >> 2], b = x1[4 + (n >> 2)];
          const uint32_t xl = (n & 3) == 0 ? a.x : (n & 3) == 1 ? a.y : (n & 3) == 2 ? a.z : a.w;
          const uint32_t xh = (n & 3) == 0 ? b.x : (n & 3) == 1 ? b.y : (n & 3) == 2 ? b.z : b.w;
          lo[t] = pack2(bf_lo(xl) + gb.x * acc[4 * n], bf_hi(xl) + gb.y * acc[4 * n + 1]);
          hi[t] = pack2(bf_lo(xh) + gb.x * acc[4 * n + 2], bf_hi(xh) + gb.y * acc[4 * n + 3]);
        }
        stage_slab(stg + ch * 16384 + cw * 8192, warp, lane, lo, hi);
        asm volatile("fence.proxy.async.shared::cta;" ::: "memory");
        __syncwarp();
        tma_store3(&p.out, stg + ch * 16384 + cw * 8192 + warp * 2048, j * 128 + ch * 64, rb * 64 + warp * 16, cw);
      }
      asm volatile("cp.async.bulk.commit_group;" ::: "memory");
      if (lane == 0) mbar_arrive(bars + 8 * B_STGF);
      asm volatile("cp.async.bulk.wait_group.read 0;" ::: "memory");
      PROF_AT(tid == 0, 14);
    }
    if (blockIdx.x == 0 && threadIdx.x == 128) asm volatile("st.relaxed.gpu.global.u32 [%0], %1;" ::"l"(p.epoch), "r"(tag) : "memory");
    if (!TAIL) {
      __syncwarp();
      cluster_arrive_relaxed();
      cluster_wait();
    }
  }
}

typedef CUresult (*EncodeFn)(CUtensorMap*, CUtensorMapDataType, cuuint32_t, void*, const cuuint64_t*, const cuuint64_t*,
                             const cuuint32_t*, const cuuint32_t*, CUtensorMapInterleave, CUtensorMapSwizzle,
                             CUtensorMapL2promotion, CUtensorMapFloatOOBfill);

void encode2d(EncodeFn fn, CUtensorMap* m, const void* ptr, uint64_t cols, uint64_t rows, uint32_t box_rows) {
  cuuint64_t dims[2] = {cols, rows};
  cuuint64_t strides[1] = {cols * 2};
  cuuint32_t box[2] = {64, box_rows};
  cuuint32_t es[2] = {1, 1};
  fn(m, CU_TENSOR_MAP_DATA_TYPE_BFLOAT16, 2, (void*)ptr, dims, strides, box, es, CU_TENSOR_MAP_INTERLEAVE_NONE,
     CU_TENSOR_MAP_SWIZZLE_128B, CU_TENSOR_MAP_L2_PROMOTION_L2_128B, CU_TENSOR_MAP_FLOAT_OOB_FILL_NONE);
}

}

extern "C" void kernel_launch(void* const* d_in, const int* in_sizes, int n_in, void* d_out, int out_size) {
  (void)in_sizes; (void)n_in; (void)out_size;
  void* fp = nullptr;
  cudaDriverEntryPointQueryResult qr;
  cudaGetDriverEntryPoint("cuTensorMapEncodeTiled", &fp, cudaEnableDefault, &qr);
  EncodeFn fn = (EncodeFn)fp;
  void *ph, *po, *ph2, *pact;
  cudaGetSymbolAddress(&ph, g_h);
  cudaGetSymbolAddress(&po, g_o);
  ph2 = ph;
  cudaGetSymbolAddress(&pact, g_act);
  Params p;
  encode2d(fn, &p.h, ph, DM, SEQ, 128);
  encode2d(fn, &p.o_ld, po, DM, SEQ, 128);
  encode2d(fn, &p.h2, ph2, DM, SEQ, 128);
  encode2d(fn, &p.act, pact, FF, SEQ, 128);
  encode2d(fn, &p.act_st, pact, FF, SEQ, 32);
  encode2d(fn, &p.wm, d_in[8], 6 * DM, DM, 64);
  encode2d(fn, &p.o_st, po, DM, SEQ, 32);
  encode2d(fn, &p.wqkv, d_in[1], 3 * DM, DM, 64);
  encode2d(fn, &p.wqkv32, d_in[1], 3 * DM, DM, 32);
  encode2d(fn, &p.wo, d_in[2], DM, DM, 64);
  encode2d(fn, &p.wg, d_in[4], FF, DM, 64);
  encode2d(fn, &p.wu, d_in[5], FF, DM, 64);
  encode2d(fn, &p.wd, d_in[6], DM, FF, 64);
  {
    cuuint64_t dims[3] = {DM, SEQ / 2, 2};
    cuuint64_t strides[2] = {DM * 4, DM * 2};
    cuuint32_t box[3] = {64, 16, 1};
    cuuint32_t es[3] = {1, 1, 1};
    fn(&p.out, CU_TENSOR_MAP_DATA_TYPE_BFLOAT16, 3, d_out, dims, strides, box, es, CU_TENSOR_MAP_INTERLEAVE_NONE,
       CU_TENSOR_MAP_SWIZZLE_128B, CU_TENSOR_MAP_L2_PROMOTION_L2_128B, CU_TENSOR_MAP_FLOAT_OOB_FILL_NONE);
  }
  p.x = (const bf16*)d_in[0];
  p.c = (const bf16*)d_in[7];
  p.wmod = (const bf16*)d_in[8];
  for (int cl = 0; cl < 64; cl++) {
    const int grp = cl < 4 ? 0 : (cl < 36 ? (cl - 4) & 7 : 1 + (cl - 36) % 7);
    const int j = cl < 4 ? 4 + cl : (cl < 36 ? (cl - 4) >> 3 : 4 + (cl - 36) / 7);
    p.slot[cl] = (uint8_t)(grp * 8 + j);
  }
  void* q;
  p.x1 = (uint4*)d_out;
  cudaGetSymbolAddress(&q, g_modll); p.modll = (uint4*)q;
  cudaGetSymbolAddress(&q, g_halo); p.halo = (uint4*)q;
  cudaGetSymbolAddress(&q, g_stats); p.stats1 = (uint4*)q; p.stats2 = p.stats1 + SEQ * 8;
  cudaGetSymbolAddress(&q, g_cnt); p.cnt = (unsigned*)q;
  cudaGetSymbolAddress(&q, g_epoch); p.epoch = (unsigned*)q;

  cudaFuncSetAttribute(fused_kernel, cudaFuncAttributeMaxDynamicSharedMemorySize, SMEM_BYTES);
  cudaLaunchConfig_t cfg = {};
  cfg.gridDim = dim3(NCTA + 4);
  cfg.blockDim = dim3(384);
  cfg.dynamicSmemBytes = SMEM_BYTES;
  cfg.stream = cudaStreamPerThread;
  cudaLaunchAttribute at[1];
  at[0].id = cudaLaunchAttributeClusterDimension;
  at[0].val.clusterDim.x = 2; at[0].val.clusterDim.y = 1; at[0].val.clusterDim.z = 1;
  cfg.attrs = at;
  cfg.numAttrs = 1;
  cudaLaunchKernelEx(&cfg, fused_kernel, p);
}
```

```cpp
#include <cuda_runtime.h>
#include <cuda_bf16.h>
#include <cuda.h>
#include <stdint.h>

typedef __nv_bfloat16 bf16;

#define MAPPING 2

#define ALIGN 0

#define PF 0

#define EF 1

#define ALIGNE 3

#define CW 1

#define PAUSE 200

#define WMD 2

#define WMDELAY 2000

#define WMPACE 0

#define NPRE0 4

#define NPRE1 1
#define GATE 0

#define WFIRST 1

#define BDELAY 1500

#define ALIAS 1

#define PB1 0
#define PB2 0

#define LN2D 0

#define PIPEPOLL 0

#define TAIL 1

#define EAGER1 1

#define X1A 5
#define X1B 8

__device__ __forceinline__ void wgmma_ss_n128(float (&d)[64], uint32_t da, uint32_t db, int scale_d) {
  asm volatile("{\n.reg .pred p;\n.reg .b64 da, db;\nsetp.ne.b32 p, %66, 0;\n"
    "mov.b64 da, {%64, 0x40000040};\nmov.b64 db, {%65, 0x40000040};\n"
    "wgmma.mma_async.sync.aligned.m64n128k16.f32.bf16.bf16 "
    "{%0, %1, %2, %3, %4, %5, %6, %7, %8, %9, %10, %11, %12, %13, %14, %15, "
    "%16, %17, %18, %19, %20, %21, %22, %23, %24, %25, %26, %27, %28, %29, %30, %31, "
    "%32, %33, %34, %35, %36, %37, %38, %39, %40, %41, %42, %43, %44, %45, %46, %47, "
    "%48, %49, %50, %51, %52, %53, %54, %55, %56, %57, %58, %59, %60, %61, %62, %63}, "
    "da, db, p, 1, 1, 0, 1;\n}\n"
    : "+f"(d[0]), "+f"(d[1]), "+f"(d[2]), "+f"(d[3]), "+f"(d[4]), "+f"(d[5]), "+f"(d[6]), "+f"(d[7]),
      "+f"(d[8]), "+f"(d[9]), "+f"(d[10]), "+f"(d[11]), "+f"(d[12]), "+f"(d[13]), "+f"(d[14]), "+f"(d[15]),
      "+f"(d[16]), "+f"(d[17]), "+f"(d[18]), "+f"(d[19]), "+f"(d[20]), "+f"(d[21]), "+f"(d[22]), "+f"(d[23]),
      "+f"(d[24]), "+f"(d[25]), "+f"(d[26]), "+f"(d[27]), "+f"(d[28]), "+f"(d[29]), "+f"(d[30]), "+f"(d[31]),
      "+f"(d[32]), "+f"(d[33]), "+f"(d[34]), "+f"(d[35]), "+f"(d[36]), "+f"(d[37]), "+f"(d[38]), "+f"(d[39]),
      "+f"(d[40]), "+f"(d[41]), "+f"(d[42]), "+f"(d[43]), "+f"(d[44]), "+f"(d[45]), "+f"(d[46]), "+f"(d[47]),
      "+f"(d[48]), "+f"(d[49]), "+f"(d[50]), "+f"(d[51]), "+f"(d[52]), "+f"(d[53]), "+f"(d[54]), "+f"(d[55]),
      "+f"(d[56]), "+f"(d[57]), "+f"(d[58]), "+f"(d[59]), "+f"(d[60]), "+f"(d[61]), "+f"(d[62]), "+f"(d[63])
    : "r"(da), "r"(db), "r"(scale_d));
}

__device__ __forceinline__ void wgmma_ss_n192(float (&d)[96], uint32_t da, uint32_t db, int scale_d) {
  asm volatile("{\n.reg .pred p;\n.reg .b64 da, db;\nsetp.ne.b32 p, %98, 0;\n"
    "mov.b64 da, {%96, 0x40000040};\nmov.b64 db, {%97, 0x40000040};\n"
    "wgmma.mma_async.sync.aligned.m64n192k16.f32.bf16.bf16 "
    "{%0, %1, %2, %3, %4, %5, %6, %7, %8, %9, %10, %11, %12, %13, %14, %15, "
    "%16, %17, %18, %19, %20, %21, %22, %23, %24, %25, %26, %27, %28, %29, %30, %31, "
    "%32, %33, %34, %35, %36, %37, %38, %39, %40, %41, %42, %43, %44, %45, %46, %47, "
    "%48, %49, %50, %51, %52, %53, %54, %55, %56, %57, %58, %59, %60, %61, %62, %63, "
    "%64, %65, %66, %67, %68, %69, %70, %71, %72, %73, %74, %75, %76, %77, %78, %79, "
    "%80, %81, %82, %83, %84, %85, %86, %87, %88, %89, %90, %91, %92, %93, %94, %95}, "
    "da, db, p, 1, 1, 0, 1;\n}\n"
    : "+f"(d[0]), "+f"(d[1]), "+f"(d[2]), "+f"(d[3]), "+f"(d[4]), "+f"(d[5]), "+f"(d[6]), "+f"(d[7]),
      "+f"(d[8]), "+f"(d[9]), "+f"(d[10]), "+f"(d[11]), "+f"(d[12]), "+f"(d[13]), "+f"(d[14]), "+f"(d[15]),
      "+f"(d[16]), "+f"(d[17]), "+f"(d[18]), "+f"(d[19]), "+f"(d[20]), "+f"(d[21]), "+f"(d[22]), "+f"(d[23]),
      "+f"(d[24]), "+f"(d[25]), "+f"(d[26]), "+f"(d[27]), "+f"(d[28]), "+f"(d[29]), "+f"(d[30]), "+f"(d[31]),
      "+f"(d[32]), "+f"(d[33]), "+f"(d[34]), "+f"(d[35]), "+f"(d[36]), "+f"(d[37]), "+f"(d[38]), "+f"(d[39]),
      "+f"(d[40]), "+f"(d[41]), "+f"(d[42]), "+f"(d[43]), "+f"(d[44]), "+f"(d[45]), "+f"(d[46]), "+f"(d[47]),
      "+f"(d[48]), "+f"(d[49]), "+f"(d[50]), "+f"(d[51]), "+f"(d[52]), "+f"(d[53]), "+f"(d[54]), "+f"(d[55]),
      "+f"(d[56]), "+f"(d[57]), "+f"(d[58]), "+f"(d[59]), "+f"(d[60]), "+f"(d[61]), "+f"(d[62]), "+f"(d[63]),
      "+f"(d[64]), "+f"(d[65]), "+f"(d[66]), "+f"(d[67]), "+f"(d[68]), "+f"(d[69]), "+f"(d[70]), "+f"(d[71]),
      "+f"(d[72]), "+f"(d[73]), "+f"(d[74]), "+f"(d[75]), "+f"(d[76]), "+f"(d[77]), "+f"(d[78]), "+f"(d[79]),
      "+f"(d[80]), "+f"(d[81]), "+f"(d[82]), "+f"(d[83]), "+f"(d[84]), "+f"(d[85]), "+f"(d[86]), "+f"(d[87]),
      "+f"(d[88]), "+f"(d[89]), "+f"(d[90]), "+f"(d[91]), "+f"(d[92]), "+f"(d[93]), "+f"(d[94]), "+f"(d[95])
    : "r"(da), "r"(db), "r"(scale_d));
}

__device__ __forceinline__ void wgmma_ss_n256(float (&d)[128], uint32_t da, uint32_t db, int scale_d) {
  asm volatile("{\n.reg .pred p;\n.reg .b64 da, db;\nsetp.ne.b32 p, %130, 0;\n"
    "mov.b64 da, {%128, 0x40000040};\nmov.b64 db, {%129, 0x40000040};\n"
    "wgmma.mma_async.sync.aligned.m64n256k16.f32.bf16.bf16 "
    "{%0, %1, %2, %3, %4, %5, %6, %7, %8, %9, %10, %11, %12, %13, %14, %15, "
    "%16, %17, %18, %19, %20, %21, %22, %23, %24, %25, %26, %27, %28, %29, %30, %31, "
    "%32, %33, %34, %35, %36, %37, %38, %39, %40, %41, %42, %43, %44, %45, %46, %47, "
    "%48, %49, %50, %51, %52, %53, %54, %55, %56, %57, %58, %59, %60, %61, %62, %63, "
    "%64, %65, %66, %67, %68, %69, %70, %71, %72, %73, %74, %75, %76, %77, %78, %79, "
    "%80, %81, %82, %83, %84, %85, %86, %87, %88, %89, %90, %91, %92, %93, %94, %95, "
    "%96, %97, %98, %99, %100, %101, %102, %103, %104, %105, %106, %107, %108, %109, %110, %111, "
    "%112, %113, %114, %115, %116, %117, %118, %119, %120, %121, %122, %123, %124, %125, %126, %127}, "
    "da, db, p, 1, 1, 0, 1;\n}\n"
    : "+f"(d[0]), "+f"(d[1]), "+f"(d[2]), "+f"(d[3]), "+f"(d[4]), "+f"(d[5]), "+f"(d[6]), "+f"(d[7]),
      "+f"(d[8]), "+f"(d[9]), "+f"(d[10]), "+f"(d[11]), "+f"(d[12]), "+f"(d[13]), "+f"(d[14]), "+f"(d[15]),
      "+f"(d[16]), "+f"(d[17]), "+f"(d[18]), "+f"(d[19]), "+f"(d[20]), "+f"(d[21]), "+f"(d[22]), "+f"(d[23]),
      "+f"(d[24]), "+f"(d[25]), "+f"(d[26]), "+f"(d[27]), "+f"(d[28]), "+f"(d[29]), "+f"(d[30]), "+f"(d[31]),
      "+f"(d[32]), "+f"(d[33]), "+f"(d[34]), "+f"(d[35]), "+f"(d[36]), "+f"(d[37]), "+f"(d[38]), "+f"(d[39]),
      "+f"(d[40]), "+f"(d[41]), "+f"(d[42]), "+f"(d[43]), "+f"(d[44]), "+f"(d[45]), "+f"(d[46]), "+f"(d[47]),
      "+f"(d[48]), "+f"(d[49]), "+f"(d[50]), "+f"(d[51]), "+f"(d[52]), "+f"(d[53]), "+f"(d[54]), "+f"(d[55]),
      "+f"(d[56]), "+f"(d[57]), "+f"(d[58]), "+f"(d[59]), "+f"(d[60]), "+f"(d[61]), "+f"(d[62]), "+f"(d[63]),
      "+f"(d[64]), "+f"(d[65]), "+f"(d[66]), "+f"(d[67]), "+f"(d[68]), "+f"(d[69]), "+f"(d[70]), "+f"(d[71]),
      "+f"(d[72]), "+f"(d[73]), "+f"(d[74]), "+f"(d[75]), "+f"(d[76]), "+f"(d[77]), "+f"(d[78]), "+f"(d[79]),
      "+f"(d[80]), "+f"(d[81]), "+f"(d[82]), "+f"(d[83]), "+f"(d[84]), "+f"(d[85]), "+f"(d[86]), "+f"(d[87]),
      "+f"(d[88]), "+f"(d[89]), "+f"(d[90]), "+f"(d[91]), "+f"(d[92]), "+f"(d[93]), "+f"(d[94]), "+f"(d[95]),
      "+f"(d[96]), "+f"(d[97]), "+f"(d[98]), "+f"(d[99]), "+f"(d[100]), "+f"(d[101]), "+f"(d[102]), "+f"(d[103]),
      "+f"(d[104]), "+f"(d[105]), "+f"(d[106]), "+f"(d[107]), "+f"(d[108]), "+f"(d[109]), "+f"(d[110]), "+f"(d[111]),
      "+f"(d[112]), "+f"(d[113]), "+f"(d[114]), "+f"(d[115]), "+f"(d[116]), "+f"(d[117]), "+f"(d[118]), "+f"(d[119]),
      "+f"(d[120]), "+f"(d[121]), "+f"(d[122]), "+f"(d[123]), "+f"(d[124]), "+f"(d[125]), "+f"(d[126]), "+f"(d[127])
    : "r"(da), "r"(db), "r"(scale_d));
}

namespace {

constexpr int SEQ = 2048, DM = 1024, FF = 3584;
constexpr int NCTA = 128;

constexpr uint32_t STG_OFF = 196608;
constexpr uint32_t MISC_OFF = STG_OFF + 32768;
constexpr uint32_t SMEM_BYTES = MISC_OFF + 3072;
constexpr uint32_t RED_OFF = 2 * 49152;
constexpr uint32_t MODB_OFF = MISC_OFF + 512;

enum { B_FQ = 0, B_EQ = 4, B_FW = 8, B_EW = 14, B_FG = 20, B_EG = 24, B_FD = 28, B_ED = 34,
       B_STGF = 40, B_MODB = 42, B_MODA = 45, B_RDY = 48, B_STGE = 56, B_COUNT = 58 };
enum { C_H = 0, C_O = 1, C_H2 = 3, C_ACT = 4, C_HA = 8, C_H2A = 9 };

struct Params {
  CUtensorMap h, o_ld, o_st, h2, act, out, wqkv, wqkv32, wo, wg, wu, wd, act_st, wm;
  const bf16* x;
  const bf16* c;
  const bf16* wmod;
  uint4* x1;
  uint4* modll;
  uint4* halo;
  uint4* stats1;
  uint4* stats2;
  unsigned* cnt;
  unsigned* epoch;
  uint8_t slot[64];
};

__device__ bf16 g_h[SEQ * DM];
__device__ bf16 g_o[SEQ * DM];
__device__ bf16 g_h2[SEQ * DM];
__device__ bf16 g_act[SEQ * FF];
__device__ uint4 g_x1[NCTA * 8 * 256];
__device__ uint4 g_modll[3072 / 2];
__device__ uint4 g_halo[16 * 8 * 2 * 2 * 8 * 32];
__device__ uint4 g_stats[2 * SEQ * 8];
__device__ unsigned g_cnt[16 * 32];
__device__ uint4 g_epoch;
#define TR(off)

__device__ __forceinline__ uint32_t smem_u32(const void* p) { return (uint32_t)__cvta_generic_to_shared(p); }
__device__ __forceinline__ void mbar_init(uint32_t bar, uint32_t count) {
  asm volatile("mbarrier.init.shared::cta.b64 [%0], %1;" ::"r"(bar), "r"(count));
}
__device__ __forceinline__ void mbar_expect_tx(uint32_t bar, uint32_t bytes) {
  asm volatile("mbarrier.arrive.expect_tx.shared::cta.b64 _, [%0], %1;" ::"r"(bar), "r"(bytes) : "memory");
}
__device__ __forceinline__ void mbar_arrive(uint32_t bar) {
  asm volatile("mbarrier.arrive.shared::cta.b64 _, [%0];" ::"r"(bar) : "memory");
}
__device__ __forceinline__ void mbar_arrive_cluster(uint32_t cluster_addr) {
  asm volatile("mbarrier.arrive.shared::cluster.b64 _, [%0];" ::"r"(cluster_addr) : "memory");
}
__device__ __forceinline__ uint32_t mapa(uint32_t addr, uint32_t cta) {
  uint32_t r;
  asm volatile("mapa.shared::cluster.u32 %0, %1, %2;" : "=r"(r) : "r"(addr), "r"(cta));
  return r;
}
__device__ __forceinline__ void mbar_wait(uint32_t bar, uint32_t parity) {
  asm volatile(
      "{\n.reg .pred p;\n"
      "WAIT_%=:\n"
      "mbarrier.try_wait.parity.shared::cta.b64 p, [%0], %1;\n"
      "@!p bra WAIT_%=;\n}\n" ::"r"(bar), "r"(parity) : "memory");
}
__device__ __forceinline__ void mbar_wait_watchdog(uint32_t bar, uint32_t parity) {
  asm volatile(
      "{\n.reg .pred p;\n.reg .u64 t0, t1;\nmov.u64 t0, %%globaltimer;\n"
      "WAIT_%=:\n"
      "mbarrier.try_wait.parity.shared::cta.b64 p, [%0], %1;\n"
      "@p bra DONE_%=;\n"
      "mov.u64 t1, %%globaltimer;\n"
      "sub.u64 t1, t1, t0;\n"
      "setp.lt.u64 p, t1, 2000000000;\n"
      "@p bra WAIT_%=;\n"
      "trap;\n"
      "DONE_%=:\n}\n" ::"r"(bar), "r"(parity) : "memory");
}
__device__ __forceinline__ void cnt_wait(const unsigned* p, unsigned target) {
  asm volatile(
      "{\n.reg .pred p;\n.reg .u32 v;\n.reg .s32 d;\n"
      "WAIT_%=:\n"
      "ld.relaxed.gpu.global.u32 v, [%0];\n"
      "sub.s32 d, v, %1;\n"
      "setp.lt.s32 p, d, 0;\n"
      "@p bra WAIT_%=;\n"
      "fence.proxy.async.global;\n"
      "}\n" ::"l"(p), "r"(target) : "memory");
}
__device__ __forceinline__ void cnt_wait_lazy(const unsigned* p, unsigned target) {
  asm volatile(
      "{\n.reg .pred p;\n.reg .u32 v;\n.reg .s32 d;\n"
      "WAIT_%=:\n"
      "nanosleep.u32 400;\n"
      "ld.relaxed.gpu.global.u32 v, [%0];\n"
      "sub.s32 d, v, %1;\n"
      "setp.lt.s32 p, d, 0;\n"
      "@p bra WAIT_%=;\n"
      "fence.proxy.async.global;\n"
      "}\n" ::"l"(p), "r"(target) : "memory");
}
__device__ __forceinline__ void cnt_signal(unsigned* p) {
  asm volatile("{\n.reg .pred p;\nelect.sync _|p, 0xffffffff;\n@p red.relaxed.gpu.global.add.u32 [%0], 1;\n}\n" ::"l"(p) : "memory");
}
__device__ __forceinline__ void ll_store(uint4* p, uint32_t a, uint32_t b, uint32_t tag) {
  asm volatile("st.relaxed.gpu.global.v2.b64 [%0], {%1, %2};" ::"l"(p), "l"((uint64_t)a | ((uint64_t)tag << 32)),
               "l"((uint64_t)b | ((uint64_t)tag << 32)) : "memory");
}
__device__ __forceinline__ uint4 ll_peek(const uint4* p) {
  uint4 v;
  asm volatile("ld.relaxed.gpu.global.v4.u32 {%0, %1, %2, %3}, [%4];" : "=r"(v.x), "=r"(v.y), "=r"(v.z), "=r"(v.w) : "l"(p) : "memory");
  return v;
}
template <int N, int SLEEP = 0, class F>
__device__ __forceinline__ void ll_poll(F addr, uint32_t tag, uint32_t (&out)[2 * N]) {
  for (;;) {
    uint4 v[N];
#pragma unroll
    for (int i = 0; i < N; i++) v[i] = ll_peek(addr(i));
    uint32_t bad = 0;
#pragma unroll
    for (int i = 0; i < N; i++) {
      bad |= (v[i].y ^ tag) | (v[i].w ^ tag);
      out[2 * i] = v[i].x;
      out[2 * i + 1] = v[i].z;
    }
    if (__all_sync(~0u, bad == 0)) break;
    if (SLEEP) __nanosleep(SLEEP);
  }
}
constexpr uint64_t POLICY_EVICT_FIRST = 0x12F0000000000000ull;
__device__ __forceinline__ void expect_tx_elect(uint32_t bar, uint32_t bytes) {
  asm volatile("{\n.reg .pred p;\nelect.sync _|p, 0xffffffff;\n@p mbarrier.arrive.expect_tx.shared::cta.b64 _, [%0], %1;\n}\n" ::"r"(bar), "r"(bytes) : "memory");
}
__device__ __forceinline__ void arrive_elect(uint32_t bar) {
  asm volatile("{\n.reg .pred p;\nelect.sync _|p, 0xffffffff;\n@p mbarrier.arrive.shared::cta.b64 _, [%0];\n}\n" ::"r"(bar) : "memory");
}
__device__ __forceinline__ void tma_load(uint32_t dst, const CUtensorMap* m, uint32_t bar, int c0, int c1) {
  asm volatile("{\n.reg .pred p;\nelect.sync _|p, 0xffffffff;\n"
               "@p cp.async.bulk.tensor.2d.shared::cluster.global.mbarrier::complete_tx::bytes [%0], [%1, {%3, %4}], [%2];\n}\n"
               ::"r"(dst), "l"(m), "r"(bar), "r"(c0), "r"(c1) : "memory");
}
__device__ __forceinline__ void tma_load_mc(uint32_t dst, const CUtensorMap* m, uint32_t bar, int c0, int c1) {
  asm volatile("{\n.reg .pred p;\nelect.sync _|p, 0xffffffff;\n"
               "@p cp.async.bulk.tensor.2d.shared::cluster.global.mbarrier::complete_tx::bytes.multicast::cluster.L2::cache_hint [%0], [%1, {%3, %4}], [%2], %5, %6;\n}\n"
               ::"r"(dst), "l"(m), "r"(bar), "r"(c0), "r"(c1), "h"((uint16_t)3), "l"(POLICY_EVICT_FIRST) : "memory");
}
__device__ __forceinline__ void tma_load_ef(uint32_t dst, const CUtensorMap* m, uint32_t bar, int c0, int c1) {
  asm volatile("{\n.reg .pred p;\nelect.sync _|p, 0xffffffff;\n"
               "@p cp.async.bulk.tensor.2d.shared::cluster.global.mbarrier::complete_tx::bytes.L2::cache_hint [%0], [%1, {%3, %4}], [%2], %5;\n}\n"
               ::"r"(dst), "l"(m), "r"(bar), "r"(c0), "r"(c1), "l"(POLICY_EVICT_FIRST) : "memory");
}
__device__ __forceinline__ void tma_store2(const CUtensorMap* m, uint32_t src, int c0, int c1) {
  asm volatile("{\n.reg .pred p;\nelect.sync _|p, 0xffffffff;\n"
               "@p cp.async.bulk.tensor.2d.global.shared::cta.bulk_group [%0, {%2, %3}], [%1];\n}\n"
               ::"l"(m), "r"(src), "r"(c0), "r"(c1) : "memory");
}
__device__ __forceinline__ void tma_store3(const CUtensorMap* m, uint32_t src, int c0, int c1, int c2) {
  asm volatile("{\n.reg .pred p;\nelect.sync _|p, 0xffffffff;\n"
               "@p cp.async.bulk.tensor.3d.global.shared::cta.bulk_group [%0, {%2, %3, %4}], [%1];\n}\n"
               ::"l"(m), "r"(src), "r"(c0), "r"(c1), "r"(c2) : "memory");
}
__device__ __forceinline__ void store_pause(bool sleep) {
  asm volatile("cp.async.bulk.commit_group;" ::: "memory");
  asm volatile("cp.async.bulk.wait_group.read 0;" ::: "memory");
  if (sleep) __nanosleep(PAUSE);
}
__device__ __forceinline__ void l2_prefetch_tile(const CUtensorMap* m, int c0, int c1) {
  asm volatile("{\n.reg .pred p;\nelect.sync _|p, 0xffffffff;\n@p cp.async.bulk.prefetch.tensor.2d.L2.global.L2::cache_hint [%0, {%1, %2}], %3;\n}\n"
               ::"l"(m), "r"(c0), "r"(c1), "l"(POLICY_EVICT_FIRST) : "memory");
}
__device__ __forceinline__ void prefetch_map(const CUtensorMap* m) {
  asm volatile("prefetch.tensormap [%0];" ::"l"(m) : "memory");
}
__device__ __forceinline__ void wg_fence() { asm volatile("wgmma.fence.sync.aligned;" ::: "memory"); }
__device__ __forceinline__ void wg_commit() { asm volatile("wgmma.commit_group.sync.aligned;" ::: "memory"); }
template <int N>
__device__ __forceinline__ void wg_wait() { asm volatile("wgmma.wait_group.sync.aligned %0;" ::"n"(N) : "memory"); }
__device__ __forceinline__ void bar_sync(int id, int n) { asm volatile("bar.sync %0, %1;" ::"r"(id), "r"(n) : "memory"); }
__device__ __forceinline__ void wg_bar(int cw) {
  asm volatile("{\n.reg .pred p;\nsetp.ne.s32 p, %0, 0;\n@p bar.sync 3, 128;\n@!p bar.sync 2, 128;\n}\n" ::"r"(cw) : "memory");
}
__device__ __forceinline__ void cluster_arrive() { asm volatile("barrier.cluster.arrive.release.aligned;" ::: "memory"); }
__device__ __forceinline__ void cluster_arrive_relaxed() { asm volatile("barrier.cluster.arrive.relaxed.aligned;" ::: "memory"); }
__device__ __forceinline__ void cluster_wait() { asm volatile("barrier.cluster.wait.acquire.aligned;" ::: "memory"); }
__device__ __forceinline__ uint32_t load_epoch(const unsigned* p) {
  uint32_t e;
  asm volatile("ld.relaxed.gpu.global.u32 %0, [%1];" : "=r"(e) : "l"(p) : "memory");
  return e;
}
__device__ __forceinline__ uint32_t pack2(float lo, float hi) {
  uint32_t r;
  asm("cvt.rn.bf16x2.f32 %0, %1, %2;" : "=r"(r) : "f"(hi), "f"(lo));
  return r;
}
__device__ __forceinline__ float bf_lo(uint32_t v) { return __uint_as_float(v << 16); }
__device__ __forceinline__ float bf_hi(uint32_t v) { return __uint_as_float(v & 0xffff0000u); }
__device__ __forceinline__ float bf_round(float v) { return __bfloat162float(__float2bfloat16_rn(v)); }
__device__ __forceinline__ float silu_f(float v) { return __fdividef(v, 1.0f + __expf(-v)); }
__device__ __forceinline__ uint4 ldg_nc(const void* p) {
  uint4 v;
  asm volatile("ld.global.nc.L1::no_allocate.v4.u32 {%0, %1, %2, %3}, [%4];" : "=r"(v.x), "=r"(v.y), "=r"(v.z), "=r"(v.w) : "l"(p));
  return v;
}
__device__ __forceinline__ uint4 ldg_stream(const void* p) {
  uint4 v;
  asm volatile("ld.global.nc.L1::no_allocate.L2::cache_hint.v4.u32 {%0, %1, %2, %3}, [%4], %5;" : "=r"(v.x), "=r"(v.y), "=r"(v.z), "=r"(v.w) : "l"(p), "l"(POLICY_EVICT_FIRST));
  return v;
}
__device__ __forceinline__ uint32_t ldg32(const void* p) {
  uint32_t v;
  asm volatile("ld.global.nc.u32 %0, [%1];" : "=r"(v) : "l"(p));
  return v;
}
__device__ __forceinline__ void stmatrix4(uint32_t addr, uint32_t a, uint32_t b, uint32_t c, uint32_t d) {
  asm volatile("stmatrix.sync.aligned.m8n8.x4.shared.b16 [%0], {%1, %2, %3, %4};" ::"r"(addr), "r"(a), "r"(b), "r"(c), "r"(d) : "memory");
}
__device__ __forceinline__ void stmatrix2(uint32_t addr, uint32_t a, uint32_t b) {
  asm volatile("stmatrix.sync.aligned.m8n8.x2.shared.b16 [%0], {%1, %2};" ::"r"(addr), "r"(a), "r"(b) : "memory");
}
__device__ __forceinline__ void stmatrix1(uint32_t addr, uint32_t a) {
  asm volatile("stmatrix.sync.aligned.m8n8.x1.shared.b16 [%0], {%1};" ::"r"(addr), "r"(a) : "memory");
}
__device__ __forceinline__ uint32_t movmatrix(uint32_t a) {
  uint32_t d;
  asm("movmatrix.sync.aligned.m8n8.trans.b16 %0, %1;" : "=r"(d) : "r"(a));
  return d;
}
__device__ __forceinline__ void mma16816(float (&d)[4], uint32_t a0, uint32_t a1, uint32_t a2, uint32_t a3, uint32_t b0, uint32_t b1) {
  asm("mma.sync.aligned.m16n8k16.row.col.f32.bf16.bf16.f32 {%0, %1, %2, %3}, {%4, %5, %6, %7}, {%8, %9}, {%0, %1, %2, %3};"
               : "+f"(d[0]), "+f"(d[1]), "+f"(d[2]), "+f"(d[3]) : "r"(a0), "r"(a1), "r"(a2), "r"(a3), "r"(b0), "r"(b1));
}
__device__ __forceinline__ void mma1688(float (&d)[4], uint32_t a0, uint32_t a1, uint32_t b0) {
  asm("mma.sync.aligned.m16n8k8.row.col.f32.bf16.bf16.f32 {%0, %1, %2, %3}, {%4, %5}, {%6}, {%0, %1, %2, %3};"
               : "+f"(d[0]), "+f"(d[1]), "+f"(d[2]), "+f"(d[3]) : "r"(a0), "r"(a1), "r"(b0));
}
__device__ __forceinline__ void ldmatrix4t(uint32_t (&b)[4], uint32_t addr) {
  asm volatile("ldmatrix.sync.aligned.m8n8.x4.trans.shared.b16 {%0, %1, %2, %3}, [%4];" : "=r"(b[0]), "=r"(b[1]), "=r"(b[2]), "=r"(b[3]) : "r"(addr) : "memory");
}
__device__ __forceinline__ void ldmatrix4(uint32_t& a, uint32_t& b, uint32_t& c, uint32_t& d, uint32_t addr) {
  asm volatile("ldmatrix.sync.aligned.m8n8.x4.shared.b16 {%0, %1, %2, %3}, [%4];" : "=r"(a), "=r"(b), "=r"(c), "=r"(d) : "r"(addr) : "memory");
}
__device__ __forceinline__ void cp_async16(uint32_t dst, const void* src) {
  asm volatile("cp.async.cg.shared.global.L2::cache_hint [%0], [%1], 16, %2;" ::"r"(dst), "l"(src), "l"(POLICY_EVICT_FIRST) : "memory");
}
__device__ __forceinline__ uint32_t lds32(uint32_t addr) {
  uint32_t v;
  asm volatile("ld.shared.u32 %0, [%1];" : "=r"(v) : "r"(addr) : "memory");
  return v;
}
__device__ __forceinline__ void sts64f(uint32_t addr, float a, float b) {
  asm volatile("st.shared.v2.f32 [%0], {%1, %2};" ::"r"(addr), "f"(a), "f"(b) : "memory");
}
constexpr float QK_SCALE = 0.17677669529663687f;
__device__ __forceinline__ float softmax8(float& p0, float& p1) {
  float m = fmaxf(p0, p1);
  m = fmaxf(m, __shfl_xor_sync(~0u, m, 1));
  m = fmaxf(m, __shfl_xor_sync(~0u, m, 2));
  asm("ex2.approx.ftz.f32 %0, %1;" : "=f"(p0) : "f"((p0 - m) * 1.4426950408889634f));
  asm("ex2.approx.ftz.f32 %0, %1;" : "=f"(p1) : "f"((p1 - m) * 1.4426950408889634f));
  float s = p0 + p1;
  s += __shfl_xor_sync(~0u, s, 1);
  s += __shfl_xor_sync(~0u, s, 2);
  float r;
  asm("rcp.approx.ftz.f32 %0, %1;" : "=f"(r) : "f"(s));
  return r;
}
__device__ __forceinline__ void sts128(uint32_t addr, uint32_t a, uint32_t b, uint32_t c, uint32_t d) {
  asm volatile("st.shared.v4.u32 [%0], {%1, %2, %3, %4};" ::"r"(addr), "r"(a), "r"(b), "r"(c), "r"(d) : "memory");
}
__device__ __forceinline__ uint4 lds128(uint32_t addr) {
  uint4 v;
  asm volatile("ld.shared.v4.u32 {%0, %1, %2, %3}, [%4];" : "=r"(v.x), "=r"(v.y), "=r"(v.z), "=r"(v.w) : "r"(addr) : "memory");
  return v;
}
__device__ __forceinline__ float2 lds64f(uint32_t addr) {
  float2 v;
  asm volatile("ld.shared.v2.f32 {%0, %1}, [%2];" : "=f"(v.x), "=f"(v.y) : "r"(addr) : "memory");
  return v;
}
__device__ __forceinline__ void sts32f(uint32_t addr, float v) {
  asm volatile("st.shared.f32 [%0], %1;" ::"r"(addr), "f"(v) : "memory");
}
__device__ __forceinline__ float lds32f(uint32_t addr) {
  float v;
  asm volatile("ld.shared.f32 %0, [%1];" : "=f"(v) : "r"(addr) : "memory");
  return v;
}
#define PROF_AT(cond, slot) do {} while (0)

constexpr uint32_t SMEM_BASE = 1024;
constexpr uint32_t DESC_A = (1u << 16) | (SMEM_BASE >> 4);
constexpr uint32_t DESC_B = ((8192u >> 4) << 16) | ((SMEM_BASE + 16384) >> 4);

template <int BN> struct Wg;
template <> struct Wg<128> { static __device__ __forceinline__ void mma(float (&d)[64], uint32_t a, uint32_t b, int s) { wgmma_ss_n128(d, a, b, s); } };
template <> struct Wg<192> { static __device__ __forceinline__ void mma(float (&d)[96], uint32_t a, uint32_t b, int s) { wgmma_ss_n192(d, a, b, s); } };
template <> struct Wg<256> { static __device__ __forceinline__ void mma(float (&d)[128], uint32_t a, uint32_t b, int s) { wgmma_ss_n256(d, a, b, s); } };

struct Ring {
  uint32_t full0, rel0;
  int s;
  uint32_t ph;
  bool releaser;
};

template <int N>
__device__ __forceinline__ void fence_regs(float (&a)[N]) {
#pragma unroll
  for (int i = 0; i < N; i++) asm volatile("" : "+f"(a[i])::"memory");
}

template <int BN, int NST, uint32_t STAGE>
__device__ __forceinline__ void kblock(float (&acc)[BN / 2], Ring& g, uint32_t a_addr, bool zero, uint32_t& prev) {
  mbar_wait(g.full0 + 8 * g.s, g.ph);
  const uint32_t da = DESC_A + (a_addr >> 4);
  const uint32_t db = DESC_B + g.s * (STAGE >> 4);
  wg_fence();
#pragma unroll
  for (int k = 0; k < 4; k++) Wg<BN>::mma(acc, da + k * 2, db + k * 128, !(zero && k == 0));
  wg_commit();
  wg_wait<1>();
  if (prev != 0) mbar_arrive_cluster(prev);
  prev = g.releaser ? g.rel0 + 8 * g.s : 0u;
  if (++g.s == NST) { g.s = 0; g.ph ^= 1; }
}
template <int N>
__device__ __forceinline__ void tile_end(float (&acc)[N], uint32_t& prev) {
  wg_wait<0>();
  if (prev != 0) mbar_arrive_cluster(prev);
  prev = 0;
  fence_regs(acc);
}

__device__ __forceinline__ int other_kb(int q, int j) {
  const int ch = q >= 7, jj = q - 7 * ch;
  return 2 * (jj < j ? jj : jj + 1) + ch;
}
__device__ __forceinline__ int own_first(int it, int j) {
  return it >= 16 ? (it & 15) : (it < 2 ? 2 * j + it : other_kb(it - 2, j));
}
__device__ __forceinline__ int qkv_kb(int it, int j) {
  return it < 4 ? 2 * j + (it & 1) : other_kb(it < 18 ? it - 4 : it - 18, j);
}
__device__ __forceinline__ int wo_k(int it, int j) {
  return it < 8 ? it * 128 : (it == 8 ? j : (it - 9 < j ? it - 9 : it - 8)) * 128 + 64;
}
__device__ __forceinline__ int down_k(int it) {
  const int r = (it >> 4) - 1, idx = it & 15;
  return r < 0 ? idx * 64 : (r < 3 ? (idx >> 1) * 448 + r * 128 + (idx & 1) * 64 : idx * 448 + 384);
}
__device__ __forceinline__ void wait_p3_free(uint32_t empty3, int i) {
  mbar_wait(empty3 + 8 * ((i * 2) / 3), 1);
  mbar_wait(empty3 + 8 * ((i * 2 + 1) / 3), 1);
}
__device__ __forceinline__ void wait_p2_free(uint32_t empty2, int i) {
  const int w0 = (i * 3) / 2, w1 = (i * 3 + 2) / 2;
  mbar_wait(empty2 + 8 * w0, w0 < 4 ? 0 : 1);
  mbar_wait(empty2 + 8 * w1, w1 < 4 ? 0 : 1);
}

__device__ __forceinline__ void chan(float& m, float& q, float m2, float q2, float n) {
  const float d = m2 - m;
  m = 0.5f * (m + m2);
  q = q + q2 + d * d * (0.5f * n);
}

template <int N>
__device__ __forceinline__ void row_stats(const uint32_t (&ll)[N], float& mean, float& rstd) {
  float ma = __uint_as_float(ll[0]), qa = __uint_as_float(ll[1]), mb = __uint_as_float(ll[4]), qb = __uint_as_float(ll[5]);
  chan(ma, qa, __uint_as_float(ll[2]), __uint_as_float(ll[3]), 128.f);
  chan(mb, qb, __uint_as_float(ll[6]), __uint_as_float(ll[7]), 128.f);
  chan(ma, qa, mb, qb, 256.f);
  const float mo = __shfl_xor_sync(~0u, ma, 16), qo = __shfl_xor_sync(~0u, qa, 16);
  chan(ma, qa, mo, qo, 512.f);
  mean = ma;
  rstd = rsqrtf(qa * (1.0f / DM) + 1e-5f);
}

__device__ __forceinline__ void publish_stats(const uint32_t (&xl)[16], const uint32_t (&xh)[16], uint4* slot, int lane, uint32_t tag) {
  float ds[4] = {0.f, 0.f, 0.f, 0.f}, dl[4] = {0.f, 0.f, 0.f, 0.f}, dh[4] = {0.f, 0.f, 0.f, 0.f};
#pragma unroll
  for (int q = 0; q < 8; q++) {
    mma16816(ds, xl[2 * q], xh[2 * q], xl[2 * q + 1], xh[2 * q + 1], 0x3f803f80u, 0x3f803f80u);
    mma16816(dl, xl[2 * q], xh[2 * q], xl[2 * q + 1], xh[2 * q + 1], xl[2 * q], xl[2 * q + 1]);
    mma16816(dh, xl[2 * q], xh[2 * q], xl[2 * q + 1], xh[2 * q + 1], xh[2 * q], xh[2 * q + 1]);
  }
  const int r = lane >> 2;
  if ((lane & 3) == (r >> 1)) {
    const float ml = ds[0] * (1.0f / 128), mh = ds[2] * (1.0f / 128);
    const float ql = fmaxf(((r & 1) ? dl[1] : dl[0]) - ds[0] * ml, 0.f), qh = fmaxf(((r & 1) ? dh[3] : dh[2]) - ds[2] * mh, 0.f);
    ll_store(slot + r, __float_as_uint(ml), __float_as_uint(ql), tag);
    ll_store(slot + r + 8, __float_as_uint(mh), __float_as_uint(qh), tag);
  }
  __syncwarp();
}

__device__ __forceinline__ void stage_slab(uint32_t chunk, int warp, int lane, const uint32_t (&lo)[8], const uint32_t (&hi)[8]) {
  const int row = warp * 16 + (lane & 7) + ((lane >> 3) & 1) * 8;
  const uint32_t rbase = chunk + row * 128;
#pragma unroll
  for (int q = 0; q < 4; q++) {
    const int grp = 2 * q + (lane >> 4);
    stmatrix4(rbase + ((grp ^ (row & 7)) << 4), lo[2 * q], hi[2 * q], lo[2 * q + 1], hi[2 * q + 1]);
  }
}
__device__ __forceinline__ float silu_mul(float g, float u) {
  float e, r;
  asm("ex2.approx.ftz.f32 %0, %1;" : "=f"(e) : "f"(g * -1.4426950408889634f));
  asm("rcp.approx.ftz.f32 %0, %1;" : "=f"(r) : "f"(1.0f + e));
  return g * r * u;
}
__device__ __forceinline__ uint32_t swiglu2(uint32_t g2, uint32_t u2) {
  asm volatile("" : "+r"(g2));
  return pack2(silu_mul(bf_lo(g2), bf_lo(u2)), silu_mul(bf_hi(g2), bf_hi(u2)));
}
__device__ __forceinline__ void stage_done(uint32_t bar, int lane) {
  asm volatile("fence.proxy.async.shared::cta;" ::: "memory");
  __syncwarp();
  if (lane == 0) mbar_arrive(bar);
}

__device__ __forceinline__ int fresh_tid() {
  int t;
  asm volatile("mov.u32 %0, %%tid.x;" : "=r"(t));
  return t;
}
#define RING_IDS()                                                                                           \
  const int tid = fresh_tid() - 128;                                                                         \
  const int cw = __shfl_sync(~0u, tid >> 7, 0), warp = __shfl_sync(~0u, (tid >> 5) & 3, 0);                  \
  const bool releaser = (tid & 31) < 2;                                                                      \
  const uint32_t rbars = mapa(bars, tid & 1);                                                                \
  const uint32_t a_base = cw * 8192
#define LANE_IDS()                                                                                           \
  const int lane = fresh_tid() & 31, r = lane >> 2, c = lane & 3;                                            \
  const int srow = warp * 16 + (lane & 7) + ((lane >> 3) & 1) * 8;                                           \
  const uint32_t slab = stg + cw * 8192 + srow * 128, sw0 = (lane >> 4) ^ (srow & 7);                        \
  (void)r; (void)c; (void)slab; (void)sw0

template <int NPRE, bool EAGER, class Step>
__device__ __forceinline__ void attention(float (&acc)[96], const Params& p, int rho, int rb, int cta, int cw, int warp, uint32_t tag,
                                          uint32_t stg, uint32_t bars, uint32_t& prev, Step step) {
  uint32_t ql[8], qh[8], k0[8], k1[8], v0[8], v1[8], hp[16];
  if (EAGER) {
    tile_end(acc, prev);
  } else {
    step();
    fence_regs(acc);
  }
#pragma unroll
  for (int t = 0; t < 8; t++) {
    k0[t] = pack2(acc[4 * (8 + t)], acc[4 * (8 + t) + 1]);
    k1[t] = pack2(acc[4 * (8 + t) + 2], acc[4 * (8 + t) + 3]);
    v0[t] = pack2(acc[4 * (16 + t)], acc[4 * (16 + t) + 1]);
    v1[t] = pack2(acc[4 * (16 + t) + 2], acc[4 * (16 + t) + 3]);
    asm volatile("" : "+r"(k0[t]), "+r"(k1[t]), "+r"(v0[t]), "+r"(v1[t]));
  }
  const int lane = fresh_tid() & 31, r = lane >> 2, c = lane & 3;
#pragma unroll
  for (int t = 0; t < 8; t++) v1[t] = movmatrix(v1[t]);
  mbar_wait(bars + 8 * B_STGE, rho);
  mbar_wait(bars + 8 * (B_STGE + 1), 0);
  const uint32_t xch = stg + 16384 + (cw * 4 + warp) * 2048 + lane * 16;
  if (warp < 3) {
    sts128(xch, k1[0], k1[1], k1[2], k1[3]);
    sts128(xch + 512, k1[4], k1[5], k1[6], k1[7]);
    sts128(xch + 1024, v1[0], v1[1], v1[2], v1[3]);
    sts128(xch + 1536, v1[4], v1[5], v1[6], v1[7]);
  } else if (rb < 15) {
    uint4* dst = p.halo + ((cta * 2 + rho) * 2 + cw) * 256 + lane;
#pragma unroll
    for (int t = 0; t < 4; t++) {
      ll_store(dst + t * 32, k1[2 * t], k1[2 * t + 1], tag);
      ll_store(dst + (4 + t) * 32, v1[2 * t], v1[2 * t + 1], tag);
    }
  }
#pragma unroll
  for (int t = 0; t < 8; t++) {
    v0[t] = movmatrix(v0[t]);
    ql[t] = pack2(acc[4 * t], acc[4 * t + 1]);
    qh[t] = pack2(acc[4 * t + 2], acc[4 * t + 3]);
    asm volatile("" : "+r"(v0[t]), "+r"(ql[t]), "+r"(qh[t]));
  }
#pragma unroll 1
  for (int i = 0; i < NPRE; i++) step();
  const uint4* src = p.halo + (((cta - 8) * 2 + rho) * 2 + cw) * 256 + lane;
  uint4 early[8] = {};
  if (warp == 0 && rb > 0) {
#pragma unroll
    for (int i = 0; i < 8; i++) early[i] = ll_peek(src + i * 32);
  }
  step();
  wg_bar(cw);
  if (warp > 0) {
#pragma unroll
    for (int t = 0; t < 4; t++) {
      const uint4 a = lds128(xch - 2048 + t * 512);
      hp[4 * t] = a.x; hp[4 * t + 1] = a.y; hp[4 * t + 2] = a.z; hp[4 * t + 3] = a.w;
    }
  } else if (rb > 0) {
    uint32_t bad = 0;
#pragma unroll
    for (int i = 0; i < 8; i++) {
      bad |= (early[i].y ^ tag) | (early[i].w ^ tag);
      hp[2 * i] = early[i].x;
      hp[2 * i + 1] = early[i].z;
    }
    if (!__all_sync(~0u, bad == 0)) ll_poll<8>([&](int i) { return src + i * 32; }, tag, hp);
  } else {
#pragma unroll
    for (int t = 0; t < 16; t++) hp[t] = 0;
  }
  wg_wait<0>();
  if (prev != 0) mbar_arrive_cluster(prev);
  prev = 0;
#pragma unroll
  for (int t = 0; t < 8; t++) asm volatile("" : "+r"(ql[t])::"memory");
  const bool up0 = 2 * c > r, up1 = 2 * c + 1 > r;
  const bool first = (rb == 0) && (warp == 0);
  uint32_t a0[2], a2[2], a3[2], a5[2];
  float il[2], ih[2];
#pragma unroll
  for (int h = 0; h < 2; h++) {
    float sp[4] = {0.f, 0.f, 0.f, 0.f}, s0[4] = {0.f, 0.f, 0.f, 0.f}, s1[4] = {0.f, 0.f, 0.f, 0.f};
#pragma unroll
    for (int ks = 0; ks < 2; ks++) {
      const int t = 4 * h + 2 * ks;
      mma16816(sp, ql[t], qh[t], ql[t + 1], qh[t + 1], hp[t], hp[t + 1]);
      mma16816(s0, ql[t], qh[t], ql[t + 1], qh[t + 1], k0[t], k0[t + 1]);
      mma16816(s1, ql[t], qh[t], ql[t + 1], qh[t + 1], k1[t], k1[t + 1]);
    }
    float p0 = (up0 ? sp[0] : s0[0]) * QK_SCALE, p1 = (up1 ? sp[1] : s0[1]) * QK_SCALE;
    float p2 = (up0 ? s0[2] : s1[2]) * QK_SCALE, p3 = (up1 ? s0[3] : s1[3]) * QK_SCALE;
    if (first && up0) p0 = -1000000000.0f;
    if (first && up1) p1 = -1000000000.0f;
    il[h] = softmax8(p0, p1);
    ih[h] = softmax8(p2, p3);
    a0[h] = pack2(up0 ? p0 : 0.f, up1 ? p1 : 0.f);
    a2[h] = pack2(up0 ? 0.f : p0, up1 ? 0.f : p1);
    a3[h] = pack2(up0 ? p2 : 0.f, up1 ? p3 : 0.f);
    a5[h] = pack2(up0 ? 0.f : p2, up1 ? 0.f : p3);
  }
  float o[8][4];
#pragma unroll
  for (int t = 0; t < 8; t++) {
#pragma unroll
    for (int q = 0; q < 4; q++) o[t][q] = 0.f;
    mma1688(o[t], 0u, a5[t >> 2], v1[t]);
    mma16816(o[t], a0[t >> 2], 0u, a2[t >> 2], a3[t >> 2], hp[8 + t], v0[t]);
  }
#pragma unroll
  for (int t = 0; t < 8; t++) fence_regs(o[t]);
  if (!EAGER) step();
  uint32_t ol[8], oh[8];
#pragma unroll
  for (int t = 0; t < 8; t++) {
    ol[t] = pack2(o[t][0] * il[t >> 2], o[t][1] * il[t >> 2]);
    oh[t] = pack2(o[t][2] * ih[t >> 2], o[t][3] * ih[t >> 2]);
  }
  stage_slab(stg + cw * 8192, warp, lane, ol, oh);
  stage_done(bars + 8 * B_STGF, lane);
}

template <class Ready>
__device__ __forceinline__ void normalize_stage(const uint32_t (&xl)[16], const uint32_t (&xh)[16], const uint4* stats, uint32_t tag, uint32_t shift,
                                                uint32_t scale, uint32_t stg, uint32_t bars, int cw, int warp, int lane, Ready ready) {
  const int r = lane >> 2, c = lane & 3;
  float nb[2], rs[2];
  {
    uint32_t st[8];
    const uint4* sp = stats + (lane >> 4) * 512 + cw * 64 + warp * 16 + (lane & 15);
    ll_poll<4>([&](int i) { return sp + i * 128; }, tag, st);
    float mu, rstd;
    row_stats(st, mu, rstd);
    mu *= -rstd;
    nb[0] = __shfl_sync(~0u, mu, r); rs[0] = __shfl_sync(~0u, rstd, r);
    nb[1] = __shfl_sync(~0u, mu, r + 8); rs[1] = __shfl_sync(~0u, rstd, r + 8);
  }
  ready();
#pragma unroll
  for (int ch = 0; ch < 2; ch++) {
    uint32_t lo[8], hi[8];
#pragma unroll
    for (int t = 0; t < 8; t++) {
      const int n = ch * 8 + t;
      const float2 sb = lds64f(shift + (8 * n + 2 * c) * 4), cb = lds64f(scale + (8 * n + 2 * c) * 4);
      lo[t] = pack2((bf_lo(xl[n]) * rs[0] + nb[0]) * cb.x + sb.x, (bf_hi(xl[n]) * rs[0] + nb[0]) * cb.y + sb.y);
      hi[t] = pack2((bf_lo(xh[n]) * rs[1] + nb[1]) * cb.x + sb.x, (bf_hi(xh[n]) * rs[1] + nb[1]) * cb.y + sb.y);
    }
    stage_slab(stg + ch * 16384 + cw * 8192, warp, lane, lo, hi);
    stage_done(bars + 8 * (B_STGF + ch), lane);
  }
  wg_bar(cw);
}

__global__ void __launch_bounds__(384, 1) fused_kernel(const __grid_constant__ Params p) {
  extern __shared__ __align__(1024) uint8_t smem_raw[];
  const uint32_t sm = smem_u32(smem_raw);
  const uint32_t bars = sm + MISC_OFF;
  const uint32_t stg = sm + STG_OFF;
  const int rank = blockIdx.x & 1;
  const int cl = blockIdx.x >> 1;
  if (cl >= NCTA / 2) {
    const int e = blockIdx.x - NCTA, wid = __shfl_sync(~0u, (int)(threadIdx.x >> 5), 0), lane = threadIdx.x & 31;
    if (threadIdx.x == 0) {
      for (int i = 0; i < 6; i++) { mbar_init(bars + 8 * i, 1); mbar_init(bars + 8 * (6 + i), 8); }
      asm volatile("fence.mbarrier_init.release.cluster;" ::: "memory");
    }
    const uint32_t tag = load_epoch(p.epoch) + 1;
    if (threadIdx.x < 256) ll_store(p.modll + 512 + (threadIdx.x >> 6) * 256 + e * 64 + (threadIdx.x & 63), 0u, 0u, 0u);
    for (int i = threadIdx.x; i < 1536; i += 384) {
      uint4 o = make_uint4(0u, 0u, 0u, 0u);
      if (i < 1024 && (i & 63) < 8) {
        const uint4 cv = ldg_nc(p.c + (i >> 6) * 64 + (i & 7) * 8);
        o = make_uint4(pack2(silu_f(bf_lo(cv.x)), silu_f(bf_hi(cv.x))), pack2(silu_f(bf_lo(cv.y)), silu_f(bf_hi(cv.y))),
                       pack2(silu_f(bf_lo(cv.z)), silu_f(bf_hi(cv.z))), pack2(silu_f(bf_lo(cv.w)), silu_f(bf_hi(cv.w))));
      }
      sts128(stg + i * 16, o.x, o.y, o.z, o.w);
    }
    asm volatile("fence.proxy.async.shared::cta;" ::: "memory");
    __syncthreads();
    if (wid == 0) {
      __nanosleep(WMDELAY);
      uint32_t ph = 1;
#pragma unroll 1
      for (int it = 0, s = 0; it < 64; it++) {
        mbar_wait(bars + 8 * (6 + s), ph);
        expect_tx_elect(bars + 8 * s, 32768);
#pragma unroll
        for (int q = 0; q < 4; q++) tma_load_ef(sm + s * 32768 + q * 8192, &p.wm, bars + 8 * s, 2048 + (it >> 4) * 1024 + e * 256 + q * 64, (it & 15) * 64);
        if (++s == 6) { s = 0; ph ^= 1; }
      }
    } else if (wid >= 4) {
      const int hf = (wid >> 2) - 1;
      uint32_t ph = 0;
      int s = 0;
#pragma unroll 1
      for (int v = 0; v < 4; v++) {
        float acc[64];
#pragma unroll 1
        for (int kb = 0; kb < 16; kb++) {
          mbar_wait_watchdog(bars + 8 * s, ph);
          const uint32_t da = DESC_A + ((STG_OFF + kb * 1024) >> 4), db = DESC_B + ((s * 32768 + hf * 16384) >> 4) - 1024;
          wg_fence();
#pragma unroll
          for (int k = 0; k < 4; k++) wgmma_ss_n128(acc, da + k * 2, db + k * 128, (kb | k) != 0);
          wg_commit();
          wg_wait<0>();
          if (lane == 0) mbar_arrive(bars + 8 * (6 + s));
          if (++s == 6) { s = 0; ph ^= 1; }
        }
        if ((wid & 3) == 0) {
#pragma unroll
          for (int n = 0; n < 16; n++) {
            const uint32_t mine = pack2(acc[4 * n], acc[4 * n + 1]), next = __shfl_down_sync(~0u, mine, 1);
            if (lane < 4 && (lane & 1) == 0) ll_store(p.modll + 512 + v * 256 + e * 64 + hf * 32 + n * 2 + (lane >> 1), mine, next, tag);
          }
        }
      }
    }
    return;
  }
  const int slot = p.slot[cl];
  const int rb = (slot >> 3) * 2 + rank, j = slot & 7;
  const int cta = rb * 8 + j;
  PROF_AT(threadIdx.x == 0, 0);

  if (threadIdx.x < 128) {
    uint32_t tag = load_epoch(p.epoch);
    asm volatile("setmaxnreg.dec.sync.aligned.u32 40;");
    const int warp = __shfl_sync(~0u, (int)(threadIdx.x >> 5), 0), lane = threadIdx.x & 31;
    if (threadIdx.x == 0) {
      if ((sm & 0x3FFFF) != SMEM_BASE) asm volatile("trap;");
      for (int i = 0; i < 4; i++) { mbar_init(bars + 8 * (B_FQ + i), 1); mbar_init(bars + 8 * (B_EQ + i), 16); }
      for (int i = 0; i < 6; i++) { mbar_init(bars + 8 * (B_FW + i), 1); mbar_init(bars + 8 * (B_EW + i), 16); }
      for (int i = 0; i < 4; i++) { mbar_init(bars + 8 * (B_FG + i), 1); mbar_init(bars + 8 * (B_EG + i), 16); }
      for (int i = 0; i < 6; i++) { mbar_init(bars + 8 * (B_FD + i), 1); mbar_init(bars + 8 * (B_ED + i), 16); }
      for (int i = 0; i < 2; i++) { mbar_init(bars + 8 * (B_STGF + i), 8); mbar_init(bars + 8 * (B_STGE + i), 1); }
      mbar_init(bars + 8 * B_MODB, 1);
      mbar_init(bars + 8 * (B_MODB + 1), 1);
      mbar_init(bars + 8 * B_MODA, 1);
      for (int i = 0; i < 8; i++) mbar_init(bars + 8 * (B_RDY + i), 1);
      asm volatile("fence.mbarrier_init.release.cluster;" ::: "memory");
    }
    __syncwarp();
    cluster_arrive_relaxed();
    tag += 1;
    const unsigned target = tag * 8;
    unsigned* cnt = p.cnt + rb * 32;
    cluster_wait();
    if (warp == 0) {
      const CUtensorMap* wgu = rank ? &p.wu : &p.wg;
      uint32_t st = sm + 16384, fb = bars + 8 * B_FQ, ph = 1;
      if (BDELAY) __nanosleep(BDELAY);
#pragma unroll 1
      for (int it = 0; it < 32; it++) {
        const int kb = qkv_kb(it, j), col = j * 128 + ((it < 4 ? it >= 2 : it >= 18) ? 64 : 0);
        mbar_wait(fb + 8 * (B_EQ - B_FQ), ph);
        expect_tx_elect(fb, it < 4 ? 24576 : 40960);
        tma_load_mc(st + rank * 8192, &p.wqkv, fb, col + rank * 1024, kb * 64);
        tma_load_mc(st + 16384 + rank * 4096, &p.wqkv32, fb, col + 2048, kb * 64 + rank * 32);
        st += 49152; fb += 8;
        if ((it & 3) == 3) { st -= 4 * 49152; fb -= 32; ph ^= 1; }
      }
      fb = bars + 8 * B_FW; ph = 1;
#pragma unroll 1
      for (int it = 0, s = 0; it < 16; it++) {
        if (it < 6) wait_p3_free(bars + 8 * B_EQ, it);
        mbar_wait(fb + 8 * (B_EW - B_FW), ph);
        expect_tx_elect(fb, it == 8 ? 16384 : 32768);
        tma_load_mc(st + rank * 8192, &p.wo, fb, j * 128 + rank * 64, wo_k(it, j));
        st += 32768; fb += 8;
        if (++s == 6) { s = 0; st -= 6 * 32768; fb -= 48; ph ^= 1; }
      }
      st = sm + 16384; fb = bars + 8 * B_FG; ph = 1;
#pragma unroll 1
      for (int it = 0; it < 48; it++) {
        const int kb = own_first(it, j), col = j * 448 + (it >> 4) * 128;
        if (it < 4) wait_p2_free(bars + 8 * B_EW, it);
        mbar_wait(fb + 8 * (B_EG - B_FG), ph);
        expect_tx_elect(fb, it < 2 ? 32768 : 49152);
        tma_load_mc(st + rank * 16384, wgu, fb, col, kb * 64);
        tma_load_mc(st + rank * 16384 + 8192, wgu, fb, col + 64, kb * 64);
        st += 49152; fb += 8;
        if ((it & 3) == 3) { st -= 4 * 49152; fb -= 32; ph ^= 1; }
      }
      fb = bars + 8 * B_FD; ph = 1;
#pragma unroll 1
      for (int it = 0, s = 0; it < 72; it++) {
        if (it < 6) wait_p3_free(bars + 8 * B_EG, it);
        mbar_wait(fb + 8 * (B_ED - B_FD), ph);
        expect_tx_elect(fb, 32768);
        tma_load_mc(st + rank * 8192, it < 16 ? wgu : &p.wd, fb, it < 16 ? j * 448 + 384 : j * 128 + rank * 64, down_k(it));
        st += 32768; fb += 8;
        if (++s == 6) { s = 0; st -= 6 * 32768; fb -= 48; ph ^= 1; }
      }
    } else if (warp == 1) {
      const int arow = rb * 128;
      uint32_t st = sm, fb = bars + 8 * B_FQ, ph = 0;
      cnt_wait(cnt + C_HA, target);
      PROF_AT(lane == 0, 16);
#pragma unroll 1
      for (int it = 4; it < 32; it++) {
        if (it == 11) mbar_wait(bars + 8 * (B_RDY + C_H), 0);
        mbar_wait(fb + 8 * (B_EQ - B_FQ), ph);
        tma_load(st, &p.h, fb, qkv_kb(it, j) * 64, arow);
        st += 49152; fb += 8;
        if ((it & 3) == 3) { st -= 4 * 49152; fb -= 32; ph ^= 1; }
      }
      fb = bars + 8 * B_FW; ph = 1;
#pragma unroll 1
      for (int it = 0, s = 0; it < 16; it++) {
        if (it < 6) wait_p3_free(bars + 8 * B_EQ, it);
        mbar_wait(fb + 8 * (B_EW - B_FW), ph);
        if (it == 0) mbar_wait(bars + 8 * (B_RDY + C_O), 0);
        if (it == 9) cnt_wait(cnt + C_O + 1, target);
        PROF_AT(lane == 0 && (it == 0 || it == 9), 17 + (it >> 3));
        if (it != 8) tma_load(st, &p.o_ld, fb, wo_k(it, j), arow);
        st += 32768; fb += 8;
        if (++s == 6) { s = 0; st -= 6 * 32768; fb -= 48; ph ^= 1; }
      }
      st = sm + 2 * 49152; fb = bars + 8 * (B_FG + 2); ph = 1;
      cnt_wait(cnt + C_H2A, target);
      PROF_AT(lane == 0, 19);
#pragma unroll 1
      for (int it = 2; it < 48; it++) {
        if (it == 9) mbar_wait(bars + 8 * (B_RDY + C_H2), 0);
        mbar_wait(fb + 8 * (B_EG - B_FG), ph);
        tma_load(st, &p.h2, fb, own_first(it, j) * 64, arow);
        st += 49152; fb += 8;
        if ((it & 3) == 3) { st -= 4 * 49152; fb -= 32; ph ^= 1; }
      }
      fb = bars + 8 * B_FD; ph = 1;
#pragma unroll 1
      for (int it = 0, s = 0; it < 72; it++) {
        if (it < 6) wait_p3_free(bars + 8 * B_EG, it);
        mbar_wait(fb + 8 * (B_ED - B_FD), ph);
        if ((it & 15) == 0 && it > 0) { mbar_wait(bars + 8 * (B_RDY + C_ACT - 1 + (it >> 4)), 0); PROF_AT(lane == 0, 19 + (it >> 4)); }
        tma_load(st, it < 16 ? &p.h2 : &p.act, fb, down_k(it), arow);
        st += 32768; fb += 8;
        if (++s == 6) { s = 0; st -= 6 * 32768; fb -= 48; ph ^= 1; }
      }
    } else if (warp == 2) {
      if (lane < 13) prefetch_map(&p.h + lane);
      __syncwarp();
      uint32_t ph1 = 0;
#pragma unroll 1
      for (int n = 0; n < 8; n++) {
        const int nch = (n == 1 || n == 2 || n == 7) ? 1 : 2;
#pragma unroll 1
        for (int ch = 0; ch < nch; ch++) {
          mbar_wait_watchdog(bars + 8 * (B_STGF + ch), ch ? ph1 : (n & 1));
          const uint32_t src = stg + ch * 16384;
          if (n == 1 || n == 2) {
#pragma unroll 1
            for (int q = 0; q < 4; q++) {
              tma_store2(&p.o_st, src + q * 4096, j * 128 + (n - 1) * 64, rb * 128 + q * 32);
              if (n == 1) store_pause(true);
            }
          } else if (n >= 4 && n < 8) {
#pragma unroll 1
            for (int q = 0; q < 4; q++) {
              tma_store2(&p.act_st, src + q * 4096, j * 448 + (n - 4) * 128 + ch * 64, rb * 128 + q * 32);
              store_pause(true);
            }
          } else {
            tma_store2(n == 0 ? &p.h : &p.h2, src, j * 128 + ch * 64, rb * 128);
            asm volatile("cp.async.bulk.commit_group;" ::: "memory");
            if (ch == 1) {
              asm volatile("cp.async.bulk.wait_group 1;" ::: "memory");
              __syncwarp();
              cnt_signal(cnt + (n == 0 ? C_HA : C_H2A));
            }
          }
          if (n >= 4 && n < 7 && ch == 0) arrive_elect(bars + 8 * B_STGE);
        }
        asm volatile("cp.async.bulk.commit_group;" ::: "memory");
        asm volatile("cp.async.bulk.wait_group 0;" ::: "memory");
        __syncwarp();
        cnt_signal(cnt + n);
        PROF_AT(lane == 0, n == 0 ? 33 : 23 + n);
        if (n == 0) {
#pragma unroll 1
          for (int t = 0; t < 36; t++) {
            ll_store(t < 32 ? p.halo + cta * 1024 + t * 32 + lane : p.stats2 + cta * 128 + (t - 32) * 32 + lane, 0u, 0u, 0u);
            __nanosleep(40);
          }
          __syncwarp();
        }
        if (!(n >= 4 && n < 7)) arrive_elect(bars + 8 * B_STGE);
        if (nch == 2) { arrive_elect(bars + 8 * (B_STGE + 1)); ph1 ^= 1; }
      }
      mbar_wait_watchdog(bars + 8 * B_STGF, 0);
      PROF_AT(lane == 0, 31);
    } else {
      if (lane < 4) ll_store(p.modll + cta * 4 + lane, 0u, 0u, 0u);
      bar_sync(1, 288);
      {
        const uint4 t4 = lds128(sm + RED_OFF + lane * 16);
        float a[4] = {__uint_as_float(t4.x), __uint_as_float(t4.y), __uint_as_float(t4.z), __uint_as_float(t4.w)};
#pragma unroll
        for (int o = 4; o < 32; o <<= 1)
#pragma unroll
          for (int q = 0; q < 4; q++) a[q] += __shfl_xor_sync(~0u, a[q], o);
        if (lane < 4) ll_store(p.modll + cta * 4 + lane, pack2(a[0], a[1]), pack2(a[2], a[3]), tag);
        PROF_AT(lane == 0, 1);
        uint32_t m[4];
        const uint4* mp = p.modll + j * 32 + lane;
        ll_poll<2>([&](int i) { return mp + i * 256; }, tag, m);
        const uint32_t c0 = pack2(1.0f + bf_lo(m[2]), 1.0f + bf_hi(m[2])), c1 = pack2(1.0f + bf_lo(m[3]), 1.0f + bf_hi(m[3]));
        sts128(sm + MODB_OFF + lane * 16, m[0] << 16, m[0] & 0xffff0000u, m[1] << 16, m[1] & 0xffff0000u);
        sts128(sm + MODB_OFF + 512 + lane * 16, c0 << 16, c0 & 0xffff0000u, c1 << 16, c1 & 0xffff0000u);
        __syncwarp();
        arrive_elect(bars + 8 * B_MODA);
      }
#pragma unroll 1
      for (int n = C_H; n <= C_O; n++) {
        cnt_wait_lazy(cnt + n, target);
        arrive_elect(bars + 8 * (B_RDY + n));
      }
      {
        uint32_t m[6];
        const uint4* src = p.modll + 512 + j * 32 + lane;
        ll_poll<3, 500>([&](int i) { return src + i * 256; }, tag, m);
#pragma unroll
        for (int vec = 0; vec < 3; vec++) {
          const float add = vec == 2 ? 1.0f : 0.0f;
          sts128(sm + MODB_OFF + (vec * 128 + lane * 4) * 4, __float_as_uint(bf_round(bf_lo(m[2 * vec]) + add)), __float_as_uint(bf_round(bf_hi(m[2 * vec]) + add)),
                 __float_as_uint(bf_round(bf_lo(m[2 * vec + 1]) + add)), __float_as_uint(bf_round(bf_hi(m[2 * vec + 1]) + add)));
        }
        __syncwarp();
        if (lane == 0) mbar_arrive(bars + 8 * B_MODB);
        PROF_AT(lane == 0, 15);
      }
      __syncwarp();
#pragma unroll 1
      for (int n = C_H2; n < 8; n++) {
        cnt_wait_lazy(cnt + n, target);
        arrive_elect(bars + 8 * (B_RDY + n));
      }
      {
        uint32_t m[2];
        const uint4* src = p.modll + 512 + 768 + j * 32 + lane;
        ll_poll<1>([&](int) { return src; }, tag, m);
        sts128(sm + MODB_OFF + (384 + lane * 4) * 4, m[0] << 16, m[0] & 0xffff0000u, m[1] << 16, m[1] & 0xffff0000u);
        __syncwarp();
        if (lane == 0) mbar_arrive(bars + 8 * (B_MODB + 1));
      }
    }
    if (!TAIL) {
      __syncwarp();
      cluster_arrive_relaxed();
      cluster_wait();
    }
  } else {
    uint32_t tag;

    {
      const int tid = threadIdx.x - 128, cw = tid >> 7, warp = (tid >> 5) & 3, lane = tid & 31;
      const int l16 = lane & 15, half = lane >> 4, w8 = cw * 4 + warp;
      const uint32_t cbuf = sm + 3 * 49152 + w8 * 512;
      if (lane <= 16) cp_async16(cbuf + lane * 16, lane < 16 ? (const void*)(p.c + w8 * 128 + lane * 8) : (const void*)p.epoch);
      asm volatile("cp.async.commit_group;" ::: "memory");
      const uint32_t wbuf = sm + cw * 49152 + warp * 4096;
      {
        const char* wp = (const char*)p.wmod + (uint32_t)(cta * 32 + (lane & 1) * 16 + (w8 * 128 + (lane >> 1)) * 12288);
#pragma unroll
        for (int i = 0; i < 8; i++) cp_async16(wbuf + i * 512 + lane * 16, wp + i * 16 * 12288);
      }
      asm volatile("cp.async.commit_group;" ::: "memory");
      const uint32_t xbuf = sm + 40960 + (cw * 2 + (l16 >> 3)) * 49152 + (warp * 16 + half) * 128;
      {
        const char* xp = (const char*)p.x + (uint32_t)((rb * 128 + (warp * 16 + half) * 2 + cw) * 2048 + j * 256 + l16 * 16);
#pragma unroll
        for (int i = 0; i < 8; i++) cp_async16(xbuf + i * 256 + (((l16 & 7) ^ ((i * 2 + half) & 7)) << 4), xp + i * 8192);
      }
      asm volatile("cp.async.commit_group;" ::: "memory");
      PROF_AT(tid == 0, 32);
      uint4* st1 = p.stats1 + (rb * 8 + j) * 128 + cw * 64 + warp * 16;
      if (lane < 16) ll_store(st1 + lane, 0u, 0u, 0u);
      __syncwarp();
      cluster_arrive_relaxed();
      asm volatile("setmaxnreg.inc.sync.aligned.u32 232;");
      uint32_t sa[4][4];
      {
        asm volatile("cp.async.wait_group 2;" ::: "memory");
        __syncwarp();
        tag = lds32(cbuf + 256) + 1;
        const float2 cv = lds64f(cbuf + lane * 8);
        const uint32_t c0 = __float_as_uint(cv.x), c1 = __float_as_uint(cv.y);
        sts64f(cbuf + lane * 8, __uint_as_float(pack2(silu_f(bf_lo(c0)), silu_f(bf_hi(c0)))), __uint_as_float(pack2(silu_f(bf_lo(c1)), silu_f(bf_hi(c1)))));
        __syncwarp();
#pragma unroll
        for (int q = 0; q < 4; q++) ldmatrix4(sa[q][0], sa[q][1], sa[q][2], sa[q][3], cbuf + q * 64 + (lane >> 3) * 16);
      }
      cluster_wait();
      asm volatile("cp.async.wait_group 1;" ::: "memory");
      __syncwarp();
      PROF_AT(tid == 0, 51);
      {
        uint32_t b[8][4];
#pragma unroll
        for (int ks = 0; ks < 8; ks++) ldmatrix4t(b[ks], wbuf + (ks * 16 + (lane & 15)) * 32 + (lane >> 4) * 16);
        float d0[4] = {0.f, 0.f, 0.f, 0.f}, d1[4] = {0.f, 0.f, 0.f, 0.f}, d2[4] = {0.f, 0.f, 0.f, 0.f}, d3[4] = {0.f, 0.f, 0.f, 0.f};
#pragma unroll
        for (int q = 0; q < 4; q++) {
          mma16816(d0, sa[q][0], sa[q][0], sa[q][1], sa[q][1], b[2 * q][0], b[2 * q][1]);
          mma16816(d1, sa[q][0], sa[q][0], sa[q][1], sa[q][1], b[2 * q][2], b[2 * q][3]);
          mma16816(d2, sa[q][2], sa[q][2], sa[q][3], sa[q][3], b[2 * q + 1][0], b[2 * q + 1][1]);
          mma16816(d3, sa[q][2], sa[q][2], sa[q][3], sa[q][3], b[2 * q + 1][2], b[2 * q + 1][3]);
        }
        d0[0] += d2[0]; d0[1] += d2[1]; d1[0] += d3[0]; d1[1] += d3[1];
        if (lane < 4) {
          sts64f(sm + RED_OFF + (w8 * 16 + lane * 2) * 4, d0[0], d0[1]);
          sts64f(sm + RED_OFF + (w8 * 16 + 8 + lane * 2) * 4, d1[0], d1[1]);
        }
        asm volatile("bar.arrive 1, 288;" ::: "memory");
      }
      asm volatile("cp.async.wait_group 0;" ::: "memory");
      __syncwarp();
      uint32_t xl[16], xh[16];
      {
        const int srow = warp * 16 + (lane & 15);
#pragma unroll
        for (int q = 0; q < 8; q++)
          ldmatrix4(xl[2 * q], xh[2 * q], xl[2 * q + 1], xh[2 * q + 1],
                    sm + 40960 + (cw * 2 + (q >> 2)) * 49152 + srow * 128 + (((half + (q & 3) * 2) ^ (srow & 7)) << 4));
      }
      publish_stats(xl, xh, st1, lane, tag);
      PROF_AT(tid == 0, 50);
      normalize_stage(xl, xh, p.stats1 + rb * 1024, tag, sm + MODB_OFF, sm + MODB_OFF + 512, stg, bars, cw, warp, lane,
                      [&]() { mbar_wait(bars + 8 * B_MODA, 0); });
      PROF_AT(tid == 0, 3);
    }

    uint32_t xl[16], xh[16];
    {
      RING_IDS();
      uint32_t prev = 0;
      float acc1[96];
      {
        Ring g{bars + 8 * B_FQ, rbars + 8 * B_EQ, 0, 0u, releaser TR(0)};
        float acc0[96];
#pragma unroll 1
        for (int kb = 0; kb < 2; kb++) kblock<192, 4, 49152>(acc0, g, a_base + STG_OFF + kb * 16384, kb == 0, prev);
#pragma unroll 1
        for (int kb = 0; kb < 2; kb++) kblock<192, 4, 49152>(acc1, g, a_base + STG_OFF + kb * 16384, kb == 0, prev);
#pragma unroll 1
        for (int kb = 0; kb < 14; kb++) kblock<192, 4, 49152>(acc0, g, a_base + g.s * 49152, false, prev);
        PROF_AT(tid == 0, 4);
        attention<NPRE0, false>(acc0, p, 0, rb, cta, cw, warp, tag, stg, bars, prev, [&]() { kblock<192, 4, 49152>(acc1, g, a_base + g.s * 49152, false, prev); });
        PROF_AT(tid == 0, 5);
        {
          LANE_IDS();
#pragma unroll
          for (int q = 0; q < 8; q++)
            ldmatrix4(xl[2 * q], xh[2 * q], xl[2 * q + 1], xh[2 * q + 1], sm + 40960 + (cw * 2 + (q >> 2)) * 49152 + srow * 128 + ((sw0 ^ ((q & 3) * 2)) << 4));
#pragma unroll
          for (int q = 0; q < 16; q++) asm volatile("" : "+r"(xl[q]), "+r"(xh[q])::"memory");
        }
#pragma unroll 1
        for (int kb = 3 + NPRE0; kb < 14; kb++) kblock<192, 4, 49152>(acc1, g, a_base + g.s * 49152, false, prev);
        PROF_AT(tid == 0, 6);
      }
      float acc[64];
      Ring g{bars + 8 * B_FW, rbars + 8 * B_EW, 0, 0u, releaser TR(32)};
      attention<NPRE1, EAGER1>(acc1, p, 1, rb, cta, cw, warp, tag, stg, bars, prev, [&]() { kblock<128, 6, 32768>(acc, g, a_base + g.s * 32768, g.s == 0, prev); });
      PROF_AT(tid == 0, 7);
      LANE_IDS();
#pragma unroll 1
      for (int kb = (EAGER1 ? 1 : 3) + NPRE1; kb < 16; kb++) {
        if (kb == 8) wg_bar(cw);
        kblock<128, 6, 32768>(acc, g, a_base + (kb == 8 ? STG_OFF : g.s * 32768), false, prev);
      }
      mbar_wait(bars + 8 * B_MODB, 0);
      float2 ga[16];
#pragma unroll
      for (int n = 0; n < 16; n++) ga[n] = lds64f(sm + MODB_OFF + (8 * n + 2 * c) * 4);
      tile_end(acc, prev);
      PROF_AT(tid == 0, 8);
      uint4* st2 = p.stats2 + (rb * 8 + j) * 128 + cw * 64 + warp * 16 + r + (c & 1) * 8;
      float sl[2] = {0.f, 0.f}, sh[2] = {0.f, 0.f}, ql[2] = {0.f, 0.f}, qh[2] = {0.f, 0.f};
#pragma unroll
      for (int n = 0; n < 16; n++) {
        acc[4 * n] = ga[n].x * acc[4 * n] + bf_lo(xl[n]); acc[4 * n + 1] = ga[n].y * acc[4 * n + 1] + bf_hi(xl[n]);
        acc[4 * n + 2] = ga[n].x * acc[4 * n + 2] + bf_lo(xh[n]); acc[4 * n + 3] = ga[n].y * acc[4 * n + 3] + bf_hi(xh[n]);
        sl[0] += acc[4 * n]; sl[1] += acc[4 * n + 1]; sh[0] += acc[4 * n + 2]; sh[1] += acc[4 * n + 3];
        ql[0] += acc[4 * n] * acc[4 * n]; ql[1] += acc[4 * n + 1] * acc[4 * n + 1];
        qh[0] += acc[4 * n + 2] * acc[4 * n + 2]; qh[1] += acc[4 * n + 3] * acc[4 * n + 3];
      }
      {
        const float ml = (sl[0] + sl[1]) * (1.0f / 32), mh = (sh[0] + sh[1]) * (1.0f / 32);
        const float vl = (ql[0] + ql[1]) - 32.0f * ml * ml, vh = (qh[0] + qh[1]) - 32.0f * mh * mh;
        const bool b0 = c & 1;
        float m = b0 ? mh : ml, q = b0 ? vh : vl;
        chan(m, q, __shfl_xor_sync(~0u, b0 ? ml : mh, 1), __shfl_xor_sync(~0u, b0 ? vl : vh, 1), 32.f);
        chan(m, q, __shfl_xor_sync(~0u, m, 2), __shfl_xor_sync(~0u, q, 2), 64.f);
        if (c < 2) ll_store(st2, __float_as_uint(m), __float_as_uint(fmaxf(q, 0.f)), tag);
        __syncwarp();
      }
      PROF_AT(tid == 0, 48);
      float2 sb[16], cb[16];
#pragma unroll
      for (int n = 0; n < 16; n++) {
        sb[n] = lds64f(sm + MODB_OFF + (128 + 8 * n + 2 * c) * 4);
        cb[n] = lds64f(sm + MODB_OFF + (256 + 8 * n + 2 * c) * 4);
        xl[n] = pack2(acc[4 * n], acc[4 * n + 1]);
        xh[n] = pack2(acc[4 * n + 2], acc[4 * n + 3]);
      }
      mbar_wait(bars + 8 * B_STGE, 0);
      PROF_AT(tid == 0, 49);
      float nb[2], rstd[2];
      {
        uint32_t st[8];
        const uint4* sp = p.stats2 + (rb * 8 + (lane >> 4) * 4) * 128 + cw * 64 + warp * 16 + (lane & 15);
        ll_poll<4, PB2>([&](int i) { return sp + i * 128; }, tag, st);
        float mu, rs;
        row_stats(st, mu, rs);
        mu *= -rs;
        nb[0] = __shfl_sync(~0u, mu, r); rstd[0] = __shfl_sync(~0u, rs, r);
        nb[1] = __shfl_sync(~0u, mu, r + 8); rstd[1] = __shfl_sync(~0u, rs, r + 8);
      }
      PROF_AT(tid == 0, 9);
#pragma unroll
      for (int ch = 0; ch < 2; ch++) {
        uint32_t lo[8], hi[8];
#pragma unroll
        for (int t = 0; t < 8; t++) {
          const int n = ch * 8 + t;
          lo[t] = pack2((acc[4 * n] * rstd[0] + nb[0]) * cb[n].x + sb[n].x, (acc[4 * n + 1] * rstd[0] + nb[0]) * cb[n].y + sb[n].y);
          hi[t] = pack2((acc[4 * n + 2] * rstd[1] + nb[1]) * cb[n].x + sb[n].x, (acc[4 * n + 3] * rstd[1] + nb[1]) * cb[n].y + sb[n].y);
        }
        stage_slab(stg + ch * 16384 + cw * 8192, warp, lane, lo, hi);
        stage_done(bars + 8 * (B_STGF + ch), lane);
      }
      wg_bar(cw);
      PROF_AT(tid == 0, 10);
    }

    uint32_t pg[32], pu[32];
    {
      RING_IDS();
      LANE_IDS();
      Ring g{bars + 8 * B_FG, rbars + 8 * B_EG, 0, 0u, releaser TR(48)};
      float acc[128];
      {
        uint32_t prev = 0;
        uint4* x1p = p.x1 + (size_t)(rb * 128 + (warp * 16 + (lane >> 4)) * 2 + cw) * 128 + j * 16 + (lane & 15);
#pragma unroll 1
        for (int kb = 0; kb < 16; kb++) {
          kblock<256, 4, 49152>(acc, g, a_base + (kb < 2 ? STG_OFF + kb * 16384 : g.s * 49152), kb == 0, prev);
          if (kb == X1A) {
#pragma unroll
            for (int q = 0; q < 4; q++) x1p[q * 512] = make_uint4(xl[4 * q], xl[4 * q + 1], xl[4 * q + 2], xl[4 * q + 3]);
          }
          if (kb == X1B) {
#pragma unroll
            for (int q = 0; q < 4; q++) x1p[(4 + q) * 512] = make_uint4(xh[4 * q], xh[4 * q + 1], xh[4 * q + 2], xh[4 * q + 3]);
          }
        }
        tile_end(acc, prev);
      }
      PROF_AT(tid == 0, 36);
#pragma unroll 1
      for (int t = 1; t < 3; t++) {
#pragma unroll
        for (int q = 0; q < 32; q++) {
          pg[q] = pack2(acc[2 * q], acc[2 * q + 1]);
          pu[q] = pack2(acc[64 + 2 * q], acc[64 + 2 * q + 1]);
        }
        uint32_t prev = 0;
#pragma unroll 1
        for (int blk = 0; blk < 4; blk++) {
          g.s = 0;
#pragma unroll
          for (int i = 0; i < 4; i++) {
            kblock<256, 4, 49152>(acc, g, a_base + i * 49152, blk == 0 && i == 0, prev);
            if ((blk & 1) == 0 && i == 0) mbar_wait(bars + 8 * (B_STGE + (blk >> 1)), t & 1);
            stmatrix2(slab + (blk >> 1) * 16384 + (((srow & 7) ^ ((blk & 1) * 4 + i)) << 4), swiglu2(pg[2 * i], pu[2 * i]), swiglu2(pg[2 * i + 1], pu[2 * i + 1]));
          }
#pragma unroll
          for (int q = 0; q < 24; q++) { pg[q] = pg[q + 8]; pu[q] = pu[q + 8]; }
          if (blk & 1) stage_done(bars + 8 * (B_STGF + (blk >> 1)), lane);
        }
        tile_end(acc, prev);
        PROF_AT(tid == 0, 36 + t);
      }
#pragma unroll
      for (int q = 0; q < 32; q++) {
        pg[q] = pack2(acc[2 * q], acc[2 * q + 1]);
        pu[q] = pack2(acc[64 + 2 * q], acc[64 + 2 * q + 1]);
      }
      PROF_AT(tid == 0, 11);
    }

    {
      RING_IDS();
      LANE_IDS();
      Ring g{bars + 8 * B_FD, rbars + 8 * B_ED, 0, 0u, releaser TR(96)};
      float acc[64];
      uint32_t prev = 0;
#pragma unroll 1
      for (int blk = 0; blk < 6; blk++) {
#pragma unroll
        for (int i = 0; i < 8; i++) {
          kblock<128, 6, 32768>(acc, g, a_base + g.s * 32768, (blk & ~2) == 0 && i == 0, prev);
          if ((blk & 1) == 0 && i == 0) mbar_wait(bars + 8 * (B_STGE + ((blk >> 1) & 1)), blk < 4);
          stmatrix1(slab + ((blk >> 1) & 1) * 16384 + (i & 1) * 1024 + (((srow & 7) ^ ((blk & 1) * 4 + (i >> 1))) << 4), swiglu2(pg[i], pu[i]));
        }
#pragma unroll
        for (int q = 0; q < 24; q++) { pg[q] = pg[q + 8]; pu[q] = pu[q + 8]; }
        if (blk & 1) stage_done(bars + 8 * (B_STGF + ((blk >> 1) & 1)), lane);
        if (blk == 1) {
          tile_end(acc, prev);
          PROF_AT(tid == 0, 39);
#pragma unroll
          for (int q = 0; q < 16; q++) {
            pg[16 + q] = pack2(acc[2 * q], acc[2 * q + 1]);
            pu[16 + q] = pack2(acc[32 + 2 * q], acc[32 + 2 * q + 1]);
          }
          PROF_AT(tid == 0, 12);
        }
      }
      uint4 x1[8];
      const int fl = fresh_tid() & 31;
      const uint4* x1p = p.x1 + (size_t)(rb * 128 + (warp * 16 + (fl >> 4)) * 2 + cw) * 128 + j * 16 + (fl & 15);
#pragma unroll
      for (int q = 0; q < 2; q++) {
#pragma unroll
        for (int e = 0; e < 4; e++) x1[4 * q + e] = ll_peek(x1p + (4 * q + e) * 512);
#pragma unroll 1
        for (int kb = 0; kb < 12; kb++) {
          if (TAIL && q == 1 && kb == 6) g.releaser = false;
          kblock<128, 6, 32768>(acc, g, a_base + g.s * 32768, false, prev);
        }
      }
      mbar_wait(bars + 8 * (B_MODB + 1), 0);
      mbar_wait(bars + 8 * B_STGE, 1);
      mbar_wait(bars + 8 * (B_STGE + 1), 0);
      float2 gbv[16];
#pragma unroll
      for (int n = 0; n < 16; n++) gbv[n] = lds64f(sm + MODB_OFF + (384 + 8 * n + 2 * c) * 4);
      tile_end(acc, prev);
      PROF_AT(tid == 0, 13);
#pragma unroll
      for (int ch = 0; ch < 2; ch++) {
        uint32_t lo[8], hi[8];
#pragma unroll
        for (int t = 0; t < 8; t++) {
          const int n = ch * 8 + t;
          const float2 gb = gbv[n];
          const uint4 a = x1[n >> 2], b = x1[4 + (n >> 2)];
          const uint32_t xl = (n & 3) == 0 ? a.x : (n & 3) == 1 ? a.y : (n & 3) == 2 ? a.z : a.w;
          const uint32_t xh = (n & 3) == 0 ? b.x : (n & 3) == 1 ? b.y : (n & 3) == 2 ? b.z : b.w;
          lo[t] = pack2(bf_lo(xl) + gb.x * acc[4 * n], bf_hi(xl) + gb.y * acc[4 * n + 1]);
          hi[t] = pack2(bf_lo(xh) + gb.x * acc[4 * n + 2], bf_hi(xh) + gb.y * acc[4 * n + 3]);
        }
        stage_slab(stg + ch * 16384 + cw * 8192, warp, lane, lo, hi);
        asm volatile("fence.proxy.async.shared::cta;" ::: "memory");
        __syncwarp();
        tma_store3(&p.out, stg + ch * 16384 + cw * 8192 + warp * 2048, j * 128 + ch * 64, rb * 64 + warp * 16, cw);
      }
      asm volatile("cp.async.bulk.commit_group;" ::: "memory");
      if (lane == 0) mbar_arrive(bars + 8 * B_STGF);
      asm volatile("cp.async.bulk.wait_group.read 0;" ::: "memory");
      PROF_AT(tid == 0, 14);
    }
    if (blockIdx.x == 0 && threadIdx.x == 128) asm volatile("st.relaxed.gpu.global.u32 [%0], %1;" ::"l"(p.epoch), "r"(tag) : "memory");
    if (!TAIL) {
      __syncwarp();
      cluster_arrive_relaxed();
      cluster_wait();
    }
  }
}

typedef CUresult (*EncodeFn)(CUtensorMap*, CUtensorMapDataType, cuuint32_t, void*, const cuuint64_t*, const cuuint64_t*,
                             const cuuint32_t*, const cuuint32_t*, CUtensorMapInterleave, CUtensorMapSwizzle,
                             CUtensorMapL2promotion, CUtensorMapFloatOOBfill);

void encode2d(EncodeFn fn, CUtensorMap* m, const void* ptr, uint64_t cols, uint64_t rows, uint32_t box_rows) {
  cuuint64_t dims[2] = {cols, rows};
  cuuint64_t strides[1] = {cols * 2};
  cuuint32_t box[2] = {64, box_rows};
  cuuint32_t es[2] = {1, 1};
  fn(m, CU_TENSOR_MAP_DATA_TYPE_BFLOAT16, 2, (void*)ptr, dims, strides, box, es, CU_TENSOR_MAP_INTERLEAVE_NONE,
     CU_TENSOR_MAP_SWIZZLE_128B, CU_TENSOR_MAP_L2_PROMOTION_L2_128B, CU_TENSOR_MAP_FLOAT_OOB_FILL_NONE);
}

}

extern "C" void kernel_launch(void* const* d_in, const int* in_sizes, int n_in, void* d_out, int out_size) {
  (void)in_sizes; (void)n_in; (void)out_size;
  void* fp = nullptr;
  cudaDriverEntryPointQueryResult qr;
  cudaGetDriverEntryPoint("cuTensorMapEncodeTiled", &fp, cudaEnableDefault, &qr);
  EncodeFn fn = (EncodeFn)fp;
  void *ph, *po, *ph2, *pact;
  cudaGetSymbolAddress(&ph, g_h);
  cudaGetSymbolAddress(&po, g_o);
  ph2 = ph;
  cudaGetSymbolAddress(&pact, g_act);
  Params p;
  encode2d(fn, &p.h, ph, DM, SEQ, 128);
  encode2d(fn, &p.o_ld, po, DM, SEQ, 128);
  encode2d(fn, &p.h2, ph2, DM, SEQ, 128);
  encode2d(fn, &p.act, pact, FF, SEQ, 128);
  encode2d(fn, &p.act_st, pact, FF, SEQ, 32);
  encode2d(fn, &p.wm, d_in[8], 6 * DM, DM, 64);
  encode2d(fn, &p.o_st, po, DM, SEQ, 32);
  encode2d(fn, &p.wqkv, d_in[1], 3 * DM, DM, 64);
  encode2d(fn, &p.wqkv32, d_in[1], 3 * DM, DM, 32);
  encode2d(fn, &p.wo, d_in[2], DM, DM, 64);
  encode2d(fn, &p.wg, d_in[4], FF, DM, 64);
  encode2d(fn, &p.wu, d_in[5], FF, DM, 64);
  encode2d(fn, &p.wd, d_in[6], DM, FF, 64);
  {
    cuuint64_t dims[3] = {DM, SEQ / 2, 2};
    cuuint64_t strides[2] = {DM * 4, DM * 2};
    cuuint32_t box[3] = {64, 16, 1};
    cuuint32_t es[3] = {1, 1, 1};
    fn(&p.out, CU_TENSOR_MAP_DATA_TYPE_BFLOAT16, 3, d_out, dims, strides, box, es, CU_TENSOR_MAP_INTERLEAVE_NONE,
       CU_TENSOR_MAP_SWIZZLE_128B, CU_TENSOR_MAP_L2_PROMOTION_L2_128B, CU_TENSOR_MAP_FLOAT_OOB_FILL_NONE);
  }
  p.x = (const bf16*)d_in[0];
  p.c = (const bf16*)d_in[7];
  p.wmod = (const bf16*)d_in[8];
  for (int cl = 0; cl < 64; cl++) {
    const int grp = cl < 4 ? 0 : (cl < 36 ? (cl - 4) & 7 : 1 + (cl - 36) % 7);
    const int j = cl < 4 ? 4 + cl : (cl < 36 ? (cl - 4) >> 3 : 4 + (cl - 36) / 7);
    p.slot[cl] = (uint8_t)(grp * 8 + j);
  }
  void* q;
  p.x1 = (uint4*)d_out;
  cudaGetSymbolAddress(&q, g_modll); p.modll = (uint4*)q;
  cudaGetSymbolAddress(&q, g_halo); p.halo = (uint4*)q;
  cudaGetSymbolAddress(&q, g_stats); p.stats1 = (uint4*)q; p.stats2 = p.stats1 + SEQ * 8;
  cudaGetSymbolAddress(&q, g_cnt); p.cnt = (unsigned*)q;
  cudaGetSymbolAddress(&q, g_epoch); p.epoch = (unsigned*)q;

  cudaFuncSetAttribute(fused_kernel, cudaFuncAttributeMaxDynamicSharedMemorySize, SMEM_BYTES);
  cudaLaunchConfig_t cfg = {};
  cfg.gridDim = dim3(NCTA + 4);
  cfg.blockDim = dim3(384);
  cfg.dynamicSmemBytes = SMEM_BYTES;
  cfg.stream = cudaStreamPerThread;
  cudaLaunchAttribute at[1];
  at[0].id = cudaLaunchAttributeClusterDimension;
  at[0].val.clusterDim.x = 2; at[0].val.clusterDim.y = 1; at[0].val.clusterDim.z = 1;
  cfg.attrs = at;
  cfg.numAttrs = 1;
  cudaLaunchKernelEx(&cfg, fused_kernel, p);
}
```

```cpp
#include <cuda_runtime.h>
#include <cuda_bf16.h>
#include <cuda.h>
#include <stdint.h>

typedef __nv_bfloat16 bf16;

#define PAUSE 200
#define WMDELAY 2000
#define BDELAY 1500
#define NPRE0 4
#define NPRE1 1
#define ALIAS 1

__device__ __forceinline__ void wgmma_ss_n128(float (&d)[64], uint32_t da, uint32_t db, int scale_d) {
  asm volatile("{\n.reg .pred p;\n.reg .b64 da, db;\nsetp.ne.b32 p, %66, 0;\n"
    "mov.b64 da, {%64, 0x40000040};\nmov.b64 db, {%65, 0x40000040};\n"
    "wgmma.mma_async.sync.aligned.m64n128k16.f32.bf16.bf16 "
    "{%0, %1, %2, %3, %4, %5, %6, %7, %8, %9, %10, %11, %12, %13, %14, %15, "
    "%16, %17, %18, %19, %20, %21, %22, %23, %24, %25, %26, %27, %28, %29, %30, %31, "
    "%32, %33, %34, %35, %36, %37, %38, %39, %40, %41, %42, %43, %44, %45, %46, %47, "
    "%48, %49, %50, %51, %52, %53, %54, %55, %56, %57, %58, %59, %60, %61, %62, %63}, "
    "da, db, p, 1, 1, 0, 1;\n}\n"
    : "+f"(d[0]), "+f"(d[1]), "+f"(d[2]), "+f"(d[3]), "+f"(d[4]), "+f"(d[5]), "+f"(d[6]), "+f"(d[7]),
      "+f"(d[8]), "+f"(d[9]), "+f"(d[10]), "+f"(d[11]), "+f"(d[12]), "+f"(d[13]), "+f"(d[14]), "+f"(d[15]),
      "+f"(d[16]), "+f"(d[17]), "+f"(d[18]), "+f"(d[19]), "+f"(d[20]), "+f"(d[21]), "+f"(d[22]), "+f"(d[23]),
      "+f"(d[24]), "+f"(d[25]), "+f"(d[26]), "+f"(d[27]), "+f"(d[28]), "+f"(d[29]), "+f"(d[30]), "+f"(d[31]),
      "+f"(d[32]), "+f"(d[33]), "+f"(d[34]), "+f"(d[35]), "+f"(d[36]), "+f"(d[37]), "+f"(d[38]), "+f"(d[39]),
      "+f"(d[40]), "+f"(d[41]), "+f"(d[42]), "+f"(d[43]), "+f"(d[44]), "+f"(d[45]), "+f"(d[46]), "+f"(d[47]),
      "+f"(d[48]), "+f"(d[49]), "+f"(d[50]), "+f"(d[51]), "+f"(d[52]), "+f"(d[53]), "+f"(d[54]), "+f"(d[55]),
      "+f"(d[56]), "+f"(d[57]), "+f"(d[58]), "+f"(d[59]), "+f"(d[60]), "+f"(d[61]), "+f"(d[62]), "+f"(d[63])
    : "r"(da), "r"(db), "r"(scale_d));
}

__device__ __forceinline__ void wgmma_ss_n192(float (&d)[96], uint32_t da, uint32_t db, int scale_d) {
  asm volatile("{\n.reg .pred p;\n.reg .b64 da, db;\nsetp.ne.b32 p, %98, 0;\n"
    "mov.b64 da, {%96, 0x40000040};\nmov.b64 db, {%97, 0x40000040};\n"
    "wgmma.mma_async.sync.aligned.m64n192k16.f32.bf16.bf16 "
    "{%0, %1, %2, %3, %4, %5, %6, %7, %8, %9, %10, %11, %12, %13, %14, %15, "
    "%16, %17, %18, %19, %20, %21, %22, %23, %24, %25, %26, %27, %28, %29, %30, %31, "
    "%32, %33, %34, %35, %36, %37, %38, %39, %40, %41, %42, %43, %44, %45, %46, %47, "
    "%48, %49, %50, %51, %52, %53, %54, %55, %56, %57, %58, %59, %60, %61, %62, %63, "
    "%64, %65, %66, %67, %68, %69, %70, %71, %72, %73, %74, %75, %76, %77, %78, %79, "
    "%80, %81, %82, %83, %84, %85, %86, %87, %88, %89, %90, %91, %92, %93, %94, %95}, "
    "da, db, p, 1, 1, 0, 1;\n}\n"
    : "+f"(d[0]), "+f"(d[1]), "+f"(d[2]), "+f"(d[3]), "+f"(d[4]), "+f"(d[5]), "+f"(d[6]), "+f"(d[7]),
      "+f"(d[8]), "+f"(d[9]), "+f"(d[10]), "+f"(d[11]), "+f"(d[12]), "+f"(d[13]), "+f"(d[14]), "+f"(d[15]),
      "+f"(d[16]), "+f"(d[17]), "+f"(d[18]), "+f"(d[19]), "+f"(d[20]), "+f"(d[21]), "+f"(d[22]), "+f"(d[23]),
      "+f"(d[24]), "+f"(d[25]), "+f"(d[26]), "+f"(d[27]), "+f"(d[28]), "+f"(d[29]), "+f"(d[30]), "+f"(d[31]),
      "+f"(d[32]), "+f"(d[33]), "+f"(d[34]), "+f"(d[35]), "+f"(d[36]), "+f"(d[37]), "+f"(d[38]), "+f"(d[39]),
      "+f"(d[40]), "+f"(d[41]), "+f"(d[42]), "+f"(d[43]), "+f"(d[44]), "+f"(d[45]), "+f"(d[46]), "+f"(d[47]),
      "+f"(d[48]), "+f"(d[49]), "+f"(d[50]), "+f"(d[51]), "+f"(d[52]), "+f"(d[53]), "+f"(d[54]), "+f"(d[55]),
      "+f"(d[56]), "+f"(d[57]), "+f"(d[58]), "+f"(d[59]), "+f"(d[60]), "+f"(d[61]), "+f"(d[62]), "+f"(d[63]),
      "+f"(d[64]), "+f"(d[65]), "+f"(d[66]), "+f"(d[67]), "+f"(d[68]), "+f"(d[69]), "+f"(d[70]), "+f"(d[71]),
      "+f"(d[72]), "+f"(d[73]), "+f"(d[74]), "+f"(d[75]), "+f"(d[76]), "+f"(d[77]), "+f"(d[78]), "+f"(d[79]),
      "+f"(d[80]), "+f"(d[81]), "+f"(d[82]), "+f"(d[83]), "+f"(d[84]), "+f"(d[85]), "+f"(d[86]), "+f"(d[87]),
      "+f"(d[88]), "+f"(d[89]), "+f"(d[90]), "+f"(d[91]), "+f"(d[92]), "+f"(d[93]), "+f"(d[94]), "+f"(d[95])
    : "r"(da), "r"(db), "r"(scale_d));
}

__device__ __forceinline__ void wgmma_ss_n256(float (&d)[128], uint32_t da, uint32_t db, int scale_d) {
  asm volatile("{\n.reg .pred p;\n.reg .b64 da, db;\nsetp.ne.b32 p, %130, 0;\n"
    "mov.b64 da, {%128, 0x40000040};\nmov.b64 db, {%129, 0x40000040};\n"
    "wgmma.mma_async.sync.aligned.m64n256k16.f32.bf16.bf16 "
    "{%0, %1, %2, %3, %4, %5, %6, %7, %8, %9, %10, %11, %12, %13, %14, %15, "
    "%16, %17, %18, %19, %20, %21, %22, %23, %24, %25, %26, %27, %28, %29, %30, %31, "
    "%32, %33, %34, %35, %36, %37, %38, %39, %40, %41, %42, %43, %44, %45, %46, %47, "
    "%48, %49, %50, %51, %52, %53, %54, %55, %56, %57, %58, %59, %60, %61, %62, %63, "
    "%64, %65, %66, %67, %68, %69, %70, %71, %72, %73, %74, %75, %76, %77, %78, %79, "
    "%80, %81, %82, %83, %84, %85, %86, %87, %88, %89, %90, %91, %92, %93, %94, %95, "
    "%96, %97, %98, %99, %100, %101, %102, %103, %104, %105, %106, %107, %108, %109, %110, %111, "
    "%112, %113, %114, %115, %116, %117, %118, %119, %120, %121, %122, %123, %124, %125, %126, %127}, "
    "da, db, p, 1, 1, 0, 1;\n}\n"
    : "+f"(d[0]), "+f"(d[1]), "+f"(d[2]), "+f"(d[3]), "+f"(d[4]), "+f"(d[5]), "+f"(d[6]), "+f"(d[7]),
      "+f"(d[8]), "+f"(d[9]), "+f"(d[10]), "+f"(d[11]), "+f"(d[12]), "+f"(d[13]), "+f"(d[14]), "+f"(d[15]),
      "+f"(d[16]), "+f"(d[17]), "+f"(d[18]), "+f"(d[19]), "+f"(d[20]), "+f"(d[21]), "+f"(d[22]), "+f"(d[23]),
      "+f"(d[24]), "+f"(d[25]), "+f"(d[26]), "+f"(d[27]), "+f"(d[28]), "+f"(d[29]), "+f"(d[30]), "+f"(d[31]),
      "+f"(d[32]), "+f"(d[33]), "+f"(d[34]), "+f"(d[35]), "+f"(d[36]), "+f"(d[37]), "+f"(d[38]), "+f"(d[39]),
      "+f"(d[40]), "+f"(d[41]), "+f"(d[42]), "+f"(d[43]), "+f"(d[44]), "+f"(d[45]), "+f"(d[46]), "+f"(d[47]),
      "+f"(d[48]), "+f"(d[49]), "+f"(d[50]), "+f"(d[51]), "+f"(d[52]), "+f"(d[53]), "+f"(d[54]), "+f"(d[55]),
      "+f"(d[56]), "+f"(d[57]), "+f"(d[58]), "+f"(d[59]), "+f"(d[60]), "+f"(d[61]), "+f"(d[62]), "+f"(d[63]),
      "+f"(d[64]), "+f"(d[65]), "+f"(d[66]), "+f"(d[67]), "+f"(d[68]), "+f"(d[69]), "+f"(d[70]), "+f"(d[71]),
      "+f"(d[72]), "+f"(d[73]), "+f"(d[74]), "+f"(d[75]), "+f"(d[76]), "+f"(d[77]), "+f"(d[78]), "+f"(d[79]),
      "+f"(d[80]), "+f"(d[81]), "+f"(d[82]), "+f"(d[83]), "+f"(d[84]), "+f"(d[85]), "+f"(d[86]), "+f"(d[87]),
      "+f"(d[88]), "+f"(d[89]), "+f"(d[90]), "+f"(d[91]), "+f"(d[92]), "+f"(d[93]), "+f"(d[94]), "+f"(d[95]),
      "+f"(d[96]), "+f"(d[97]), "+f"(d[98]), "+f"(d[99]), "+f"(d[100]), "+f"(d[101]), "+f"(d[102]), "+f"(d[103]),
      "+f"(d[104]), "+f"(d[105]), "+f"(d[106]), "+f"(d[107]), "+f"(d[108]), "+f"(d[109]), "+f"(d[110]), "+f"(d[111]),
      "+f"(d[112]), "+f"(d[113]), "+f"(d[114]), "+f"(d[115]), "+f"(d[116]), "+f"(d[117]), "+f"(d[118]), "+f"(d[119]),
      "+f"(d[120]), "+f"(d[121]), "+f"(d[122]), "+f"(d[123]), "+f"(d[124]), "+f"(d[125]), "+f"(d[126]), "+f"(d[127])
    : "r"(da), "r"(db), "r"(scale_d));
}

namespace {

constexpr int SEQ = 2048, DM = 1024, FF = 3584;
constexpr int NCTA = 128;

constexpr uint32_t STG_OFF = 196608;
constexpr uint32_t MISC_OFF = STG_OFF + 32768;
constexpr uint32_t SMEM_BYTES = MISC_OFF + 3072;
constexpr uint32_t RED_OFF = 2 * 49152;
constexpr uint32_t MODB_OFF = MISC_OFF + 512;

enum { B_FQ = 0, B_EQ = 4, B_FW = 8, B_EW = 14, B_FG = 20, B_EG = 24, B_FD = 28, B_ED = 34,
       B_STGF = 40, B_MODB = 42, B_MODA = 45, B_RDY = 48, B_STGE = 56, B_COUNT = 58 };
enum { C_H = 0, C_O = 1, C_H2 = 3, C_ACT = 4, C_HA = 8, C_H2A = 9 };

struct Params {
  CUtensorMap h, o_ld, o_st, h2, act, out, wqkv, wqkv32, wo, wg, wu, wd, act_st, wm;
  const bf16* x;
  const bf16* c;
  const bf16* wmod;
  uint4* x1;
  uint4* modll;
  uint4* halo;
  uint4* stats1;
  uint4* stats2;
  unsigned* cnt;
  unsigned* epoch;
  uint8_t slot[64];
};

__device__ __align__(1024) bf16 g_h[SEQ * DM];
__device__ __align__(1024) bf16 g_o[SEQ * DM];
__device__ __align__(1024) bf16 g_act[SEQ * FF];
__device__ __align__(1024) uint4 g_modll[3072 / 2];
__device__ __align__(1024) uint4 g_halo[16 * 8 * 2 * 2 * 8 * 32];
__device__ __align__(1024) uint4 g_stats[2 * SEQ * 8];
__device__ __align__(1024) unsigned g_cnt[16 * 32];
__device__ uint4 g_epoch;
#define TR(off)

__device__ __forceinline__ uint32_t smem_u32(const void* p) { return (uint32_t)__cvta_generic_to_shared(p); }
__device__ __forceinline__ void mbar_init(uint32_t bar, uint32_t count) {
  asm volatile("mbarrier.init.shared::cta.b64 [%0], %1;" ::"r"(bar), "r"(count));
}
__device__ __forceinline__ void mbar_arrive(uint32_t bar) {
  asm volatile("mbarrier.arrive.shared::cta.b64 _, [%0];" ::"r"(bar) : "memory");
}
__device__ __forceinline__ void mbar_arrive_cluster(uint32_t cluster_addr) {
  asm volatile("mbarrier.arrive.shared::cluster.b64 _, [%0];" ::"r"(cluster_addr) : "memory");
}
__device__ __forceinline__ uint32_t mapa(uint32_t addr, uint32_t cta) {
  uint32_t r;
  asm volatile("mapa.shared::cluster.u32 %0, %1, %2;" : "=r"(r) : "r"(addr), "r"(cta));
  return r;
}
__device__ __forceinline__ void mbar_wait(uint32_t bar, uint32_t parity) {
  asm volatile(
      "{\n.reg .pred p;\n"
      "WAIT_%=:\n"
      "mbarrier.try_wait.parity.shared::cta.b64 p, [%0], %1;\n"
      "@!p bra WAIT_%=;\n}\n" ::"r"(bar), "r"(parity) : "memory");
}
__device__ __forceinline__ void mbar_wait_watchdog(uint32_t bar, uint32_t parity) {
  asm volatile(
      "{\n.reg .pred p;\n.reg .u64 t0, t1;\nmov.u64 t0, %%globaltimer;\n"
      "WAIT_%=:\n"
      "mbarrier.try_wait.parity.shared::cta.b64 p, [%0], %1;\n"
      "@p bra DONE_%=;\n"
      "mov.u64 t1, %%globaltimer;\n"
      "sub.u64 t1, t1, t0;\n"
      "setp.lt.u64 p, t1, 2000000000;\n"
      "@p bra WAIT_%=;\n"
      "trap;\n"
      "DONE_%=:\n}\n" ::"r"(bar), "r"(parity) : "memory");
}
__device__ __forceinline__ void cnt_wait(const unsigned* p, unsigned target) {
  asm volatile(
      "{\n.reg .pred p;\n.reg .u32 v;\n.reg .s32 d;\n"
      "WAIT_%=:\n"
      "ld.relaxed.gpu.global.u32 v, [%0];\n"
      "sub.s32 d, v, %1;\n"
      "setp.lt.s32 p, d, 0;\n"
      "@p bra WAIT_%=;\n"
      "fence.proxy.async.global;\n"
      "}\n" ::"l"(p), "r"(target) : "memory");
}
__device__ __forceinline__ void cnt_wait_lazy(const unsigned* p, unsigned target) {
  asm volatile(
      "{\n.reg .pred p;\n.reg .u32 v;\n.reg .s32 d;\n"
      "WAIT_%=:\n"
      "nanosleep.u32 400;\n"
      "ld.relaxed.gpu.global.u32 v, [%0];\n"
      "sub.s32 d, v, %1;\n"
      "setp.lt.s32 p, d, 0;\n"
      "@p bra WAIT_%=;\n"
      "fence.proxy.async.global;\n"
      "}\n" ::"l"(p), "r"(target) : "memory");
}
__device__ __forceinline__ void cnt_signal(unsigned* p) {
  asm volatile("{\n.reg .pred p;\nelect.sync _|p, 0xffffffff;\n@p red.relaxed.gpu.global.add.u32 [%0], 1;\n}\n" ::"l"(p) : "memory");
}
__device__ __forceinline__ void ll_store(uint4* p, uint32_t a, uint32_t b, uint32_t tag) {
  asm volatile("st.relaxed.gpu.global.v2.b64 [%0], {%1, %2};" ::"l"(p), "l"((uint64_t)a | ((uint64_t)tag << 32)),
               "l"((uint64_t)b | ((uint64_t)tag << 32)) : "memory");
}
__device__ __forceinline__ uint4 ll_peek(const uint4* p) {
  uint4 v;
  asm volatile("ld.relaxed.gpu.global.v4.u32 {%0, %1, %2, %3}, [%4];" : "=r"(v.x), "=r"(v.y), "=r"(v.z), "=r"(v.w) : "l"(p) : "memory");
  return v;
}
template <int N, int SLEEP = 0, class F>
__device__ __forceinline__ void ll_poll(F addr, uint32_t tag, uint32_t (&out)[2 * N]) {
  for (;;) {
    uint4 v[N];
#pragma unroll
    for (int i = 0; i < N; i++) v[i] = ll_peek(addr(i));
    uint32_t bad = 0;
#pragma unroll
    for (int i = 0; i < N; i++) {
      bad |= (v[i].y ^ tag) | (v[i].w ^ tag);
      out[2 * i] = v[i].x;
      out[2 * i + 1] = v[i].z;
    }
    if (__all_sync(~0u, bad == 0)) break;
    if (SLEEP) __nanosleep(SLEEP);
  }
}
constexpr uint64_t POLICY_EVICT_FIRST = 0x12F0000000000000ull;
__device__ __forceinline__ void expect_tx_elect(uint32_t bar, uint32_t bytes) {
  asm volatile("{\n.reg .pred p;\nelect.sync _|p, 0xffffffff;\n@p mbarrier.arrive.expect_tx.shared::cta.b64 _, [%0], %1;\n}\n" ::"r"(bar), "r"(bytes) : "memory");
}
__device__ __forceinline__ void arrive_elect(uint32_t bar) {
  asm volatile("{\n.reg .pred p;\nelect.sync _|p, 0xffffffff;\n@p mbarrier.arrive.shared::cta.b64 _, [%0];\n}\n" ::"r"(bar) : "memory");
}
__device__ __forceinline__ void tma_load(uint32_t dst, const CUtensorMap* m, uint32_t bar, int c0, int c1) {
  asm volatile("{\n.reg .pred p;\nelect.sync _|p, 0xffffffff;\n"
               "@p cp.async.bulk.tensor.2d.shared::cluster.global.mbarrier::complete_tx::bytes [%0], [%1, {%3, %4}], [%2];\n}\n"
               ::"r"(dst), "l"(m), "r"(bar), "r"(c0), "r"(c1) : "memory");
}
__device__ __forceinline__ void tma_load_mc(uint32_t dst, const CUtensorMap* m, uint32_t bar, int c0, int c1) {
  asm volatile("{\n.reg .pred p;\nelect.sync _|p, 0xffffffff;\n"
               "@p cp.async.bulk.tensor.2d.shared::cluster.global.mbarrier::complete_tx::bytes.multicast::cluster.L2::cache_hint [%0], [%1, {%3, %4}], [%2], %5, %6;\n}\n"
               ::"r"(dst), "l"(m), "r"(bar), "r"(c0), "r"(c1), "h"((uint16_t)3), "l"(POLICY_EVICT_FIRST) : "memory");
}
__device__ __forceinline__ void tma_load_ef(uint32_t dst, const CUtensorMap* m, uint32_t bar, int c0, int c1) {
  asm volatile("{\n.reg .pred p;\nelect.sync _|p, 0xffffffff;\n"
               "@p cp.async.bulk.tensor.2d.shared::cluster.global.mbarrier::complete_tx::bytes.L2::cache_hint [%0], [%1, {%3, %4}], [%2], %5;\n}\n"
               ::"r"(dst), "l"(m), "r"(bar), "r"(c0), "r"(c1), "l"(POLICY_EVICT_FIRST) : "memory");
}
__device__ __forceinline__ void tma_store2(const CUtensorMap* m, uint32_t src, int c0, int c1) {
  asm volatile("{\n.reg .pred p;\nelect.sync _|p, 0xffffffff;\n"
               "@p cp.async.bulk.tensor.2d.global.shared::cta.bulk_group [%0, {%2, %3}], [%1];\n}\n"
               ::"l"(m), "r"(src), "r"(c0), "r"(c1) : "memory");
}
__device__ __forceinline__ void tma_store3(const CUtensorMap* m, uint32_t src, int c0, int c1, int c2) {
  asm volatile("{\n.reg .pred p;\nelect.sync _|p, 0xffffffff;\n"
               "@p cp.async.bulk.tensor.3d.global.shared::cta.bulk_group [%0, {%2, %3, %4}], [%1];\n}\n"
               ::"l"(m), "r"(src), "r"(c0), "r"(c1), "r"(c2) : "memory");
}
__device__ __forceinline__ void store_pause(bool sleep) {
  asm volatile("cp.async.bulk.commit_group;" ::: "memory");
  asm volatile("cp.async.bulk.wait_group.read 0;" ::: "memory");
  if (sleep) __nanosleep(PAUSE);
}
__device__ __forceinline__ void prefetch_map(const CUtensorMap* m) {
  asm volatile("prefetch.tensormap [%0];" ::"l"(m) : "memory");
}
__device__ __forceinline__ void wg_fence() { asm volatile("wgmma.fence.sync.aligned;" ::: "memory"); }
__device__ __forceinline__ void wg_commit() { asm volatile("wgmma.commit_group.sync.aligned;" ::: "memory"); }
template <int N>
__device__ __forceinline__ void wg_wait() { asm volatile("wgmma.wait_group.sync.aligned %0;" ::"n"(N) : "memory"); }
__device__ __forceinline__ void bar_sync(int id, int n) { asm volatile("bar.sync %0, %1;" ::"r"(id), "r"(n) : "memory"); }
__device__ __forceinline__ void wg_bar(int cw) {
  asm volatile("{\n.reg .pred p;\nsetp.ne.s32 p, %0, 0;\n@p bar.sync 3, 128;\n@!p bar.sync 2, 128;\n}\n" ::"r"(cw) : "memory");
}
__device__ __forceinline__ void cluster_arrive_relaxed() { asm volatile("barrier.cluster.arrive.relaxed.aligned;" ::: "memory"); }
__device__ __forceinline__ void cluster_wait() { asm volatile("barrier.cluster.wait.acquire.aligned;" ::: "memory"); }
__device__ __forceinline__ uint32_t load_epoch(const unsigned* p) {
  uint32_t e;
  asm volatile("ld.relaxed.gpu.global.u32 %0, [%1];" : "=r"(e) : "l"(p) : "memory");
  return e;
}
__device__ __forceinline__ uint32_t pack2(float lo, float hi) {
  uint32_t r;
  asm("cvt.rn.bf16x2.f32 %0, %1, %2;" : "=r"(r) : "f"(hi), "f"(lo));
  return r;
}
__device__ __forceinline__ float bf_lo(uint32_t v) { return __uint_as_float(v << 16); }
__device__ __forceinline__ float bf_hi(uint32_t v) { return __uint_as_float(v & 0xffff0000u); }
__device__ __forceinline__ float bf_round(float v) { return __bfloat162float(__float2bfloat16_rn(v)); }
__device__ __forceinline__ float silu_f(float v) { return __fdividef(v, 1.0f + __expf(-v)); }
__device__ __forceinline__ uint4 ldg_nc(const void* p) {
  uint4 v;
  asm volatile("ld.global.nc.L1::no_allocate.v4.u32 {%0, %1, %2, %3}, [%4];" : "=r"(v.x), "=r"(v.y), "=r"(v.z), "=r"(v.w) : "l"(p));
  return v;
}
__device__ __forceinline__ void stmatrix4(uint32_t addr, uint32_t a, uint32_t b, uint32_t c, uint32_t d) {
  asm volatile("stmatrix.sync.aligned.m8n8.x4.shared.b16 [%0], {%1, %2, %3, %4};" ::"r"(addr), "r"(a), "r"(b), "r"(c), "r"(d) : "memory");
}
__device__ __forceinline__ void stmatrix2(uint32_t addr, uint32_t a, uint32_t b) {
  asm volatile("stmatrix.sync.aligned.m8n8.x2.shared.b16 [%0], {%1, %2};" ::"r"(addr), "r"(a), "r"(b) : "memory");
}
__device__ __forceinline__ void stmatrix1(uint32_t addr, uint32_t a) {
  asm volatile("stmatrix.sync.aligned.m8n8.x1.shared.b16 [%0], {%1};" ::"r"(addr), "r"(a) : "memory");
}
__device__ __forceinline__ uint32_t movmatrix(uint32_t a) {
  uint32_t d;
  asm("movmatrix.sync.aligned.m8n8.trans.b16 %0, %1;" : "=r"(d) : "r"(a));
  return d;
}
__device__ __forceinline__ void mma16816(float (&d)[4], uint32_t a0, uint32_t a1, uint32_t a2, uint32_t a3, uint32_t b0, uint32_t b1) {
  asm("mma.sync.aligned.m16n8k16.row.col.f32.bf16.bf16.f32 {%0, %1, %2, %3}, {%4, %5, %6, %7}, {%8, %9}, {%0, %1, %2, %3};"
               : "+f"(d[0]), "+f"(d[1]), "+f"(d[2]), "+f"(d[3]) : "r"(a0), "r"(a1), "r"(a2), "r"(a3), "r"(b0), "r"(b1));
}
__device__ __forceinline__ void mma1688(float (&d)[4], uint32_t a0, uint32_t a1, uint32_t b0) {
  asm("mma.sync.aligned.m16n8k8.row.col.f32.bf16.bf16.f32 {%0, %1, %2, %3}, {%4, %5}, {%6}, {%0, %1, %2, %3};"
               : "+f"(d[0]), "+f"(d[1]), "+f"(d[2]), "+f"(d[3]) : "r"(a0), "r"(a1), "r"(b0));
}
__device__ __forceinline__ void ldmatrix4t(uint32_t (&b)[4], uint32_t addr) {
  asm volatile("ldmatrix.sync.aligned.m8n8.x4.trans.shared.b16 {%0, %1, %2, %3}, [%4];" : "=r"(b[0]), "=r"(b[1]), "=r"(b[2]), "=r"(b[3]) : "r"(addr) : "memory");
}
__device__ __forceinline__ void ldmatrix4(uint32_t& a, uint32_t& b, uint32_t& c, uint32_t& d, uint32_t addr) {
  asm volatile("ldmatrix.sync.aligned.m8n8.x4.shared.b16 {%0, %1, %2, %3}, [%4];" : "=r"(a), "=r"(b), "=r"(c), "=r"(d) : "r"(addr) : "memory");
}
__device__ __forceinline__ void cp_async16(uint32_t dst, const void* src) {
  asm volatile("cp.async.cg.shared.global.L2::cache_hint [%0], [%1], 16, %2;" ::"r"(dst), "l"(src), "l"(POLICY_EVICT_FIRST) : "memory");
}
__device__ __forceinline__ uint32_t lds32(uint32_t addr) {
  uint32_t v;
  asm volatile("ld.shared.u32 %0, [%1];" : "=r"(v) : "r"(addr) : "memory");
  return v;
}
__device__ __forceinline__ void sts64f(uint32_t addr, float a, float b) {
  asm volatile("st.shared.v2.f32 [%0], {%1, %2};" ::"r"(addr), "f"(a), "f"(b) : "memory");
}
constexpr float QK_SCALE = 0.17677669529663687f;
__device__ __forceinline__ float softmax8(float& p0, float& p1) {
  float m = fmaxf(p0, p1);
  m = fmaxf(m, __shfl_xor_sync(~0u, m, 1));
  m = fmaxf(m, __shfl_xor_sync(~0u, m, 2));
  asm("ex2.approx.ftz.f32 %0, %1;" : "=f"(p0) : "f"((p0 - m) * 1.4426950408889634f));
  asm("ex2.approx.ftz.f32 %0, %1;" : "=f"(p1) : "f"((p1 - m) * 1.4426950408889634f));
  float s = p0 + p1;
  s += __shfl_xor_sync(~0u, s, 1);
  s += __shfl_xor_sync(~0u, s, 2);
  float r;
  asm("rcp.approx.ftz.f32 %0, %1;" : "=f"(r) : "f"(s));
  return r;
}
__device__ __forceinline__ void sts128(uint32_t addr, uint32_t a, uint32_t b, uint32_t c, uint32_t d) {
  asm volatile("st.shared.v4.u32 [%0], {%1, %2, %3, %4};" ::"r"(addr), "r"(a), "r"(b), "r"(c), "r"(d) : "memory");
}
__device__ __forceinline__ uint4 lds128(uint32_t addr) {
  uint4 v;
  asm volatile("ld.shared.v4.u32 {%0, %1, %2, %3}, [%4];" : "=r"(v.x), "=r"(v.y), "=r"(v.z), "=r"(v.w) : "r"(addr) : "memory");
  return v;
}
__device__ __forceinline__ float2 lds64f(uint32_t addr) {
  float2 v;
  asm volatile("ld.shared.v2.f32 {%0, %1}, [%2];" : "=f"(v.x), "=f"(v.y) : "r"(addr) : "memory");
  return v;
}
#define PROF_AT(cond, slot) do {} while (0)

constexpr uint32_t SMEM_BASE = 1024;
constexpr uint32_t DESC_A = (1u << 16) | (SMEM_BASE >> 4);
constexpr uint32_t DESC_B = ((8192u >> 4) << 16) | ((SMEM_BASE + 16384) >> 4);

template <int BN> struct Wg;
template <> struct Wg<128> { static __device__ __forceinline__ void mma(float (&d)[64], uint32_t a, uint32_t b, int s) { wgmma_ss_n128(d, a, b, s); } };
template <> struct Wg<192> { static __device__ __forceinline__ void mma(float (&d)[96], uint32_t a, uint32_t b, int s) { wgmma_ss_n192(d, a, b, s); } };
template <> struct Wg<256> { static __device__ __forceinline__ void mma(float (&d)[128], uint32_t a, uint32_t b, int s) { wgmma_ss_n256(d, a, b, s); } };

struct Ring {
  uint32_t full0, rel0;
  int s;
  uint32_t ph;
  bool releaser;
};

template <int N>
__device__ __forceinline__ void fence_regs(float (&a)[N]) {
#pragma unroll
  for (int i = 0; i < N; i++) asm volatile("" : "+f"(a[i])::"memory");
}

template <int BN, int NST, uint32_t STAGE>
__device__ __forceinline__ void kblock(float (&acc)[BN / 2], Ring& g, uint32_t a_addr, bool zero, uint32_t& prev) {
  mbar_wait(g.full0 + 8 * g.s, g.ph);
  const uint32_t da = DESC_A + (a_addr >> 4);
  const uint32_t db = DESC_B + g.s * (STAGE >> 4);
  wg_fence();
#pragma unroll
  for (int k = 0; k < 4; k++) Wg<BN>::mma(acc, da + k * 2, db + k * 128, !(zero && k == 0));
  wg_commit();
  wg_wait<1>();
  if (prev != 0) mbar_arrive_cluster(prev);
  prev = g.releaser ? g.rel0 + 8 * g.s : 0u;
  if (++g.s == NST) { g.s = 0; g.ph ^= 1; }
}
template <int N>
__device__ __forceinline__ void tile_end(float (&acc)[N], uint32_t& prev) {
  wg_wait<0>();
  if (prev != 0) mbar_arrive_cluster(prev);
  prev = 0;
  fence_regs(acc);
}

__device__ __forceinline__ int other_kb(int q, int j) {
  const int ch = q >= 7, jj = q - 7 * ch;
  return 2 * (jj < j ? jj : jj + 1) + ch;
}
__device__ __forceinline__ int own_first(int it, int j) {
  return it >= 16 ? (it & 15) : (it < 2 ? 2 * j + it : other_kb(it - 2, j));
}
__device__ __forceinline__ int qkv_kb(int it, int j) {
  return it < 4 ? 2 * j + (it & 1) : other_kb(it < 18 ? it - 4 : it - 18, j);
}
__device__ __forceinline__ int wo_k(int it, int j) {
  return it < 8 ? it * 128 : (it == 8 ? j : (it - 9 < j ? it - 9 : it - 8)) * 128 + 64;
}
__device__ __forceinline__ int down_k(int it) {
  const int r = (it >> 4) - 1, idx = it & 15;
  return r < 0 ? idx * 64 : (r < 3 ? (idx >> 1) * 448 + r * 128 + (idx & 1) * 64 : idx * 448 + 384);
}
__device__ __forceinline__ void wait_p3_free(uint32_t empty3, int i) {
  mbar_wait(empty3 + 8 * ((i * 2) / 3), 1);
  mbar_wait(empty3 + 8 * ((i * 2 + 1) / 3), 1);
}
__device__ __forceinline__ void wait_p2_free(uint32_t empty2, int i) {
  const int w0 = (i * 3) / 2, w1 = (i * 3 + 2) / 2;
  mbar_wait(empty2 + 8 * w0, w0 < 4 ? 0 : 1);
  mbar_wait(empty2 + 8 * w1, w1 < 4 ? 0 : 1);
}

__device__ __forceinline__ void chan(float& m, float& q, float m2, float q2, float n) {
  const float d = m2 - m;
  m = 0.5f * (m + m2);
  q = q + q2 + d * d * (0.5f * n);
}

template <int N>
__device__ __forceinline__ void row_stats(const uint32_t (&ll)[N], float& mean, float& rstd) {
  float ma = __uint_as_float(ll[0]), qa = __uint_as_float(ll[1]), mb = __uint_as_float(ll[4]), qb = __uint_as_float(ll[5]);
  chan(ma, qa, __uint_as_float(ll[2]), __uint_as_float(ll[3]), 128.f);
  chan(mb, qb, __uint_as_float(ll[6]), __uint_as_float(ll[7]), 128.f);
  chan(ma, qa, mb, qb, 256.f);
  const float mo = __shfl_xor_sync(~0u, ma, 16), qo = __shfl_xor_sync(~0u, qa, 16);
  chan(ma, qa, mo, qo, 512.f);
  mean = ma;
  rstd = rsqrtf(qa * (1.0f / DM) + 1e-5f);
}

__device__ __forceinline__ void publish_stats(const uint32_t (&xl)[16], const uint32_t (&xh)[16], uint4* slot, int lane, uint32_t tag) {
  float ds[4] = {0.f, 0.f, 0.f, 0.f}, dl[4] = {0.f, 0.f, 0.f, 0.f}, dh[4] = {0.f, 0.f, 0.f, 0.f};
#pragma unroll
  for (int q = 0; q < 8; q++) {
    mma16816(ds, xl[2 * q], xh[2 * q], xl[2 * q + 1], xh[2 * q + 1], 0x3f803f80u, 0x3f803f80u);
    mma16816(dl, xl[2 * q], xh[2 * q], xl[2 * q + 1], xh[2 * q + 1], xl[2 * q], xl[2 * q + 1]);
    mma16816(dh, xl[2 * q], xh[2 * q], xl[2 * q + 1], xh[2 * q + 1], xh[2 * q], xh[2 * q + 1]);
  }
  const int r = lane >> 2;
  if ((lane & 3) == (r >> 1)) {
    const float ml = ds[0] * (1.0f / 128), mh = ds[2] * (1.0f / 128);
    const float ql = fmaxf(((r & 1) ? dl[1] : dl[0]) - ds[0] * ml, 0.f), qh = fmaxf(((r & 1) ? dh[3] : dh[2]) - ds[2] * mh, 0.f);
    ll_store(slot + r, __float_as_uint(ml), __float_as_uint(ql), tag);
    ll_store(slot + r + 8, __float_as_uint(mh), __float_as_uint(qh), tag);
  }
  __syncwarp();
}

__device__ __forceinline__ void stage_slab(uint32_t chunk, int warp, int lane, const uint32_t (&lo)[8], const uint32_t (&hi)[8]) {
  const int row = warp * 16 + (lane & 7) + ((lane >> 3) & 1) * 8;
  const uint32_t rbase = chunk + row * 128;
#pragma unroll
  for (int q = 0; q < 4; q++) {
    const int grp = 2 * q + (lane >> 4);
    stmatrix4(rbase + ((grp ^ (row & 7)) << 4), lo[2 * q], hi[2 * q], lo[2 * q + 1], hi[2 * q + 1]);
  }
}
__device__ __forceinline__ float silu_mul(float g, float u) {
  float e, r;
  asm("ex2.approx.ftz.f32 %0, %1;" : "=f"(e) : "f"(g * -1.4426950408889634f));
  asm("rcp.approx.ftz.f32 %0, %1;" : "=f"(r) : "f"(1.0f + e));
  return g * r * u;
}
__device__ __forceinline__ uint32_t swiglu2(uint32_t g2, uint32_t u2) {
  asm volatile("" : "+r"(g2));
  return pack2(silu_mul(bf_lo(g2), bf_lo(u2)), silu_mul(bf_hi(g2), bf_hi(u2)));
}
__device__ __forceinline__ void stage_done(uint32_t bar, int lane) {
  asm volatile("fence.proxy.async.shared::cta;" ::: "memory");
  __syncwarp();
  if (lane == 0) mbar_arrive(bar);
}

__device__ __forceinline__ int fresh_tid() {
  int t;
  asm volatile("mov.u32 %0, %%tid.x;" : "=r"(t));
  return t;
}
#define RING_IDS()                                                                                           \
  const int tid = fresh_tid() - 128;                                                                         \
  const int cw = __shfl_sync(~0u, tid >> 7, 0), warp = __shfl_sync(~0u, (tid >> 5) & 3, 0);                  \
  const bool releaser = (tid & 31) < 2;                                                                      \
  const uint32_t rbars = mapa(bars, tid & 1);                                                                \
  const uint32_t a_base = cw * 8192
#define LANE_IDS()                                                                                           \
  const int lane = fresh_tid() & 31, r = lane >> 2, c = lane & 3;                                            \
  const int srow = warp * 16 + (lane & 7) + ((lane >> 3) & 1) * 8;                                           \
  const uint32_t slab = stg + cw * 8192 + srow * 128, sw0 = (lane >> 4) ^ (srow & 7);                        \
  (void)r; (void)c; (void)slab; (void)sw0

template <int NPRE, bool EAGER, class Step>
__device__ __forceinline__ void attention(float (&acc)[96], const Params& p, int rho, int rb, int cta, int cw, int warp, uint32_t tag,
                                          uint32_t stg, uint32_t bars, uint32_t& prev, Step step) {
  uint32_t ql[8], qh[8], k0[8], k1[8], v0[8], v1[8], hp[16];
  if (EAGER) {
    tile_end(acc, prev);
  } else {
    step();
    fence_regs(acc);
  }
#pragma unroll
  for (int t = 0; t < 8; t++) {
    k0[t] = pack2(acc[4 * (8 + t)], acc[4 * (8 + t) + 1]);
    k1[t] = pack2(acc[4 * (8 + t) + 2], acc[4 * (8 + t) + 3]);
    v0[t] = pack2(acc[4 * (16 + t)], acc[4 * (16 + t) + 1]);
    v1[t] = pack2(acc[4 * (16 + t) + 2], acc[4 * (16 + t) + 3]);
    asm volatile("" : "+r"(k0[t]), "+r"(k1[t]), "+r"(v0[t]), "+r"(v1[t]));
  }
  const int lane = fresh_tid() & 31, r = lane >> 2, c = lane & 3;
#pragma unroll
  for (int t = 0; t < 8; t++) v1[t] = movmatrix(v1[t]);
  mbar_wait(bars + 8 * B_STGE, rho);
  mbar_wait(bars + 8 * (B_STGE + 1), 0);
  const uint32_t xch = stg + 16384 + (cw * 4 + warp) * 2048 + lane * 16;
  if (warp < 3) {
    sts128(xch, k1[0], k1[1], k1[2], k1[3]);
    sts128(xch + 512, k1[4], k1[5], k1[6], k1[7]);
    sts128(xch + 1024, v1[0], v1[1], v1[2], v1[3]);
    sts128(xch + 1536, v1[4], v1[5], v1[6], v1[7]);
  } else if (rb < 15) {
    uint4* dst = p.halo + ((cta * 2 + rho) * 2 + cw) * 256 + lane;
#pragma unroll
    for (int t = 0; t < 4; t++) {
      ll_store(dst + t * 32, k1[2 * t], k1[2 * t + 1], tag);
      ll_store(dst + (4 + t) * 32, v1[2 * t], v1[2 * t + 1], tag);
    }
  }
#pragma unroll
  for (int t = 0; t < 8; t++) {
    v0[t] = movmatrix(v0[t]);
    ql[t] = pack2(acc[4 * t], acc[4 * t + 1]);
    qh[t] = pack2(acc[4 * t + 2], acc[4 * t + 3]);
    asm volatile("" : "+r"(v0[t]), "+r"(ql[t]), "+r"(qh[t]));
  }
#pragma unroll 1
  for (int i = 0; i < NPRE; i++) step();
  const uint4* src = p.halo + (((cta - 8) * 2 + rho) * 2 + cw) * 256 + lane;
  uint4 early[8] = {};
  if (warp == 0 && rb > 0) {
#pragma unroll
    for (int i = 0; i < 8; i++) early[i] = ll_peek(src + i * 32);
  }
  step();
  wg_bar(cw);
  if (warp > 0) {
#pragma unroll
    for (int t = 0; t < 4; t++) {
      const uint4 a = lds128(xch - 2048 + t * 512);
      hp[4 * t] = a.x; hp[4 * t + 1] = a.y; hp[4 * t + 2] = a.z; hp[4 * t + 3] = a.w;
    }
  } else if (rb > 0) {
    uint32_t bad = 0;
#pragma unroll
    for (int i = 0; i < 8; i++) {
      bad |= (early[i].y ^ tag) | (early[i].w ^ tag);
      hp[2 * i] = early[i].x;
      hp[2 * i + 1] = early[i].z;
    }
    if (!__all_sync(~0u, bad == 0)) ll_poll<8>([&](int i) { return src + i * 32; }, tag, hp);
  } else {
#pragma unroll
    for (int t = 0; t < 16; t++) hp[t] = 0;
  }
  wg_wait<0>();
  if (prev != 0) mbar_arrive_cluster(prev);
  prev = 0;
#pragma unroll
  for (int t = 0; t < 8; t++) asm volatile("" : "+r"(ql[t])::"memory");
  const bool up0 = 2 * c > r, up1 = 2 * c + 1 > r;
  const bool first = (rb == 0) && (warp == 0);
  uint32_t a0[2], a2[2], a3[2], a5[2];
  float il[2], ih[2];
#pragma unroll
  for (int h = 0; h < 2; h++) {
    float sp[4] = {0.f, 0.f, 0.f, 0.f}, s0[4] = {0.f, 0.f, 0.f, 0.f}, s1[4] = {0.f, 0.f, 0.f, 0.f};
#pragma unroll
    for (int ks = 0; ks < 2; ks++) {
      const int t = 4 * h + 2 * ks;
      mma16816(sp, ql[t], qh[t], ql[t + 1], qh[t + 1], hp[t], hp[t + 1]);
      mma16816(s0, ql[t], qh[t], ql[t + 1], qh[t + 1], k0[t], k0[t + 1]);
      mma16816(s1, ql[t], qh[t], ql[t + 1], qh[t + 1], k1[t], k1[t + 1]);
    }
    float p0 = (up0 ? sp[0] : s0[0]) * QK_SCALE, p1 = (up1 ? sp[1] : s0[1]) * QK_SCALE;
    float p2 = (up0 ? s0[2] : s1[2]) * QK_SCALE, p3 = (up1 ? s0[3] : s1[3]) * QK_SCALE;
    if (first && up0) p0 = -1000000000.0f;
    if (first && up1) p1 = -1000000000.0f;
    il[h] = softmax8(p0, p1);
    ih[h] = softmax8(p2, p3);
    a0[h] = pack2(up0 ? p0 : 0.f, up1 ? p1 : 0.f);
    a2[h] = pack2(up0 ? 0.f : p0, up1 ? 0.f : p1);
    a3[h] = pack2(up0 ? p2 : 0.f, up1 ? p3 : 0.f);
    a5[h] = pack2(up0 ? 0.f : p2, up1 ? 0.f : p3);
  }
  float o[8][4];
#pragma unroll
  for (int t = 0; t < 8; t++) {
#pragma unroll
    for (int q = 0; q < 4; q++) o[t][q] = 0.f;
    mma1688(o[t], 0u, a5[t >> 2], v1[t]);
    mma16816(o[t], a0[t >> 2], 0u, a2[t >> 2], a3[t >> 2], hp[8 + t], v0[t]);
  }
#pragma unroll
  for (int t = 0; t < 8; t++) fence_regs(o[t]);
  if (!EAGER) step();
  uint32_t ol[8], oh[8];
#pragma unroll
  for (int t = 0; t < 8; t++) {
    ol[t] = pack2(o[t][0] * il[t >> 2], o[t][1] * il[t >> 2]);
    oh[t] = pack2(o[t][2] * ih[t >> 2], o[t][3] * ih[t >> 2]);
  }
  stage_slab(stg + cw * 8192, warp, lane, ol, oh);
  stage_done(bars + 8 * B_STGF, lane);
}

template <class Ready>
__device__ __forceinline__ void normalize_stage(const uint32_t (&xl)[16], const uint32_t (&xh)[16], const uint4* stats, uint32_t tag, uint32_t shift,
                                                uint32_t scale, uint32_t stg, uint32_t bars, int cw, int warp, int lane, Ready ready) {
  const int r = lane >> 2, c = lane & 3;
  float nb[2], rs[2];
  {
    uint32_t st[8];
    const uint4* sp = stats + (lane >> 4) * 512 + cw * 64 + warp * 16 + (lane & 15);
    ll_poll<4>([&](int i) { return sp + i * 128; }, tag, st);
    float mu, rstd;
    row_stats(st, mu, rstd);
    mu *= -rstd;
    nb[0] = __shfl_sync(~0u, mu, r); rs[0] = __shfl_sync(~0u, rstd, r);
    nb[1] = __shfl_sync(~0u, mu, r + 8); rs[1] = __shfl_sync(~0u, rstd, r + 8);
  }
  ready();
#pragma unroll
  for (int ch = 0; ch < 2; ch++) {
    uint32_t lo[8], hi[8];
#pragma unroll
    for (int t = 0; t < 8; t++) {
      const int n = ch * 8 + t;
      const float2 sb = lds64f(shift + (8 * n + 2 * c) * 4), cb = lds64f(scale + (8 * n + 2 * c) * 4);
      lo[t] = pack2((bf_lo(xl[n]) * rs[0] + nb[0]) * cb.x + sb.x, (bf_hi(xl[n]) * rs[0] + nb[0]) * cb.y + sb.y);
      hi[t] = pack2((bf_lo(xh[n]) * rs[1] + nb[1]) * cb.x + sb.x, (bf_hi(xh[n]) * rs[1] + nb[1]) * cb.y + sb.y);
    }
    stage_slab(stg + ch * 16384 + cw * 8192, warp, lane, lo, hi);
    stage_done(bars + 8 * (B_STGF + ch), lane);
  }
  wg_bar(cw);
}

__global__ void __launch_bounds__(384, 1) fused_kernel(const __grid_constant__ Params p) {
  extern __shared__ __align__(1024) uint8_t smem_raw[];
  const uint32_t sm = smem_u32(smem_raw);
  const uint32_t bars = sm + MISC_OFF;
  const uint32_t stg = sm + STG_OFF;
  const int rank = blockIdx.x & 1;
  const int cl = blockIdx.x >> 1;
  if (cl >= NCTA / 2) {
    const int e = blockIdx.x - NCTA, wid = __shfl_sync(~0u, (int)(threadIdx.x >> 5), 0), lane = threadIdx.x & 31;
    if (threadIdx.x == 0) {
      for (int i = 0; i < 6; i++) { mbar_init(bars + 8 * i, 1); mbar_init(bars + 8 * (6 + i), 8); }
      asm volatile("fence.mbarrier_init.release.cluster;" ::: "memory");
    }
    const uint32_t tag = load_epoch(p.epoch) + 1;
    if (threadIdx.x < 256) ll_store(p.modll + 512 + (threadIdx.x >> 6) * 256 + e * 64 + (threadIdx.x & 63), 0u, 0u, 0u);
    for (int i = threadIdx.x; i < 1536; i += 384) {
      uint4 o = make_uint4(0u, 0u, 0u, 0u);
      if (i < 1024 && (i & 63) < 8) {
        const uint4 cv = ldg_nc(p.c + (i >> 6) * 64 + (i & 7) * 8);
        o = make_uint4(pack2(silu_f(bf_lo(cv.x)), silu_f(bf_hi(cv.x))), pack2(silu_f(bf_lo(cv.y)), silu_f(bf_hi(cv.y))),
                       pack2(silu_f(bf_lo(cv.z)), silu_f(bf_hi(cv.z))), pack2(silu_f(bf_lo(cv.w)), silu_f(bf_hi(cv.w))));
      }
      sts128(stg + i * 16, o.x, o.y, o.z, o.w);
    }
    asm volatile("fence.proxy.async.shared::cta;" ::: "memory");
    __syncthreads();
    if (wid == 0) {
      __nanosleep(WMDELAY);
      uint32_t ph = 1;
#pragma unroll 1
      for (int it = 0, s = 0; it < 64; it++) {
        mbar_wait(bars + 8 * (6 + s), ph);
        expect_tx_elect(bars + 8 * s, 32768);
#pragma unroll
        for (int q = 0; q < 4; q++) tma_load_ef(sm + s * 32768 + q * 8192, &p.wm, bars + 8 * s, 2048 + (it >> 4) * 1024 + e * 256 + q * 64, (it & 15) * 64);
        if (++s == 6) { s = 0; ph ^= 1; }
      }
    } else if (wid >= 4) {
      const int hf = (wid >> 2) - 1;
      uint32_t ph = 0;
      int s = 0;
#pragma unroll 1
      for (int v = 0; v < 4; v++) {
        float acc[64];
#pragma unroll 1
        for (int kb = 0; kb < 16; kb++) {
          mbar_wait_watchdog(bars + 8 * s, ph);
          const uint32_t da = DESC_A + ((STG_OFF + kb * 1024) >> 4), db = DESC_B + ((s * 32768 + hf * 16384) >> 4) - 1024;
          wg_fence();
#pragma unroll
          for (int k = 0; k < 4; k++) wgmma_ss_n128(acc, da + k * 2, db + k * 128, (kb | k) != 0);
          wg_commit();
          wg_wait<0>();
          if (lane == 0) mbar_arrive(bars + 8 * (6 + s));
          if (++s == 6) { s = 0; ph ^= 1; }
        }
        if ((wid & 3) == 0) {
#pragma unroll
          for (int n = 0; n < 16; n++) {
            const uint32_t mine = pack2(acc[4 * n], acc[4 * n + 1]), next = __shfl_down_sync(~0u, mine, 1);
            if (lane < 4 && (lane & 1) == 0) ll_store(p.modll + 512 + v * 256 + e * 64 + hf * 32 + n * 2 + (lane >> 1), mine, next, tag);
          }
        }
      }
    }
    return;
  }
  const int slot = p.slot[cl];
  const int rb = (slot >> 3) * 2 + rank, j = slot & 7;
  const int cta = rb * 8 + j;
  PROF_AT(threadIdx.x == 0, 0);

  if (threadIdx.x < 128) {
    uint32_t tag = load_epoch(p.epoch);
    asm volatile("setmaxnreg.dec.sync.aligned.u32 40;");
    const int warp = __shfl_sync(~0u, (int)(threadIdx.x >> 5), 0), lane = threadIdx.x & 31;
    if (threadIdx.x == 0) {
      if ((sm & 0x3FFFF) != SMEM_BASE) asm volatile("trap;");
      for (int i = 0; i < 4; i++) { mbar_init(bars + 8 * (B_FQ + i), 1); mbar_init(bars + 8 * (B_EQ + i), 16); }
      for (int i = 0; i < 6; i++) { mbar_init(bars + 8 * (B_FW + i), 1); mbar_init(bars + 8 * (B_EW + i), 16); }
      for (int i = 0; i < 4; i++) { mbar_init(bars + 8 * (B_FG + i), 1); mbar_init(bars + 8 * (B_EG + i), 16); }
      for (int i = 0; i < 6; i++) { mbar_init(bars + 8 * (B_FD + i), 1); mbar_init(bars + 8 * (B_ED + i), 16); }
      for (int i = 0; i < 2; i++) { mbar_init(bars + 8 * (B_STGF + i), 8); mbar_init(bars + 8 * (B_STGE + i), 1); }
      mbar_init(bars + 8 * B_MODB, 1);
      mbar_init(bars + 8 * (B_MODB + 1), 1);
      mbar_init(bars + 8 * B_MODA, 1);
      for (int i = 0; i < 8; i++) mbar_init(bars + 8 * (B_RDY + i), 1);
      asm volatile("fence.mbarrier_init.release.cluster;" ::: "memory");
    }
    __syncwarp();
    cluster_arrive_relaxed();
    tag += 1;
    const unsigned target = tag * 8;
    unsigned* cnt = p.cnt + rb * 32;
    cluster_wait();
    if (warp == 0) {
      const CUtensorMap* wgu = rank ? &p.wu : &p.wg;
      uint32_t st = sm + 16384, fb = bars + 8 * B_FQ, ph = 1;
      __nanosleep(BDELAY);
#pragma unroll 1
      for (int it = 0; it < 32; it++) {
        const int kb = qkv_kb(it, j), col = j * 128 + ((it < 4 ? it >= 2 : it >= 18) ? 64 : 0);
        mbar_wait(fb + 8 * (B_EQ - B_FQ), ph);
        expect_tx_elect(fb, it < 4 ? 24576 : 40960);
        tma_load_mc(st + rank * 8192, &p.wqkv, fb, col + rank * 1024, kb * 64);
        tma_load_mc(st + 16384 + rank * 4096, &p.wqkv32, fb, col + 2048, kb * 64 + rank * 32);
        st += 49152; fb += 8;
        if ((it & 3) == 3) { st -= 4 * 49152; fb -= 32; ph ^= 1; }
      }
      fb = bars + 8 * B_FW; ph = 1;
#pragma unroll 1
      for (int it = 0, s = 0; it < 16; it++) {
        if (it < 6) wait_p3_free(bars + 8 * B_EQ, it);
        mbar_wait(fb + 8 * (B_EW - B_FW), ph);
        expect_tx_elect(fb, it == 8 ? 16384 : 32768);
        tma_load_mc(st + rank * 8192, &p.wo, fb, j * 128 + rank * 64, wo_k(it, j));
        st += 32768; fb += 8;
        if (++s == 6) { s = 0; st -= 6 * 32768; fb -= 48; ph ^= 1; }
      }
      st = sm + 16384; fb = bars + 8 * B_FG; ph = 1;
#pragma unroll 1
      for (int it = 0; it < 48; it++) {
        const int kb = own_first(it, j), col = j * 448 + (it >> 4) * 128;
        if (it < 4) wait_p2_free(bars + 8 * B_EW, it);
        mbar_wait(fb + 8 * (B_EG - B_FG), ph);
        expect_tx_elect(fb, it < 2 ? 32768 : 49152);
        tma_load_mc(st + rank * 16384, wgu, fb, col, kb * 64);
        tma_load_mc(st + rank * 16384 + 8192, wgu, fb, col + 64, kb * 64);
        st += 49152; fb += 8;
        if ((it & 3) == 3) { st -= 4 * 49152; fb -= 32; ph ^= 1; }
      }
      fb = bars + 8 * B_FD; ph = 1;
#pragma unroll 1
      for (int it = 0, s = 0; it < 72; it++) {
        if (it < 6) wait_p3_free(bars + 8 * B_EG, it);
        mbar_wait(fb + 8 * (B_ED - B_FD), ph);
        expect_tx_elect(fb, 32768);
        tma_load_mc(st + rank * 8192, it < 16 ? wgu : &p.wd, fb, it < 16 ? j * 448 + 384 : j * 128 + rank * 64, down_k(it));
        st += 32768; fb += 8;
        if (++s == 6) { s = 0; st -= 6 * 32768; fb -= 48; ph ^= 1; }
      }
    } else if (warp == 1) {
      const int arow = rb * 128;
      uint32_t st = sm, fb = bars + 8 * B_FQ, ph = 0;
      cnt_wait(cnt + C_HA, target);
      PROF_AT(lane == 0, 16);
#pragma unroll 1
      for (int it = 4; it < 32; it++) {
        if (it == 11) mbar_wait(bars + 8 * (B_RDY + C_H), 0);
        mbar_wait(fb + 8 * (B_EQ - B_FQ), ph);
        tma_load(st, &p.h, fb, qkv_kb(it, j) * 64, arow);
        st += 49152; fb += 8;
        if ((it & 3) == 3) { st -= 4 * 49152; fb -= 32; ph ^= 1; }
      }
      fb = bars + 8 * B_FW; ph = 1;
#pragma unroll 1
      for (int it = 0, s = 0; it < 16; it++) {
        if (it < 6) wait_p3_free(bars + 8 * B_EQ, it);
        mbar_wait(fb + 8 * (B_EW - B_FW), ph);
        if (it == 0) mbar_wait(bars + 8 * (B_RDY + C_O), 0);
        if (it == 9) cnt_wait(cnt + C_O + 1, target);
        PROF_AT(lane == 0 && (it == 0 || it == 9), 17 + (it >> 3));
        if (it != 8) tma_load(st, &p.o_ld, fb, wo_k(it, j), arow);
        st += 32768; fb += 8;
        if (++s == 6) { s = 0; st -= 6 * 32768; fb -= 48; ph ^= 1; }
      }
      st = sm + 2 * 49152; fb = bars + 8 * (B_FG + 2); ph = 1;
      cnt_wait(cnt + C_H2A, target);
      PROF_AT(lane == 0, 19);
#pragma unroll 1
      for (int it = 2; it < 48; it++) {
        if (it == 9) mbar_wait(bars + 8 * (B_RDY + C_H2), 0);
        mbar_wait(fb + 8 * (B_EG - B_FG), ph);
        tma_load(st, &p.h2, fb, own_first(it, j) * 64, arow);
        st += 49152; fb += 8;
        if ((it & 3) == 3) { st -= 4 * 49152; fb -= 32; ph ^= 1; }
      }
      fb = bars + 8 * B_FD; ph = 1;
#pragma unroll 1
      for (int it = 0, s = 0; it < 72; it++) {
        if (it < 6) wait_p3_free(bars + 8 * B_EG, it);
        mbar_wait(fb + 8 * (B_ED - B_FD), ph);
        if ((it & 15) == 0 && it > 0) { mbar_wait(bars + 8 * (B_RDY + C_ACT - 1 + (it >> 4)), 0); PROF_AT(lane == 0, 19 + (it >> 4)); }
        tma_load(st, it < 16 ? &p.h2 : &p.act, fb, down_k(it), arow);
        st += 32768; fb += 8;
        if (++s == 6) { s = 0; st -= 6 * 32768; fb -= 48; ph ^= 1; }
      }
    } else if (warp == 2) {
      if (lane < 13) prefetch_map(&p.h + lane);
      __syncwarp();
      uint32_t ph1 = 0;
#pragma unroll 1
      for (int n = 0; n < 8; n++) {
        const int nch = (n == 1 || n == 2 || n == 7) ? 1 : 2;
#pragma unroll 1
        for (int ch = 0; ch < nch; ch++) {
          mbar_wait_watchdog(bars + 8 * (B_STGF + ch), ch ? ph1 : (n & 1));
          const uint32_t src = stg + ch * 16384;
          if (n == 1 || n == 2) {
#pragma unroll 1
            for (int q = 0; q < 4; q++) {
              tma_store2(&p.o_st, src + q * 4096, j * 128 + (n - 1) * 64, rb * 128 + q * 32);
              if (n == 1) store_pause(true);
            }
          } else if (n >= 4 && n < 8) {
#pragma unroll 1
            for (int q = 0; q < 4; q++) {
              tma_store2(&p.act_st, src + q * 4096, j * 448 + (n - 4) * 128 + ch * 64, rb * 128 + q * 32);
              store_pause(true);
            }
          } else {
            tma_store2(n == 0 ? &p.h : &p.h2, src, j * 128 + ch * 64, rb * 128);
            asm volatile("cp.async.bulk.commit_group;" ::: "memory");
            if (ch == 1) {
              asm volatile("cp.async.bulk.wait_group 1;" ::: "memory");
              __syncwarp();
              cnt_signal(cnt + (n == 0 ? C_HA : C_H2A));
            }
          }
          if (n >= 4 && n < 7 && ch == 0) arrive_elect(bars + 8 * B_STGE);
        }
        asm volatile("cp.async.bulk.commit_group;" ::: "memory");
        asm volatile("cp.async.bulk.wait_group 0;" ::: "memory");
        __syncwarp();
        cnt_signal(cnt + n);
        PROF_AT(lane == 0, n == 0 ? 33 : 23 + n);
        if (n == 0) {
#pragma unroll 1
          for (int t = 0; t < 36; t++) {
            ll_store(t < 32 ? p.halo + cta * 1024 + t * 32 + lane : p.stats2 + cta * 128 + (t - 32) * 32 + lane, 0u, 0u, 0u);
            __nanosleep(40);
          }
          __syncwarp();
        }
        if (!(n >= 4 && n < 7)) arrive_elect(bars + 8 * B_STGE);
        if (nch == 2) { arrive_elect(bars + 8 * (B_STGE + 1)); ph1 ^= 1; }
      }
      mbar_wait_watchdog(bars + 8 * B_STGF, 0);
      PROF_AT(lane == 0, 31);
    } else {
      if (lane < 4) ll_store(p.modll + cta * 4 + lane, 0u, 0u, 0u);
      bar_sync(1, 288);
      {
        const uint4 t4 = lds128(sm + RED_OFF + lane * 16);
        float a[4] = {__uint_as_float(t4.x), __uint_as_float(t4.y), __uint_as_float(t4.z), __uint_as_float(t4.w)};
#pragma unroll
        for (int o = 4; o < 32; o <<= 1)
#pragma unroll
          for (int q = 0; q < 4; q++) a[q] += __shfl_xor_sync(~0u, a[q], o);
        if (lane < 4) ll_store(p.modll + cta * 4 + lane, pack2(a[0], a[1]), pack2(a[2], a[3]), tag);
        PROF_AT(lane == 0, 1);
        uint32_t m[4];
        const uint4* mp = p.modll + j * 32 + lane;
        ll_poll<2>([&](int i) { return mp + i * 256; }, tag, m);
        const uint32_t c0 = pack2(1.0f + bf_lo(m[2]), 1.0f + bf_hi(m[2])), c1 = pack2(1.0f + bf_lo(m[3]), 1.0f + bf_hi(m[3]));
        sts128(sm + MODB_OFF + lane * 16, m[0] << 16, m[0] & 0xffff0000u, m[1] << 16, m[1] & 0xffff0000u);
        sts128(sm + MODB_OFF + 512 + lane * 16, c0 << 16, c0 & 0xffff0000u, c1 << 16, c1 & 0xffff0000u);
        __syncwarp();
        arrive_elect(bars + 8 * B_MODA);
      }
#pragma unroll 1
      for (int n = C_H; n <= C_O; n++) {
        cnt_wait_lazy(cnt + n, target);
        arrive_elect(bars + 8 * (B_RDY + n));
      }
      {
        uint32_t m[6];
        const uint4* src = p.modll + 512 + j * 32 + lane;
        ll_poll<3, 500>([&](int i) { return src + i * 256; }, tag, m);
#pragma unroll
        for (int vec = 0; vec < 3; vec++) {
          const float add = vec == 2 ? 1.0f : 0.0f;
          sts128(sm + MODB_OFF + (vec * 128 + lane * 4) * 4, __float_as_uint(bf_round(bf_lo(m[2 * vec]) + add)), __float_as_uint(bf_round(bf_hi(m[2 * vec]) + add)),
                 __float_as_uint(bf_round(bf_lo(m[2 * vec + 1]) + add)), __float_as_uint(bf_round(bf_hi(m[2 * vec + 1]) + add)));
        }
        __syncwarp();
        if (lane == 0) mbar_arrive(bars + 8 * B_MODB);
        PROF_AT(lane == 0, 15);
      }
      __syncwarp();
#pragma unroll 1
      for (int n = C_H2; n < 8; n++) {
        cnt_wait_lazy(cnt + n, target);
        arrive_elect(bars + 8 * (B_RDY + n));
      }
      {
        uint32_t m[2];
        const uint4* src = p.modll + 512 + 768 + j * 32 + lane;
        ll_poll<1>([&](int) { return src; }, tag, m);
        sts128(sm + MODB_OFF + (384 + lane * 4) * 4, m[0] << 16, m[0] & 0xffff0000u, m[1] << 16, m[1] & 0xffff0000u);
        __syncwarp();
        if (lane == 0) mbar_arrive(bars + 8 * (B_MODB + 1));
      }
    }
  } else {
    uint32_t tag;

    {
      const int tid = threadIdx.x - 128, cw = tid >> 7, warp = (tid >> 5) & 3, lane = tid & 31;
      const int l16 = lane & 15, half = lane >> 4, w8 = cw * 4 + warp;
      const uint32_t cbuf = sm + 3 * 49152 + w8 * 512;
      if (lane <= 16) cp_async16(cbuf + lane * 16, lane < 16 ? (const void*)(p.c + w8 * 128 + lane * 8) : (const void*)p.epoch);
      asm volatile("cp.async.commit_group;" ::: "memory");
      const uint32_t wbuf = sm + cw * 49152 + warp * 4096;
      {
        const char* wp = (const char*)p.wmod + (uint32_t)(cta * 32 + (lane & 1) * 16 + (w8 * 128 + (lane >> 1)) * 12288);
#pragma unroll
        for (int i = 0; i < 8; i++) cp_async16(wbuf + i * 512 + lane * 16, wp + i * 16 * 12288);
      }
      asm volatile("cp.async.commit_group;" ::: "memory");
      const uint32_t xbuf = sm + 40960 + (cw * 2 + (l16 >> 3)) * 49152 + (warp * 16 + half) * 128;
      {
        const char* xp = (const char*)p.x + (uint32_t)((rb * 128 + (warp * 16 + half) * 2 + cw) * 2048 + j * 256 + l16 * 16);
#pragma unroll
        for (int i = 0; i < 8; i++) cp_async16(xbuf + i * 256 + (((l16 & 7) ^ ((i * 2 + half) & 7)) << 4), xp + i * 8192);
      }
      asm volatile("cp.async.commit_group;" ::: "memory");
      PROF_AT(tid == 0, 32);
      uint4* st1 = p.stats1 + (rb * 8 + j) * 128 + cw * 64 + warp * 16;
      if (lane < 16) ll_store(st1 + lane, 0u, 0u, 0u);
      __syncwarp();
      cluster_arrive_relaxed();
      asm volatile("setmaxnreg.inc.sync.aligned.u32 232;");
      uint32_t sa[4][4];
      {
        asm volatile("cp.async.wait_group 2;" ::: "memory");
        __syncwarp();
        tag = lds32(cbuf + 256) + 1;
        const float2 cv = lds64f(cbuf + lane * 8);
        const uint32_t c0 = __float_as_uint(cv.x), c1 = __float_as_uint(cv.y);
        sts64f(cbuf + lane * 8, __uint_as_float(pack2(silu_f(bf_lo(c0)), silu_f(bf_hi(c0)))), __uint_as_float(pack2(silu_f(bf_lo(c1)), silu_f(bf_hi(c1)))));
        __syncwarp();
#pragma unroll
        for (int q = 0; q < 4; q++) ldmatrix4(sa[q][0], sa[q][1], sa[q][2], sa[q][3], cbuf + q * 64 + (lane >> 3) * 16);
      }
      cluster_wait();
      asm volatile("cp.async.wait_group 1;" ::: "memory");
      __syncwarp();
      PROF_AT(tid == 0, 51);
      {
        uint32_t b[8][4];
#pragma unroll
        for (int ks = 0; ks < 8; ks++) ldmatrix4t(b[ks], wbuf + (ks * 16 + (lane & 15)) * 32 + (lane >> 4) * 16);
        float d0[4] = {0.f, 0.f, 0.f, 0.f}, d1[4] = {0.f, 0.f, 0.f, 0.f}, d2[4] = {0.f, 0.f, 0.f, 0.f}, d3[4] = {0.f, 0.f, 0.f, 0.f};
#pragma unroll
        for (int q = 0; q < 4; q++) {
          mma16816(d0, sa[q][0], sa[q][0], sa[q][1], sa[q][1], b[2 * q][0], b[2 * q][1]);
          mma16816(d1, sa[q][0], sa[q][0], sa[q][1], sa[q][1], b[2 * q][2], b[2 * q][3]);
          mma16816(d2, sa[q][2], sa[q][2], sa[q][3], sa[q][3], b[2 * q + 1][0], b[2 * q + 1][1]);
          mma16816(d3, sa[q][2], sa[q][2], sa[q][3], sa[q][3], b[2 * q + 1][2], b[2 * q + 1][3]);
        }
        d0[0] += d2[0]; d0[1] += d2[1]; d1[0] += d3[0]; d1[1] += d3[1];
        if (lane < 4) {
          sts64f(sm + RED_OFF + (w8 * 16 + lane * 2) * 4, d0[0], d0[1]);
          sts64f(sm + RED_OFF + (w8 * 16 + 8 + lane * 2) * 4, d1[0], d1[1]);
        }
        asm volatile("bar.arrive 1, 288;" ::: "memory");
      }
      asm volatile("cp.async.wait_group 0;" ::: "memory");
      __syncwarp();
      uint32_t xl[16], xh[16];
      {
        const int srow = warp * 16 + (lane & 15);
#pragma unroll
        for (int q = 0; q < 8; q++)
          ldmatrix4(xl[2 * q], xh[2 * q], xl[2 * q + 1], xh[2 * q + 1],
                    sm + 40960 + (cw * 2 + (q >> 2)) * 49152 + srow * 128 + (((half + (q & 3) * 2) ^ (srow & 7)) << 4));
      }
      publish_stats(xl, xh, st1, lane, tag);
      PROF_AT(tid == 0, 50);
      normalize_stage(xl, xh, p.stats1 + rb * 1024, tag, sm + MODB_OFF, sm + MODB_OFF + 512, stg, bars, cw, warp, lane,
                      [&]() { mbar_wait(bars + 8 * B_MODA, 0); });
      PROF_AT(tid == 0, 3);
    }

    uint32_t xl[16], xh[16];
    {
      RING_IDS();
      uint32_t prev = 0;
      float acc1[96];
      {
        Ring g{bars + 8 * B_FQ, rbars + 8 * B_EQ, 0, 0u, releaser TR(0)};
        float acc0[96];
#pragma unroll 1
        for (int kb = 0; kb < 2; kb++) kblock<192, 4, 49152>(acc0, g, a_base + STG_OFF + kb * 16384, kb == 0, prev);
#pragma unroll 1
        for (int kb = 0; kb < 2; kb++) kblock<192, 4, 49152>(acc1, g, a_base + STG_OFF + kb * 16384, kb == 0, prev);
#pragma unroll 1
        for (int kb = 0; kb < 14; kb++) kblock<192, 4, 49152>(acc0, g, a_base + g.s * 49152, false, prev);
        PROF_AT(tid == 0, 4);
        attention<NPRE0, false>(acc0, p, 0, rb, cta, cw, warp, tag, stg, bars, prev, [&]() { kblock<192, 4, 49152>(acc1, g, a_base + g.s * 49152, false, prev); });
        PROF_AT(tid == 0, 5);
        {
          LANE_IDS();
#pragma unroll
          for (int q = 0; q < 8; q++)
            ldmatrix4(xl[2 * q], xh[2 * q], xl[2 * q + 1], xh[2 * q + 1], sm + 40960 + (cw * 2 + (q >> 2)) * 49152 + srow * 128 + ((sw0 ^ ((q & 3) * 2)) << 4));
#pragma unroll
          for (int q = 0; q < 16; q++) asm volatile("" : "+r"(xl[q]), "+r"(xh[q])::"memory");
        }
#pragma unroll 1
        for (int kb = 3 + NPRE0; kb < 14; kb++) kblock<192, 4, 49152>(acc1, g, a_base + g.s * 49152, false, prev);
        PROF_AT(tid == 0, 6);
      }
      float acc[64];
      Ring g{bars + 8 * B_FW, rbars + 8 * B_EW, 0, 0u, releaser TR(32)};
      attention<NPRE1, true>(acc1, p, 1, rb, cta, cw, warp, tag, stg, bars, prev, [&]() { kblock<128, 6, 32768>(acc, g, a_base + g.s * 32768, g.s == 0, prev); });
      PROF_AT(tid == 0, 7);
      LANE_IDS();
#pragma unroll 1
      for (int kb = 1 + NPRE1; kb < 16; kb++) {
        if (kb == 8) wg_bar(cw);
        kblock<128, 6, 32768>(acc, g, a_base + (kb == 8 ? STG_OFF : g.s * 32768), false, prev);
      }
      mbar_wait(bars + 8 * B_MODB, 0);
      float2 ga[16];
#pragma unroll
      for (int n = 0; n < 16; n++) ga[n] = lds64f(sm + MODB_OFF + (8 * n + 2 * c) * 4);
      tile_end(acc, prev);
      PROF_AT(tid == 0, 8);
      uint4* st2 = p.stats2 + (rb * 8 + j) * 128 + cw * 64 + warp * 16 + r + (c & 1) * 8;
      float sl[2] = {0.f, 0.f}, sh[2] = {0.f, 0.f}, ql[2] = {0.f, 0.f}, qh[2] = {0.f, 0.f};
#pragma unroll
      for (int n = 0; n < 16; n++) {
        acc[4 * n] = ga[n].x * acc[4 * n] + bf_lo(xl[n]); acc[4 * n + 1] = ga[n].y * acc[4 * n + 1] + bf_hi(xl[n]);
        acc[4 * n + 2] = ga[n].x * acc[4 * n + 2] + bf_lo(xh[n]); acc[4 * n + 3] = ga[n].y * acc[4 * n + 3] + bf_hi(xh[n]);
        sl[0] += acc[4 * n]; sl[1] += acc[4 * n + 1]; sh[0] += acc[4 * n + 2]; sh[1] += acc[4 * n + 3];
        ql[0] += acc[4 * n] * acc[4 * n]; ql[1] += acc[4 * n + 1] * acc[4 * n + 1];
        qh[0] += acc[4 * n + 2] * acc[4 * n + 2]; qh[1] += acc[4 * n + 3] * acc[4 * n + 3];
      }
      {
        const float ml = (sl[0] + sl[1]) * (1.0f / 32), mh = (sh[0] + sh[1]) * (1.0f / 32);
        const float vl = (ql[0] + ql[1]) - 32.0f * ml * ml, vh = (qh[0] + qh[1]) - 32.0f * mh * mh;
        const bool b0 = c & 1;
        float m = b0 ? mh : ml, q = b0 ? vh : vl;
        chan(m, q, __shfl_xor_sync(~0u, b0 ? ml : mh, 1), __shfl_xor_sync(~0u, b0 ? vl : vh, 1), 32.f);
        chan(m, q, __shfl_xor_sync(~0u, m, 2), __shfl_xor_sync(~0u, q, 2), 64.f);
        if (c < 2) ll_store(st2, __float_as_uint(m), __float_as_uint(fmaxf(q, 0.f)), tag);
        __syncwarp();
      }
      PROF_AT(tid == 0, 48);
      float2 sb[16], cb[16];
#pragma unroll
      for (int n = 0; n < 16; n++) {
        sb[n] = lds64f(sm + MODB_OFF + (128 + 8 * n + 2 * c) * 4);
        cb[n] = lds64f(sm + MODB_OFF + (256 + 8 * n + 2 * c) * 4);
        xl[n] = pack2(acc[4 * n], acc[4 * n + 1]);
        xh[n] = pack2(acc[4 * n + 2], acc[4 * n + 3]);
      }
      mbar_wait(bars + 8 * B_STGE, 0);
      PROF_AT(tid == 0, 49);
      float nb[2], rstd[2];
      {
        uint32_t st[8];
        const uint4* sp = p.stats2 + (rb * 8 + (lane >> 4) * 4) * 128 + cw * 64 + warp * 16 + (lane & 15);
        ll_poll<4>([&](int i) { return sp + i * 128; }, tag, st);
        float mu, rs;
        row_stats(st, mu, rs);
        mu *= -rs;
        nb[0] = __shfl_sync(~0u, mu, r); rstd[0] = __shfl_sync(~0u, rs, r);
        nb[1] = __shfl_sync(~0u, mu, r + 8); rstd[1] = __shfl_sync(~0u, rs, r + 8);
      }
      PROF_AT(tid == 0, 9);
#pragma unroll
      for (int ch = 0; ch < 2; ch++) {
        uint32_t lo[8], hi[8];
#pragma unroll
        for (int t = 0; t < 8; t++) {
          const int n = ch * 8 + t;
          lo[t] = pack2((acc[4 * n] * rstd[0] + nb[0]) * cb[n].x + sb[n].x, (acc[4 * n + 1] * rstd[0] + nb[0]) * cb[n].y + sb[n].y);
          hi[t] = pack2((acc[4 * n + 2] * rstd[1] + nb[1]) * cb[n].x + sb[n].x, (acc[4 * n + 3] * rstd[1] + nb[1]) * cb[n].y + sb[n].y);
        }
        stage_slab(stg + ch * 16384 + cw * 8192, warp, lane, lo, hi);
        stage_done(bars + 8 * (B_STGF + ch), lane);
      }
      wg_bar(cw);
      PROF_AT(tid == 0, 10);
    }

    uint32_t pg[32], pu[32];
    {
      RING_IDS();
      LANE_IDS();
      Ring g{bars + 8 * B_FG, rbars + 8 * B_EG, 0, 0u, releaser TR(48)};
      float acc[128];
      {
        uint32_t prev = 0;
        uint4* x1p = p.x1 + (size_t)(rb * 128 + (warp * 16 + (lane >> 4)) * 2 + cw) * 128 + j * 16 + (lane & 15);
#pragma unroll 1
        for (int kb = 0; kb < 16; kb++) {
          kblock<256, 4, 49152>(acc, g, a_base + (kb < 2 ? STG_OFF + kb * 16384 : g.s * 49152), kb == 0, prev);
          if (kb == 5) {
#pragma unroll
            for (int q = 0; q < 4; q++) x1p[q * 512] = make_uint4(xl[4 * q], xl[4 * q + 1], xl[4 * q + 2], xl[4 * q + 3]);
          }
          if (kb == 8) {
#pragma unroll
            for (int q = 0; q < 4; q++) x1p[(4 + q) * 512] = make_uint4(xh[4 * q], xh[4 * q + 1], xh[4 * q + 2], xh[4 * q + 3]);
          }
        }
        tile_end(acc, prev);
      }
      PROF_AT(tid == 0, 36);
#pragma unroll 1
      for (int t = 1; t < 3; t++) {
#pragma unroll
        for (int q = 0; q < 32; q++) {
          pg[q] = pack2(acc[2 * q], acc[2 * q + 1]);
          pu[q] = pack2(acc[64 + 2 * q], acc[64 + 2 * q + 1]);
        }
        uint32_t prev = 0;
#pragma unroll 1
        for (int blk = 0; blk < 4; blk++) {
          g.s = 0;
#pragma unroll
          for (int i = 0; i < 4; i++) {
            kblock<256, 4, 49152>(acc, g, a_base + i * 49152, blk == 0 && i == 0, prev);
            if ((blk & 1) == 0 && i == 0) mbar_wait(bars + 8 * (B_STGE + (blk >> 1)), t & 1);
            stmatrix2(slab + (blk >> 1) * 16384 + (((srow & 7) ^ ((blk & 1) * 4 + i)) << 4), swiglu2(pg[2 * i], pu[2 * i]), swiglu2(pg[2 * i + 1], pu[2 * i + 1]));
          }
#pragma unroll
          for (int q = 0; q < 24; q++) { pg[q] = pg[q + 8]; pu[q] = pu[q + 8]; }
          if (blk & 1) stage_done(bars + 8 * (B_STGF + (blk >> 1)), lane);
        }
        tile_end(acc, prev);
        PROF_AT(tid == 0, 36 + t);
      }
#pragma unroll
      for (int q = 0; q < 32; q++) {
        pg[q] = pack2(acc[2 * q], acc[2 * q + 1]);
        pu[q] = pack2(acc[64 + 2 * q], acc[64 + 2 * q + 1]);
      }
      PROF_AT(tid == 0, 11);
    }

    {
      RING_IDS();
      LANE_IDS();
      Ring g{bars + 8 * B_FD, rbars + 8 * B_ED, 0, 0u, releaser TR(96)};
      float acc[64];
      uint32_t prev = 0;
#pragma unroll 1
      for (int blk = 0; blk < 6; blk++) {
#pragma unroll
        for (int i = 0; i < 8; i++) {
          kblock<128, 6, 32768>(acc, g, a_base + g.s * 32768, (blk & ~2) == 0 && i == 0, prev);
          if ((blk & 1) == 0 && i == 0) mbar_wait(bars + 8 * (B_STGE + ((blk >> 1) & 1)), blk < 4);
          stmatrix1(slab + ((blk >> 1) & 1) * 16384 + (i & 1) * 1024 + (((srow & 7) ^ ((blk & 1) * 4 + (i >> 1))) << 4), swiglu2(pg[i], pu[i]));
        }
#pragma unroll
        for (int q = 0; q < 24; q++) { pg[q] = pg[q + 8]; pu[q] = pu[q + 8]; }
        if (blk & 1) stage_done(bars + 8 * (B_STGF + ((blk >> 1) & 1)), lane);
        if (blk == 1) {
          tile_end(acc, prev);
          PROF_AT(tid == 0, 39);
#pragma unroll
          for (int q = 0; q < 16; q++) {
            pg[16 + q] = pack2(acc[2 * q], acc[2 * q + 1]);
            pu[16 + q] = pack2(acc[32 + 2 * q], acc[32 + 2 * q + 1]);
          }
          PROF_AT(tid == 0, 12);
        }
      }
      uint4 x1[8];
      const int fl = fresh_tid() & 31;
      const uint4* x1p = p.x1 + (size_t)(rb * 128 + (warp * 16 + (fl >> 4)) * 2 + cw) * 128 + j * 16 + (fl & 15);
#pragma unroll
      for (int q = 0; q < 2; q++) {
#pragma unroll
        for (int e = 0; e < 4; e++) x1[4 * q + e] = ll_peek(x1p + (4 * q + e) * 512);
#pragma unroll 1
        for (int kb = 0; kb < 12; kb++) {
          if (q == 1 && kb == 6) g.releaser = false;
          kblock<128, 6, 32768>(acc, g, a_base + g.s * 32768, false, prev);
        }
      }
      mbar_wait(bars + 8 * (B_MODB + 1), 0);
      mbar_wait(bars + 8 * B_STGE, 1);
      mbar_wait(bars + 8 * (B_STGE + 1), 0);
      float2 gbv[16];
#pragma unroll
      for (int n = 0; n < 16; n++) gbv[n] = lds64f(sm + MODB_OFF + (384 + 8 * n + 2 * c) * 4);
      tile_end(acc, prev);
      PROF_AT(tid == 0, 13);
#pragma unroll
      for (int ch = 0; ch < 2; ch++) {
        uint32_t lo[8], hi[8];
#pragma unroll
        for (int t = 0; t < 8; t++) {
          const int n = ch * 8 + t;
          const float2 gb = gbv[n];
          const uint4 a = x1[n >> 2], b = x1[4 + (n >> 2)];
          const uint32_t xl = (n & 3) == 0 ? a.x : (n & 3) == 1 ? a.y : (n & 3) == 2 ? a.z : a.w;
          const uint32_t xh = (n & 3) == 0 ? b.x : (n & 3) == 1 ? b.y : (n & 3) == 2 ? b.z : b.w;
          lo[t] = pack2(bf_lo(xl) + gb.x * acc[4 * n], bf_hi(xl) + gb.y * acc[4 * n + 1]);
          hi[t] = pack2(bf_lo(xh) + gb.x * acc[4 * n + 2], bf_hi(xh) + gb.y * acc[4 * n + 3]);
        }
        stage_slab(stg + ch * 16384 + cw * 8192, warp, lane, lo, hi);
        asm volatile("fence.proxy.async.shared::cta;" ::: "memory");
        __syncwarp();
        tma_store3(&p.out, stg + ch * 16384 + cw * 8192 + warp * 2048, j * 128 + ch * 64, rb * 64 + warp * 16, cw);
      }
      asm volatile("cp.async.bulk.commit_group;" ::: "memory");
      if (lane == 0) mbar_arrive(bars + 8 * B_STGF);
      asm volatile("cp.async.bulk.wait_group.read 0;" ::: "memory");
      PROF_AT(tid == 0, 14);
    }
    if (blockIdx.x == 0 && threadIdx.x == 128) asm volatile("st.relaxed.gpu.global.u32 [%0], %1;" ::"l"(p.epoch), "r"(tag) : "memory");
  }
}

typedef CUresult (*EncodeFn)(CUtensorMap*, CUtensorMapDataType, cuuint32_t, void*, const cuuint64_t*, const cuuint64_t*,
                             const cuuint32_t*, const cuuint32_t*, CUtensorMapInterleave, CUtensorMapSwizzle,
                             CUtensorMapL2promotion, CUtensorMapFloatOOBfill);

void encode2d(EncodeFn fn, CUtensorMap* m, const void* ptr, uint64_t cols, uint64_t rows, uint32_t box_rows) {
  cuuint64_t dims[2] = {cols, rows};
  cuuint64_t strides[1] = {cols * 2};
  cuuint32_t box[2] = {64, box_rows};
  cuuint32_t es[2] = {1, 1};
  fn(m, CU_TENSOR_MAP_DATA_TYPE_BFLOAT16, 2, (void*)ptr, dims, strides, box, es, CU_TENSOR_MAP_INTERLEAVE_NONE,
     CU_TENSOR_MAP_SWIZZLE_128B, CU_TENSOR_MAP_L2_PROMOTION_L2_128B, CU_TENSOR_MAP_FLOAT_OOB_FILL_NONE);
}

}

extern "C" void kernel_launch(void* const* d_in, const int* in_sizes, int n_in, void* d_out, int out_size) {
  (void)in_sizes; (void)n_in; (void)out_size;
  void* fp = nullptr;
  cudaDriverEntryPointQueryResult qr;
  cudaGetDriverEntryPoint("cuTensorMapEncodeTiled", &fp, cudaEnableDefault, &qr);
  EncodeFn fn = (EncodeFn)fp;
  void *ph, *po, *ph2, *pact;
  cudaGetSymbolAddress(&ph, g_h);
  cudaGetSymbolAddress(&po, g_o);
  ph2 = ph;
  cudaGetSymbolAddress(&pact, g_act);
  Params p;
  encode2d(fn, &p.h, ph, DM, SEQ, 128);
  encode2d(fn, &p.o_ld, po, DM, SEQ, 128);
  encode2d(fn, &p.h2, ph2, DM, SEQ, 128);
  encode2d(fn, &p.act, pact, FF, SEQ, 128);
  encode2d(fn, &p.act_st, pact, FF, SEQ, 32);
  encode2d(fn, &p.wm, d_in[8], 6 * DM, DM, 64);
  encode2d(fn, &p.o_st, po, DM, SEQ, 32);
  encode2d(fn, &p.wqkv, d_in[1], 3 * DM, DM, 64);
  encode2d(fn, &p.wqkv32, d_in[1], 3 * DM, DM, 32);
  encode2d(fn, &p.wo, d_in[2], DM, DM, 64);
  encode2d(fn, &p.wg, d_in[4], FF, DM, 64);
  encode2d(fn, &p.wu, d_in[5], FF, DM, 64);
  encode2d(fn, &p.wd, d_in[6], DM, FF, 64);
  {
    cuuint64_t dims[3] = {DM, SEQ / 2, 2};
    cuuint64_t strides[2] = {DM * 4, DM * 2};
    cuuint32_t box[3] = {64, 16, 1};
    cuuint32_t es[3] = {1, 1, 1};
    fn(&p.out, CU_TENSOR_MAP_DATA_TYPE_BFLOAT16, 3, d_out, dims, strides, box, es, CU_TENSOR_MAP_INTERLEAVE_NONE,
       CU_TENSOR_MAP_SWIZZLE_128B, CU_TENSOR_MAP_L2_PROMOTION_L2_128B, CU_TENSOR_MAP_FLOAT_OOB_FILL_NONE);
  }
  p.x = (const bf16*)d_in[0];
  p.c = (const bf16*)d_in[7];
  p.wmod = (const bf16*)d_in[8];
  for (int cl = 0; cl < 64; cl++) {
    const int grp = cl < 4 ? 0 : (cl < 36 ? (cl - 4) & 7 : 1 + (cl - 36) % 7);
    const int j = cl < 4 ? 4 + cl : (cl < 36 ? (cl - 4) >> 3 : 4 + (cl - 36) / 7);
    p.slot[cl] = (uint8_t)(grp * 8 + j);
  }
  void* q;
  p.x1 = (uint4*)d_out;
  cudaGetSymbolAddress(&q, g_modll); p.modll = (uint4*)q;
  cudaGetSymbolAddress(&q, g_halo); p.halo = (uint4*)q;
  cudaGetSymbolAddress(&q, g_stats); p.stats1 = (uint4*)q; p.stats2 = p.stats1 + SEQ * 8;
  cudaGetSymbolAddress(&q, g_cnt); p.cnt = (unsigned*)q;
  cudaGetSymbolAddress(&q, g_epoch); p.epoch = (unsigned*)q;

  cudaFuncSetAttribute(fused_kernel, cudaFuncAttributeMaxDynamicSharedMemorySize, SMEM_BYTES);
  cudaLaunchConfig_t cfg = {};
  cfg.gridDim = dim3(NCTA + 4);
  cfg.blockDim = dim3(384);
  cfg.dynamicSmemBytes = SMEM_BYTES;
  cfg.stream = cudaStreamPerThread;
  cudaLaunchAttribute at[1];
  at[0].id = cudaLaunchAttributeClusterDimension;
  at[0].val.clusterDim.x = 2; at[0].val.clusterDim.y = 1; at[0].val.clusterDim.z = 1;
  cfg.attrs = at;
  cfg.numAttrs = 1;
  cudaLaunchKernelEx(&cfg, fused_kernel, p);
}
```

```cpp
#include <cuda_runtime.h>
#include <cuda_bf16.h>
#include <cuda.h>
#include <stdint.h>

typedef __nv_bfloat16 bf16;

#define PAUSE 200
#define WMDELAY 2000
#define BDELAY 1500
#define NPRE0 3
#define NPRE1 1
#define ALIAS 1

#define PFW 8000
#define PFP 0

__device__ __forceinline__ void wgmma_ss_n128(float (&d)[64], uint32_t da, uint32_t db, int scale_d) {
  asm volatile("{\n.reg .pred p;\n.reg .b64 da, db;\nsetp.ne.b32 p, %66, 0;\n"
    "mov.b64 da, {%64, 0x40000040};\nmov.b64 db, {%65, 0x40000040};\n"
    "wgmma.mma_async.sync.aligned.m64n128k16.f32.bf16.bf16 "
    "{%0, %1, %2, %3, %4, %5, %6, %7, %8, %9, %10, %11, %12, %13, %14, %15, "
    "%16, %17, %18, %19, %20, %21, %22, %23, %24, %25, %26, %27, %28, %29, %30, %31, "
    "%32, %33, %34, %35, %36, %37, %38, %39, %40, %41, %42, %43, %44, %45, %46, %47, "
    "%48, %49, %50, %51, %52, %53, %54, %55, %56, %57, %58, %59, %60, %61, %62, %63}, "
    "da, db, p, 1, 1, 0, 1;\n}\n"
    : "+f"(d[0]), "+f"(d[1]), "+f"(d[2]), "+f"(d[3]), "+f"(d[4]), "+f"(d[5]), "+f"(d[6]), "+f"(d[7]),
      "+f"(d[8]), "+f"(d[9]), "+f"(d[10]), "+f"(d[11]), "+f"(d[12]), "+f"(d[13]), "+f"(d[14]), "+f"(d[15]),
      "+f"(d[16]), "+f"(d[17]), "+f"(d[18]), "+f"(d[19]), "+f"(d[20]), "+f"(d[21]), "+f"(d[22]), "+f"(d[23]),
      "+f"(d[24]), "+f"(d[25]), "+f"(d[26]), "+f"(d[27]), "+f"(d[28]), "+f"(d[29]), "+f"(d[30]), "+f"(d[31]),
      "+f"(d[32]), "+f"(d[33]), "+f"(d[34]), "+f"(d[35]), "+f"(d[36]), "+f"(d[37]), "+f"(d[38]), "+f"(d[39]),
      "+f"(d[40]), "+f"(d[41]), "+f"(d[42]), "+f"(d[43]), "+f"(d[44]), "+f"(d[45]), "+f"(d[46]), "+f"(d[47]),
      "+f"(d[48]), "+f"(d[49]), "+f"(d[50]), "+f"(d[51]), "+f"(d[52]), "+f"(d[53]), "+f"(d[54]), "+f"(d[55]),
      "+f"(d[56]), "+f"(d[57]), "+f"(d[58]), "+f"(d[59]), "+f"(d[60]), "+f"(d[61]), "+f"(d[62]), "+f"(d[63])
    : "r"(da), "r"(db), "r"(scale_d));
}

__device__ __forceinline__ void wgmma_ss_n192(float (&d)[96], uint32_t da, uint32_t db, int scale_d) {
  asm volatile("{\n.reg .pred p;\n.reg .b64 da, db;\nsetp.ne.b32 p, %98, 0;\n"
    "mov.b64 da, {%96, 0x40000040};\nmov.b64 db, {%97, 0x40000040};\n"
    "wgmma.mma_async.sync.aligned.m64n192k16.f32.bf16.bf16 "
    "{%0, %1, %2, %3, %4, %5, %6, %7, %8, %9, %10, %11, %12, %13, %14, %15, "
    "%16, %17, %18, %19, %20, %21, %22, %23, %24, %25, %26, %27, %28, %29, %30, %31, "
    "%32, %33, %34, %35, %36, %37, %38, %39, %40, %41, %42, %43, %44, %45, %46, %47, "
    "%48, %49, %50, %51, %52, %53, %54, %55, %56, %57, %58, %59, %60, %61, %62, %63, "
    "%64, %65, %66, %67, %68, %69, %70, %71, %72, %73, %74, %75, %76, %77, %78, %79, "
    "%80, %81, %82, %83, %84, %85, %86, %87, %88, %89, %90, %91, %92, %93, %94, %95}, "
    "da, db, p, 1, 1, 0, 1;\n}\n"
    : "+f"(d[0]), "+f"(d[1]), "+f"(d[2]), "+f"(d[3]), "+f"(d[4]), "+f"(d[5]), "+f"(d[6]), "+f"(d[7]),
      "+f"(d[8]), "+f"(d[9]), "+f"(d[10]), "+f"(d[11]), "+f"(d[12]), "+f"(d[13]), "+f"(d[14]), "+f"(d[15]),
      "+f"(d[16]), "+f"(d[17]), "+f"(d[18]), "+f"(d[19]), "+f"(d[20]), "+f"(d[21]), "+f"(d[22]), "+f"(d[23]),
      "+f"(d[24]), "+f"(d[25]), "+f"(d[26]), "+f"(d[27]), "+f"(d[28]), "+f"(d[29]), "+f"(d[30]), "+f"(d[31]),
      "+f"(d[32]), "+f"(d[33]), "+f"(d[34]), "+f"(d[35]), "+f"(d[36]), "+f"(d[37]), "+f"(d[38]), "+f"(d[39]),
      "+f"(d[40]), "+f"(d[41]), "+f"(d[42]), "+f"(d[43]), "+f"(d[44]), "+f"(d[45]), "+f"(d[46]), "+f"(d[47]),
      "+f"(d[48]), "+f"(d[49]), "+f"(d[50]), "+f"(d[51]), "+f"(d[52]), "+f"(d[53]), "+f"(d[54]), "+f"(d[55]),
      "+f"(d[56]), "+f"(d[57]), "+f"(d[58]), "+f"(d[59]), "+f"(d[60]), "+f"(d[61]), "+f"(d[62]), "+f"(d[63]),
      "+f"(d[64]), "+f"(d[65]), "+f"(d[66]), "+f"(d[67]), "+f"(d[68]), "+f"(d[69]), "+f"(d[70]), "+f"(d[71]),
      "+f"(d[72]), "+f"(d[73]), "+f"(d[74]), "+f"(d[75]), "+f"(d[76]), "+f"(d[77]), "+f"(d[78]), "+f"(d[79]),
      "+f"(d[80]), "+f"(d[81]), "+f"(d[82]), "+f"(d[83]), "+f"(d[84]), "+f"(d[85]), "+f"(d[86]), "+f"(d[87]),
      "+f"(d[88]), "+f"(d[89]), "+f"(d[90]), "+f"(d[91]), "+f"(d[92]), "+f"(d[93]), "+f"(d[94]), "+f"(d[95])
    : "r"(da), "r"(db), "r"(scale_d));
}

__device__ __forceinline__ void wgmma_ss_n256(float (&d)[128], uint32_t da, uint32_t db, int scale_d) {
  asm volatile("{\n.reg .pred p;\n.reg .b64 da, db;\nsetp.ne.b32 p, %130, 0;\n"
    "mov.b64 da, {%128, 0x40000040};\nmov.b64 db, {%129, 0x40000040};\n"
    "wgmma.mma_async.sync.aligned.m64n256k16.f32.bf16.bf16 "
    "{%0, %1, %2, %3, %4, %5, %6, %7, %8, %9, %10, %11, %12, %13, %14, %15, "
    "%16, %17, %18, %19, %20, %21, %22, %23, %24, %25, %26, %27, %28, %29, %30, %31, "
    "%32, %33, %34, %35, %36, %37, %38, %39, %40, %41, %42, %43, %44, %45, %46, %47, "
    "%48, %49, %50, %51, %52, %53, %54, %55, %56, %57, %58, %59, %60, %61, %62, %63, "
    "%64, %65, %66, %67, %68, %69, %70, %71, %72, %73, %74, %75, %76, %77, %78, %79, "
    "%80, %81, %82, %83, %84, %85, %86, %87, %88, %89, %90, %91, %92, %93, %94, %95, "
    "%96, %97, %98, %99, %100, %101, %102, %103, %104, %105, %106, %107, %108, %109, %110, %111, "
    "%112, %113, %114, %115, %116, %117, %118, %119, %120, %121, %122, %123, %124, %125, %126, %127}, "
    "da, db, p, 1, 1, 0, 1;\n}\n"
    : "+f"(d[0]), "+f"(d[1]), "+f"(d[2]), "+f"(d[3]), "+f"(d[4]), "+f"(d[5]), "+f"(d[6]), "+f"(d[7]),
      "+f"(d[8]), "+f"(d[9]), "+f"(d[10]), "+f"(d[11]), "+f"(d[12]), "+f"(d[13]), "+f"(d[14]), "+f"(d[15]),
      "+f"(d[16]), "+f"(d[17]), "+f"(d[18]), "+f"(d[19]), "+f"(d[20]), "+f"(d[21]), "+f"(d[22]), "+f"(d[23]),
      "+f"(d[24]), "+f"(d[25]), "+f"(d[26]), "+f"(d[27]), "+f"(d[28]), "+f"(d[29]), "+f"(d[30]), "+f"(d[31]),
      "+f"(d[32]), "+f"(d[33]), "+f"(d[34]), "+f"(d[35]), "+f"(d[36]), "+f"(d[37]), "+f"(d[38]), "+f"(d[39]),
      "+f"(d[40]), "+f"(d[41]), "+f"(d[42]), "+f"(d[43]), "+f"(d[44]), "+f"(d[45]), "+f"(d[46]), "+f"(d[47]),
      "+f"(d[48]), "+f"(d[49]), "+f"(d[50]), "+f"(d[51]), "+f"(d[52]), "+f"(d[53]), "+f"(d[54]), "+f"(d[55]),
      "+f"(d[56]), "+f"(d[57]), "+f"(d[58]), "+f"(d[59]), "+f"(d[60]), "+f"(d[61]), "+f"(d[62]), "+f"(d[63]),
      "+f"(d[64]), "+f"(d[65]), "+f"(d[66]), "+f"(d[67]), "+f"(d[68]), "+f"(d[69]), "+f"(d[70]), "+f"(d[71]),
      "+f"(d[72]), "+f"(d[73]), "+f"(d[74]), "+f"(d[75]), "+f"(d[76]), "+f"(d[77]), "+f"(d[78]), "+f"(d[79]),
      "+f"(d[80]), "+f"(d[81]), "+f"(d[82]), "+f"(d[83]), "+f"(d[84]), "+f"(d[85]), "+f"(d[86]), "+f"(d[87]),
      "+f"(d[88]), "+f"(d[89]), "+f"(d[90]), "+f"(d[91]), "+f"(d[92]), "+f"(d[93]), "+f"(d[94]), "+f"(d[95]),
      "+f"(d[96]), "+f"(d[97]), "+f"(d[98]), "+f"(d[99]), "+f"(d[100]), "+f"(d[101]), "+f"(d[102]), "+f"(d[103]),
      "+f"(d[104]), "+f"(d[105]), "+f"(d[106]), "+f"(d[107]), "+f"(d[108]), "+f"(d[109]), "+f"(d[110]), "+f"(d[111]),
      "+f"(d[112]), "+f"(d[113]), "+f"(d[114]), "+f"(d[115]), "+f"(d[116]), "+f"(d[117]), "+f"(d[118]), "+f"(d[119]),
      "+f"(d[120]), "+f"(d[121]), "+f"(d[122]), "+f"(d[123]), "+f"(d[124]), "+f"(d[125]), "+f"(d[126]), "+f"(d[127])
    : "r"(da), "r"(db), "r"(scale_d));
}

namespace {

constexpr int SEQ = 2048, DM = 1024, FF = 3584;
constexpr int NCTA = 128;

constexpr uint32_t STG_OFF = 196608;
constexpr uint32_t MISC_OFF = STG_OFF + 32768;
constexpr uint32_t SMEM_BYTES = MISC_OFF + 3072;
constexpr uint32_t RED_OFF = 2 * 49152;
constexpr uint32_t MODB_OFF = MISC_OFF + 512;

enum { B_FQ = 0, B_EQ = 4, B_FW = 8, B_EW = 14, B_FG = 20, B_EG = 24, B_FD = 28, B_ED = 34,
       B_STGF = 40, B_MODB = 42, B_MODA = 45, B_RDY = 48, B_STGE = 56, B_COUNT = 58 };
enum { C_H = 0, C_O = 1, C_H2 = 3, C_ACT = 4, C_HA = 8, C_H2A = 9 };

struct Params {
  CUtensorMap h, o_ld, o_st, h2, act, out, wqkv, wqkv32, wo, wg, wu, wd, act_st, wm;
  const bf16* x;
  const bf16* c;
  const bf16* wmod;
  uint4* x1;
  uint4* modll;
  uint4* halo;
  uint4* stats1;
  uint4* stats2;
  unsigned* cnt;
  unsigned* epoch;
  uint8_t slot[64];
};

__device__ __align__(1024) bf16 g_h[SEQ * DM];
__device__ __align__(1024) bf16 g_o[SEQ * DM];
__device__ __align__(1024) bf16 g_act[SEQ * FF];
__device__ __align__(1024) uint4 g_modll[3072 / 2];
__device__ __align__(1024) uint4 g_halo[16 * 8 * 2 * 2 * 8 * 32];
__device__ __align__(1024) uint4 g_stats[2 * SEQ * 8];
__device__ __align__(1024) unsigned g_cnt[16 * 32];
__device__ uint4 g_epoch;
#define TR(off)

__device__ __forceinline__ uint32_t smem_u32(const void* p) { return (uint32_t)__cvta_generic_to_shared(p); }
__device__ __forceinline__ void mbar_init(uint32_t bar, uint32_t count) {
  asm volatile("mbarrier.init.shared::cta.b64 [%0], %1;" ::"r"(bar), "r"(count));
}
__device__ __forceinline__ void mbar_arrive(uint32_t bar) {
  asm volatile("mbarrier.arrive.shared::cta.b64 _, [%0];" ::"r"(bar) : "memory");
}
__device__ __forceinline__ void mbar_arrive_cluster(uint32_t cluster_addr) {
  asm volatile("mbarrier.arrive.shared::cluster.b64 _, [%0];" ::"r"(cluster_addr) : "memory");
}
__device__ __forceinline__ uint32_t mapa(uint32_t addr, uint32_t cta) {
  uint32_t r;
  asm volatile("mapa.shared::cluster.u32 %0, %1, %2;" : "=r"(r) : "r"(addr), "r"(cta));
  return r;
}
__device__ __forceinline__ void mbar_wait(uint32_t bar, uint32_t parity) {
  asm volatile(
      "{\n.reg .pred p;\n"
      "WAIT_%=:\n"
      "mbarrier.try_wait.parity.shared::cta.b64 p, [%0], %1;\n"
      "@!p bra WAIT_%=;\n}\n" ::"r"(bar), "r"(parity) : "memory");
}
__device__ __forceinline__ void mbar_wait_watchdog(uint32_t bar, uint32_t parity) {
  asm volatile(
      "{\n.reg .pred p;\n.reg .u64 t0, t1;\nmov.u64 t0, %%globaltimer;\n"
      "WAIT_%=:\n"
      "mbarrier.try_wait.parity.shared::cta.b64 p, [%0], %1;\n"
      "@p bra DONE_%=;\n"
      "mov.u64 t1, %%globaltimer;\n"
      "sub.u64 t1, t1, t0;\n"
      "setp.lt.u64 p, t1, 2000000000;\n"
      "@p bra WAIT_%=;\n"
      "trap;\n"
      "DONE_%=:\n}\n" ::"r"(bar), "r"(parity) : "memory");
}
__device__ __forceinline__ void cnt_wait(const unsigned* p, unsigned target) {
  asm volatile(
      "{\n.reg .pred p;\n.reg .u32 v;\n.reg .s32 d;\n"
      "WAIT_%=:\n"
      "ld.relaxed.gpu.global.u32 v, [%0];\n"
      "sub.s32 d, v, %1;\n"
      "setp.lt.s32 p, d, 0;\n"
      "@p bra WAIT_%=;\n"
      "fence.proxy.async.global;\n"
      "}\n" ::"l"(p), "r"(target) : "memory");
}
__device__ __forceinline__ void cnt_wait_lazy(const unsigned* p, unsigned target) {
  asm volatile(
      "{\n.reg .pred p;\n.reg .u32 v;\n.reg .s32 d;\n"
      "WAIT_%=:\n"
      "nanosleep.u32 400;\n"
      "ld.relaxed.gpu.global.u32 v, [%0];\n"
      "sub.s32 d, v, %1;\n"
      "setp.lt.s32 p, d, 0;\n"
      "@p bra WAIT_%=;\n"
      "fence.proxy.async.global;\n"
      "}\n" ::"l"(p), "r"(target) : "memory");
}
__device__ __forceinline__ void cnt_signal(unsigned* p) {
  asm volatile("{\n.reg .pred p;\nelect.sync _|p, 0xffffffff;\n@p red.relaxed.gpu.global.add.u32 [%0], 1;\n}\n" ::"l"(p) : "memory");
}
__device__ __forceinline__ void ll_store(uint4* p, uint32_t a, uint32_t b, uint32_t tag) {
  asm volatile("st.relaxed.gpu.global.v2.b64 [%0], {%1, %2};" ::"l"(p), "l"((uint64_t)a | ((uint64_t)tag << 32)),
               "l"((uint64_t)b | ((uint64_t)tag << 32)) : "memory");
}
__device__ __forceinline__ uint4 ll_peek(const uint4* p) {
  uint4 v;
  asm volatile("ld.relaxed.gpu.global.v4.u32 {%0, %1, %2, %3}, [%4];" : "=r"(v.x), "=r"(v.y), "=r"(v.z), "=r"(v.w) : "l"(p) : "memory");
  return v;
}
template <int N, int SLEEP = 0, class F>
__device__ __forceinline__ void ll_poll(F addr, uint32_t tag, uint32_t (&out)[2 * N]) {
  for (;;) {
    uint4 v[N];
#pragma unroll
    for (int i = 0; i < N; i++) v[i] = ll_peek(addr(i));
    uint32_t bad = 0;
#pragma unroll
    for (int i = 0; i < N; i++) {
      bad |= (v[i].y ^ tag) | (v[i].w ^ tag);
      out[2 * i] = v[i].x;
      out[2 * i + 1] = v[i].z;
    }
    if (__all_sync(~0u, bad == 0)) break;
    if (SLEEP) __nanosleep(SLEEP);
  }
}
constexpr uint64_t POLICY_EVICT_FIRST = 0x12F0000000000000ull;
__device__ __forceinline__ void expect_tx_elect(uint32_t bar, uint32_t bytes) {
  asm volatile("{\n.reg .pred p;\nelect.sync _|p, 0xffffffff;\n@p mbarrier.arrive.expect_tx.shared::cta.b64 _, [%0], %1;\n}\n" ::"r"(bar), "r"(bytes) : "memory");
}
__device__ __forceinline__ void arrive_elect(uint32_t bar) {
  asm volatile("{\n.reg .pred p;\nelect.sync _|p, 0xffffffff;\n@p mbarrier.arrive.shared::cta.b64 _, [%0];\n}\n" ::"r"(bar) : "memory");
}
__device__ __forceinline__ void tma_load(uint32_t dst, const CUtensorMap* m, uint32_t bar, int c0, int c1) {
  asm volatile("{\n.reg .pred p;\nelect.sync _|p, 0xffffffff;\n"
               "@p cp.async.bulk.tensor.2d.shared::cluster.global.mbarrier::complete_tx::bytes [%0], [%1, {%3, %4}], [%2];\n}\n"
               ::"r"(dst), "l"(m), "r"(bar), "r"(c0), "r"(c1) : "memory");
}
__device__ __forceinline__ void tma_load_mc(uint32_t dst, const CUtensorMap* m, uint32_t bar, int c0, int c1) {
  asm volatile("{\n.reg .pred p;\nelect.sync _|p, 0xffffffff;\n"
               "@p cp.async.bulk.tensor.2d.shared::cluster.global.mbarrier::complete_tx::bytes.multicast::cluster.L2::cache_hint [%0], [%1, {%3, %4}], [%2], %5, %6;\n}\n"
               ::"r"(dst), "l"(m), "r"(bar), "r"(c0), "r"(c1), "h"((uint16_t)3), "l"(POLICY_EVICT_FIRST) : "memory");
}
__device__ __forceinline__ void tma_load_ef(uint32_t dst, const CUtensorMap* m, uint32_t bar, int c0, int c1) {
  asm volatile("{\n.reg .pred p;\nelect.sync _|p, 0xffffffff;\n"
               "@p cp.async.bulk.tensor.2d.shared::cluster.global.mbarrier::complete_tx::bytes.L2::cache_hint [%0], [%1, {%3, %4}], [%2], %5;\n}\n"
               ::"r"(dst), "l"(m), "r"(bar), "r"(c0), "r"(c1), "l"(POLICY_EVICT_FIRST) : "memory");
}
__device__ __forceinline__ void tma_store2(const CUtensorMap* m, uint32_t src, int c0, int c1) {
  asm volatile("{\n.reg .pred p;\nelect.sync _|p, 0xffffffff;\n"
               "@p cp.async.bulk.tensor.2d.global.shared::cta.bulk_group [%0, {%2, %3}], [%1];\n}\n"
               ::"l"(m), "r"(src), "r"(c0), "r"(c1) : "memory");
}
__device__ __forceinline__ void tma_store3(const CUtensorMap* m, uint32_t src, int c0, int c1, int c2) {
  asm volatile("{\n.reg .pred p;\nelect.sync _|p, 0xffffffff;\n"
               "@p cp.async.bulk.tensor.3d.global.shared::cta.bulk_group [%0, {%2, %3, %4}], [%1];\n}\n"
               ::"l"(m), "r"(src), "r"(c0), "r"(c1), "r"(c2) : "memory");
}
__device__ __forceinline__ void store_pause(bool sleep) {
  asm volatile("cp.async.bulk.commit_group;" ::: "memory");
  asm volatile("cp.async.bulk.wait_group.read 0;" ::: "memory");
  if (sleep) __nanosleep(PAUSE);
}
__device__ __forceinline__ void l2_prefetch_tile(const CUtensorMap* m, int c0, int c1) {
  asm volatile("{\n.reg .pred p;\nelect.sync _|p, 0xffffffff;\n@p cp.async.bulk.prefetch.tensor.2d.L2.global [%0, {%1, %2}];\n}\n"
               ::"l"(m), "r"(c0), "r"(c1) : "memory");
}
__device__ __forceinline__ void prefetch_map(const CUtensorMap* m) {
  asm volatile("prefetch.tensormap [%0];" ::"l"(m) : "memory");
}
__device__ __forceinline__ void wg_fence() { asm volatile("wgmma.fence.sync.aligned;" ::: "memory"); }
__device__ __forceinline__ void wg_commit() { asm volatile("wgmma.commit_group.sync.aligned;" ::: "memory"); }
template <int N>
__device__ __forceinline__ void wg_wait() { asm volatile("wgmma.wait_group.sync.aligned %0;" ::"n"(N) : "memory"); }
__device__ __forceinline__ void bar_sync(int id, int n) { asm volatile("bar.sync %0, %1;" ::"r"(id), "r"(n) : "memory"); }
__device__ __forceinline__ void wg_bar(int cw) {
  asm volatile("{\n.reg .pred p;\nsetp.ne.s32 p, %0, 0;\n@p bar.sync 3, 128;\n@!p bar.sync 2, 128;\n}\n" ::"r"(cw) : "memory");
}
__device__ __forceinline__ void cluster_arrive_relaxed() { asm volatile("barrier.cluster.arrive.relaxed.aligned;" ::: "memory"); }
__device__ __forceinline__ void cluster_wait() { asm volatile("barrier.cluster.wait.acquire.aligned;" ::: "memory"); }
__device__ __forceinline__ uint32_t load_epoch(const unsigned* p) {
  uint32_t e;
  asm volatile("ld.relaxed.gpu.global.u32 %0, [%1];" : "=r"(e) : "l"(p) : "memory");
  return e;
}
__device__ __forceinline__ uint32_t pack2(float lo, float hi) {
  uint32_t r;
  asm("cvt.rn.bf16x2.f32 %0, %1, %2;" : "=r"(r) : "f"(hi), "f"(lo));
  return r;
}
__device__ __forceinline__ float bf_lo(uint32_t v) { return __uint_as_float(v << 16); }
__device__ __forceinline__ float bf_hi(uint32_t v) { return __uint_as_float(v & 0xffff0000u); }
__device__ __forceinline__ float bf_round(float v) { return __bfloat162float(__float2bfloat16_rn(v)); }
__device__ __forceinline__ float silu_f(float v) { return __fdividef(v, 1.0f + __expf(-v)); }
__device__ __forceinline__ uint4 ldg_nc(const void* p) {
  uint4 v;
  asm volatile("ld.global.nc.L1::no_allocate.v4.u32 {%0, %1, %2, %3}, [%4];" : "=r"(v.x), "=r"(v.y), "=r"(v.z), "=r"(v.w) : "l"(p));
  return v;
}
__device__ __forceinline__ void stmatrix4(uint32_t addr, uint32_t a, uint32_t b, uint32_t c, uint32_t d) {
  asm volatile("stmatrix.sync.aligned.m8n8.x4.shared.b16 [%0], {%1, %2, %3, %4};" ::"r"(addr), "r"(a), "r"(b), "r"(c), "r"(d) : "memory");
}
__device__ __forceinline__ void stmatrix2(uint32_t addr, uint32_t a, uint32_t b) {
  asm volatile("stmatrix.sync.aligned.m8n8.x2.shared.b16 [%0], {%1, %2};" ::"r"(addr), "r"(a), "r"(b) : "memory");
}
__device__ __forceinline__ void stmatrix1(uint32_t addr, uint32_t a) {
  asm volatile("stmatrix.sync.aligned.m8n8.x1.shared.b16 [%0], {%1};" ::"r"(addr), "r"(a) : "memory");
}
__device__ __forceinline__ uint32_t movmatrix(uint32_t a) {
  uint32_t d;
  asm("movmatrix.sync.aligned.m8n8.trans.b16 %0, %1;" : "=r"(d) : "r"(a));
  return d;
}
__device__ __forceinline__ void mma16816(float (&d)[4], uint32_t a0, uint32_t a1, uint32_t a2, uint32_t a3, uint32_t b0, uint32_t b1) {
  asm("mma.sync.aligned.m16n8k16.row.col.f32.bf16.bf16.f32 {%0, %1, %2, %3}, {%4, %5, %6, %7}, {%8, %9}, {%0, %1, %2, %3};"
               : "+f"(d[0]), "+f"(d[1]), "+f"(d[2]), "+f"(d[3]) : "r"(a0), "r"(a1), "r"(a2), "r"(a3), "r"(b0), "r"(b1));
}
__device__ __forceinline__ void mma1688(float (&d)[4], uint32_t a0, uint32_t a1, uint32_t b0) {
  asm("mma.sync.aligned.m16n8k8.row.col.f32.bf16.bf16.f32 {%0, %1, %2, %3}, {%4, %5}, {%6}, {%0, %1, %2, %3};"
               : "+f"(d[0]), "+f"(d[1]), "+f"(d[2]), "+f"(d[3]) : "r"(a0), "r"(a1), "r"(b0));
}
__device__ __forceinline__ void ldmatrix4t(uint32_t (&b)[4], uint32_t addr) {
  asm volatile("ldmatrix.sync.aligned.m8n8.x4.trans.shared.b16 {%0, %1, %2, %3}, [%4];" : "=r"(b[0]), "=r"(b[1]), "=r"(b[2]), "=r"(b[3]) : "r"(addr) : "memory");
}
__device__ __forceinline__ void ldmatrix4(uint32_t& a, uint32_t& b, uint32_t& c, uint32_t& d, uint32_t addr) {
  asm volatile("ldmatrix.sync.aligned.m8n8.x4.shared.b16 {%0, %1, %2, %3}, [%4];" : "=r"(a), "=r"(b), "=r"(c), "=r"(d) : "r"(addr) : "memory");
}
__device__ __forceinline__ void cp_async16(uint32_t dst, const void* src) {
  asm volatile("cp.async.cg.shared.global.L2::cache_hint [%0], [%1], 16, %2;" ::"r"(dst), "l"(src), "l"(POLICY_EVICT_FIRST) : "memory");
}
__device__ __forceinline__ uint32_t lds32(uint32_t addr) {
  uint32_t v;
  asm volatile("ld.shared.u32 %0, [%1];" : "=r"(v) : "r"(addr) : "memory");
  return v;
}
__device__ __forceinline__ void sts64f(uint32_t addr, float a, float b) {
  asm volatile("st.shared.v2.f32 [%0], {%1, %2};" ::"r"(addr), "f"(a), "f"(b) : "memory");
}
constexpr float QK_SCALE = 0.17677669529663687f;
__device__ __forceinline__ float softmax8(float& p0, float& p1) {
  float m = fmaxf(p0, p1);
  m = fmaxf(m, __shfl_xor_sync(~0u, m, 1));
  m = fmaxf(m, __shfl_xor_sync(~0u, m, 2));
  asm("ex2.approx.ftz.f32 %0, %1;" : "=f"(p0) : "f"((p0 - m) * 1.4426950408889634f));
  asm("ex2.approx.ftz.f32 %0, %1;" : "=f"(p1) : "f"((p1 - m) * 1.4426950408889634f));
  float s = p0 + p1;
  s += __shfl_xor_sync(~0u, s, 1);
  s += __shfl_xor_sync(~0u, s, 2);
  float r;
  asm("rcp.approx.ftz.f32 %0, %1;" : "=f"(r) : "f"(s));
  return r;
}
__device__ __forceinline__ void sts128(uint32_t addr, uint32_t a, uint32_t b, uint32_t c, uint32_t d) {
  asm volatile("st.shared.v4.u32 [%0], {%1, %2, %3, %4};" ::"r"(addr), "r"(a), "r"(b), "r"(c), "r"(d) : "memory");
}
__device__ __forceinline__ uint4 lds128(uint32_t addr) {
  uint4 v;
  asm volatile("ld.shared.v4.u32 {%0, %1, %2, %3}, [%4];" : "=r"(v.x), "=r"(v.y), "=r"(v.z), "=r"(v.w) : "r"(addr) : "memory");
  return v;
}
__device__ __forceinline__ float2 lds64f(uint32_t addr) {
  float2 v;
  asm volatile("ld.shared.v2.f32 {%0, %1}, [%2];" : "=f"(v.x), "=f"(v.y) : "r"(addr) : "memory");
  return v;
}
#define PROF_AT(cond, slot) do {} while (0)

constexpr uint32_t SMEM_BASE = 1024;
constexpr uint32_t DESC_A = (1u << 16) | (SMEM_BASE >> 4);
constexpr uint32_t DESC_B = ((8192u >> 4) << 16) | ((SMEM_BASE + 16384) >> 4);

template <int BN> struct Wg;
template <> struct Wg<128> { static __device__ __forceinline__ void mma(float (&d)[64], uint32_t a, uint32_t b, int s) { wgmma_ss_n128(d, a, b, s); } };
template <> struct Wg<192> { static __device__ __forceinline__ void mma(float (&d)[96], uint32_t a, uint32_t b, int s) { wgmma_ss_n192(d, a, b, s); } };
template <> struct Wg<256> { static __device__ __forceinline__ void mma(float (&d)[128], uint32_t a, uint32_t b, int s) { wgmma_ss_n256(d, a, b, s); } };

struct Ring {
  uint32_t full0, rel0;
  int s;
  uint32_t ph;
  bool releaser;
};

template <int N>
__device__ __forceinline__ void fence_regs(float (&a)[N]) {
#pragma unroll
  for (int i = 0; i < N; i++) asm volatile("" : "+f"(a[i])::"memory");
}

template <int BN, int NST, uint32_t STAGE>
__device__ __forceinline__ void kblock(float (&acc)[BN / 2], Ring& g, uint32_t a_addr, bool zero, uint32_t& prev) {
  mbar_wait(g.full0 + 8 * g.s, g.ph);
  const uint32_t da = DESC_A + (a_addr >> 4);
  const uint32_t db = DESC_B + g.s * (STAGE >> 4);
  wg_fence();
#pragma unroll
  for (int k = 0; k < 4; k++) Wg<BN>::mma(acc, da + k * 2, db + k * 128, !(zero && k == 0));
  wg_commit();
  wg_wait<1>();
  if (prev != 0) mbar_arrive_cluster(prev);
  prev = g.releaser ? g.rel0 + 8 * g.s : 0u;
  if (++g.s == NST) { g.s = 0; g.ph ^= 1; }
}
template <int N>
__device__ __forceinline__ void tile_end(float (&acc)[N], uint32_t& prev) {
  wg_wait<0>();
  if (prev != 0) mbar_arrive_cluster(prev);
  prev = 0;
  fence_regs(acc);
}

__device__ __forceinline__ int other_kb(int q, int j) {
  const int ch = q >= 7, jj = q - 7 * ch;
  return 2 * (jj < j ? jj : jj + 1) + ch;
}
__device__ __forceinline__ int own_first(int it, int j) {
  return it >= 16 ? (it & 15) : (it < 2 ? 2 * j + it : other_kb(it - 2, j));
}
__device__ __forceinline__ int qkv_kb(int it, int j) {
  return it < 4 ? 2 * j + (it & 1) : other_kb(it < 18 ? it - 4 : it - 18, j);
}
__device__ __forceinline__ int wo_k(int it, int j) {
  return it < 8 ? it * 128 : (it == 8 ? j : (it - 9 < j ? it - 9 : it - 8)) * 128 + 64;
}
__device__ __forceinline__ int down_k(int it) {
  const int r = (it >> 4) - 1, idx = it & 15;
  return r < 0 ? idx * 64 : (r < 3 ? (idx >> 1) * 448 + r * 128 + (idx & 1) * 64 : idx * 448 + 384);
}
__device__ __forceinline__ void wait_p3_free(uint32_t empty3, int i) {
  mbar_wait(empty3 + 8 * ((i * 2) / 3), 1);
  mbar_wait(empty3 + 8 * ((i * 2 + 1) / 3), 1);
}
__device__ __forceinline__ void wait_p2_free(uint32_t empty2, int i) {
  const int w0 = (i * 3) / 2, w1 = (i * 3 + 2) / 2;
  mbar_wait(empty2 + 8 * w0, w0 < 4 ? 0 : 1);
  mbar_wait(empty2 + 8 * w1, w1 < 4 ? 0 : 1);
}

__device__ __forceinline__ void chan(float& m, float& q, float m2, float q2, float n) {
  const float d = m2 - m;
  m = 0.5f * (m + m2);
  q = q + q2 + d * d * (0.5f * n);
}

template <int N>
__device__ __forceinline__ void row_stats(const uint32_t (&ll)[N], float& mean, float& rstd) {
  float ma = __uint_as_float(ll[0]), qa = __uint_as_float(ll[1]), mb = __uint_as_float(ll[4]), qb = __uint_as_float(ll[5]);
  chan(ma, qa, __uint_as_float(ll[2]), __uint_as_float(ll[3]), 128.f);
  chan(mb, qb, __uint_as_float(ll[6]), __uint_as_float(ll[7]), 128.f);
  chan(ma, qa, mb, qb, 256.f);
  const float mo = __shfl_xor_sync(~0u, ma, 16), qo = __shfl_xor_sync(~0u, qa, 16);
  chan(ma, qa, mo, qo, 512.f);
  mean = ma;
  rstd = rsqrtf(qa * (1.0f / DM) + 1e-5f);
}

__device__ __forceinline__ void publish_stats(const uint32_t (&xl)[16], const uint32_t (&xh)[16], uint4* slot, int lane, uint32_t tag) {
  float ds[4] = {0.f, 0.f, 0.f, 0.f}, dl[4] = {0.f, 0.f, 0.f, 0.f}, dh[4] = {0.f, 0.f, 0.f, 0.f};
#pragma unroll
  for (int q = 0; q < 8; q++) {
    mma16816(ds, xl[2 * q], xh[2 * q], xl[2 * q + 1], xh[2 * q + 1], 0x3f803f80u, 0x3f803f80u);
    mma16816(dl, xl[2 * q], xh[2 * q], xl[2 * q + 1], xh[2 * q + 1], xl[2 * q], xl[2 * q + 1]);
    mma16816(dh, xl[2 * q], xh[2 * q], xl[2 * q + 1], xh[2 * q + 1], xh[2 * q], xh[2 * q + 1]);
  }
  const int r = lane >> 2;
  if ((lane & 3) == (r >> 1)) {
    const float ml = ds[0] * (1.0f / 128), mh = ds[2] * (1.0f / 128);
    const float ql = fmaxf(((r & 1) ? dl[1] : dl[0]) - ds[0] * ml, 0.f), qh = fmaxf(((r & 1) ? dh[3] : dh[2]) - ds[2] * mh, 0.f);
    ll_store(slot + r, __float_as_uint(ml), __float_as_uint(ql), tag);
    ll_store(slot + r + 8, __float_as_uint(mh), __float_as_uint(qh), tag);
  }
  __syncwarp();
}

__device__ __forceinline__ void stage_slab(uint32_t chunk, int warp, int lane, const uint32_t (&lo)[8], const uint32_t (&hi)[8]) {
  const int row = warp * 16 + (lane & 7) + ((lane >> 3) & 1) * 8;
  const uint32_t rbase = chunk + row * 128;
#pragma unroll
  for (int q = 0; q < 4; q++) {
    const int grp = 2 * q + (lane >> 4);
    stmatrix4(rbase + ((grp ^ (row & 7)) << 4), lo[2 * q], hi[2 * q], lo[2 * q + 1], hi[2 * q + 1]);
  }
}
__device__ __forceinline__ float silu_mul(float g, float u) {
  float e, r;
  asm("ex2.approx.ftz.f32 %0, %1;" : "=f"(e) : "f"(g * -1.4426950408889634f));
  asm("rcp.approx.ftz.f32 %0, %1;" : "=f"(r) : "f"(1.0f + e));
  return g * r * u;
}
__device__ __forceinline__ uint32_t swiglu2(uint32_t g2, uint32_t u2) {
  asm volatile("" : "+r"(g2));
  return pack2(silu_mul(bf_lo(g2), bf_lo(u2)), silu_mul(bf_hi(g2), bf_hi(u2)));
}
__device__ __forceinline__ void stage_done(uint32_t bar, int lane) {
  asm volatile("fence.proxy.async.shared::cta;" ::: "memory");
  __syncwarp();
  if (lane == 0) mbar_arrive(bar);
}

__device__ __forceinline__ int fresh_tid() {
  int t;
  asm volatile("mov.u32 %0, %%tid.x;" : "=r"(t));
  return t;
}
#define RING_IDS()                                                                                           \
  const int tid = fresh_tid() - 128;                                                                         \
  const int cw = __shfl_sync(~0u, tid >> 7, 0), warp = __shfl_sync(~0u, (tid >> 5) & 3, 0);                  \
  const bool releaser = (tid & 31) < 2;                                                                      \
  const uint32_t rbars = mapa(bars, tid & 1);                                                                \
  const uint32_t a_base = cw * 8192
#define LANE_IDS()                                                                                           \
  const int lane = fresh_tid() & 31, r = lane >> 2, c = lane & 3;                                            \
  const int srow = warp * 16 + (lane & 7) + ((lane >> 3) & 1) * 8;                                           \
  const uint32_t slab = stg + cw * 8192 + srow * 128, sw0 = (lane >> 4) ^ (srow & 7);                        \
  (void)r; (void)c; (void)slab; (void)sw0

template <int NPRE, bool EAGER, class Step>
__device__ __forceinline__ void attention(float (&acc)[96], const Params& p, int rho, int rb, int cta, int cw, int warp, uint32_t tag,
                                          uint32_t stg, uint32_t bars, uint32_t& prev, Step step) {
  uint32_t ql[8], qh[8], k0[8], k1[8], v0[8], v1[8], hp[16];
  if (EAGER) {
    tile_end(acc, prev);
  } else {
    step();
    fence_regs(acc);
  }
#pragma unroll
  for (int t = 0; t < 8; t++) {
    k0[t] = pack2(acc[4 * (8 + t)], acc[4 * (8 + t) + 1]);
    k1[t] = pack2(acc[4 * (8 + t) + 2], acc[4 * (8 + t) + 3]);
    v0[t] = pack2(acc[4 * (16 + t)], acc[4 * (16 + t) + 1]);
    v1[t] = pack2(acc[4 * (16 + t) + 2], acc[4 * (16 + t) + 3]);
    asm volatile("" : "+r"(k0[t]), "+r"(k1[t]), "+r"(v0[t]), "+r"(v1[t]));
  }
  const int lane = fresh_tid() & 31, r = lane >> 2, c = lane & 3;
#pragma unroll
  for (int t = 0; t < 8; t++) v1[t] = movmatrix(v1[t]);
  mbar_wait(bars + 8 * B_STGE, rho);
  mbar_wait(bars + 8 * (B_STGE + 1), 0);
  const uint32_t xch = stg + 16384 + (cw * 4 + warp) * 2048 + lane * 16;
  if (warp < 3) {
    sts128(xch, k1[0], k1[1], k1[2], k1[3]);
    sts128(xch + 512, k1[4], k1[5], k1[6], k1[7]);
    sts128(xch + 1024, v1[0], v1[1], v1[2], v1[3]);
    sts128(xch + 1536, v1[4], v1[5], v1[6], v1[7]);
  } else if (rb < 15) {
    uint4* dst = p.halo + ((cta * 2 + rho) * 2 + cw) * 256 + lane;
#pragma unroll
    for (int t = 0; t < 4; t++) {
      ll_store(dst + t * 32, k1[2 * t], k1[2 * t + 1], tag);
      ll_store(dst + (4 + t) * 32, v1[2 * t], v1[2 * t + 1], tag);
    }
  }
#pragma unroll
  for (int t = 0; t < 8; t++) {
    v0[t] = movmatrix(v0[t]);
    ql[t] = pack2(acc[4 * t], acc[4 * t + 1]);
    qh[t] = pack2(acc[4 * t + 2], acc[4 * t + 3]);
    asm volatile("" : "+r"(v0[t]), "+r"(ql[t]), "+r"(qh[t]));
  }
#pragma unroll 1
  for (int i = 0; i < NPRE; i++) step();
  const uint4* src = p.halo + (((cta - 8) * 2 + rho) * 2 + cw) * 256 + lane;
  uint4 early[8] = {};
  if (warp == 0 && rb > 0) {
#pragma unroll
    for (int i = 0; i < 8; i++) early[i] = ll_peek(src + i * 32);
  }
  step();
  wg_bar(cw);
  if (warp > 0) {
#pragma unroll
    for (int t = 0; t < 4; t++) {
      const uint4 a = lds128(xch - 2048 + t * 512);
      hp[4 * t] = a.x; hp[4 * t + 1] = a.y; hp[4 * t + 2] = a.z; hp[4 * t + 3] = a.w;
    }
  } else if (rb > 0) {
    uint32_t bad = 0;
#pragma unroll
    for (int i = 0; i < 8; i++) {
      bad |= (early[i].y ^ tag) | (early[i].w ^ tag);
      hp[2 * i] = early[i].x;
      hp[2 * i + 1] = early[i].z;
    }
    if (!__all_sync(~0u, bad == 0)) ll_poll<8>([&](int i) { return src + i * 32; }, tag, hp);
  } else {
#pragma unroll
    for (int t = 0; t < 16; t++) hp[t] = 0;
  }
  wg_wait<0>();
  if (prev != 0) mbar_arrive_cluster(prev);
  prev = 0;
#pragma unroll
  for (int t = 0; t < 8; t++) asm volatile("" : "+r"(ql[t])::"memory");
  const bool up0 = 2 * c > r, up1 = 2 * c + 1 > r;
  const bool first = (rb == 0) && (warp == 0);
  uint32_t a0[2], a2[2], a3[2], a5[2];
  float il[2], ih[2];
#pragma unroll
  for (int h = 0; h < 2; h++) {
    float sp[4] = {0.f, 0.f, 0.f, 0.f}, s0[4] = {0.f, 0.f, 0.f, 0.f}, s1[4] = {0.f, 0.f, 0.f, 0.f};
#pragma unroll
    for (int ks = 0; ks < 2; ks++) {
      const int t = 4 * h + 2 * ks;
      mma16816(sp, ql[t], qh[t], ql[t + 1], qh[t + 1], hp[t], hp[t + 1]);
      mma16816(s0, ql[t], qh[t], ql[t + 1], qh[t + 1], k0[t], k0[t + 1]);
      mma16816(s1, ql[t], qh[t], ql[t + 1], qh[t + 1], k1[t], k1[t + 1]);
    }
    float p0 = (up0 ? sp[0] : s0[0]) * QK_SCALE, p1 = (up1 ? sp[1] : s0[1]) * QK_SCALE;
    float p2 = (up0 ? s0[2] : s1[2]) * QK_SCALE, p3 = (up1 ? s0[3] : s1[3]) * QK_SCALE;
    if (first && up0) p0 = -1000000000.0f;
    if (first && up1) p1 = -1000000000.0f;
    il[h] = softmax8(p0, p1);
    ih[h] = softmax8(p2, p3);
    a0[h] = pack2(up0 ? p0 : 0.f, up1 ? p1 : 0.f);
    a2[h] = pack2(up0 ? 0.f : p0, up1 ? 0.f : p1);
    a3[h] = pack2(up0 ? p2 : 0.f, up1 ? p3 : 0.f);
    a5[h] = pack2(up0 ? 0.f : p2, up1 ? 0.f : p3);
  }
  float o[8][4];
#pragma unroll
  for (int t = 0; t < 8; t++) {
#pragma unroll
    for (int q = 0; q < 4; q++) o[t][q] = 0.f;
    mma1688(o[t], 0u, a5[t >> 2], v1[t]);
    mma16816(o[t], a0[t >> 2], 0u, a2[t >> 2], a3[t >> 2], hp[8 + t], v0[t]);
  }
#pragma unroll
  for (int t = 0; t < 8; t++) fence_regs(o[t]);
  if (!EAGER) step();
  uint32_t ol[8], oh[8];
#pragma unroll
  for (int t = 0; t < 8; t++) {
    ol[t] = pack2(o[t][0] * il[t >> 2], o[t][1] * il[t >> 2]);
    oh[t] = pack2(o[t][2] * ih[t >> 2], o[t][3] * ih[t >> 2]);
  }
  if (!EAGER) step();
  stage_slab(stg + cw * 8192, warp, lane, ol, oh);
  stage_done(bars + 8 * B_STGF, lane);
  if (!EAGER) step();
}

template <class Ready>
__device__ __forceinline__ void normalize_stage(const uint32_t (&xl)[16], const uint32_t (&xh)[16], const uint4* stats, uint32_t tag, uint32_t shift,
                                                uint32_t scale, uint32_t stg, uint32_t bars, int cw, int warp, int lane, Ready ready) {
  const int r = lane >> 2, c = lane & 3;
  float nb[2], rs[2];
  {
    uint32_t st[8];
    const uint4* sp = stats + (lane >> 4) * 512 + cw * 64 + warp * 16 + (lane & 15);
    ll_poll<4>([&](int i) { return sp + i * 128; }, tag, st);
    float mu, rstd;
    row_stats(st, mu, rstd);
    mu *= -rstd;
    nb[0] = __shfl_sync(~0u, mu, r); rs[0] = __shfl_sync(~0u, rstd, r);
    nb[1] = __shfl_sync(~0u, mu, r + 8); rs[1] = __shfl_sync(~0u, rstd, r + 8);
  }
  ready();
#pragma unroll
  for (int ch = 0; ch < 2; ch++) {
    uint32_t lo[8], hi[8];
#pragma unroll
    for (int t = 0; t < 8; t++) {
      const int n = ch * 8 + t;
      const float2 sb = lds64f(shift + (8 * n + 2 * c) * 4), cb = lds64f(scale + (8 * n + 2 * c) * 4);
      lo[t] = pack2((bf_lo(xl[n]) * rs[0] + nb[0]) * cb.x + sb.x, (bf_hi(xl[n]) * rs[0] + nb[0]) * cb.y + sb.y);
      hi[t] = pack2((bf_lo(xh[n]) * rs[1] + nb[1]) * cb.x + sb.x, (bf_hi(xh[n]) * rs[1] + nb[1]) * cb.y + sb.y);
    }
    stage_slab(stg + ch * 16384 + cw * 8192, warp, lane, lo, hi);
    stage_done(bars + 8 * (B_STGF + ch), lane);
  }
  wg_bar(cw);
}

__global__ void __launch_bounds__(384, 1) fused_kernel(const __grid_constant__ Params p) {
  extern __shared__ __align__(1024) uint8_t smem_raw[];
  const uint32_t sm = smem_u32(smem_raw);
  const uint32_t bars = sm + MISC_OFF;
  const uint32_t stg = sm + STG_OFF;
  const int rank = blockIdx.x & 1;
  const int cl = blockIdx.x >> 1;
  if (cl >= NCTA / 2) {
    const int e = blockIdx.x - NCTA, wid = __shfl_sync(~0u, (int)(threadIdx.x >> 5), 0), lane = threadIdx.x & 31;
    if (threadIdx.x == 0) {
      for (int i = 0; i < 6; i++) { mbar_init(bars + 8 * i, 1); mbar_init(bars + 8 * (6 + i), 8); }
      asm volatile("fence.mbarrier_init.release.cluster;" ::: "memory");
    }
    const uint32_t tag = load_epoch(p.epoch) + 1;
    if (threadIdx.x < 256) ll_store(p.modll + 512 + (threadIdx.x >> 6) * 256 + e * 64 + (threadIdx.x & 63), 0u, 0u, 0u);
    for (int i = threadIdx.x; i < 1536; i += 384) {
      uint4 o = make_uint4(0u, 0u, 0u, 0u);
      if (i < 1024 && (i & 63) < 8) {
        const uint4 cv = ldg_nc(p.c + (i >> 6) * 64 + (i & 7) * 8);
        o = make_uint4(pack2(silu_f(bf_lo(cv.x)), silu_f(bf_hi(cv.x))), pack2(silu_f(bf_lo(cv.y)), silu_f(bf_hi(cv.y))),
                       pack2(silu_f(bf_lo(cv.z)), silu_f(bf_hi(cv.z))), pack2(silu_f(bf_lo(cv.w)), silu_f(bf_hi(cv.w))));
      }
      sts128(stg + i * 16, o.x, o.y, o.z, o.w);
    }
    asm volatile("fence.proxy.async.shared::cta;" ::: "memory");
    __syncthreads();
    if (wid == 0) {
      __nanosleep(WMDELAY);
      uint32_t ph = 1;
#pragma unroll 1
      for (int it = 0, s = 0; it < 64; it++) {
        mbar_wait(bars + 8 * (6 + s), ph);
        expect_tx_elect(bars + 8 * s, 32768);
#pragma unroll
        for (int q = 0; q < 4; q++) tma_load_ef(sm + s * 32768 + q * 8192, &p.wm, bars + 8 * s, 2048 + (it >> 4) * 1024 + e * 256 + q * 64, (it & 15) * 64);
        if (++s == 6) { s = 0; ph ^= 1; }
      }
    } else if (wid == 1 && PFW) {
      __nanosleep(PFW);
#pragma unroll 1
      for (int i = 0; i < 64; i++) {
        l2_prefetch_tile(&p.wo, (i & 15) * 64, (e * 4 + (i >> 4)) * 64);
        if (PFP) __nanosleep(PFP);
      }
#pragma unroll 1
      for (int i = 0; i < 128; i++) {
        l2_prefetch_tile((i & 2) ? &p.wu : &p.wg, ((i >> 2) & 7) * 448 + (i & 1) * 64, ((i >> 5) * 4 + e) * 64);
        if (PFP) __nanosleep(PFP);
      }
    } else if (wid >= 4) {
      const int hf = (wid >> 2) - 1;
      uint32_t ph = 0;
      int s = 0;
#pragma unroll 1
      for (int v = 0; v < 4; v++) {
        float acc[64];
#pragma unroll 1
        for (int kb = 0; kb < 16; kb++) {
          mbar_wait_watchdog(bars + 8 * s, ph);
          const uint32_t da = DESC_A + ((STG_OFF + kb * 1024) >> 4), db = DESC_B + ((s * 32768 + hf * 16384) >> 4) - 1024;
          wg_fence();
#pragma unroll
          for (int k = 0; k < 4; k++) wgmma_ss_n128(acc, da + k * 2, db + k * 128, (kb | k) != 0);
          wg_commit();
          wg_wait<0>();
          if (lane == 0) mbar_arrive(bars + 8 * (6 + s));
          if (++s == 6) { s = 0; ph ^= 1; }
        }
        if ((wid & 3) == 0) {
#pragma unroll
          for (int n = 0; n < 16; n++) {
            const uint32_t mine = pack2(acc[4 * n], acc[4 * n + 1]), next = __shfl_down_sync(~0u, mine, 1);
            if (lane < 4 && (lane & 1) == 0) ll_store(p.modll + 512 + v * 256 + e * 64 + hf * 32 + n * 2 + (lane >> 1), mine, next, tag);
          }
        }
      }
    }
    return;
  }
  const int slot = p.slot[cl];
  const int rb = (slot >> 3) * 2 + rank, j = slot & 7;
  const int cta = rb * 8 + j;
  PROF_AT(threadIdx.x == 0, 0);

  if (threadIdx.x < 128) {
    uint32_t tag = load_epoch(p.epoch);
    asm volatile("setmaxnreg.dec.sync.aligned.u32 40;");
    const int warp = __shfl_sync(~0u, (int)(threadIdx.x >> 5), 0), lane = threadIdx.x & 31;
    if (threadIdx.x == 0) {
      if ((sm & 0x3FFFF) != SMEM_BASE) asm volatile("trap;");
      for (int i = 0; i < 4; i++) { mbar_init(bars + 8 * (B_FQ + i), 1); mbar_init(bars + 8 * (B_EQ + i), 16); }
      for (int i = 0; i < 6; i++) { mbar_init(bars + 8 * (B_FW + i), 1); mbar_init(bars + 8 * (B_EW + i), 16); }
      for (int i = 0; i < 4; i++) { mbar_init(bars + 8 * (B_FG + i), 1); mbar_init(bars + 8 * (B_EG + i), 16); }
      for (int i = 0; i < 6; i++) { mbar_init(bars + 8 * (B_FD + i), 1); mbar_init(bars + 8 * (B_ED + i), 16); }
      for (int i = 0; i < 2; i++) { mbar_init(bars + 8 * (B_STGF + i), 8); mbar_init(bars + 8 * (B_STGE + i), 1); }
      mbar_init(bars + 8 * B_MODB, 1);
      mbar_init(bars + 8 * (B_MODB + 1), 1);
      mbar_init(bars + 8 * B_MODA, 1);
      for (int i = 0; i < 8; i++) mbar_init(bars + 8 * (B_RDY + i), 1);
      asm volatile("fence.mbarrier_init.release.cluster;" ::: "memory");
    }
    __syncwarp();
    cluster_arrive_relaxed();
    tag += 1;
    const unsigned target = tag * 8;
    unsigned* cnt = p.cnt + rb * 32;
    cluster_wait();
    if (warp == 0) {
      const CUtensorMap* wgu = rank ? &p.wu : &p.wg;
      uint32_t st = sm + 16384, fb = bars + 8 * B_FQ, ph = 1;
      __nanosleep(BDELAY);
#pragma unroll 1
      for (int it = 0; it < 32; it++) {
        const int kb = qkv_kb(it, j), col = j * 128 + ((it < 4 ? it >= 2 : it >= 18) ? 64 : 0);
        mbar_wait(fb + 8 * (B_EQ - B_FQ), ph);
        expect_tx_elect(fb, it < 4 ? 24576 : 40960);
        tma_load_mc(st + rank * 8192, &p.wqkv, fb, col + rank * 1024, kb * 64);
        tma_load_mc(st + 16384 + rank * 4096, &p.wqkv32, fb, col + 2048, kb * 64 + rank * 32);
        st += 49152; fb += 8;
        if ((it & 3) == 3) { st -= 4 * 49152; fb -= 32; ph ^= 1; }
      }
      fb = bars + 8 * B_FW; ph = 1;
#pragma unroll 1
      for (int it = 0, s = 0; it < 16; it++) {
        if (it < 6) wait_p3_free(bars + 8 * B_EQ, it);
        mbar_wait(fb + 8 * (B_EW - B_FW), ph);
        expect_tx_elect(fb, it == 8 ? 16384 : 32768);
        tma_load_mc(st + rank * 8192, &p.wo, fb, j * 128 + rank * 64, wo_k(it, j));
        st += 32768; fb += 8;
        if (++s == 6) { s = 0; st -= 6 * 32768; fb -= 48; ph ^= 1; }
      }
      st = sm + 16384; fb = bars + 8 * B_FG; ph = 1;
#pragma unroll 1
      for (int it = 0; it < 48; it++) {
        const int kb = own_first(it, j), col = j * 448 + (it >> 4) * 128;
        if (it < 4) wait_p2_free(bars + 8 * B_EW, it);
        mbar_wait(fb + 8 * (B_EG - B_FG), ph);
        expect_tx_elect(fb, it < 2 ? 32768 : 49152);
        tma_load_mc(st + rank * 16384, wgu, fb, col, kb * 64);
        tma_load_mc(st + rank * 16384 + 8192, wgu, fb, col + 64, kb * 64);
        st += 49152; fb += 8;
        if ((it & 3) == 3) { st -= 4 * 49152; fb -= 32; ph ^= 1; }
      }
      fb = bars + 8 * B_FD; ph = 1;
#pragma unroll 1
      for (int it = 0, s = 0; it < 72; it++) {
        if (it < 6) wait_p3_free(bars + 8 * B_EG, it);
        mbar_wait(fb + 8 * (B_ED - B_FD), ph);
        expect_tx_elect(fb, 32768);
        tma_load_mc(st + rank * 8192, it < 16 ? wgu : &p.wd, fb, it < 16 ? j * 448 + 384 : j * 128 + rank * 64, down_k(it));
        st += 32768; fb += 8;
        if (++s == 6) { s = 0; st -= 6 * 32768; fb -= 48; ph ^= 1; }
      }
    } else if (warp == 1) {
      const int arow = rb * 128;
      uint32_t st = sm, fb = bars + 8 * B_FQ, ph = 0;
      cnt_wait(cnt + C_HA, target);
      PROF_AT(lane == 0, 16);
#pragma unroll 1
      for (int it = 4; it < 32; it++) {
        if (it == 11) mbar_wait(bars + 8 * (B_RDY + C_H), 0);
        mbar_wait(fb + 8 * (B_EQ - B_FQ), ph);
        tma_load(st, &p.h, fb, qkv_kb(it, j) * 64, arow);
        st += 49152; fb += 8;
        if ((it & 3) == 3) { st -= 4 * 49152; fb -= 32; ph ^= 1; }
      }
      fb = bars + 8 * B_FW; ph = 1;
#pragma unroll 1
      for (int it = 0, s = 0; it < 16; it++) {
        if (it < 6) wait_p3_free(bars + 8 * B_EQ, it);
        mbar_wait(fb + 8 * (B_EW - B_FW), ph);
        if (it == 0) mbar_wait(bars + 8 * (B_RDY + C_O), 0);
        if (it == 9) cnt_wait(cnt + C_O + 1, target);
        PROF_AT(lane == 0 && (it == 0 || it == 9), 17 + (it >> 3));
        if (it != 8) tma_load(st, &p.o_ld, fb, wo_k(it, j), arow);
        st += 32768; fb += 8;
        if (++s == 6) { s = 0; st -= 6 * 32768; fb -= 48; ph ^= 1; }
      }
      st = sm + 2 * 49152; fb = bars + 8 * (B_FG + 2); ph = 1;
      cnt_wait(cnt + C_H2A, target);
      PROF_AT(lane == 0, 19);
#pragma unroll 1
      for (int it = 2; it < 48; it++) {
        if (it == 9) mbar_wait(bars + 8 * (B_RDY + C_H2), 0);
        mbar_wait(fb + 8 * (B_EG - B_FG), ph);
        tma_load(st, &p.h2, fb, own_first(it, j) * 64, arow);
        st += 49152; fb += 8;
        if ((it & 3) == 3) { st -= 4 * 49152; fb -= 32; ph ^= 1; }
      }
      fb = bars + 8 * B_FD; ph = 1;
#pragma unroll 1
      for (int it = 0, s = 0; it < 72; it++) {
        if (it < 6) wait_p3_free(bars + 8 * B_EG, it);
        mbar_wait(fb + 8 * (B_ED - B_FD), ph);
        if ((it & 15) == 0 && it > 0) { mbar_wait(bars + 8 * (B_RDY + C_ACT - 1 + (it >> 4)), 0); PROF_AT(lane == 0, 19 + (it >> 4)); }
        tma_load(st, it < 16 ? &p.h2 : &p.act, fb, down_k(it), arow);
        st += 32768; fb += 8;
        if (++s == 6) { s = 0; st -= 6 * 32768; fb -= 48; ph ^= 1; }
      }
    } else if (warp == 2) {
      if (lane < 13) prefetch_map(&p.h + lane);
      __syncwarp();
      uint32_t ph1 = 0;
#pragma unroll 1
      for (int n = 0; n < 8; n++) {
        const int nch = (n == 1 || n == 2 || n == 7) ? 1 : 2;
#pragma unroll 1
        for (int ch = 0; ch < nch; ch++) {
          mbar_wait_watchdog(bars + 8 * (B_STGF + ch), ch ? ph1 : (n & 1));
          const uint32_t src = stg + ch * 16384;
          if (n == 1 || n == 2) {
#pragma unroll 1
            for (int q = 0; q < 4; q++) {
              tma_store2(&p.o_st, src + q * 4096, j * 128 + (n - 1) * 64, rb * 128 + q * 32);
              if (n == 1) store_pause(true);
            }
          } else if (n >= 4 && n < 8) {
#pragma unroll 1
            for (int q = 0; q < 4; q++) {
              tma_store2(&p.act_st, src + q * 4096, j * 448 + (n - 4) * 128 + ch * 64, rb * 128 + q * 32);
              store_pause(true);
            }
          } else {
            tma_store2(n == 0 ? &p.h : &p.h2, src, j * 128 + ch * 64, rb * 128);
            asm volatile("cp.async.bulk.commit_group;" ::: "memory");
            if (ch == 1) {
              asm volatile("cp.async.bulk.wait_group 1;" ::: "memory");
              __syncwarp();
              cnt_signal(cnt + (n == 0 ? C_HA : C_H2A));
            }
          }
          if (n >= 4 && n < 7 && ch == 0) arrive_elect(bars + 8 * B_STGE);
        }
        asm volatile("cp.async.bulk.commit_group;" ::: "memory");
        asm volatile("cp.async.bulk.wait_group 0;" ::: "memory");
        __syncwarp();
        cnt_signal(cnt + n);
        PROF_AT(lane == 0, n == 0 ? 33 : 23 + n);
        if (n == 0) {
#pragma unroll 1
          for (int t = 0; t < 36; t++) {
            ll_store(t < 32 ? p.halo + cta * 1024 + t * 32 + lane : p.stats2 + cta * 128 + (t - 32) * 32 + lane, 0u, 0u, 0u);
            __nanosleep(40);
          }
          __syncwarp();
        }
        if (!(n >= 4 && n < 7)) arrive_elect(bars + 8 * B_STGE);
        if (nch == 2) { arrive_elect(bars + 8 * (B_STGE + 1)); ph1 ^= 1; }
      }
      mbar_wait_watchdog(bars + 8 * B_STGF, 0);
      PROF_AT(lane == 0, 31);
    } else {
      if (lane < 4) ll_store(p.modll + cta * 4 + lane, 0u, 0u, 0u);
      bar_sync(1, 288);
      {
        const uint4 t4 = lds128(sm + RED_OFF + lane * 16);
        float a[4] = {__uint_as_float(t4.x), __uint_as_float(t4.y), __uint_as_float(t4.z), __uint_as_float(t4.w)};
#pragma unroll
        for (int o = 4; o < 32; o <<= 1)
#pragma unroll
          for (int q = 0; q < 4; q++) a[q] += __shfl_xor_sync(~0u, a[q], o);
        if (lane < 4) ll_store(p.modll + cta * 4 + lane, pack2(a[0], a[1]), pack2(a[2], a[3]), tag);
        PROF_AT(lane == 0, 1);
        uint32_t m[4];
        const uint4* mp = p.modll + j * 32 + lane;
        ll_poll<2>([&](int i) { return mp + i * 256; }, tag, m);
        const uint32_t c0 = pack2(1.0f + bf_lo(m[2]), 1.0f + bf_hi(m[2])), c1 = pack2(1.0f + bf_lo(m[3]), 1.0f + bf_hi(m[3]));
        sts128(sm + MODB_OFF + lane * 16, m[0] << 16, m[0] & 0xffff0000u, m[1] << 16, m[1] & 0xffff0000u);
        sts128(sm + MODB_OFF + 512 + lane * 16, c0 << 16, c0 & 0xffff0000u, c1 << 16, c1 & 0xffff0000u);
        __syncwarp();
        arrive_elect(bars + 8 * B_MODA);
      }
#pragma unroll 1
      for (int n = C_H; n <= C_O; n++) {
        cnt_wait_lazy(cnt + n, target);
        arrive_elect(bars + 8 * (B_RDY + n));
      }
      {
        uint32_t m[6];
        const uint4* src = p.modll + 512 + j * 32 + lane;
        ll_poll<3, 500>([&](int i) { return src + i * 256; }, tag, m);
#pragma unroll
        for (int vec = 0; vec < 3; vec++) {
          const float add = vec == 2 ? 1.0f : 0.0f;
          sts128(sm + MODB_OFF + (vec * 128 + lane * 4) * 4, __float_as_uint(bf_round(bf_lo(m[2 * vec]) + add)), __float_as_uint(bf_round(bf_hi(m[2 * vec]) + add)),
                 __float_as_uint(bf_round(bf_lo(m[2 * vec + 1]) + add)), __float_as_uint(bf_round(bf_hi(m[2 * vec + 1]) + add)));
        }
        __syncwarp();
        if (lane == 0) mbar_arrive(bars + 8 * B_MODB);
        PROF_AT(lane == 0, 15);
      }
      __syncwarp();
#pragma unroll 1
      for (int n = C_H2; n < 8; n++) {
        cnt_wait_lazy(cnt + n, target);
        arrive_elect(bars + 8 * (B_RDY + n));
      }
      {
        uint32_t m[2];
        const uint4* src = p.modll + 512 + 768 + j * 32 + lane;
        ll_poll<1>([&](int) { return src; }, tag, m);
        sts128(sm + MODB_OFF + (384 + lane * 4) * 4, m[0] << 16, m[0] & 0xffff0000u, m[1] << 16, m[1] & 0xffff0000u);
        __syncwarp();
        if (lane == 0) mbar_arrive(bars + 8 * (B_MODB + 1));
      }
    }
  } else {
    uint32_t tag;

    {
      const int tid = threadIdx.x - 128, cw = tid >> 7, warp = (tid >> 5) & 3, lane = tid & 31;
      const int l16 = lane & 15, half = lane >> 4, w8 = cw * 4 + warp;
      const uint32_t cbuf = sm + 3 * 49152 + w8 * 512;
      if (lane <= 16) cp_async16(cbuf + lane * 16, lane < 16 ? (const void*)(p.c + w8 * 128 + lane * 8) : (const void*)p.epoch);
      asm volatile("cp.async.commit_group;" ::: "memory");
      const uint32_t wbuf = sm + cw * 49152 + warp * 4096;
      {
        const char* wp = (const char*)p.wmod + (uint32_t)(cta * 32 + (lane & 1) * 16 + (w8 * 128 + (lane >> 1)) * 12288);
#pragma unroll
        for (int i = 0; i < 8; i++) cp_async16(wbuf + i * 512 + lane * 16, wp + i * 16 * 12288);
      }
      asm volatile("cp.async.commit_group;" ::: "memory");
      const uint32_t xbuf = sm + 40960 + (cw * 2 + (l16 >> 3)) * 49152 + (warp * 16 + half) * 128;
      {
        const char* xp = (const char*)p.x + (uint32_t)((rb * 128 + (warp * 16 + half) * 2 + cw) * 2048 + j * 256 + l16 * 16);
#pragma unroll
        for (int i = 0; i < 8; i++) cp_async16(xbuf + i * 256 + (((l16 & 7) ^ ((i * 2 + half) & 7)) << 4), xp + i * 8192);
      }
      asm volatile("cp.async.commit_group;" ::: "memory");
      PROF_AT(tid == 0, 32);
      uint4* st1 = p.stats1 + (rb * 8 + j) * 128 + cw * 64 + warp * 16;
      if (lane < 16) ll_store(st1 + lane, 0u, 0u, 0u);
      __syncwarp();
      cluster_arrive_relaxed();
      asm volatile("setmaxnreg.inc.sync.aligned.u32 232;");
      uint32_t sa[4][4];
      {
        asm volatile("cp.async.wait_group 2;" ::: "memory");
        __syncwarp();
        tag = lds32(cbuf + 256) + 1;
        const float2 cv = lds64f(cbuf + lane * 8);
        const uint32_t c0 = __float_as_uint(cv.x), c1 = __float_as_uint(cv.y);
        sts64f(cbuf + lane * 8, __uint_as_float(pack2(silu_f(bf_lo(c0)), silu_f(bf_hi(c0)))), __uint_as_float(pack2(silu_f(bf_lo(c1)), silu_f(bf_hi(c1)))));
        __syncwarp();
#pragma unroll
        for (int q = 0; q < 4; q++) ldmatrix4(sa[q][0], sa[q][1], sa[q][2], sa[q][3], cbuf + q * 64 + (lane >> 3) * 16);
      }
      cluster_wait();
      asm volatile("cp.async.wait_group 1;" ::: "memory");
      __syncwarp();
      PROF_AT(tid == 0, 51);
      {
        uint32_t b[8][4];
#pragma unroll
        for (int ks = 0; ks < 8; ks++) ldmatrix4t(b[ks], wbuf + (ks * 16 + (lane & 15)) * 32 + (lane >> 4) * 16);
        float d0[4] = {0.f, 0.f, 0.f, 0.f}, d1[4] = {0.f, 0.f, 0.f, 0.f}, d2[4] = {0.f, 0.f, 0.f, 0.f}, d3[4] = {0.f, 0.f, 0.f, 0.f};
#pragma unroll
        for (int q = 0; q < 4; q++) {
          mma16816(d0, sa[q][0], sa[q][0], sa[q][1], sa[q][1], b[2 * q][0], b[2 * q][1]);
          mma16816(d1, sa[q][0], sa[q][0], sa[q][1], sa[q][1], b[2 * q][2], b[2 * q][3]);
          mma16816(d2, sa[q][2], sa[q][2], sa[q][3], sa[q][3], b[2 * q + 1][0], b[2 * q + 1][1]);
          mma16816(d3, sa[q][2], sa[q][2], sa[q][3], sa[q][3], b[2 * q + 1][2], b[2 * q + 1][3]);
        }
        d0[0] += d2[0]; d0[1] += d2[1]; d1[0] += d3[0]; d1[1] += d3[1];
        if (lane < 4) {
          sts64f(sm + RED_OFF + (w8 * 16 + lane * 2) * 4, d0[0], d0[1]);
          sts64f(sm + RED_OFF + (w8 * 16 + 8 + lane * 2) * 4, d1[0], d1[1]);
        }
        asm volatile("bar.arrive 1, 288;" ::: "memory");
      }
      asm volatile("cp.async.wait_group 0;" ::: "memory");
      __syncwarp();
      uint32_t xl[16], xh[16];
      {
        const int srow = warp * 16 + (lane & 15);
#pragma unroll
        for (int q = 0; q < 8; q++)
          ldmatrix4(xl[2 * q], xh[2 * q], xl[2 * q + 1], xh[2 * q + 1],
                    sm + 40960 + (cw * 2 + (q >> 2)) * 49152 + srow * 128 + (((half + (q & 3) * 2) ^ (srow & 7)) << 4));
      }
      publish_stats(xl, xh, st1, lane, tag);
      PROF_AT(tid == 0, 50);
      normalize_stage(xl, xh, p.stats1 + rb * 1024, tag, sm + MODB_OFF, sm + MODB_OFF + 512, stg, bars, cw, warp, lane,
                      [&]() { mbar_wait(bars + 8 * B_MODA, 0); });
      PROF_AT(tid == 0, 3);
    }

    uint32_t xl[16], xh[16];
    {
      RING_IDS();
      uint32_t prev = 0;
      float acc1[96];
      {
        Ring g{bars + 8 * B_FQ, rbars + 8 * B_EQ, 0, 0u, releaser TR(0)};
        float acc0[96];
#pragma unroll 1
        for (int kb = 0; kb < 2; kb++) kblock<192, 4, 49152>(acc0, g, a_base + STG_OFF + kb * 16384, kb == 0, prev);
#pragma unroll 1
        for (int kb = 0; kb < 2; kb++) kblock<192, 4, 49152>(acc1, g, a_base + STG_OFF + kb * 16384, kb == 0, prev);
#pragma unroll 1
        for (int kb = 0; kb < 14; kb++) kblock<192, 4, 49152>(acc0, g, a_base + g.s * 49152, false, prev);
        PROF_AT(tid == 0, 4);
        attention<NPRE0, false>(acc0, p, 0, rb, cta, cw, warp, tag, stg, bars, prev, [&]() { kblock<192, 4, 49152>(acc1, g, a_base + g.s * 49152, false, prev); });
        PROF_AT(tid == 0, 5);
        {
          LANE_IDS();
#pragma unroll
          for (int q = 0; q < 8; q++)
            ldmatrix4(xl[2 * q], xh[2 * q], xl[2 * q + 1], xh[2 * q + 1], sm + 40960 + (cw * 2 + (q >> 2)) * 49152 + srow * 128 + ((sw0 ^ ((q & 3) * 2)) << 4));
#pragma unroll
          for (int q = 0; q < 16; q++) asm volatile("" : "+r"(xl[q]), "+r"(xh[q])::"memory");
        }
#pragma unroll 1
        for (int kb = 5 + NPRE0; kb < 14; kb++) kblock<192, 4, 49152>(acc1, g, a_base + g.s * 49152, false, prev);
        PROF_AT(tid == 0, 6);
      }
      float acc[64];
      Ring g{bars + 8 * B_FW, rbars + 8 * B_EW, 0, 0u, releaser TR(32)};
      attention<NPRE1, true>(acc1, p, 1, rb, cta, cw, warp, tag, stg, bars, prev, [&]() { kblock<128, 6, 32768>(acc, g, a_base + g.s * 32768, g.s == 0, prev); });
      PROF_AT(tid == 0, 7);
      LANE_IDS();
#pragma unroll 1
      for (int kb = 1 + NPRE1; kb < 16; kb++) {
        if (kb == 8) wg_bar(cw);
        kblock<128, 6, 32768>(acc, g, a_base + (kb == 8 ? STG_OFF : g.s * 32768), false, prev);
      }
      mbar_wait(bars + 8 * B_MODB, 0);
      float2 ga[16];
#pragma unroll
      for (int n = 0; n < 16; n++) ga[n] = lds64f(sm + MODB_OFF + (8 * n + 2 * c) * 4);
      tile_end(acc, prev);
      PROF_AT(tid == 0, 8);
      uint4* st2 = p.stats2 + (rb * 8 + j) * 128 + cw * 64 + warp * 16 + r + (c & 1) * 8;
      float sl[2] = {0.f, 0.f}, sh[2] = {0.f, 0.f}, ql[2] = {0.f, 0.f}, qh[2] = {0.f, 0.f};
#pragma unroll
      for (int n = 0; n < 16; n++) {
        acc[4 * n] = ga[n].x * acc[4 * n] + bf_lo(xl[n]); acc[4 * n + 1] = ga[n].y * acc[4 * n + 1] + bf_hi(xl[n]);
        acc[4 * n + 2] = ga[n].x * acc[4 * n + 2] + bf_lo(xh[n]); acc[4 * n + 3] = ga[n].y * acc[4 * n + 3] + bf_hi(xh[n]);
        sl[0] += acc[4 * n]; sl[1] += acc[4 * n + 1]; sh[0] += acc[4 * n + 2]; sh[1] += acc[4 * n + 3];
        ql[0] += acc[4 * n] * acc[4 * n]; ql[1] += acc[4 * n + 1] * acc[4 * n + 1];
        qh[0] += acc[4 * n + 2] * acc[4 * n + 2]; qh[1] += acc[4 * n + 3] * acc[4 * n + 3];
      }
      {
        const float ml = (sl[0] + sl[1]) * (1.0f / 32), mh = (sh[0] + sh[1]) * (1.0f / 32);
        const float vl = (ql[0] + ql[1]) - 32.0f * ml * ml, vh = (qh[0] + qh[1]) - 32.0f * mh * mh;
        const bool b0 = c & 1;
        float m = b0 ? mh : ml, q = b0 ? vh : vl;
        chan(m, q, __shfl_xor_sync(~0u, b0 ? ml : mh, 1), __shfl_xor_sync(~0u, b0 ? vl : vh, 1), 32.f);
        chan(m, q, __shfl_xor_sync(~0u, m, 2), __shfl_xor_sync(~0u, q, 2), 64.f);
        if (c < 2) ll_store(st2, __float_as_uint(m), __float_as_uint(fmaxf(q, 0.f)), tag);
        __syncwarp();
      }
      PROF_AT(tid == 0, 48);
      float2 sb[16], cb[16];
#pragma unroll
      for (int n = 0; n < 16; n++) {
        sb[n] = lds64f(sm + MODB_OFF + (128 + 8 * n + 2 * c) * 4);
        cb[n] = lds64f(sm + MODB_OFF + (256 + 8 * n + 2 * c) * 4);
        xl[n] = pack2(acc[4 * n], acc[4 * n + 1]);
        xh[n] = pack2(acc[4 * n + 2], acc[4 * n + 3]);
      }
      mbar_wait(bars + 8 * B_STGE, 0);
      PROF_AT(tid == 0, 49);
      float nb[2], rstd[2];
      {
        uint32_t st[8];
        const uint4* sp = p.stats2 + (rb * 8 + (lane >> 4) * 4) * 128 + cw * 64 + warp * 16 + (lane & 15);
        ll_poll<4>([&](int i) { return sp + i * 128; }, tag, st);
        float mu, rs;
        row_stats(st, mu, rs);
        mu *= -rs;
        nb[0] = __shfl_sync(~0u, mu, r); rstd[0] = __shfl_sync(~0u, rs, r);
        nb[1] = __shfl_sync(~0u, mu, r + 8); rstd[1] = __shfl_sync(~0u, rs, r + 8);
      }
      PROF_AT(tid == 0, 9);
#pragma unroll
      for (int ch = 0; ch < 2; ch++) {
        uint32_t lo[8], hi[8];
#pragma unroll
        for (int t = 0; t < 8; t++) {
          const int n = ch * 8 + t;
          lo[t] = pack2((acc[4 * n] * rstd[0] + nb[0]) * cb[n].x + sb[n].x, (acc[4 * n + 1] * rstd[0] + nb[0]) * cb[n].y + sb[n].y);
          hi[t] = pack2((acc[4 * n + 2] * rstd[1] + nb[1]) * cb[n].x + sb[n].x, (acc[4 * n + 3] * rstd[1] + nb[1]) * cb[n].y + sb[n].y);
        }
        stage_slab(stg + ch * 16384 + cw * 8192, warp, lane, lo, hi);
        stage_done(bars + 8 * (B_STGF + ch), lane);
      }
      wg_bar(cw);
      PROF_AT(tid == 0, 10);
    }

    uint32_t pg[32], pu[32];
    {
      RING_IDS();
      LANE_IDS();
      Ring g{bars + 8 * B_FG, rbars + 8 * B_EG, 0, 0u, releaser TR(48)};
      float acc[128];
      {
        uint32_t prev = 0;
        uint4* x1p = p.x1 + (size_t)(rb * 128 + (warp * 16 + (lane >> 4)) * 2 + cw) * 128 + j * 16 + (lane & 15);
#pragma unroll 1
        for (int kb = 0; kb < 16; kb++) {
          kblock<256, 4, 49152>(acc, g, a_base + (kb < 2 ? STG_OFF + kb * 16384 : g.s * 49152), kb == 0, prev);
          if (kb == 5) {
#pragma unroll
            for (int q = 0; q < 4; q++) x1p[q * 512] = make_uint4(xl[4 * q], xl[4 * q + 1], xl[4 * q + 2], xl[4 * q + 3]);
          }
          if (kb == 8) {
#pragma unroll
            for (int q = 0; q < 4; q++) x1p[(4 + q) * 512] = make_uint4(xh[4 * q], xh[4 * q + 1], xh[4 * q + 2], xh[4 * q + 3]);
          }
        }
        tile_end(acc, prev);
      }
      PROF_AT(tid == 0, 36);
#pragma unroll 1
      for (int t = 1; t < 3; t++) {
#pragma unroll
        for (int q = 0; q < 32; q++) {
          pg[q] = pack2(acc[2 * q], acc[2 * q + 1]);
          pu[q] = pack2(acc[64 + 2 * q], acc[64 + 2 * q + 1]);
        }
        uint32_t prev = 0;
#pragma unroll 1
        for (int blk = 0; blk < 4; blk++) {
          g.s = 0;
#pragma unroll
          for (int i = 0; i < 4; i++) {
            kblock<256, 4, 49152>(acc, g, a_base + i * 49152, blk == 0 && i == 0, prev);
            if ((blk & 1) == 0 && i == 0) mbar_wait(bars + 8 * (B_STGE + (blk >> 1)), t & 1);
            stmatrix2(slab + (blk >> 1) * 16384 + (((srow & 7) ^ ((blk & 1) * 4 + i)) << 4), swiglu2(pg[2 * i], pu[2 * i]), swiglu2(pg[2 * i + 1], pu[2 * i + 1]));
          }
#pragma unroll
          for (int q = 0; q < 24; q++) { pg[q] = pg[q + 8]; pu[q] = pu[q + 8]; }
          if (blk & 1) stage_done(bars + 8 * (B_STGF + (blk >> 1)), lane);
        }
        tile_end(acc, prev);
        PROF_AT(tid == 0, 36 + t);
      }
#pragma unroll
      for (int q = 0; q < 32; q++) {
        pg[q] = pack2(acc[2 * q], acc[2 * q + 1]);
        pu[q] = pack2(acc[64 + 2 * q], acc[64 + 2 * q + 1]);
      }
      PROF_AT(tid == 0, 11);
    }

    {
      RING_IDS();
      LANE_IDS();
      Ring g{bars + 8 * B_FD, rbars + 8 * B_ED, 0, 0u, releaser TR(96)};
      float acc[64];
      uint32_t prev = 0;
#pragma unroll 1
      for (int blk = 0; blk < 6; blk++) {
#pragma unroll
        for (int i = 0; i < 8; i++) {
          kblock<128, 6, 32768>(acc, g, a_base + g.s * 32768, (blk & ~2) == 0 && i == 0, prev);
          if ((blk & 1) == 0 && i == 0) mbar_wait(bars + 8 * (B_STGE + ((blk >> 1) & 1)), blk < 4);
          stmatrix1(slab + ((blk >> 1) & 1) * 16384 + (i & 1) * 1024 + (((srow & 7) ^ ((blk & 1) * 4 + (i >> 1))) << 4), swiglu2(pg[i], pu[i]));
        }
#pragma unroll
        for (int q = 0; q < 24; q++) { pg[q] = pg[q + 8]; pu[q] = pu[q + 8]; }
        if (blk & 1) stage_done(bars + 8 * (B_STGF + ((blk >> 1) & 1)), lane);
        if (blk == 1) {
          tile_end(acc, prev);
          PROF_AT(tid == 0, 39);
#pragma unroll
          for (int q = 0; q < 16; q++) {
            pg[16 + q] = pack2(acc[2 * q], acc[2 * q + 1]);
            pu[16 + q] = pack2(acc[32 + 2 * q], acc[32 + 2 * q + 1]);
          }
          PROF_AT(tid == 0, 12);
        }
      }
      uint4 x1[8];
      const int fl = fresh_tid() & 31;
      const uint4* x1p = p.x1 + (size_t)(rb * 128 + (warp * 16 + (fl >> 4)) * 2 + cw) * 128 + j * 16 + (fl & 15);
#pragma unroll
      for (int q = 0; q < 2; q++) {
#pragma unroll
        for (int e = 0; e < 4; e++) x1[4 * q + e] = ll_peek(x1p + (4 * q + e) * 512);
#pragma unroll 1
        for (int kb = 0; kb < 12; kb++) {
          if (q == 1 && kb == 6) g.releaser = false;
          kblock<128, 6, 32768>(acc, g, a_base + g.s * 32768, false, prev);
        }
      }
      mbar_wait(bars + 8 * (B_MODB + 1), 0);
      mbar_wait(bars + 8 * B_STGE, 1);
      mbar_wait(bars + 8 * (B_STGE + 1), 0);
      float2 gbv[16];
#pragma unroll
      for (int n = 0; n < 16; n++) gbv[n] = lds64f(sm + MODB_OFF + (384 + 8 * n + 2 * c) * 4);
      tile_end(acc, prev);
      PROF_AT(tid == 0, 13);
#pragma unroll
      for (int ch = 0; ch < 2; ch++) {
        uint32_t lo[8], hi[8];
#pragma unroll
        for (int t = 0; t < 8; t++) {
          const int n = ch * 8 + t;
          const float2 gb = gbv[n];
          const uint4 a = x1[n >> 2], b = x1[4 + (n >> 2)];
          const uint32_t xl = (n & 3) == 0 ? a.x : (n & 3) == 1 ? a.y : (n & 3) == 2 ? a.z : a.w;
          const uint32_t xh = (n & 3) == 0 ? b.x : (n & 3) == 1 ? b.y : (n & 3) == 2 ? b.z : b.w;
          lo[t] = pack2(bf_lo(xl) + gb.x * acc[4 * n], bf_hi(xl) + gb.y * acc[4 * n + 1]);
          hi[t] = pack2(bf_lo(xh) + gb.x * acc[4 * n + 2], bf_hi(xh) + gb.y * acc[4 * n + 3]);
        }
        stage_slab(stg + ch * 16384 + cw * 8192, warp, lane, lo, hi);
        asm volatile("fence.proxy.async.shared::cta;" ::: "memory");
        __syncwarp();
        tma_store3(&p.out, stg + ch * 16384 + cw * 8192 + warp * 2048, j * 128 + ch * 64, rb * 64 + warp * 16, cw);
      }
      asm volatile("cp.async.bulk.commit_group;" ::: "memory");
      if (lane == 0) mbar_arrive(bars + 8 * B_STGF);
      asm volatile("cp.async.bulk.wait_group.read 0;" ::: "memory");
      PROF_AT(tid == 0, 14);
    }
    if (blockIdx.x == 0 && threadIdx.x == 128) asm volatile("st.relaxed.gpu.global.u32 [%0], %1;" ::"l"(p.epoch), "r"(tag) : "memory");
  }
}

typedef CUresult (*EncodeFn)(CUtensorMap*, CUtensorMapDataType, cuuint32_t, void*, const cuuint64_t*, const cuuint64_t*,
                             const cuuint32_t*, const cuuint32_t*, CUtensorMapInterleave, CUtensorMapSwizzle,
                             CUtensorMapL2promotion, CUtensorMapFloatOOBfill);

void encode2d(EncodeFn fn, CUtensorMap* m, const void* ptr, uint64_t cols, uint64_t rows, uint32_t box_rows) {
  cuuint64_t dims[2] = {cols, rows};
  cuuint64_t strides[1] = {cols * 2};
  cuuint32_t box[2] = {64, box_rows};
  cuuint32_t es[2] = {1, 1};
  fn(m, CU_TENSOR_MAP_DATA_TYPE_BFLOAT16, 2, (void*)ptr, dims, strides, box, es, CU_TENSOR_MAP_INTERLEAVE_NONE,
     CU_TENSOR_MAP_SWIZZLE_128B, CU_TENSOR_MAP_L2_PROMOTION_L2_128B, CU_TENSOR_MAP_FLOAT_OOB_FILL_NONE);
}

}

extern "C" void kernel_launch(void* const* d_in, const int* in_sizes, int n_in, void* d_out, int out_size) {
  (void)in_sizes; (void)n_in; (void)out_size;
  void* fp = nullptr;
  cudaDriverEntryPointQueryResult qr;
  cudaGetDriverEntryPoint("cuTensorMapEncodeTiled", &fp, cudaEnableDefault, &qr);
  EncodeFn fn = (EncodeFn)fp;
  void *ph, *po, *ph2, *pact;
  cudaGetSymbolAddress(&ph, g_h);
  cudaGetSymbolAddress(&po, g_o);
  ph2 = ph;
  cudaGetSymbolAddress(&pact, g_act);
  Params p;
  encode2d(fn, &p.h, ph, DM, SEQ, 128);
  encode2d(fn, &p.o_ld, po, DM, SEQ, 128);
  encode2d(fn, &p.h2, ph2, DM, SEQ, 128);
  encode2d(fn, &p.act, pact, FF, SEQ, 128);
  encode2d(fn, &p.act_st, pact, FF, SEQ, 32);
  encode2d(fn, &p.wm, d_in[8], 6 * DM, DM, 64);
  encode2d(fn, &p.o_st, po, DM, SEQ, 32);
  encode2d(fn, &p.wqkv, d_in[1], 3 * DM, DM, 64);
  encode2d(fn, &p.wqkv32, d_in[1], 3 * DM, DM, 32);
  encode2d(fn, &p.wo, d_in[2], DM, DM, 64);
  encode2d(fn, &p.wg, d_in[4], FF, DM, 64);
  encode2d(fn, &p.wu, d_in[5], FF, DM, 64);
  encode2d(fn, &p.wd, d_in[6], DM, FF, 64);
  {
    cuuint64_t dims[3] = {DM, SEQ / 2, 2};
    cuuint64_t strides[2] = {DM * 4, DM * 2};
    cuuint32_t box[3] = {64, 16, 1};
    cuuint32_t es[3] = {1, 1, 1};
    fn(&p.out, CU_TENSOR_MAP_DATA_TYPE_BFLOAT16, 3, d_out, dims, strides, box, es, CU_TENSOR_MAP_INTERLEAVE_NONE,
       CU_TENSOR_MAP_SWIZZLE_128B, CU_TENSOR_MAP_L2_PROMOTION_L2_128B, CU_TENSOR_MAP_FLOAT_OOB_FILL_NONE);
  }
  p.x = (const bf16*)d_in[0];
  p.c = (const bf16*)d_in[7];
  p.wmod = (const bf16*)d_in[8];
  for (int cl = 0; cl < 64; cl++) {
    const int grp = cl < 4 ? 0 : (cl < 36 ? (cl - 4) & 7 : 1 + (cl - 36) % 7);
    const int j = cl < 4 ? 4 + cl : (cl < 36 ? (cl - 4) >> 3 : 4 + (cl - 36) / 7);
    p.slot[cl] = (uint8_t)(grp * 8 + j);
  }
  void* q;
  p.x1 = (uint4*)d_out;
  cudaGetSymbolAddress(&q, g_modll); p.modll = (uint4*)q;
  cudaGetSymbolAddress(&q, g_halo); p.halo = (uint4*)q;
  cudaGetSymbolAddress(&q, g_stats); p.stats1 = (uint4*)q; p.stats2 = p.stats1 + SEQ * 8;
  cudaGetSymbolAddress(&q, g_cnt); p.cnt = (unsigned*)q;
  cudaGetSymbolAddress(&q, g_epoch); p.epoch = (unsigned*)q;

  cudaFuncSetAttribute(fused_kernel, cudaFuncAttributeMaxDynamicSharedMemorySize, SMEM_BYTES);
  cudaLaunchConfig_t cfg = {};
  cfg.gridDim = dim3(NCTA + 4);
  cfg.blockDim = dim3(384);
  cfg.dynamicSmemBytes = SMEM_BYTES;
  cfg.stream = cudaStreamPerThread;
  cudaLaunchAttribute at[1];
  at[0].id = cudaLaunchAttributeClusterDimension;
  at[0].val.clusterDim.x = 2; at[0].val.clusterDim.y = 1; at[0].val.clusterDim.z = 1;
  cfg.attrs = at;
  cfg.numAttrs = 1;
  cudaLaunchKernelEx(&cfg, fused_kernel, p);
}
```

```cpp
#include <cuda_runtime.h>
#include <cuda_bf16.h>
#include <cuda.h>
#include <stdint.h>

typedef __nv_bfloat16 bf16;

#define PAUSE 200
#define WMDELAY 2000
#define BDELAY 1500
#define NPRE0 3
#define NPRE1 1
#define ALIAS 1

#define PFW 8000
#define PFP 0

__device__ __forceinline__ void wgmma_ss_n128(float (&d)[64], uint32_t da, uint32_t db, int scale_d) {
  asm volatile("{\n.reg .pred p;\n.reg .b64 da, db;\nsetp.ne.b32 p, %66, 0;\n"
    "mov.b64 da, {%64, 0x40000040};\nmov.b64 db, {%65, 0x40000040};\n"
    "wgmma.mma_async.sync.aligned.m64n128k16.f32.bf16.bf16 "
    "{%0, %1, %2, %3, %4, %5, %6, %7, %8, %9, %10, %11, %12, %13, %14, %15, "
    "%16, %17, %18, %19, %20, %21, %22, %23, %24, %25, %26, %27, %28, %29, %30, %31, "
    "%32, %33, %34, %35, %36, %37, %38, %39, %40, %41, %42, %43, %44, %45, %46, %47, "
    "%48, %49, %50, %51, %52, %53, %54, %55, %56, %57, %58, %59, %60, %61, %62, %63}, "
    "da, db, p, 1, 1, 0, 1;\n}\n"
    : "+f"(d[0]), "+f"(d[1]), "+f"(d[2]), "+f"(d[3]), "+f"(d[4]), "+f"(d[5]), "+f"(d[6]), "+f"(d[7]),
      "+f"(d[8]), "+f"(d[9]), "+f"(d[10]), "+f"(d[11]), "+f"(d[12]), "+f"(d[13]), "+f"(d[14]), "+f"(d[15]),
      "+f"(d[16]), "+f"(d[17]), "+f"(d[18]), "+f"(d[19]), "+f"(d[20]), "+f"(d[21]), "+f"(d[22]), "+f"(d[23]),
      "+f"(d[24]), "+f"(d[25]), "+f"(d[26]), "+f"(d[27]), "+f"(d[28]), "+f"(d[29]), "+f"(d[30]), "+f"(d[31]),
      "+f"(d[32]), "+f"(d[33]), "+f"(d[34]), "+f"(d[35]), "+f"(d[36]), "+f"(d[37]), "+f"(d[38]), "+f"(d[39]),
      "+f"(d[40]), "+f"(d[41]), "+f"(d[42]), "+f"(d[43]), "+f"(d[44]), "+f"(d[45]), "+f"(d[46]), "+f"(d[47]),
      "+f"(d[48]), "+f"(d[49]), "+f"(d[50]), "+f"(d[51]), "+f"(d[52]), "+f"(d[53]), "+f"(d[54]), "+f"(d[55]),
      "+f"(d[56]), "+f"(d[57]), "+f"(d[58]), "+f"(d[59]), "+f"(d[60]), "+f"(d[61]), "+f"(d[62]), "+f"(d[63])
    : "r"(da), "r"(db), "r"(scale_d));
}

__device__ __forceinline__ void wgmma_ss_n192(float (&d)[96], uint32_t da, uint32_t db, int scale_d) {
  asm volatile("{\n.reg .pred p;\n.reg .b64 da, db;\nsetp.ne.b32 p, %98, 0;\n"
    "mov.b64 da, {%96, 0x40000040};\nmov.b64 db, {%97, 0x40000040};\n"
    "wgmma.mma_async.sync.aligned.m64n192k16.f32.bf16.bf16 "
    "{%0, %1, %2, %3, %4, %5, %6, %7, %8, %9, %10, %11, %12, %13, %14, %15, "
    "%16, %17, %18, %19, %20, %21, %22, %23, %24, %25, %26, %27, %28, %29, %30, %31, "
    "%32, %33, %34, %35, %36, %37, %38, %39, %40, %41, %42, %43, %44, %45, %46, %47, "
    "%48, %49, %50, %51, %52, %53, %54, %55, %56, %57, %58, %59, %60, %61, %62, %63, "
    "%64, %65, %66, %67, %68, %69, %70, %71, %72, %73, %74, %75, %76, %77, %78, %79, "
    "%80, %81, %82, %83, %84, %85, %86, %87, %88, %89, %90, %91, %92, %93, %94, %95}, "
    "da, db, p, 1, 1, 0, 1;\n}\n"
    : "+f"(d[0]), "+f"(d[1]), "+f"(d[2]), "+f"(d[3]), "+f"(d[4]), "+f"(d[5]), "+f"(d[6]), "+f"(d[7]),
      "+f"(d[8]), "+f"(d[9]), "+f"(d[10]), "+f"(d[11]), "+f"(d[12]), "+f"(d[13]), "+f"(d[14]), "+f"(d[15]),
      "+f"(d[16]), "+f"(d[17]), "+f"(d[18]), "+f"(d[19]), "+f"(d[20]), "+f"(d[21]), "+f"(d[22]), "+f"(d[23]),
      "+f"(d[24]), "+f"(d[25]), "+f"(d[26]), "+f"(d[27]), "+f"(d[28]), "+f"(d[29]), "+f"(d[30]), "+f"(d[31]),
      "+f"(d[32]), "+f"(d[33]), "+f"(d[34]), "+f"(d[35]), "+f"(d[36]), "+f"(d[37]), "+f"(d[38]), "+f"(d[39]),
      "+f"(d[40]), "+f"(d[41]), "+f"(d[42]), "+f"(d[43]), "+f"(d[44]), "+f"(d[45]), "+f"(d[46]), "+f"(d[47]),
      "+f"(d[48]), "+f"(d[49]), "+f"(d[50]), "+f"(d[51]), "+f"(d[52]), "+f"(d[53]), "+f"(d[54]), "+f"(d[55]),
      "+f"(d[56]), "+f"(d[57]), "+f"(d[58]), "+f"(d[59]), "+f"(d[60]), "+f"(d[61]), "+f"(d[62]), "+f"(d[63]),
      "+f"(d[64]), "+f"(d[65]), "+f"(d[66]), "+f"(d[67]), "+f"(d[68]), "+f"(d[69]), "+f"(d[70]), "+f"(d[71]),
      "+f"(d[72]), "+f"(d[73]), "+f"(d[74]), "+f"(d[75]), "+f"(d[76]), "+f"(d[77]), "+f"(d[78]), "+f"(d[79]),
      "+f"(d[80]), "+f"(d[81]), "+f"(d[82]), "+f"(d[83]), "+f"(d[84]), "+f"(d[85]), "+f"(d[86]), "+f"(d[87]),
      "+f"(d[88]), "+f"(d[89]), "+f"(d[90]), "+f"(d[91]), "+f"(d[92]), "+f"(d[93]), "+f"(d[94]), "+f"(d[95])
    : "r"(da), "r"(db), "r"(scale_d));
}

__device__ __forceinline__ void wgmma_ss_n256(float (&d)[128], uint32_t da, uint32_t db, int scale_d) {
  asm volatile("{\n.reg .pred p;\n.reg .b64 da, db;\nsetp.ne.b32 p, %130, 0;\n"
    "mov.b64 da, {%128, 0x40000040};\nmov.b64 db, {%129, 0x40000040};\n"
    "wgmma.mma_async.sync.aligned.m64n256k16.f32.bf16.bf16 "
    "{%0, %1, %2, %3, %4, %5, %6, %7, %8, %9, %10, %11, %12, %13, %14, %15, "
    "%16, %17, %18, %19, %20, %21, %22, %23, %24, %25, %26, %27, %28, %29, %30, %31, "
    "%32, %33, %34, %35, %36, %37, %38, %39, %40, %41, %42, %43, %44, %45, %46, %47, "
    "%48, %49, %50, %51, %52, %53, %54, %55, %56, %57, %58, %59, %60, %61, %62, %63, "
    "%64, %65, %66, %67, %68, %69, %70, %71, %72, %73, %74, %75, %76, %77, %78, %79, "
    "%80, %81, %82, %83, %84, %85, %86, %87, %88, %89, %90, %91, %92, %93, %94, %95, "
    "%96, %97, %98, %99, %100, %101, %102, %103, %104, %105, %106, %107, %108, %109, %110, %111, "
    "%112, %113, %114, %115, %116, %117, %118, %119, %120, %121, %122, %123, %124, %125, %126, %127}, "
    "da, db, p, 1, 1, 0, 1;\n}\n"
    : "+f"(d[0]), "+f"(d[1]), "+f"(d[2]), "+f"(d[3]), "+f"(d[4]), "+f"(d[5]), "+f"(d[6]), "+f"(d[7]),
      "+f"(d[8]), "+f"(d[9]), "+f"(d[10]), "+f"(d[11]), "+f"(d[12]), "+f"(d[13]), "+f"(d[14]), "+f"(d[15]),
      "+f"(d[16]), "+f"(d[17]), "+f"(d[18]), "+f"(d[19]), "+f"(d[20]), "+f"(d[21]), "+f"(d[22]), "+f"(d[23]),
      "+f"(d[24]), "+f"(d[25]), "+f"(d[26]), "+f"(d[27]), "+f"(d[28]), "+f"(d[29]), "+f"(d[30]), "+f"(d[31]),
      "+f"(d[32]), "+f"(d[33]), "+f"(d[34]), "+f"(d[35]), "+f"(d[36]), "+f"(d[37]), "+f"(d[38]), "+f"(d[39]),
      "+f"(d[40]), "+f"(d[41]), "+f"(d[42]), "+f"(d[43]), "+f"(d[44]), "+f"(d[45]), "+f"(d[46]), "+f"(d[47]),
      "+f"(d[48]), "+f"(d[49]), "+f"(d[50]), "+f"(d[51]), "+f"(d[52]), "+f"(d[53]), "+f"(d[54]), "+f"(d[55]),
      "+f"(d[56]), "+f"(d[57]), "+f"(d[58]), "+f"(d[59]), "+f"(d[60]), "+f"(d[61]), "+f"(d[62]), "+f"(d[63]),
      "+f"(d[64]), "+f"(d[65]), "+f"(d[66]), "+f"(d[67]), "+f"(d[68]), "+f"(d[69]), "+f"(d[70]), "+f"(d[71]),
      "+f"(d[72]), "+f"(d[73]), "+f"(d[74]), "+f"(d[75]), "+f"(d[76]), "+f"(d[77]), "+f"(d[78]), "+f"(d[79]),
      "+f"(d[80]), "+f"(d[81]), "+f"(d[82]), "+f"(d[83]), "+f"(d[84]), "+f"(d[85]), "+f"(d[86]), "+f"(d[87]),
      "+f"(d[88]), "+f"(d[89]), "+f"(d[90]), "+f"(d[91]), "+f"(d[92]), "+f"(d[93]), "+f"(d[94]), "+f"(d[95]),
      "+f"(d[96]), "+f"(d[97]), "+f"(d[98]), "+f"(d[99]), "+f"(d[100]), "+f"(d[101]), "+f"(d[102]), "+f"(d[103]),
      "+f"(d[104]), "+f"(d[105]), "+f"(d[106]), "+f"(d[107]), "+f"(d[108]), "+f"(d[109]), "+f"(d[110]), "+f"(d[111]),
      "+f"(d[112]), "+f"(d[113]), "+f"(d[114]), "+f"(d[115]), "+f"(d[116]), "+f"(d[117]), "+f"(d[118]), "+f"(d[119]),
      "+f"(d[120]), "+f"(d[121]), "+f"(d[122]), "+f"(d[123]), "+f"(d[124]), "+f"(d[125]), "+f"(d[126]), "+f"(d[127])
    : "r"(da), "r"(db), "r"(scale_d));
}

namespace {

constexpr int SEQ = 2048, DM = 1024, FF = 3584;
constexpr int NCTA = 128;

constexpr uint32_t STG_OFF = 196608;
constexpr uint32_t MISC_OFF = STG_OFF + 32768;
constexpr uint32_t SMEM_BYTES = MISC_OFF + 3072;
constexpr uint32_t RED_OFF = 2 * 49152;
constexpr uint32_t MODB_OFF = MISC_OFF + 512;

enum { B_FQ = 0, B_EQ = 4, B_FW = 8, B_EW = 14, B_FG = 20, B_EG = 24, B_FD = 28, B_ED = 34,
       B_STGF = 40, B_MODB = 42, B_MODA = 45, B_RDY = 48, B_STGE = 56, B_COUNT = 58 };
enum { C_H = 0, C_O = 1, C_H2 = 3, C_ACT = 4, C_HA = 8, C_H2A = 9 };

struct Params {
  CUtensorMap h, o_ld, o_st, h2, act, out, wqkv, wqkv32, wo, wg, wu, wd, act_st, wm;
  const bf16* x;
  const bf16* c;
  const bf16* wmod;
  uint4* x1;
  uint4* modll;
  uint4* halo;
  uint4* stats1;
  uint4* stats2;
  unsigned* cnt;
  unsigned* epoch;
  uint8_t slot[64];
};

__device__ __align__(1024) bf16 g_h[SEQ * DM];
__device__ __align__(1024) bf16 g_o[SEQ * DM];
__device__ __align__(1024) bf16 g_act[SEQ * FF];
__device__ __align__(1024) uint4 g_modll[3072 / 2];
__device__ __align__(1024) uint4 g_halo[16 * 8 * 2 * 2 * 8 * 32];
__device__ __align__(1024) uint4 g_stats[2 * SEQ * 8];
__device__ __align__(1024) unsigned g_cnt[16 * 32];
__device__ uint4 g_epoch;
#define TR(off)

__device__ __forceinline__ uint32_t smem_u32(const void* p) { return (uint32_t)__cvta_generic_to_shared(p); }
__device__ __forceinline__ void mbar_init(uint32_t bar, uint32_t count) {
  asm volatile("mbarrier.init.shared::cta.b64 [%0], %1;" ::"r"(bar), "r"(count));
}
__device__ __forceinline__ void mbar_arrive(uint32_t bar) {
  asm volatile("mbarrier.arrive.shared::cta.b64 _, [%0];" ::"r"(bar) : "memory");
}
__device__ __forceinline__ void mbar_arrive_cluster(uint32_t cluster_addr) {
  asm volatile("mbarrier.arrive.shared::cluster.b64 _, [%0];" ::"r"(cluster_addr) : "memory");
}
__device__ __forceinline__ uint32_t mapa(uint32_t addr, uint32_t cta) {
  uint32_t r;
  asm volatile("mapa.shared::cluster.u32 %0, %1, %2;" : "=r"(r) : "r"(addr), "r"(cta));
  return r;
}
__device__ __forceinline__ void mbar_wait(uint32_t bar, uint32_t parity) {
  asm volatile(
      "{\n.reg .pred p;\n"
      "WAIT_%=:\n"
      "mbarrier.try_wait.parity.shared::cta.b64 p, [%0], %1;\n"
      "@!p bra WAIT_%=;\n}\n" ::"r"(bar), "r"(parity) : "memory");
}
__device__ __forceinline__ void mbar_wait_watchdog(uint32_t bar, uint32_t parity) {
  asm volatile(
      "{\n.reg .pred p;\n.reg .u64 t0, t1;\nmov.u64 t0, %%globaltimer;\n"
      "WAIT_%=:\n"
      "mbarrier.try_wait.parity.shared::cta.b64 p, [%0], %1;\n"
      "@p bra DONE_%=;\n"
      "mov.u64 t1, %%globaltimer;\n"
      "sub.u64 t1, t1, t0;\n"
      "setp.lt.u64 p, t1, 2000000000;\n"
      "@p bra WAIT_%=;\n"
      "trap;\n"
      "DONE_%=:\n}\n" ::"r"(bar), "r"(parity) : "memory");
}
__device__ __forceinline__ void cnt_wait(const unsigned* p, unsigned target) {
  asm volatile(
      "{\n.reg .pred p;\n.reg .u32 v;\n.reg .s32 d;\n"
      "WAIT_%=:\n"
      "ld.relaxed.gpu.global.u32 v, [%0];\n"
      "sub.s32 d, v, %1;\n"
      "setp.lt.s32 p, d, 0;\n"
      "@p bra WAIT_%=;\n"
      "fence.proxy.async.global;\n"
      "}\n" ::"l"(p), "r"(target) : "memory");
}
__device__ __forceinline__ void cnt_wait_lazy(const unsigned* p, unsigned target) {
  asm volatile(
      "{\n.reg .pred p;\n.reg .u32 v;\n.reg .s32 d;\n"
      "WAIT_%=:\n"
      "nanosleep.u32 400;\n"
      "ld.relaxed.gpu.global.u32 v, [%0];\n"
      "sub.s32 d, v, %1;\n"
      "setp.lt.s32 p, d, 0;\n"
      "@p bra WAIT_%=;\n"
      "fence.proxy.async.global;\n"
      "}\n" ::"l"(p), "r"(target) : "memory");
}
__device__ __forceinline__ void cnt_signal(unsigned* p) {
  asm volatile("{\n.reg .pred p;\nelect.sync _|p, 0xffffffff;\n@p red.relaxed.gpu.global.add.u32 [%0], 1;\n}\n" ::"l"(p) : "memory");
}
__device__ __forceinline__ void ll_store(uint4* p, uint32_t a, uint32_t b, uint32_t tag) {
  asm volatile("st.relaxed.gpu.global.v2.b64 [%0], {%1, %2};" ::"l"(p), "l"((uint64_t)a | ((uint64_t)tag << 32)),
               "l"((uint64_t)b | ((uint64_t)tag << 32)) : "memory");
}
__device__ __forceinline__ uint4 ll_peek(const uint4* p) {
  uint4 v;
  asm volatile("ld.relaxed.gpu.global.v4.u32 {%0, %1, %2, %3}, [%4];" : "=r"(v.x), "=r"(v.y), "=r"(v.z), "=r"(v.w) : "l"(p) : "memory");
  return v;
}
template <int N, int SLEEP = 0, class F>
__device__ __forceinline__ void ll_poll(F addr, uint32_t tag, uint32_t (&out)[2 * N]) {
  for (;;) {
    uint4 v[N];
#pragma unroll
    for (int i = 0; i < N; i++) v[i] = ll_peek(addr(i));
    uint32_t bad = 0;
#pragma unroll
    for (int i = 0; i < N; i++) {
      bad |= (v[i].y ^ tag) | (v[i].w ^ tag);
      out[2 * i] = v[i].x;
      out[2 * i + 1] = v[i].z;
    }
    if (__all_sync(~0u, bad == 0)) break;
    if (SLEEP) __nanosleep(SLEEP);
  }
}
constexpr uint64_t POLICY_EVICT_FIRST = 0x12F0000000000000ull;
__device__ __forceinline__ void expect_tx_elect(uint32_t bar, uint32_t bytes) {
  asm volatile("{\n.reg .pred p;\nelect.sync _|p, 0xffffffff;\n@p mbarrier.arrive.expect_tx.shared::cta.b64 _, [%0], %1;\n}\n" ::"r"(bar), "r"(bytes) : "memory");
}
__device__ __forceinline__ void arrive_elect(uint32_t bar) {
  asm volatile("{\n.reg .pred p;\nelect.sync _|p, 0xffffffff;\n@p mbarrier.arrive.shared::cta.b64 _, [%0];\n}\n" ::"r"(bar) : "memory");
}
__device__ __forceinline__ void tma_load(uint32_t dst, const CUtensorMap* m, uint32_t bar, int c0, int c1) {
  asm volatile("{\n.reg .pred p;\nelect.sync _|p, 0xffffffff;\n"
               "@p cp.async.bulk.tensor.2d.shared::cluster.global.mbarrier::complete_tx::bytes [%0], [%1, {%3, %4}], [%2];\n}\n"
               ::"r"(dst), "l"(m), "r"(bar), "r"(c0), "r"(c1) : "memory");
}
__device__ __forceinline__ void tma_load_mc(uint32_t dst, const CUtensorMap* m, uint32_t bar, int c0, int c1) {
  asm volatile("{\n.reg .pred p;\nelect.sync _|p, 0xffffffff;\n"
               "@p cp.async.bulk.tensor.2d.shared::cluster.global.mbarrier::complete_tx::bytes.multicast::cluster.L2::cache_hint [%0], [%1, {%3, %4}], [%2], %5, %6;\n}\n"
               ::"r"(dst), "l"(m), "r"(bar), "r"(c0), "r"(c1), "h"((uint16_t)3), "l"(POLICY_EVICT_FIRST) : "memory");
}
__device__ __forceinline__ void tma_load_ef(uint32_t dst, const CUtensorMap* m, uint32_t bar, int c0, int c1) {
  asm volatile("{\n.reg .pred p;\nelect.sync _|p, 0xffffffff;\n"
               "@p cp.async.bulk.tensor.2d.shared::cluster.global.mbarrier::complete_tx::bytes.L2::cache_hint [%0], [%1, {%3, %4}], [%2], %5;\n}\n"
               ::"r"(dst), "l"(m), "r"(bar), "r"(c0), "r"(c1), "l"(POLICY_EVICT_FIRST) : "memory");
}
__device__ __forceinline__ void tma_store2(const CUtensorMap* m, uint32_t src, int c0, int c1) {
  asm volatile("{\n.reg .pred p;\nelect.sync _|p, 0xffffffff;\n"
               "@p cp.async.bulk.tensor.2d.global.shared::cta.bulk_group [%0, {%2, %3}], [%1];\n}\n"
               ::"l"(m), "r"(src), "r"(c0), "r"(c1) : "memory");
}
__device__ __forceinline__ void tma_store3(const CUtensorMap* m, uint32_t src, int c0, int c1, int c2) {
  asm volatile("{\n.reg .pred p;\nelect.sync _|p, 0xffffffff;\n"
               "@p cp.async.bulk.tensor.3d.global.shared::cta.bulk_group [%0, {%2, %3, %4}], [%1];\n}\n"
               ::"l"(m), "r"(src), "r"(c0), "r"(c1), "r"(c2) : "memory");
}
__device__ __forceinline__ void store_pause(bool sleep) {
  asm volatile("cp.async.bulk.commit_group;" ::: "memory");
  asm volatile("cp.async.bulk.wait_group.read 0;" ::: "memory");
  if (sleep) __nanosleep(PAUSE);
}
__device__ __forceinline__ void l2_prefetch_tile(const CUtensorMap* m, int c0, int c1) {
  asm volatile("{\n.reg .pred p;\nelect.sync _|p, 0xffffffff;\n@p cp.async.bulk.prefetch.tensor.2d.L2.global [%0, {%1, %2}];\n}\n"
               ::"l"(m), "r"(c0), "r"(c1) : "memory");
}
__device__ __forceinline__ void prefetch_map(const CUtensorMap* m) {
  asm volatile("prefetch.tensormap [%0];" ::"l"(m) : "memory");
}
__device__ __forceinline__ void wg_fence() { asm volatile("wgmma.fence.sync.aligned;" ::: "memory"); }
__device__ __forceinline__ void wg_commit() { asm volatile("wgmma.commit_group.sync.aligned;" ::: "memory"); }
template <int N>
__device__ __forceinline__ void wg_wait() { asm volatile("wgmma.wait_group.sync.aligned %0;" ::"n"(N) : "memory"); }
__device__ __forceinline__ void bar_sync(int id, int n) { asm volatile("bar.sync %0, %1;" ::"r"(id), "r"(n) : "memory"); }
__device__ __forceinline__ void wg_bar(int cw) {
  asm volatile("{\n.reg .pred p;\nsetp.ne.s32 p, %0, 0;\n@p bar.sync 3, 128;\n@!p bar.sync 2, 128;\n}\n" ::"r"(cw) : "memory");
}
__device__ __forceinline__ void cluster_arrive_relaxed() { asm volatile("barrier.cluster.arrive.relaxed.aligned;" ::: "memory"); }
__device__ __forceinline__ void cluster_wait() { asm volatile("barrier.cluster.wait.acquire.aligned;" ::: "memory"); }
__device__ __forceinline__ uint32_t load_epoch(const unsigned* p) {
  uint32_t e;
  asm volatile("ld.relaxed.gpu.global.u32 %0, [%1];" : "=r"(e) : "l"(p) : "memory");
  return e;
}
__device__ __forceinline__ uint32_t pack2(float lo, float hi) {
  uint32_t r;
  asm("cvt.rn.bf16x2.f32 %0, %1, %2;" : "=r"(r) : "f"(hi), "f"(lo));
  return r;
}
__device__ __forceinline__ float bf_lo(uint32_t v) { return __uint_as_float(v << 16); }
__device__ __forceinline__ float bf_hi(uint32_t v) { return __uint_as_float(v & 0xffff0000u); }
__device__ __forceinline__ uint32_t fma_bf2(uint32_t a, uint32_t b, uint32_t c) {
  uint32_t d;
  asm("fma.rn.bf16x2 %0, %1, %2, %3;" : "=r"(d) : "r"(a), "r"(b), "r"(c));
  return d;
}
__device__ __forceinline__ float bf_round(float v) { return __bfloat162float(__float2bfloat16_rn(v)); }
__device__ __forceinline__ float silu_f(float v) { return __fdividef(v, 1.0f + __expf(-v)); }
__device__ __forceinline__ uint4 ldg_nc(const void* p) {
  uint4 v;
  asm volatile("ld.global.nc.L1::no_allocate.v4.u32 {%0, %1, %2, %3}, [%4];" : "=r"(v.x), "=r"(v.y), "=r"(v.z), "=r"(v.w) : "l"(p));
  return v;
}
__device__ __forceinline__ void stmatrix4(uint32_t addr, uint32_t a, uint32_t b, uint32_t c, uint32_t d) {
  asm volatile("stmatrix.sync.aligned.m8n8.x4.shared.b16 [%0], {%1, %2, %3, %4};" ::"r"(addr), "r"(a), "r"(b), "r"(c), "r"(d) : "memory");
}
__device__ __forceinline__ void stmatrix2(uint32_t addr, uint32_t a, uint32_t b) {
  asm volatile("stmatrix.sync.aligned.m8n8.x2.shared.b16 [%0], {%1, %2};" ::"r"(addr), "r"(a), "r"(b) : "memory");
}
__device__ __forceinline__ void stmatrix1(uint32_t addr, uint32_t a) {
  asm volatile("stmatrix.sync.aligned.m8n8.x1.shared.b16 [%0], {%1};" ::"r"(addr), "r"(a) : "memory");
}
__device__ __forceinline__ uint32_t movmatrix(uint32_t a) {
  uint32_t d;
  asm("movmatrix.sync.aligned.m8n8.trans.b16 %0, %1;" : "=r"(d) : "r"(a));
  return d;
}
__device__ __forceinline__ void mma16816(float (&d)[4], uint32_t a0, uint32_t a1, uint32_t a2, uint32_t a3, uint32_t b0, uint32_t b1) {
  asm("mma.sync.aligned.m16n8k16.row.col.f32.bf16.bf16.f32 {%0, %1, %2, %3}, {%4, %5, %6, %7}, {%8, %9}, {%0, %1, %2, %3};"
               : "+f"(d[0]), "+f"(d[1]), "+f"(d[2]), "+f"(d[3]) : "r"(a0), "r"(a1), "r"(a2), "r"(a3), "r"(b0), "r"(b1));
}
__device__ __forceinline__ void mma1688(float (&d)[4], uint32_t a0, uint32_t a1, uint32_t b0) {
  asm("mma.sync.aligned.m16n8k8.row.col.f32.bf16.bf16.f32 {%0, %1, %2, %3}, {%4, %5}, {%6}, {%0, %1, %2, %3};"
               : "+f"(d[0]), "+f"(d[1]), "+f"(d[2]), "+f"(d[3]) : "r"(a0), "r"(a1), "r"(b0));
}
__device__ __forceinline__ void ldmatrix4t(uint32_t (&b)[4], uint32_t addr) {
  asm volatile("ldmatrix.sync.aligned.m8n8.x4.trans.shared.b16 {%0, %1, %2, %3}, [%4];" : "=r"(b[0]), "=r"(b[1]), "=r"(b[2]), "=r"(b[3]) : "r"(addr) : "memory");
}
__device__ __forceinline__ void ldmatrix4(uint32_t& a, uint32_t& b, uint32_t& c, uint32_t& d, uint32_t addr) {
  asm volatile("ldmatrix.sync.aligned.m8n8.x4.shared.b16 {%0, %1, %2, %3}, [%4];" : "=r"(a), "=r"(b), "=r"(c), "=r"(d) : "r"(addr) : "memory");
}
__device__ __forceinline__ void cp_async16(uint32_t dst, const void* src) {
  asm volatile("cp.async.cg.shared.global.L2::cache_hint [%0], [%1], 16, %2;" ::"r"(dst), "l"(src), "l"(POLICY_EVICT_FIRST) : "memory");
}
__device__ __forceinline__ uint32_t lds32(uint32_t addr) {
  uint32_t v;
  asm volatile("ld.shared.u32 %0, [%1];" : "=r"(v) : "r"(addr) : "memory");
  return v;
}
__device__ __forceinline__ void sts64f(uint32_t addr, float a, float b) {
  asm volatile("st.shared.v2.f32 [%0], {%1, %2};" ::"r"(addr), "f"(a), "f"(b) : "memory");
}
constexpr float QK_SCALE = 0.17677669529663687f;
__device__ __forceinline__ float softmax8(float& p0, float& p1) {
  float m = fmaxf(p0, p1);
  m = fmaxf(m, __shfl_xor_sync(~0u, m, 1));
  m = fmaxf(m, __shfl_xor_sync(~0u, m, 2));
  asm("ex2.approx.ftz.f32 %0, %1;" : "=f"(p0) : "f"((p0 - m) * 1.4426950408889634f));
  asm("ex2.approx.ftz.f32 %0, %1;" : "=f"(p1) : "f"((p1 - m) * 1.4426950408889634f));
  float s = p0 + p1;
  s += __shfl_xor_sync(~0u, s, 1);
  s += __shfl_xor_sync(~0u, s, 2);
  float r;
  asm("rcp.approx.ftz.f32 %0, %1;" : "=f"(r) : "f"(s));
  return r;
}
__device__ __forceinline__ void sts128(uint32_t addr, uint32_t a, uint32_t b, uint32_t c, uint32_t d) {
  asm volatile("st.shared.v4.u32 [%0], {%1, %2, %3, %4};" ::"r"(addr), "r"(a), "r"(b), "r"(c), "r"(d) : "memory");
}
__device__ __forceinline__ uint4 lds128(uint32_t addr) {
  uint4 v;
  asm volatile("ld.shared.v4.u32 {%0, %1, %2, %3}, [%4];" : "=r"(v.x), "=r"(v.y), "=r"(v.z), "=r"(v.w) : "r"(addr) : "memory");
  return v;
}
__device__ __forceinline__ float2 lds64f(uint32_t addr) {
  float2 v;
  asm volatile("ld.shared.v2.f32 {%0, %1}, [%2];" : "=f"(v.x), "=f"(v.y) : "r"(addr) : "memory");
  return v;
}
#define PROF_AT(cond, slot) do {} while (0)

constexpr uint32_t SMEM_BASE = 1024;
constexpr uint32_t DESC_A = (1u << 16) | (SMEM_BASE >> 4);
constexpr uint32_t DESC_B = ((8192u >> 4) << 16) | ((SMEM_BASE + 16384) >> 4);

template <int BN> struct Wg;
template <> struct Wg<128> { static __device__ __forceinline__ void mma(float (&d)[64], uint32_t a, uint32_t b, int s) { wgmma_ss_n128(d, a, b, s); } };
template <> struct Wg<192> { static __device__ __forceinline__ void mma(float (&d)[96], uint32_t a, uint32_t b, int s) { wgmma_ss_n192(d, a, b, s); } };
template <> struct Wg<256> { static __device__ __forceinline__ void mma(float (&d)[128], uint32_t a, uint32_t b, int s) { wgmma_ss_n256(d, a, b, s); } };

struct Ring {
  uint32_t full0, rel0;
  int s;
  uint32_t ph;
  bool releaser;
};

template <int N>
__device__ __forceinline__ void fence_regs(float (&a)[N]) {
#pragma unroll
  for (int i = 0; i < N; i++) asm volatile("" : "+f"(a[i])::"memory");
}

template <int BN, int NST, uint32_t STAGE>
__device__ __forceinline__ void kblock(float (&acc)[BN / 2], Ring& g, uint32_t a_addr, bool zero, uint32_t& prev) {
  mbar_wait(g.full0 + 8 * g.s, g.ph);
  const uint32_t da = DESC_A + (a_addr >> 4);
  const uint32_t db = DESC_B + g.s * (STAGE >> 4);
  wg_fence();
#pragma unroll
  for (int k = 0; k < 4; k++) Wg<BN>::mma(acc, da + k * 2, db + k * 128, !(zero && k == 0));
  wg_commit();
  wg_wait<1>();
  if (prev != 0) mbar_arrive_cluster(prev);
  prev = g.releaser ? g.rel0 + 8 * g.s : 0u;
  if (++g.s == NST) { g.s = 0; g.ph ^= 1; }
}
template <int N>
__device__ __forceinline__ void tile_end(float (&acc)[N], uint32_t& prev) {
  wg_wait<0>();
  if (prev != 0) mbar_arrive_cluster(prev);
  prev = 0;
  fence_regs(acc);
}

__device__ __forceinline__ int other_kb(int q, int j) {
  const int ch = q >= 7, jj = q - 7 * ch;
  return 2 * (jj < j ? jj : jj + 1) + ch;
}
__device__ __forceinline__ int own_first(int it, int j) {
  return it >= 16 ? (it & 15) : (it < 2 ? 2 * j + it : other_kb(it - 2, j));
}
__device__ __forceinline__ int qkv_kb(int it, int j) {
  return it < 4 ? 2 * j + (it & 1) : other_kb(it < 18 ? it - 4 : it - 18, j);
}
__device__ __forceinline__ int wo_k(int it, int j) {
  return it < 8 ? it * 128 : (it == 8 ? j : (it - 9 < j ? it - 9 : it - 8)) * 128 + 64;
}
__device__ __forceinline__ int down_k(int it) {
  const int r = (it >> 4) - 1, idx = it & 15;
  return r < 0 ? idx * 64 : (r < 3 ? (idx >> 1) * 448 + r * 128 + (idx & 1) * 64 : idx * 448 + 384);
}
__device__ __forceinline__ void wait_p3_free(uint32_t empty3, int i) {
  mbar_wait(empty3 + 8 * ((i * 2) / 3), 1);
  mbar_wait(empty3 + 8 * ((i * 2 + 1) / 3), 1);
}
__device__ __forceinline__ void wait_p2_free(uint32_t empty2, int i) {
  const int w0 = (i * 3) / 2, w1 = (i * 3 + 2) / 2;
  mbar_wait(empty2 + 8 * w0, w0 < 4 ? 0 : 1);
  mbar_wait(empty2 + 8 * w1, w1 < 4 ? 0 : 1);
}

__device__ __forceinline__ void chan(float& m, float& q, float m2, float q2, float n) {
  const float d = m2 - m;
  m = 0.5f * (m + m2);
  q = q + q2 + d * d * (0.5f * n);
}

template <int N>
__device__ __forceinline__ void row_stats(const uint32_t (&ll)[N], float& mean, float& rstd) {
  float ma = __uint_as_float(ll[0]), qa = __uint_as_float(ll[1]), mb = __uint_as_float(ll[4]), qb = __uint_as_float(ll[5]);
  chan(ma, qa, __uint_as_float(ll[2]), __uint_as_float(ll[3]), 128.f);
  chan(mb, qb, __uint_as_float(ll[6]), __uint_as_float(ll[7]), 128.f);
  chan(ma, qa, mb, qb, 256.f);
  const float mo = __shfl_xor_sync(~0u, ma, 16), qo = __shfl_xor_sync(~0u, qa, 16);
  chan(ma, qa, mo, qo, 512.f);
  mean = ma;
  rstd = rsqrtf(qa * (1.0f / DM) + 1e-5f);
}

__device__ __forceinline__ void publish_stats(const uint32_t (&xl)[16], const uint32_t (&xh)[16], uint4* slot, int lane, uint32_t tag) {
  float ds[4] = {0.f, 0.f, 0.f, 0.f}, dl[4] = {0.f, 0.f, 0.f, 0.f}, dh[4] = {0.f, 0.f, 0.f, 0.f};
#pragma unroll
  for (int q = 0; q < 8; q++) {
    mma16816(ds, xl[2 * q], xh[2 * q], xl[2 * q + 1], xh[2 * q + 1], 0x3f803f80u, 0x3f803f80u);
    mma16816(dl, xl[2 * q], xh[2 * q], xl[2 * q + 1], xh[2 * q + 1], xl[2 * q], xl[2 * q + 1]);
    mma16816(dh, xl[2 * q], xh[2 * q], xl[2 * q + 1], xh[2 * q + 1], xh[2 * q], xh[2 * q + 1]);
  }
  const int r = lane >> 2;
  if ((lane & 3) == (r >> 1)) {
    const float ml = ds[0] * (1.0f / 128), mh = ds[2] * (1.0f / 128);
    const float ql = fmaxf(((r & 1) ? dl[1] : dl[0]) - ds[0] * ml, 0.f), qh = fmaxf(((r & 1) ? dh[3] : dh[2]) - ds[2] * mh, 0.f);
    ll_store(slot + r, __float_as_uint(ml), __float_as_uint(ql), tag);
    ll_store(slot + r + 8, __float_as_uint(mh), __float_as_uint(qh), tag);
  }
  __syncwarp();
}

__device__ __forceinline__ void stage_slab(uint32_t chunk, int warp, int lane, const uint32_t (&lo)[8], const uint32_t (&hi)[8]) {
  const int row = warp * 16 + (lane & 7) + ((lane >> 3) & 1) * 8;
  const uint32_t rbase = chunk + row * 128;
#pragma unroll
  for (int q = 0; q < 4; q++) {
    const int grp = 2 * q + (lane >> 4);
    stmatrix4(rbase + ((grp ^ (row & 7)) << 4), lo[2 * q], hi[2 * q], lo[2 * q + 1], hi[2 * q + 1]);
  }
}
__device__ __forceinline__ float silu_mul(float g, float u) {
  float e, r;
  asm("ex2.approx.ftz.f32 %0, %1;" : "=f"(e) : "f"(g * -1.4426950408889634f));
  asm("rcp.approx.ftz.f32 %0, %1;" : "=f"(r) : "f"(1.0f + e));
  return g * r * u;
}
__device__ __forceinline__ uint32_t swiglu2(uint32_t g2, uint32_t u2) {
  asm volatile("" : "+r"(g2));
  return pack2(silu_mul(bf_lo(g2), bf_lo(u2)), silu_mul(bf_hi(g2), bf_hi(u2)));
}
__device__ __forceinline__ void stage_done(uint32_t bar, int lane) {
  asm volatile("fence.proxy.async.shared::cta;" ::: "memory");
  __syncwarp();
  if (lane == 0) mbar_arrive(bar);
}

__device__ __forceinline__ int fresh_tid() {
  int t;
  asm volatile("mov.u32 %0, %%tid.x;" : "=r"(t));
  return t;
}
#define RING_IDS()                                                                                           \
  const int tid = fresh_tid() - 128;                                                                         \
  const int cw = __shfl_sync(~0u, tid >> 7, 0), warp = __shfl_sync(~0u, (tid >> 5) & 3, 0);                  \
  const bool releaser = (tid & 31) < 2;                                                                      \
  const uint32_t rbars = mapa(bars, tid & 1);                                                                \
  const uint32_t a_base = cw * 8192
#define LANE_IDS()                                                                                           \
  const int lane = fresh_tid() & 31, r = lane >> 2, c = lane & 3;                                            \
  const int srow = warp * 16 + (lane & 7) + ((lane >> 3) & 1) * 8;                                           \
  const uint32_t slab = stg + cw * 8192 + srow * 128, sw0 = (lane >> 4) ^ (srow & 7);                        \
  (void)r; (void)c; (void)slab; (void)sw0

template <int NPRE, bool EAGER, class Step>
__device__ __forceinline__ void attention(float (&acc)[96], const Params& p, int rho, int rb, int cta, int cw, int warp, uint32_t tag,
                                          uint32_t stg, uint32_t bars, uint32_t& prev, Step step) {
  uint32_t ql[8], qh[8], k0[8], k1[8], v0[8], v1[8], hp[16];
  if (EAGER) {
    tile_end(acc, prev);
  } else {
    step();
    fence_regs(acc);
  }
#pragma unroll
  for (int t = 0; t < 8; t++) {
    k0[t] = pack2(acc[4 * (8 + t)], acc[4 * (8 + t) + 1]);
    k1[t] = pack2(acc[4 * (8 + t) + 2], acc[4 * (8 + t) + 3]);
    v0[t] = pack2(acc[4 * (16 + t)], acc[4 * (16 + t) + 1]);
    v1[t] = pack2(acc[4 * (16 + t) + 2], acc[4 * (16 + t) + 3]);
    asm volatile("" : "+r"(k0[t]), "+r"(k1[t]), "+r"(v0[t]), "+r"(v1[t]));
  }
  const int lane = fresh_tid() & 31, r = lane >> 2, c = lane & 3;
#pragma unroll
  for (int t = 0; t < 8; t++) v1[t] = movmatrix(v1[t]);
  mbar_wait(bars + 8 * B_STGE, rho);
  mbar_wait(bars + 8 * (B_STGE + 1), 0);
  const uint32_t xch = stg + 16384 + (cw * 4 + warp) * 2048 + lane * 16;
  if (warp < 3) {
    sts128(xch, k1[0], k1[1], k1[2], k1[3]);
    sts128(xch + 512, k1[4], k1[5], k1[6], k1[7]);
    sts128(xch + 1024, v1[0], v1[1], v1[2], v1[3]);
    sts128(xch + 1536, v1[4], v1[5], v1[6], v1[7]);
  } else if (rb < 15) {
    uint4* dst = p.halo + ((cta * 2 + rho) * 2 + cw) * 256 + lane;
#pragma unroll
    for (int t = 0; t < 4; t++) {
      ll_store(dst + t * 32, k1[2 * t], k1[2 * t + 1], tag);
      ll_store(dst + (4 + t) * 32, v1[2 * t], v1[2 * t + 1], tag);
    }
  }
#pragma unroll
  for (int t = 0; t < 8; t++) {
    v0[t] = movmatrix(v0[t]);
    ql[t] = pack2(acc[4 * t], acc[4 * t + 1]);
    qh[t] = pack2(acc[4 * t + 2], acc[4 * t + 3]);
    asm volatile("" : "+r"(v0[t]), "+r"(ql[t]), "+r"(qh[t]));
  }
#pragma unroll 1
  for (int i = 0; i < NPRE; i++) step();
  const uint4* src = p.halo + (((cta - 8) * 2 + rho) * 2 + cw) * 256 + lane;
  uint4 early[8] = {};
  if (warp == 0 && rb > 0) {
#pragma unroll
    for (int i = 0; i < 8; i++) early[i] = ll_peek(src + i * 32);
  }
  step();
  wg_bar(cw);
  if (warp > 0) {
#pragma unroll
    for (int t = 0; t < 4; t++) {
      const uint4 a = lds128(xch - 2048 + t * 512);
      hp[4 * t] = a.x; hp[4 * t + 1] = a.y; hp[4 * t + 2] = a.z; hp[4 * t + 3] = a.w;
    }
  } else if (rb > 0) {
    uint32_t bad = 0;
#pragma unroll
    for (int i = 0; i < 8; i++) {
      bad |= (early[i].y ^ tag) | (early[i].w ^ tag);
      hp[2 * i] = early[i].x;
      hp[2 * i + 1] = early[i].z;
    }
    if (!__all_sync(~0u, bad == 0)) ll_poll<8>([&](int i) { return src + i * 32; }, tag, hp);
  } else {
#pragma unroll
    for (int t = 0; t < 16; t++) hp[t] = 0;
  }
  wg_wait<0>();
  if (prev != 0) mbar_arrive_cluster(prev);
  prev = 0;
#pragma unroll
  for (int t = 0; t < 8; t++) asm volatile("" : "+r"(ql[t])::"memory");
  const bool up0 = 2 * c > r, up1 = 2 * c + 1 > r;
  const bool first = (rb == 0) && (warp == 0);
  uint32_t a0[2], a2[2], a3[2], a5[2];
  float il[2], ih[2];
#pragma unroll
  for (int h = 0; h < 2; h++) {
    float sp[4] = {0.f, 0.f, 0.f, 0.f}, s0[4] = {0.f, 0.f, 0.f, 0.f}, s1[4] = {0.f, 0.f, 0.f, 0.f};
#pragma unroll
    for (int ks = 0; ks < 2; ks++) {
      const int t = 4 * h + 2 * ks;
      mma16816(sp, ql[t], qh[t], ql[t + 1], qh[t + 1], hp[t], hp[t + 1]);
      mma16816(s0, ql[t], qh[t], ql[t + 1], qh[t + 1], k0[t], k0[t + 1]);
      mma16816(s1, ql[t], qh[t], ql[t + 1], qh[t + 1], k1[t], k1[t + 1]);
    }
    float p0 = (up0 ? sp[0] : s0[0]) * QK_SCALE, p1 = (up1 ? sp[1] : s0[1]) * QK_SCALE;
    float p2 = (up0 ? s0[2] : s1[2]) * QK_SCALE, p3 = (up1 ? s0[3] : s1[3]) * QK_SCALE;
    if (first && up0) p0 = -1000000000.0f;
    if (first && up1) p1 = -1000000000.0f;
    il[h] = softmax8(p0, p1);
    ih[h] = softmax8(p2, p3);
    a0[h] = pack2(up0 ? p0 : 0.f, up1 ? p1 : 0.f);
    a2[h] = pack2(up0 ? 0.f : p0, up1 ? 0.f : p1);
    a3[h] = pack2(up0 ? p2 : 0.f, up1 ? p3 : 0.f);
    a5[h] = pack2(up0 ? 0.f : p2, up1 ? 0.f : p3);
  }
  float o[8][4];
#pragma unroll
  for (int t = 0; t < 8; t++) {
#pragma unroll
    for (int q = 0; q < 4; q++) o[t][q] = 0.f;
    mma1688(o[t], 0u, a5[t >> 2], v1[t]);
    mma16816(o[t], a0[t >> 2], 0u, a2[t >> 2], a3[t >> 2], hp[8 + t], v0[t]);
  }
#pragma unroll
  for (int t = 0; t < 8; t++) fence_regs(o[t]);
  if (!EAGER) step();
  uint32_t ol[8], oh[8];
#pragma unroll
  for (int t = 0; t < 8; t++) {
    ol[t] = pack2(o[t][0] * il[t >> 2], o[t][1] * il[t >> 2]);
    oh[t] = pack2(o[t][2] * ih[t >> 2], o[t][3] * ih[t >> 2]);
  }
  if (!EAGER) step();
  stage_slab(stg + cw * 8192, warp, lane, ol, oh);
  stage_done(bars + 8 * B_STGF, lane);
  if (!EAGER) step();
}

__global__ void __launch_bounds__(384, 1) fused_kernel(const __grid_constant__ Params p) {
  extern __shared__ __align__(1024) uint8_t smem_raw[];
  const uint32_t sm = smem_u32(smem_raw);
  const uint32_t bars = sm + MISC_OFF;
  const uint32_t stg = sm + STG_OFF;
  const int rank = blockIdx.x & 1;
  const int cl = blockIdx.x >> 1;
  if (cl >= NCTA / 2) {
    const int e = blockIdx.x - NCTA, wid = __shfl_sync(~0u, (int)(threadIdx.x >> 5), 0), lane = threadIdx.x & 31;
    if (threadIdx.x == 0) {
      for (int i = 0; i < 6; i++) { mbar_init(bars + 8 * i, 1); mbar_init(bars + 8 * (6 + i), 8); }
      asm volatile("fence.mbarrier_init.release.cluster;" ::: "memory");
    }
    const uint32_t tag = load_epoch(p.epoch) + 1;
    if (threadIdx.x < 256) ll_store(p.modll + 512 + (threadIdx.x >> 6) * 256 + e * 64 + (threadIdx.x & 63), 0u, 0u, 0u);
    for (int i = threadIdx.x; i < 1536; i += 384) {
      uint4 o = make_uint4(0u, 0u, 0u, 0u);
      if (i < 1024 && (i & 63) < 8) {
        const uint4 cv = ldg_nc(p.c + (i >> 6) * 64 + (i & 7) * 8);
        o = make_uint4(pack2(silu_f(bf_lo(cv.x)), silu_f(bf_hi(cv.x))), pack2(silu_f(bf_lo(cv.y)), silu_f(bf_hi(cv.y))),
                       pack2(silu_f(bf_lo(cv.z)), silu_f(bf_hi(cv.z))), pack2(silu_f(bf_lo(cv.w)), silu_f(bf_hi(cv.w))));
      }
      sts128(stg + i * 16, o.x, o.y, o.z, o.w);
    }
    asm volatile("fence.proxy.async.shared::cta;" ::: "memory");
    __syncthreads();
    if (wid == 0) {
      __nanosleep(WMDELAY);
      uint32_t ph = 1;
#pragma unroll 1
      for (int it = 0, s = 0; it < 64; it++) {
        mbar_wait(bars + 8 * (6 + s), ph);
        expect_tx_elect(bars + 8 * s, 32768);
#pragma unroll
        for (int q = 0; q < 4; q++) tma_load_ef(sm + s * 32768 + q * 8192, &p.wm, bars + 8 * s, 2048 + (it >> 4) * 1024 + e * 256 + q * 64, (it & 15) * 64);
        if (++s == 6) { s = 0; ph ^= 1; }
      }
    } else if (wid == 1 && PFW) {
      __nanosleep(PFW);
#pragma unroll 1
      for (int i = 0; i < 64; i++) {
        l2_prefetch_tile(&p.wo, (i & 15) * 64, (e * 4 + (i >> 4)) * 64);
        if (PFP) __nanosleep(PFP);
      }
#pragma unroll 1
      for (int i = 0; i < 128; i++) {
        l2_prefetch_tile((i & 2) ? &p.wu : &p.wg, ((i >> 2) & 7) * 448 + (i & 1) * 64, ((i >> 5) * 4 + e) * 64);
        if (PFP) __nanosleep(PFP);
      }
    } else if (wid >= 4) {
      const int hf = (wid >> 2) - 1;
      uint32_t ph = 0;
      int s = 0;
#pragma unroll 1
      for (int v = 0; v < 4; v++) {
        float acc[64];
#pragma unroll 1
        for (int kb = 0; kb < 16; kb++) {
          mbar_wait_watchdog(bars + 8 * s, ph);
          const uint32_t da = DESC_A + ((STG_OFF + kb * 1024) >> 4), db = DESC_B + ((s * 32768 + hf * 16384) >> 4) - 1024;
          wg_fence();
#pragma unroll
          for (int k = 0; k < 4; k++) wgmma_ss_n128(acc, da + k * 2, db + k * 128, (kb | k) != 0);
          wg_commit();
          wg_wait<0>();
          if (lane == 0) mbar_arrive(bars + 8 * (6 + s));
          if (++s == 6) { s = 0; ph ^= 1; }
        }
        if ((wid & 3) == 0) {
#pragma unroll
          for (int n = 0; n < 16; n++) {
            const uint32_t mine = pack2(acc[4 * n], acc[4 * n + 1]), next = __shfl_down_sync(~0u, mine, 1);
            if (lane < 4 && (lane & 1) == 0) ll_store(p.modll + 512 + v * 256 + e * 64 + hf * 32 + n * 2 + (lane >> 1), mine, next, tag);
          }
        }
      }
    }
    return;
  }
  const int slot = p.slot[cl];
  const int rb = (slot >> 3) * 2 + rank, j = slot & 7;
  const int cta = rb * 8 + j;
  PROF_AT(threadIdx.x == 0, 0);

  if (threadIdx.x < 128) {
    uint32_t tag = load_epoch(p.epoch);
    asm volatile("setmaxnreg.dec.sync.aligned.u32 40;");
    const int warp = __shfl_sync(~0u, (int)(threadIdx.x >> 5), 0), lane = threadIdx.x & 31;
    if (threadIdx.x == 0) {
      if ((sm & 0x3FFFF) != SMEM_BASE) asm volatile("trap;");
      for (int i = 0; i < 4; i++) { mbar_init(bars + 8 * (B_FQ + i), 1); mbar_init(bars + 8 * (B_EQ + i), 16); }
      for (int i = 0; i < 6; i++) { mbar_init(bars + 8 * (B_FW + i), 1); mbar_init(bars + 8 * (B_EW + i), 16); }
      for (int i = 0; i < 4; i++) { mbar_init(bars + 8 * (B_FG + i), 1); mbar_init(bars + 8 * (B_EG + i), 16); }
      for (int i = 0; i < 6; i++) { mbar_init(bars + 8 * (B_FD + i), 1); mbar_init(bars + 8 * (B_ED + i), 16); }
      for (int i = 0; i < 2; i++) { mbar_init(bars + 8 * (B_STGF + i), 8); mbar_init(bars + 8 * (B_STGE + i), 1); }
      mbar_init(bars + 8 * B_MODB, 1);
      mbar_init(bars + 8 * (B_MODB + 1), 1);
      mbar_init(bars + 8 * B_MODA, 1);
      for (int i = 0; i < 8; i++) mbar_init(bars + 8 * (B_RDY + i), 1);
      asm volatile("fence.mbarrier_init.release.cluster;" ::: "memory");
    }
    __syncwarp();
    cluster_arrive_relaxed();
    tag += 1;
    const unsigned target = tag * 8;
    unsigned* cnt = p.cnt + rb * 32;
    cluster_wait();
    if (warp == 0) {
      const CUtensorMap* wgu = rank ? &p.wu : &p.wg;
      uint32_t st = sm + 16384, fb = bars + 8 * B_FQ, ph = 1;
      __nanosleep(BDELAY);
#pragma unroll 1
      for (int it = 0; it < 32; it++) {
        const int kb = qkv_kb(it, j), col = j * 128 + ((it < 4 ? it >= 2 : it >= 18) ? 64 : 0);
        mbar_wait(fb + 8 * (B_EQ - B_FQ), ph);
        expect_tx_elect(fb, it < 4 ? 24576 : 40960);
        tma_load_mc(st + rank * 8192, &p.wqkv, fb, col + rank * 1024, kb * 64);
        tma_load_mc(st + 16384 + rank * 4096, &p.wqkv32, fb, col + 2048, kb * 64 + rank * 32);
        st += 49152; fb += 8;
        if ((it & 3) == 3) { st -= 4 * 49152; fb -= 32; ph ^= 1; }
      }
      fb = bars + 8 * B_FW; ph = 1;
#pragma unroll 1
      for (int it = 0, s = 0; it < 16; it++) {
        if (it < 6) wait_p3_free(bars + 8 * B_EQ, it);
        mbar_wait(fb + 8 * (B_EW - B_FW), ph);
        expect_tx_elect(fb, it == 8 ? 16384 : 32768);
        tma_load_mc(st + rank * 8192, &p.wo, fb, j * 128 + rank * 64, wo_k(it, j));
        st += 32768; fb += 8;
        if (++s == 6) { s = 0; st -= 6 * 32768; fb -= 48; ph ^= 1; }
      }
      st = sm + 16384; fb = bars + 8 * B_FG; ph = 1;
#pragma unroll 1
      for (int it = 0; it < 48; it++) {
        const int kb = own_first(it, j), col = j * 448 + (it >> 4) * 128;
        if (it < 4) wait_p2_free(bars + 8 * B_EW, it);
        mbar_wait(fb + 8 * (B_EG - B_FG), ph);
        expect_tx_elect(fb, it < 2 ? 32768 : 49152);
        tma_load_mc(st + rank * 16384, wgu, fb, col, kb * 64);
        tma_load_mc(st + rank * 16384 + 8192, wgu, fb, col + 64, kb * 64);
        st += 49152; fb += 8;
        if ((it & 3) == 3) { st -= 4 * 49152; fb -= 32; ph ^= 1; }
      }
      fb = bars + 8 * B_FD; ph = 1;
#pragma unroll 1
      for (int it = 0, s = 0; it < 72; it++) {
        if (it < 6) wait_p3_free(bars + 8 * B_EG, it);
        mbar_wait(fb + 8 * (B_ED - B_FD), ph);
        expect_tx_elect(fb, 32768);
        tma_load_mc(st + rank * 8192, it < 16 ? wgu : &p.wd, fb, it < 16 ? j * 448 + 384 : j * 128 + rank * 64, down_k(it));
        st += 32768; fb += 8;
        if (++s == 6) { s = 0; st -= 6 * 32768; fb -= 48; ph ^= 1; }
      }
    } else if (warp == 1) {
      const int arow = rb * 128;
      uint32_t st = sm, fb = bars + 8 * B_FQ, ph = 0;
      cnt_wait(cnt + C_HA, target);
      PROF_AT(lane == 0, 16);
#pragma unroll 1
      for (int it = 4; it < 32; it++) {
        if (it == 11) mbar_wait(bars + 8 * (B_RDY + C_H), 0);
        mbar_wait(fb + 8 * (B_EQ - B_FQ), ph);
        tma_load(st, &p.h, fb, qkv_kb(it, j) * 64, arow);
        st += 49152; fb += 8;
        if ((it & 3) == 3) { st -= 4 * 49152; fb -= 32; ph ^= 1; }
      }
      fb = bars + 8 * B_FW; ph = 1;
#pragma unroll 1
      for (int it = 0, s = 0; it < 16; it++) {
        if (it < 6) wait_p3_free(bars + 8 * B_EQ, it);
        mbar_wait(fb + 8 * (B_EW - B_FW), ph);
        if (it == 0) mbar_wait(bars + 8 * (B_RDY + C_O), 0);
        if (it == 9) cnt_wait(cnt + C_O + 1, target);
        PROF_AT(lane == 0 && (it == 0 || it == 9), 17 + (it >> 3));
        if (it != 8) tma_load(st, &p.o_ld, fb, wo_k(it, j), arow);
        st += 32768; fb += 8;
        if (++s == 6) { s = 0; st -= 6 * 32768; fb -= 48; ph ^= 1; }
      }
      st = sm + 2 * 49152; fb = bars + 8 * (B_FG + 2); ph = 1;
      cnt_wait(cnt + C_H2A, target);
      PROF_AT(lane == 0, 19);
#pragma unroll 1
      for (int it = 2; it < 48; it++) {
        if (it == 9) mbar_wait(bars + 8 * (B_RDY + C_H2), 0);
        mbar_wait(fb + 8 * (B_EG - B_FG), ph);
        tma_load(st, &p.h2, fb, own_first(it, j) * 64, arow);
        st += 49152; fb += 8;
        if ((it & 3) == 3) { st -= 4 * 49152; fb -= 32; ph ^= 1; }
      }
      fb = bars + 8 * B_FD; ph = 1;
#pragma unroll 1
      for (int it = 0, s = 0; it < 72; it++) {
        if (it < 6) wait_p3_free(bars + 8 * B_EG, it);
        mbar_wait(fb + 8 * (B_ED - B_FD), ph);
        if ((it & 15) == 0 && it > 0) { mbar_wait(bars + 8 * (B_RDY + C_ACT - 1 + (it >> 4)), 0); PROF_AT(lane == 0, 19 + (it >> 4)); }
        tma_load(st, it < 16 ? &p.h2 : &p.act, fb, down_k(it), arow);
        st += 32768; fb += 8;
        if (++s == 6) { s = 0; st -= 6 * 32768; fb -= 48; ph ^= 1; }
      }
    } else if (warp == 2) {
      if (lane < 13) prefetch_map(&p.h + lane);
      __syncwarp();
      uint32_t ph1 = 0;
#pragma unroll 1
      for (int n = 0; n < 8; n++) {
        const int nch = (n == 1 || n == 2 || n == 7) ? 1 : 2;
#pragma unroll 1
        for (int ch = 0; ch < nch; ch++) {
          mbar_wait_watchdog(bars + 8 * (B_STGF + ch), ch ? ph1 : (n & 1));
          const uint32_t src = stg + ch * 16384;
          if (n == 1 || n == 2) {
#pragma unroll 1
            for (int q = 0; q < 4; q++) {
              tma_store2(&p.o_st, src + q * 4096, j * 128 + (n - 1) * 64, rb * 128 + q * 32);
              if (n == 1) store_pause(true);
            }
          } else if (n >= 4 && n < 8) {
#pragma unroll 1
            for (int q = 0; q < 4; q++) {
              tma_store2(&p.act_st, src + q * 4096, j * 448 + (n - 4) * 128 + ch * 64, rb * 128 + q * 32);
              store_pause(true);
            }
          } else {
            tma_store2(n == 0 ? &p.h : &p.h2, src, j * 128 + ch * 64, rb * 128);
            asm volatile("cp.async.bulk.commit_group;" ::: "memory");
            if (ch == 1) {
              asm volatile("cp.async.bulk.wait_group 1;" ::: "memory");
              __syncwarp();
              cnt_signal(cnt + (n == 0 ? C_HA : C_H2A));
            }
          }
          if (n >= 4 && n < 7 && ch == 0) arrive_elect(bars + 8 * B_STGE);
        }
        asm volatile("cp.async.bulk.commit_group;" ::: "memory");
        asm volatile("cp.async.bulk.wait_group 0;" ::: "memory");
        __syncwarp();
        cnt_signal(cnt + n);
        PROF_AT(lane == 0, n == 0 ? 33 : 23 + n);
        if (n == 0) {
#pragma unroll 1
          for (int t = 0; t < 36; t++) {
            ll_store(t < 32 ? p.halo + cta * 1024 + t * 32 + lane : p.stats2 + cta * 128 + (t - 32) * 32 + lane, 0u, 0u, 0u);
            __nanosleep(40);
          }
          __syncwarp();
        }
        if (!(n >= 4 && n < 7)) arrive_elect(bars + 8 * B_STGE);
        if (nch == 2) { arrive_elect(bars + 8 * (B_STGE + 1)); ph1 ^= 1; }
      }
      mbar_wait_watchdog(bars + 8 * B_STGF, 0);
      PROF_AT(lane == 0, 31);
    } else {
      if (lane < 4) ll_store(p.modll + cta * 4 + lane, 0u, 0u, 0u);
      bar_sync(1, 288);
      {
        const uint4 t4 = lds128(sm + RED_OFF + lane * 16);
        float a[4] = {__uint_as_float(t4.x), __uint_as_float(t4.y), __uint_as_float(t4.z), __uint_as_float(t4.w)};
#pragma unroll
        for (int o = 4; o < 32; o <<= 1)
#pragma unroll
          for (int q = 0; q < 4; q++) a[q] += __shfl_xor_sync(~0u, a[q], o);
        if (lane < 4) ll_store(p.modll + cta * 4 + lane, pack2(a[0], a[1]), pack2(a[2], a[3]), tag);
        PROF_AT(lane == 0, 1);
        uint32_t m[4];
        const uint4* mp = p.modll + j * 32 + lane;
        ll_poll<2>([&](int i) { return mp + i * 256; }, tag, m);
        const uint32_t c0 = pack2(1.0f + bf_lo(m[2]), 1.0f + bf_hi(m[2])), c1 = pack2(1.0f + bf_lo(m[3]), 1.0f + bf_hi(m[3]));
        sts128(sm + MODB_OFF + lane * 16, c0, m[0], c1, m[1]);
        __syncwarp();
        arrive_elect(bars + 8 * B_MODA);
      }
#pragma unroll 1
      for (int n = C_H; n <= C_O; n++) {
        cnt_wait_lazy(cnt + n, target);
        arrive_elect(bars + 8 * (B_RDY + n));
      }
      {
        uint32_t m[6];
        const uint4* src = p.modll + 512 + j * 32 + lane;
        ll_poll<3, 500>([&](int i) { return src + i * 256; }, tag, m);
#pragma unroll
        for (int vec = 0; vec < 3; vec++) {
          const float add = vec == 2 ? 1.0f : 0.0f;
          sts128(sm + MODB_OFF + (vec * 128 + lane * 4) * 4, __float_as_uint(bf_round(bf_lo(m[2 * vec]) + add)), __float_as_uint(bf_round(bf_hi(m[2 * vec]) + add)),
                 __float_as_uint(bf_round(bf_lo(m[2 * vec + 1]) + add)), __float_as_uint(bf_round(bf_hi(m[2 * vec + 1]) + add)));
        }
        __syncwarp();
        if (lane == 0) mbar_arrive(bars + 8 * B_MODB);
        PROF_AT(lane == 0, 15);
      }
      __syncwarp();
#pragma unroll 1
      for (int n = C_H2; n < 8; n++) {
        cnt_wait_lazy(cnt + n, target);
        arrive_elect(bars + 8 * (B_RDY + n));
      }
      {
        uint32_t m[2];
        const uint4* src = p.modll + 512 + 768 + j * 32 + lane;
        ll_poll<1>([&](int) { return src; }, tag, m);
        sts128(sm + MODB_OFF + (384 + lane * 4) * 4, m[0] << 16, m[0] & 0xffff0000u, m[1] << 16, m[1] & 0xffff0000u);
        __syncwarp();
        if (lane == 0) mbar_arrive(bars + 8 * (B_MODB + 1));
      }
    }
  } else {
    uint32_t tag;

    {
      const int tid = threadIdx.x - 128, cw = tid >> 7, warp = (tid >> 5) & 3, lane = tid & 31;
      const int l16 = lane & 15, half = lane >> 4, w8 = cw * 4 + warp;
      const uint32_t cbuf = sm + 3 * 49152 + w8 * 512;
      if (lane <= 16) cp_async16(cbuf + lane * 16, lane < 16 ? (const void*)(p.c + w8 * 128 + lane * 8) : (const void*)p.epoch);
      asm volatile("cp.async.commit_group;" ::: "memory");
      const uint32_t xbuf = sm + 40960 + (cw * 2 + (l16 >> 3)) * 49152 + (warp * 16 + half) * 128;
      {
        const char* xp = (const char*)p.x + (uint32_t)((rb * 128 + (warp * 16 + half) * 2 + cw) * 2048 + j * 256 + l16 * 16);
#pragma unroll
        for (int i = 0; i < 8; i++) cp_async16(xbuf + i * 256 + (((l16 & 7) ^ ((i * 2 + half) & 7)) << 4), xp + i * 8192);
      }
      asm volatile("cp.async.commit_group;" ::: "memory");
      const uint32_t wbuf = sm + cw * 49152 + warp * 4096;
      {
        const char* wp = (const char*)p.wmod + (uint32_t)(cta * 32 + (lane & 1) * 16 + (w8 * 128 + (lane >> 1)) * 12288);
#pragma unroll
        for (int i = 0; i < 8; i++) cp_async16(wbuf + i * 512 + lane * 16, wp + i * 16 * 12288);
      }
      asm volatile("cp.async.commit_group;" ::: "memory");
      PROF_AT(tid == 0, 32);
      uint4* st1 = p.stats1 + (rb * 8 + j) * 128 + cw * 64 + warp * 16;
      if (lane < 16) ll_store(st1 + lane, 0u, 0u, 0u);
      __syncwarp();
      cluster_arrive_relaxed();
      asm volatile("setmaxnreg.inc.sync.aligned.u32 232;");
      uint32_t sa[4][4];
      {
        asm volatile("cp.async.wait_group 2;" ::: "memory");
        __syncwarp();
        tag = lds32(cbuf + 256) + 1;
        const float2 cv = lds64f(cbuf + lane * 8);
        const uint32_t c0 = __float_as_uint(cv.x), c1 = __float_as_uint(cv.y);
        sts64f(cbuf + lane * 8, __uint_as_float(pack2(silu_f(bf_lo(c0)), silu_f(bf_hi(c0)))), __uint_as_float(pack2(silu_f(bf_lo(c1)), silu_f(bf_hi(c1)))));
        __syncwarp();
#pragma unroll
        for (int q = 0; q < 4; q++) ldmatrix4(sa[q][0], sa[q][1], sa[q][2], sa[q][3], cbuf + q * 64 + (lane >> 3) * 16);
      }
      cluster_wait();
      asm volatile("cp.async.wait_group 1;" ::: "memory");
      __syncwarp();
      uint32_t xl[16], xh[16];
      {
        const int srow = warp * 16 + (lane & 15);
#pragma unroll
        for (int q = 0; q < 8; q++)
          ldmatrix4(xl[2 * q], xh[2 * q], xl[2 * q + 1], xh[2 * q + 1],
                    sm + 40960 + (cw * 2 + (q >> 2)) * 49152 + srow * 128 + (((half + (q & 3) * 2) ^ (srow & 7)) << 4));
      }
      publish_stats(xl, xh, st1, lane, tag);
      PROF_AT(tid == 0, 50);
      asm volatile("cp.async.wait_group 0;" ::: "memory");
      __syncwarp();
      PROF_AT(tid == 0, 51);
      {
        uint32_t b[8][4];
#pragma unroll
        for (int ks = 0; ks < 8; ks++) ldmatrix4t(b[ks], wbuf + (ks * 16 + (lane & 15)) * 32 + (lane >> 4) * 16);
        float d0[4] = {0.f, 0.f, 0.f, 0.f}, d1[4] = {0.f, 0.f, 0.f, 0.f}, d2[4] = {0.f, 0.f, 0.f, 0.f}, d3[4] = {0.f, 0.f, 0.f, 0.f};
#pragma unroll
        for (int q = 0; q < 4; q++) {
          mma16816(d0, sa[q][0], sa[q][0], sa[q][1], sa[q][1], b[2 * q][0], b[2 * q][1]);
          mma16816(d1, sa[q][0], sa[q][0], sa[q][1], sa[q][1], b[2 * q][2], b[2 * q][3]);
          mma16816(d2, sa[q][2], sa[q][2], sa[q][3], sa[q][3], b[2 * q + 1][0], b[2 * q + 1][1]);
          mma16816(d3, sa[q][2], sa[q][2], sa[q][3], sa[q][3], b[2 * q + 1][2], b[2 * q + 1][3]);
        }
        d0[0] += d2[0]; d0[1] += d2[1]; d1[0] += d3[0]; d1[1] += d3[1];
        if (lane < 4) {
          sts64f(sm + RED_OFF + (w8 * 16 + lane * 2) * 4, d0[0], d0[1]);
          sts64f(sm + RED_OFF + (w8 * 16 + 8 + lane * 2) * 4, d1[0], d1[1]);
        }
        asm volatile("bar.arrive 1, 288;" ::: "memory");
      }
      {
        const int r = lane >> 2, c = lane & 3;
        uint32_t st[8];
        const uint4* sp = p.stats1 + rb * 1024 + half * 512 + cw * 64 + warp * 16 + l16;
        ll_poll<4>([&](int i) { return sp + i * 128; }, tag, st);
        float mu, rstd;
        row_stats(st, mu, rstd);
        mu *= -rstd;
        const float n0 = __shfl_sync(~0u, mu, r), r0 = __shfl_sync(~0u, rstd, r), n1 = __shfl_sync(~0u, mu, r + 8), r1 = __shfl_sync(~0u, rstd, r + 8);
#pragma unroll
        for (int n = 0; n < 16; n++) {
          xl[n] = pack2(bf_lo(xl[n]) * r0 + n0, bf_hi(xl[n]) * r0 + n0);
          xh[n] = pack2(bf_lo(xh[n]) * r1 + n1, bf_hi(xh[n]) * r1 + n1);
        }
        const int srow = warp * 16 + l16;
        const uint32_t slab = stg + cw * 8192 + srow * 128;
#pragma unroll
        for (int q = 0; q < 8; q++)
          stmatrix4(slab + (q >> 2) * 16384 + (((half + (q & 3) * 2) ^ (srow & 7)) << 4), xl[2 * q], xh[2 * q], xl[2 * q + 1], xh[2 * q + 1]);
        PROF_AT(tid == 0, 52);
        mbar_wait(bars + 8 * B_MODA, 0);
        PROF_AT(tid == 0, 2);
#pragma unroll
        for (int q = 0; q < 8; q++) {
          const float2 m0 = lds64f(sm + MODB_OFF + (8 * q + c) * 8), m1 = lds64f(sm + MODB_OFF + (8 * q + 4 + c) * 8);
          const uint32_t c0 = __float_as_uint(m0.x), s0 = __float_as_uint(m0.y), c1 = __float_as_uint(m1.x), s1 = __float_as_uint(m1.y);
          stmatrix4(slab + (q >> 2) * 16384 + (((half + (q & 3) * 2) ^ (srow & 7)) << 4), fma_bf2(xl[2 * q], c0, s0), fma_bf2(xh[2 * q], c0, s0),
                    fma_bf2(xl[2 * q + 1], c1, s1), fma_bf2(xh[2 * q + 1], c1, s1));
          if ((q & 3) == 3) stage_done(bars + 8 * (B_STGF + (q >> 2)), lane);
        }
        wg_bar(cw);
      }
      PROF_AT(tid == 0, 3);
    }

    uint32_t xl[16], xh[16];
    {
      RING_IDS();
      uint32_t prev = 0;
      float acc1[96];
      {
        Ring g{bars + 8 * B_FQ, rbars + 8 * B_EQ, 0, 0u, releaser TR(0)};
        float acc0[96];
#pragma unroll 1
        for (int kb = 0; kb < 2; kb++) kblock<192, 4, 49152>(acc0, g, a_base + STG_OFF + kb * 16384, kb == 0, prev);
#pragma unroll 1
        for (int kb = 0; kb < 2; kb++) kblock<192, 4, 49152>(acc1, g, a_base + STG_OFF + kb * 16384, kb == 0, prev);
#pragma unroll 1
        for (int kb = 0; kb < 14; kb++) kblock<192, 4, 49152>(acc0, g, a_base + g.s * 49152, false, prev);
        PROF_AT(tid == 0, 4);
        attention<NPRE0, false>(acc0, p, 0, rb, cta, cw, warp, tag, stg, bars, prev, [&]() { kblock<192, 4, 49152>(acc1, g, a_base + g.s * 49152, false, prev); });
        PROF_AT(tid == 0, 5);
        {
          LANE_IDS();
#pragma unroll
          for (int q = 0; q < 8; q++)
            ldmatrix4(xl[2 * q], xh[2 * q], xl[2 * q + 1], xh[2 * q + 1], sm + 40960 + (cw * 2 + (q >> 2)) * 49152 + srow * 128 + ((sw0 ^ ((q & 3) * 2)) << 4));
#pragma unroll
          for (int q = 0; q < 16; q++) asm volatile("" : "+r"(xl[q]), "+r"(xh[q])::"memory");
        }
#pragma unroll 1
        for (int kb = 5 + NPRE0; kb < 14; kb++) kblock<192, 4, 49152>(acc1, g, a_base + g.s * 49152, false, prev);
        PROF_AT(tid == 0, 6);
      }
      float acc[64];
      Ring g{bars + 8 * B_FW, rbars + 8 * B_EW, 0, 0u, releaser TR(32)};
      attention<NPRE1, true>(acc1, p, 1, rb, cta, cw, warp, tag, stg, bars, prev, [&]() { kblock<128, 6, 32768>(acc, g, a_base + g.s * 32768, g.s == 0, prev); });
      PROF_AT(tid == 0, 7);
      LANE_IDS();
#pragma unroll 1
      for (int kb = 1 + NPRE1; kb < 16; kb++) {
        if (kb == 8) wg_bar(cw);
        kblock<128, 6, 32768>(acc, g, a_base + (kb == 8 ? STG_OFF : g.s * 32768), false, prev);
      }
      mbar_wait(bars + 8 * B_MODB, 0);
      float2 ga[16];
#pragma unroll
      for (int n = 0; n < 16; n++) ga[n] = lds64f(sm + MODB_OFF + (8 * n + 2 * c) * 4);
      tile_end(acc, prev);
      PROF_AT(tid == 0, 8);
      uint4* st2 = p.stats2 + (rb * 8 + j) * 128 + cw * 64 + warp * 16 + r + (c & 1) * 8;
      float sl[2] = {0.f, 0.f}, sh[2] = {0.f, 0.f}, ql[2] = {0.f, 0.f}, qh[2] = {0.f, 0.f};
#pragma unroll
      for (int n = 0; n < 16; n++) {
        acc[4 * n] = ga[n].x * acc[4 * n] + bf_lo(xl[n]); acc[4 * n + 1] = ga[n].y * acc[4 * n + 1] + bf_hi(xl[n]);
        acc[4 * n + 2] = ga[n].x * acc[4 * n + 2] + bf_lo(xh[n]); acc[4 * n + 3] = ga[n].y * acc[4 * n + 3] + bf_hi(xh[n]);
        sl[0] += acc[4 * n]; sl[1] += acc[4 * n + 1]; sh[0] += acc[4 * n + 2]; sh[1] += acc[4 * n + 3];
        ql[0] += acc[4 * n] * acc[4 * n]; ql[1] += acc[4 * n + 1] * acc[4 * n + 1];
        qh[0] += acc[4 * n + 2] * acc[4 * n + 2]; qh[1] += acc[4 * n + 3] * acc[4 * n + 3];
      }
      {
        const float ml = (sl[0] + sl[1]) * (1.0f / 32), mh = (sh[0] + sh[1]) * (1.0f / 32);
        const float vl = (ql[0] + ql[1]) - 32.0f * ml * ml, vh = (qh[0] + qh[1]) - 32.0f * mh * mh;
        const bool b0 = c & 1;
        float m = b0 ? mh : ml, q = b0 ? vh : vl;
        chan(m, q, __shfl_xor_sync(~0u, b0 ? ml : mh, 1), __shfl_xor_sync(~0u, b0 ? vl : vh, 1), 32.f);
        chan(m, q, __shfl_xor_sync(~0u, m, 2), __shfl_xor_sync(~0u, q, 2), 64.f);
        if (c < 2) ll_store(st2, __float_as_uint(m), __float_as_uint(fmaxf(q, 0.f)), tag);
        __syncwarp();
      }
      PROF_AT(tid == 0, 48);
      float2 sb[16], cb[16];
#pragma unroll
      for (int n = 0; n < 16; n++) {
        sb[n] = lds64f(sm + MODB_OFF + (128 + 8 * n + 2 * c) * 4);
        cb[n] = lds64f(sm + MODB_OFF + (256 + 8 * n + 2 * c) * 4);
        xl[n] = pack2(acc[4 * n], acc[4 * n + 1]);
        xh[n] = pack2(acc[4 * n + 2], acc[4 * n + 3]);
      }
      mbar_wait(bars + 8 * B_STGE, 0);
      PROF_AT(tid == 0, 49);
      float nb[2], rstd[2];
      {
        uint32_t st[8];
        const uint4* sp = p.stats2 + (rb * 8 + (lane >> 4) * 4) * 128 + cw * 64 + warp * 16 + (lane & 15);
        ll_poll<4>([&](int i) { return sp + i * 128; }, tag, st);
        float mu, rs;
        row_stats(st, mu, rs);
        mu *= -rs;
        nb[0] = __shfl_sync(~0u, mu, r); rstd[0] = __shfl_sync(~0u, rs, r);
        nb[1] = __shfl_sync(~0u, mu, r + 8); rstd[1] = __shfl_sync(~0u, rs, r + 8);
      }
      PROF_AT(tid == 0, 9);
#pragma unroll
      for (int ch = 0; ch < 2; ch++) {
        uint32_t lo[8], hi[8];
#pragma unroll
        for (int t = 0; t < 8; t++) {
          const int n = ch * 8 + t;
          lo[t] = pack2((acc[4 * n] * rstd[0] + nb[0]) * cb[n].x + sb[n].x, (acc[4 * n + 1] * rstd[0] + nb[0]) * cb[n].y + sb[n].y);
          hi[t] = pack2((acc[4 * n + 2] * rstd[1] + nb[1]) * cb[n].x + sb[n].x, (acc[4 * n + 3] * rstd[1] + nb[1]) * cb[n].y + sb[n].y);
        }
        stage_slab(stg + ch * 16384 + cw * 8192, warp, lane, lo, hi);
        stage_done(bars + 8 * (B_STGF + ch), lane);
      }
      wg_bar(cw);
      PROF_AT(tid == 0, 10);
    }

    uint32_t pg[32], pu[32];
    {
      RING_IDS();
      LANE_IDS();
      Ring g{bars + 8 * B_FG, rbars + 8 * B_EG, 0, 0u, releaser TR(48)};
      float acc[128];
      {
        uint32_t prev = 0;
        uint4* x1p = p.x1 + (size_t)(rb * 128 + (warp * 16 + (lane >> 4)) * 2 + cw) * 128 + j * 16 + (lane & 15);
#pragma unroll 1
        for (int kb = 0; kb < 16; kb++) {
          kblock<256, 4, 49152>(acc, g, a_base + (kb < 2 ? STG_OFF + kb * 16384 : g.s * 49152), kb == 0, prev);
          if (kb == 5) {
#pragma unroll
            for (int q = 0; q < 4; q++) x1p[q * 512] = make_uint4(xl[4 * q], xl[4 * q + 1], xl[4 * q + 2], xl[4 * q + 3]);
          }
          if (kb == 8) {
#pragma unroll
            for (int q = 0; q < 4; q++) x1p[(4 + q) * 512] = make_uint4(xh[4 * q], xh[4 * q + 1], xh[4 * q + 2], xh[4 * q + 3]);
          }
        }
        tile_end(acc, prev);
      }
      PROF_AT(tid == 0, 36);
#pragma unroll 1
      for (int t = 1; t < 3; t++) {
#pragma unroll
        for (int q = 0; q < 32; q++) {
          pg[q] = pack2(acc[2 * q], acc[2 * q + 1]);
          pu[q] = pack2(acc[64 + 2 * q], acc[64 + 2 * q + 1]);
        }
        uint32_t prev = 0;
#pragma unroll 1
        for (int blk = 0; blk < 4; blk++) {
          g.s = 0;
#pragma unroll
          for (int i = 0; i < 4; i++) {
            kblock<256, 4, 49152>(acc, g, a_base + i * 49152, blk == 0 && i == 0, prev);
            if ((blk & 1) == 0 && i == 0) mbar_wait(bars + 8 * (B_STGE + (blk >> 1)), t & 1);
            stmatrix2(slab + (blk >> 1) * 16384 + (((srow & 7) ^ ((blk & 1) * 4 + i)) << 4), swiglu2(pg[2 * i], pu[2 * i]), swiglu2(pg[2 * i + 1], pu[2 * i + 1]));
          }
#pragma unroll
          for (int q = 0; q < 24; q++) { pg[q] = pg[q + 8]; pu[q] = pu[q + 8]; }
          if (blk & 1) stage_done(bars + 8 * (B_STGF + (blk >> 1)), lane);
        }
        tile_end(acc, prev);
        PROF_AT(tid == 0, 36 + t);
      }
#pragma unroll
      for (int q = 0; q < 32; q++) {
        pg[q] = pack2(acc[2 * q], acc[2 * q + 1]);
        pu[q] = pack2(acc[64 + 2 * q], acc[64 + 2 * q + 1]);
      }
      PROF_AT(tid == 0, 11);
    }

    {
      RING_IDS();
      LANE_IDS();
      Ring g{bars + 8 * B_FD, rbars + 8 * B_ED, 0, 0u, releaser TR(96)};
      float acc[64];
      uint32_t prev = 0;
#pragma unroll 1
      for (int blk = 0; blk < 6; blk++) {
#pragma unroll
        for (int i = 0; i < 8; i++) {
          kblock<128, 6, 32768>(acc, g, a_base + g.s * 32768, (blk & ~2) == 0 && i == 0, prev);
          if ((blk & 1) == 0 && i == 0) mbar_wait(bars + 8 * (B_STGE + ((blk >> 1) & 1)), blk < 4);
          stmatrix1(slab + ((blk >> 1) & 1) * 16384 + (i & 1) * 1024 + (((srow & 7) ^ ((blk & 1) * 4 + (i >> 1))) << 4), swiglu2(pg[i], pu[i]));
        }
#pragma unroll
        for (int q = 0; q < 24; q++) { pg[q] = pg[q + 8]; pu[q] = pu[q + 8]; }
        if (blk & 1) stage_done(bars + 8 * (B_STGF + ((blk >> 1) & 1)), lane);
        if (blk == 1) {
          tile_end(acc, prev);
          PROF_AT(tid == 0, 39);
#pragma unroll
          for (int q = 0; q < 16; q++) {
            pg[16 + q] = pack2(acc[2 * q], acc[2 * q + 1]);
            pu[16 + q] = pack2(acc[32 + 2 * q], acc[32 + 2 * q + 1]);
          }
          PROF_AT(tid == 0, 12);
        }
      }
      uint4 x1[8];
      const int fl = fresh_tid() & 31;
      const uint4* x1p = p.x1 + (size_t)(rb * 128 + (warp * 16 + (fl >> 4)) * 2 + cw) * 128 + j * 16 + (fl & 15);
#pragma unroll
      for (int q = 0; q < 2; q++) {
#pragma unroll
        for (int e = 0; e < 4; e++) x1[4 * q + e] = ll_peek(x1p + (4 * q + e) * 512);
#pragma unroll 1
        for (int kb = 0; kb < 12; kb++) {
          if (q == 1 && kb == 6) g.releaser = false;
          kblock<128, 6, 32768>(acc, g, a_base + g.s * 32768, false, prev);
        }
      }
      mbar_wait(bars + 8 * (B_MODB + 1), 0);
      mbar_wait(bars + 8 * B_STGE, 1);
      mbar_wait(bars + 8 * (B_STGE + 1), 0);
      float2 gbv[16];
#pragma unroll
      for (int n = 0; n < 16; n++) gbv[n] = lds64f(sm + MODB_OFF + (384 + 8 * n + 2 * c) * 4);
      tile_end(acc, prev);
      PROF_AT(tid == 0, 13);
#pragma unroll
      for (int ch = 0; ch < 2; ch++) {
        uint32_t lo[8], hi[8];
#pragma unroll
        for (int t = 0; t < 8; t++) {
          const int n = ch * 8 + t;
          const float2 gb = gbv[n];
          const uint4 a = x1[n >> 2], b = x1[4 + (n >> 2)];
          const uint32_t xl = (n & 3) == 0 ? a.x : (n & 3) == 1 ? a.y : (n & 3) == 2 ? a.z : a.w;
          const uint32_t xh = (n & 3) == 0 ? b.x : (n & 3) == 1 ? b.y : (n & 3) == 2 ? b.z : b.w;
          lo[t] = pack2(bf_lo(xl) + gb.x * acc[4 * n], bf_hi(xl) + gb.y * acc[4 * n + 1]);
          hi[t] = pack2(bf_lo(xh) + gb.x * acc[4 * n + 2], bf_hi(xh) + gb.y * acc[4 * n + 3]);
        }
        stage_slab(stg + ch * 16384 + cw * 8192, warp, lane, lo, hi);
        asm volatile("fence.proxy.async.shared::cta;" ::: "memory");
        __syncwarp();
        tma_store3(&p.out, stg + ch * 16384 + cw * 8192 + warp * 2048, j * 128 + ch * 64, rb * 64 + warp * 16, cw);
      }
      asm volatile("cp.async.bulk.commit_group;" ::: "memory");
      if (lane == 0) mbar_arrive(bars + 8 * B_STGF);
      asm volatile("cp.async.bulk.wait_group.read 0;" ::: "memory");
      PROF_AT(tid == 0, 14);
    }
    if (blockIdx.x == 0 && threadIdx.x == 128) asm volatile("st.relaxed.gpu.global.u32 [%0], %1;" ::"l"(p.epoch), "r"(tag) : "memory");
  }
}

typedef CUresult (*EncodeFn)(CUtensorMap*, CUtensorMapDataType, cuuint32_t, void*, const cuuint64_t*, const cuuint64_t*,
                             const cuuint32_t*, const cuuint32_t*, CUtensorMapInterleave, CUtensorMapSwizzle,
                             CUtensorMapL2promotion, CUtensorMapFloatOOBfill);

void encode2d(EncodeFn fn, CUtensorMap* m, const void* ptr, uint64_t cols, uint64_t rows, uint32_t box_rows) {
  cuuint64_t dims[2] = {cols, rows};
  cuuint64_t strides[1] = {cols * 2};
  cuuint32_t box[2] = {64, box_rows};
  cuuint32_t es[2] = {1, 1};
  fn(m, CU_TENSOR_MAP_DATA_TYPE_BFLOAT16, 2, (void*)ptr, dims, strides, box, es, CU_TENSOR_MAP_INTERLEAVE_NONE,
     CU_TENSOR_MAP_SWIZZLE_128B, CU_TENSOR_MAP_L2_PROMOTION_L2_128B, CU_TENSOR_MAP_FLOAT_OOB_FILL_NONE);
}

}

extern "C" void kernel_launch(void* const* d_in, const int* in_sizes, int n_in, void* d_out, int out_size) {
  (void)in_sizes; (void)n_in; (void)out_size;
  void* fp = nullptr;
  cudaDriverEntryPointQueryResult qr;
  cudaGetDriverEntryPoint("cuTensorMapEncodeTiled", &fp, cudaEnableDefault, &qr);
  EncodeFn fn = (EncodeFn)fp;
  void *ph, *po, *ph2, *pact;
  cudaGetSymbolAddress(&ph, g_h);
  cudaGetSymbolAddress(&po, g_o);
  ph2 = ph;
  cudaGetSymbolAddress(&pact, g_act);
  Params p;
  encode2d(fn, &p.h, ph, DM, SEQ, 128);
  encode2d(fn, &p.o_ld, po, DM, SEQ, 128);
  encode2d(fn, &p.h2, ph2, DM, SEQ, 128);
  encode2d(fn, &p.act, pact, FF, SEQ, 128);
  encode2d(fn, &p.act_st, pact, FF, SEQ, 32);
  encode2d(fn, &p.wm, d_in[8], 6 * DM, DM, 64);
  encode2d(fn, &p.o_st, po, DM, SEQ, 32);
  encode2d(fn, &p.wqkv, d_in[1], 3 * DM, DM, 64);
  encode2d(fn, &p.wqkv32, d_in[1], 3 * DM, DM, 32);
  encode2d(fn, &p.wo, d_in[2], DM, DM, 64);
  encode2d(fn, &p.wg, d_in[4], FF, DM, 64);
  encode2d(fn, &p.wu, d_in[5], FF, DM, 64);
  encode2d(fn, &p.wd, d_in[6], DM, FF, 64);
  {
    cuuint64_t dims[3] = {DM, SEQ / 2, 2};
    cuuint64_t strides[2] = {DM * 4, DM * 2};
    cuuint32_t box[3] = {64, 16, 1};
    cuuint32_t es[3] = {1, 1, 1};
    fn(&p.out, CU_TENSOR_MAP_DATA_TYPE_BFLOAT16, 3, d_out, dims, strides, box, es, CU_TENSOR_MAP_INTERLEAVE_NONE,
       CU_TENSOR_MAP_SWIZZLE_128B, CU_TENSOR_MAP_L2_PROMOTION_L2_128B, CU_TENSOR_MAP_FLOAT_OOB_FILL_NONE);
  }
  p.x = (const bf16*)d_in[0];
  p.c = (const bf16*)d_in[7];
  p.wmod = (const bf16*)d_in[8];
  for (int cl = 0; cl < 64; cl++) {
    const int grp = cl < 4 ? 0 : (cl < 36 ? (cl - 4) & 7 : 1 + (cl - 36) % 7);
    const int j = cl < 4 ? 4 + cl : (cl < 36 ? (cl - 4) >> 3 : 4 + (cl - 36) / 7);
    p.slot[cl] = (uint8_t)(grp * 8 + j);
  }
  void* q;
  p.x1 = (uint4*)d_out;
  cudaGetSymbolAddress(&q, g_modll); p.modll = (uint4*)q;
  cudaGetSymbolAddress(&q, g_halo); p.halo = (uint4*)q;
  cudaGetSymbolAddress(&q, g_stats); p.stats1 = (uint4*)q; p.stats2 = p.stats1 + SEQ * 8;
  cudaGetSymbolAddress(&q, g_cnt); p.cnt = (unsigned*)q;
  cudaGetSymbolAddress(&q, g_epoch); p.epoch = (unsigned*)q;

  cudaFuncSetAttribute(fused_kernel, cudaFuncAttributeMaxDynamicSharedMemorySize, SMEM_BYTES);
  cudaLaunchConfig_t cfg = {};
  cfg.gridDim = dim3(NCTA + 4);
  cfg.blockDim = dim3(384);
  cfg.dynamicSmemBytes = SMEM_BYTES;
  cfg.stream = cudaStreamPerThread;
  cudaLaunchAttribute at[1];
  at[0].id = cudaLaunchAttributeClusterDimension;
  at[0].val.clusterDim.x = 2; at[0].val.clusterDim.y = 1; at[0].val.clusterDim.z = 1;
  cfg.attrs = at;
  cfg.numAttrs = 1;
  cudaLaunchKernelEx(&cfg, fused_kernel, p);
}
```

```cpp
#include <cuda_runtime.h>
#include <cuda_bf16.h>
#include <cuda.h>
#include <stdint.h>

typedef __nv_bfloat16 bf16;

#define PAUSE 200
#define WMDELAY 2000
#define BDELAY 1500
#define NPRE0 3
#define NPRE1 1
#define ALIAS 1

#define PFW 8000
#define PFP 0

#define OSIG 3

__device__ __forceinline__ void wgmma_ss_n128(float (&d)[64], uint32_t da, uint32_t db, int scale_d) {
  asm volatile("{\n.reg .pred p;\n.reg .b64 da, db;\nsetp.ne.b32 p, %66, 0;\n"
    "mov.b64 da, {%64, 0x40000040};\nmov.b64 db, {%65, 0x40000040};\n"
    "wgmma.mma_async.sync.aligned.m64n128k16.f32.bf16.bf16 "
    "{%0, %1, %2, %3, %4, %5, %6, %7, %8, %9, %10, %11, %12, %13, %14, %15, "
    "%16, %17, %18, %19, %20, %21, %22, %23, %24, %25, %26, %27, %28, %29, %30, %31, "
    "%32, %33, %34, %35, %36, %37, %38, %39, %40, %41, %42, %43, %44, %45, %46, %47, "
    "%48, %49, %50, %51, %52, %53, %54, %55, %56, %57, %58, %59, %60, %61, %62, %63}, "
    "da, db, p, 1, 1, 0, 1;\n}\n"
    : "+f"(d[0]), "+f"(d[1]), "+f"(d[2]), "+f"(d[3]), "+f"(d[4]), "+f"(d[5]), "+f"(d[6]), "+f"(d[7]),
      "+f"(d[8]), "+f"(d[9]), "+f"(d[10]), "+f"(d[11]), "+f"(d[12]), "+f"(d[13]), "+f"(d[14]), "+f"(d[15]),
      "+f"(d[16]), "+f"(d[17]), "+f"(d[18]), "+f"(d[19]), "+f"(d[20]), "+f"(d[21]), "+f"(d[22]), "+f"(d[23]),
      "+f"(d[24]), "+f"(d[25]), "+f"(d[26]), "+f"(d[27]), "+f"(d[28]), "+f"(d[29]), "+f"(d[30]), "+f"(d[31]),
      "+f"(d[32]), "+f"(d[33]), "+f"(d[34]), "+f"(d[35]), "+f"(d[36]), "+f"(d[37]), "+f"(d[38]), "+f"(d[39]),
      "+f"(d[40]), "+f"(d[41]), "+f"(d[42]), "+f"(d[43]), "+f"(d[44]), "+f"(d[45]), "+f"(d[46]), "+f"(d[47]),
      "+f"(d[48]), "+f"(d[49]), "+f"(d[50]), "+f"(d[51]), "+f"(d[52]), "+f"(d[53]), "+f"(d[54]), "+f"(d[55]),
      "+f"(d[56]), "+f"(d[57]), "+f"(d[58]), "+f"(d[59]), "+f"(d[60]), "+f"(d[61]), "+f"(d[62]), "+f"(d[63])
    : "r"(da), "r"(db), "r"(scale_d));
}

__device__ __forceinline__ void wgmma_ss_n192(float (&d)[96], uint32_t da, uint32_t db, int scale_d) {
  asm volatile("{\n.reg .pred p;\n.reg .b64 da, db;\nsetp.ne.b32 p, %98, 0;\n"
    "mov.b64 da, {%96, 0x40000040};\nmov.b64 db, {%97, 0x40000040};\n"
    "wgmma.mma_async.sync.aligned.m64n192k16.f32.bf16.bf16 "
    "{%0, %1, %2, %3, %4, %5, %6, %7, %8, %9, %10, %11, %12, %13, %14, %15, "
    "%16, %17, %18, %19, %20, %21, %22, %23, %24, %25, %26, %27, %28, %29, %30, %31, "
    "%32, %33, %34, %35, %36, %37, %38, %39, %40, %41, %42, %43, %44, %45, %46, %47, "
    "%48, %49, %50, %51, %52, %53, %54, %55, %56, %57, %58, %59, %60, %61, %62, %63, "
    "%64, %65, %66, %67, %68, %69, %70, %71, %72, %73, %74, %75, %76, %77, %78, %79, "
    "%80, %81, %82, %83, %84, %85, %86, %87, %88, %89, %90, %91, %92, %93, %94, %95}, "
    "da, db, p, 1, 1, 0, 1;\n}\n"
    : "+f"(d[0]), "+f"(d[1]), "+f"(d[2]), "+f"(d[3]), "+f"(d[4]), "+f"(d[5]), "+f"(d[6]), "+f"(d[7]),
      "+f"(d[8]), "+f"(d[9]), "+f"(d[10]), "+f"(d[11]), "+f"(d[12]), "+f"(d[13]), "+f"(d[14]), "+f"(d[15]),
      "+f"(d[16]), "+f"(d[17]), "+f"(d[18]), "+f"(d[19]), "+f"(d[20]), "+f"(d[21]), "+f"(d[22]), "+f"(d[23]),
      "+f"(d[24]), "+f"(d[25]), "+f"(d[26]), "+f"(d[27]), "+f"(d[28]), "+f"(d[29]), "+f"(d[30]), "+f"(d[31]),
      "+f"(d[32]), "+f"(d[33]), "+f"(d[34]), "+f"(d[35]), "+f"(d[36]), "+f"(d[37]), "+f"(d[38]), "+f"(d[39]),
      "+f"(d[40]), "+f"(d[41]), "+f"(d[42]), "+f"(d[43]), "+f"(d[44]), "+f"(d[45]), "+f"(d[46]), "+f"(d[47]),
      "+f"(d[48]), "+f"(d[49]), "+f"(d[50]), "+f"(d[51]), "+f"(d[52]), "+f"(d[53]), "+f"(d[54]), "+f"(d[55]),
      "+f"(d[56]), "+f"(d[57]), "+f"(d[58]), "+f"(d[59]), "+f"(d[60]), "+f"(d[61]), "+f"(d[62]), "+f"(d[63]),
      "+f"(d[64]), "+f"(d[65]), "+f"(d[66]), "+f"(d[67]), "+f"(d[68]), "+f"(d[69]), "+f"(d[70]), "+f"(d[71]),
      "+f"(d[72]), "+f"(d[73]), "+f"(d[74]), "+f"(d[75]), "+f"(d[76]), "+f"(d[77]), "+f"(d[78]), "+f"(d[79]),
      "+f"(d[80]), "+f"(d[81]), "+f"(d[82]), "+f"(d[83]), "+f"(d[84]), "+f"(d[85]), "+f"(d[86]), "+f"(d[87]),
      "+f"(d[88]), "+f"(d[89]), "+f"(d[90]), "+f"(d[91]), "+f"(d[92]), "+f"(d[93]), "+f"(d[94]), "+f"(d[95])
    : "r"(da), "r"(db), "r"(scale_d));
}

__device__ __forceinline__ void wgmma_ss_n256(float (&d)[128], uint32_t da, uint32_t db, int scale_d) {
  asm volatile("{\n.reg .pred p;\n.reg .b64 da, db;\nsetp.ne.b32 p, %130, 0;\n"
    "mov.b64 da, {%128, 0x40000040};\nmov.b64 db, {%129, 0x40000040};\n"
    "wgmma.mma_async.sync.aligned.m64n256k16.f32.bf16.bf16 "
    "{%0, %1, %2, %3, %4, %5, %6, %7, %8, %9, %10, %11, %12, %13, %14, %15, "
    "%16, %17, %18, %19, %20, %21, %22, %23, %24, %25, %26, %27, %28, %29, %30, %31, "
    "%32, %33, %34, %35, %36, %37, %38, %39, %40, %41, %42, %43, %44, %45, %46, %47, "
    "%48, %49, %50, %51, %52, %53, %54, %55, %56, %57, %58, %59, %60, %61, %62, %63, "
    "%64, %65, %66, %67, %68, %69, %70, %71, %72, %73, %74, %75, %76, %77, %78, %79, "
    "%80, %81, %82, %83, %84, %85, %86, %87, %88, %89, %90, %91, %92, %93, %94, %95, "
    "%96, %97, %98, %99, %100, %101, %102, %103, %104, %105, %106, %107, %108, %109, %110, %111, "
    "%112, %113, %114, %115, %116, %117, %118, %119, %120, %121, %122, %123, %124, %125, %126, %127}, "
    "da, db, p, 1, 1, 0, 1;\n}\n"
    : "+f"(d[0]), "+f"(d[1]), "+f"(d[2]), "+f"(d[3]), "+f"(d[4]), "+f"(d[5]), "+f"(d[6]), "+f"(d[7]),
      "+f"(d[8]), "+f"(d[9]), "+f"(d[10]), "+f"(d[11]), "+f"(d[12]), "+f"(d[13]), "+f"(d[14]), "+f"(d[15]),
      "+f"(d[16]), "+f"(d[17]), "+f"(d[18]), "+f"(d[19]), "+f"(d[20]), "+f"(d[21]), "+f"(d[22]), "+f"(d[23]),
      "+f"(d[24]), "+f"(d[25]), "+f"(d[26]), "+f"(d[27]), "+f"(d[28]), "+f"(d[29]), "+f"(d[30]), "+f"(d[31]),
      "+f"(d[32]), "+f"(d[33]), "+f"(d[34]), "+f"(d[35]), "+f"(d[36]), "+f"(d[37]), "+f"(d[38]), "+f"(d[39]),
      "+f"(d[40]), "+f"(d[41]), "+f"(d[42]), "+f"(d[43]), "+f"(d[44]), "+f"(d[45]), "+f"(d[46]), "+f"(d[47]),
      "+f"(d[48]), "+f"(d[49]), "+f"(d[50]), "+f"(d[51]), "+f"(d[52]), "+f"(d[53]), "+f"(d[54]), "+f"(d[55]),
      "+f"(d[56]), "+f"(d[57]), "+f"(d[58]), "+f"(d[59]), "+f"(d[60]), "+f"(d[61]), "+f"(d[62]), "+f"(d[63]),
      "+f"(d[64]), "+f"(d[65]), "+f"(d[66]), "+f"(d[67]), "+f"(d[68]), "+f"(d[69]), "+f"(d[70]), "+f"(d[71]),
      "+f"(d[72]), "+f"(d[73]), "+f"(d[74]), "+f"(d[75]), "+f"(d[76]), "+f"(d[77]), "+f"(d[78]), "+f"(d[79]),
      "+f"(d[80]), "+f"(d[81]), "+f"(d[82]), "+f"(d[83]), "+f"(d[84]), "+f"(d[85]), "+f"(d[86]), "+f"(d[87]),
      "+f"(d[88]), "+f"(d[89]), "+f"(d[90]), "+f"(d[91]), "+f"(d[92]), "+f"(d[93]), "+f"(d[94]), "+f"(d[95]),
      "+f"(d[96]), "+f"(d[97]), "+f"(d[98]), "+f"(d[99]), "+f"(d[100]), "+f"(d[101]), "+f"(d[102]), "+f"(d[103]),
      "+f"(d[104]), "+f"(d[105]), "+f"(d[106]), "+f"(d[107]), "+f"(d[108]), "+f"(d[109]), "+f"(d[110]), "+f"(d[111]),
      "+f"(d[112]), "+f"(d[113]), "+f"(d[114]), "+f"(d[115]), "+f"(d[116]), "+f"(d[117]), "+f"(d[118]), "+f"(d[119]),
      "+f"(d[120]), "+f"(d[121]), "+f"(d[122]), "+f"(d[123]), "+f"(d[124]), "+f"(d[125]), "+f"(d[126]), "+f"(d[127])
    : "r"(da), "r"(db), "r"(scale_d));
}

namespace {

constexpr int SEQ = 2048, DM = 1024, FF = 3584;
constexpr int NCTA = 128;

constexpr uint32_t STG_OFF = 196608;
constexpr uint32_t MISC_OFF = STG_OFF + 32768;
constexpr uint32_t SMEM_BYTES = MISC_OFF + 3072;
constexpr uint32_t RED_OFF = 2 * 49152;
constexpr uint32_t MODB_OFF = MISC_OFF + 512;

enum { B_FQ = 0, B_EQ = 4, B_FW = 8, B_EW = 14, B_FG = 20, B_EG = 24, B_FD = 28, B_ED = 34,
       B_STGF = 40, B_MODB = 42, B_MODA = 45, B_RDY = 48, B_STGE = 56, B_COUNT = 58 };
enum { C_H = 0, C_O = 1, C_H2 = 3, C_ACT = 4, C_HA = 8, C_H2A = 9 };

struct Params {
  CUtensorMap h, o_ld, o_st, h2, act, out, wqkv, wqkv32, wo, wg, wu, wd, act_st, h2_st, wm;
  const bf16* x;
  const bf16* c;
  const bf16* wmod;
  uint4* x1;
  uint4* modll;
  uint4* halo;
  uint4* stats1;
  uint4* stats2;
  unsigned* cnt;
  unsigned* epoch;
  uint8_t slot[64];
};

__device__ __align__(1024) bf16 g_h[SEQ * DM];
__device__ __align__(1024) bf16 g_o[SEQ * DM];
__device__ __align__(1024) bf16 g_act[SEQ * FF];
__device__ __align__(1024) uint4 g_modll[3072 / 2];
__device__ __align__(1024) uint4 g_halo[16 * 8 * 2 * 2 * 8 * 32];
__device__ __align__(1024) uint4 g_stats[2 * SEQ * 8];
__device__ __align__(1024) unsigned g_cnt[16 * 32];
__device__ uint4 g_epoch;
#define TR(off)

__device__ __forceinline__ uint32_t smem_u32(const void* p) { return (uint32_t)__cvta_generic_to_shared(p); }
__device__ __forceinline__ void mbar_init(uint32_t bar, uint32_t count) {
  asm volatile("mbarrier.init.shared::cta.b64 [%0], %1;" ::"r"(bar), "r"(count));
}
__device__ __forceinline__ void mbar_arrive(uint32_t bar) {
  asm volatile("mbarrier.arrive.shared::cta.b64 _, [%0];" ::"r"(bar) : "memory");
}
__device__ __forceinline__ void mbar_arrive_cluster(uint32_t cluster_addr) {
  asm volatile("mbarrier.arrive.shared::cluster.b64 _, [%0];" ::"r"(cluster_addr) : "memory");
}
__device__ __forceinline__ uint32_t mapa(uint32_t addr, uint32_t cta) {
  uint32_t r;
  asm volatile("mapa.shared::cluster.u32 %0, %1, %2;" : "=r"(r) : "r"(addr), "r"(cta));
  return r;
}
__device__ __forceinline__ void mbar_wait(uint32_t bar, uint32_t parity) {
  asm volatile(
      "{\n.reg .pred p;\n"
      "WAIT_%=:\n"
      "mbarrier.try_wait.parity.shared::cta.b64 p, [%0], %1;\n"
      "@!p bra WAIT_%=;\n}\n" ::"r"(bar), "r"(parity) : "memory");
}
__device__ __forceinline__ void mbar_wait_watchdog(uint32_t bar, uint32_t parity) {
  asm volatile(
      "{\n.reg .pred p;\n.reg .u64 t0, t1;\nmov.u64 t0, %%globaltimer;\n"
      "WAIT_%=:\n"
      "mbarrier.try_wait.parity.shared::cta.b64 p, [%0], %1;\n"
      "@p bra DONE_%=;\n"
      "mov.u64 t1, %%globaltimer;\n"
      "sub.u64 t1, t1, t0;\n"
      "setp.lt.u64 p, t1, 2000000000;\n"
      "@p bra WAIT_%=;\n"
      "trap;\n"
      "DONE_%=:\n}\n" ::"r"(bar), "r"(parity) : "memory");
}
__device__ __forceinline__ void cnt_wait(const unsigned* p, unsigned target) {
  asm volatile(
      "{\n.reg .pred p;\n.reg .u32 v;\n.reg .s32 d;\n"
      "WAIT_%=:\n"
      "ld.relaxed.gpu.global.u32 v, [%0];\n"
      "sub.s32 d, v, %1;\n"
      "setp.lt.s32 p, d, 0;\n"
      "@p bra WAIT_%=;\n"
      "fence.proxy.async.global;\n"
      "}\n" ::"l"(p), "r"(target) : "memory");
}
__device__ __forceinline__ void cnt_wait_lazy(const unsigned* p, unsigned target) {
  asm volatile(
      "{\n.reg .pred p;\n.reg .u32 v;\n.reg .s32 d;\n"
      "WAIT_%=:\n"
      "nanosleep.u32 400;\n"
      "ld.relaxed.gpu.global.u32 v, [%0];\n"
      "sub.s32 d, v, %1;\n"
      "setp.lt.s32 p, d, 0;\n"
      "@p bra WAIT_%=;\n"
      "fence.proxy.async.global;\n"
      "}\n" ::"l"(p), "r"(target) : "memory");
}
__device__ __forceinline__ void cnt_signal(unsigned* p) {
  asm volatile("{\n.reg .pred p;\nelect.sync _|p, 0xffffffff;\n@p red.relaxed.gpu.global.add.u32 [%0], 1;\n}\n" ::"l"(p) : "memory");
}
__device__ __forceinline__ void ll_store(uint4* p, uint32_t a, uint32_t b, uint32_t tag) {
  asm volatile("st.relaxed.gpu.global.v2.b64 [%0], {%1, %2};" ::"l"(p), "l"((uint64_t)a | ((uint64_t)tag << 32)),
               "l"((uint64_t)b | ((uint64_t)tag << 32)) : "memory");
}
__device__ __forceinline__ uint4 ll_peek(const uint4* p) {
  uint4 v;
  asm volatile("ld.relaxed.gpu.global.v4.u32 {%0, %1, %2, %3}, [%4];" : "=r"(v.x), "=r"(v.y), "=r"(v.z), "=r"(v.w) : "l"(p) : "memory");
  return v;
}
template <int N, int SLEEP = 0, class F>
__device__ __forceinline__ void ll_poll(F addr, uint32_t tag, uint32_t (&out)[2 * N]) {
  for (;;) {
    uint4 v[N];
#pragma unroll
    for (int i = 0; i < N; i++) v[i] = ll_peek(addr(i));
    uint32_t bad = 0;
#pragma unroll
    for (int i = 0; i < N; i++) {
      bad |= (v[i].y ^ tag) | (v[i].w ^ tag);
      out[2 * i] = v[i].x;
      out[2 * i + 1] = v[i].z;
    }
    if (__all_sync(~0u, bad == 0)) break;
    if (SLEEP) __nanosleep(SLEEP);
  }
}
constexpr uint64_t POLICY_EVICT_FIRST = 0x12F0000000000000ull;
__device__ __forceinline__ void expect_tx_elect(uint32_t bar, uint32_t bytes) {
  asm volatile("{\n.reg .pred p;\nelect.sync _|p, 0xffffffff;\n@p mbarrier.arrive.expect_tx.shared::cta.b64 _, [%0], %1;\n}\n" ::"r"(bar), "r"(bytes) : "memory");
}
__device__ __forceinline__ void arrive_elect(uint32_t bar) {
  asm volatile("{\n.reg .pred p;\nelect.sync _|p, 0xffffffff;\n@p mbarrier.arrive.shared::cta.b64 _, [%0];\n}\n" ::"r"(bar) : "memory");
}
__device__ __forceinline__ void tma_load(uint32_t dst, const CUtensorMap* m, uint32_t bar, int c0, int c1) {
  asm volatile("{\n.reg .pred p;\nelect.sync _|p, 0xffffffff;\n"
               "@p cp.async.bulk.tensor.2d.shared::cluster.global.mbarrier::complete_tx::bytes [%0], [%1, {%3, %4}], [%2];\n}\n"
               ::"r"(dst), "l"(m), "r"(bar), "r"(c0), "r"(c1) : "memory");
}
__device__ __forceinline__ void tma_load_mc(uint32_t dst, const CUtensorMap* m, uint32_t bar, int c0, int c1) {
  asm volatile("{\n.reg .pred p;\nelect.sync _|p, 0xffffffff;\n"
               "@p cp.async.bulk.tensor.2d.shared::cluster.global.mbarrier::complete_tx::bytes.multicast::cluster.L2::cache_hint [%0], [%1, {%3, %4}], [%2], %5, %6;\n}\n"
               ::"r"(dst), "l"(m), "r"(bar), "r"(c0), "r"(c1), "h"((uint16_t)3), "l"(POLICY_EVICT_FIRST) : "memory");
}
__device__ __forceinline__ void tma_load_ef(uint32_t dst, const CUtensorMap* m, uint32_t bar, int c0, int c1) {
  asm volatile("{\n.reg .pred p;\nelect.sync _|p, 0xffffffff;\n"
               "@p cp.async.bulk.tensor.2d.shared::cluster.global.mbarrier::complete_tx::bytes.L2::cache_hint [%0], [%1, {%3, %4}], [%2], %5;\n}\n"
               ::"r"(dst), "l"(m), "r"(bar), "r"(c0), "r"(c1), "l"(POLICY_EVICT_FIRST) : "memory");
}
__device__ __forceinline__ void tma_store2(const CUtensorMap* m, uint32_t src, int c0, int c1) {
  asm volatile("{\n.reg .pred p;\nelect.sync _|p, 0xffffffff;\n"
               "@p cp.async.bulk.tensor.2d.global.shared::cta.bulk_group [%0, {%2, %3}], [%1];\n}\n"
               ::"l"(m), "r"(src), "r"(c0), "r"(c1) : "memory");
}
__device__ __forceinline__ void tma_store3(const CUtensorMap* m, uint32_t src, int c0, int c1, int c2) {
  asm volatile("{\n.reg .pred p;\nelect.sync _|p, 0xffffffff;\n"
               "@p cp.async.bulk.tensor.3d.global.shared::cta.bulk_group [%0, {%2, %3, %4}], [%1];\n}\n"
               ::"l"(m), "r"(src), "r"(c0), "r"(c1), "r"(c2) : "memory");
}
__device__ __forceinline__ void store_pause(bool sleep) {
  asm volatile("cp.async.bulk.commit_group;" ::: "memory");
  asm volatile("cp.async.bulk.wait_group.read 0;" ::: "memory");
  if (sleep) __nanosleep(PAUSE);
}
__device__ __forceinline__ void l2_prefetch_tile(const CUtensorMap* m, int c0, int c1) {
  asm volatile("{\n.reg .pred p;\nelect.sync _|p, 0xffffffff;\n@p cp.async.bulk.prefetch.tensor.2d.L2.global [%0, {%1, %2}];\n}\n"
               ::"l"(m), "r"(c0), "r"(c1) : "memory");
}
__device__ __forceinline__ void prefetch_map(const CUtensorMap* m) {
  asm volatile("prefetch.tensormap [%0];" ::"l"(m) : "memory");
}
__device__ __forceinline__ void wg_fence() { asm volatile("wgmma.fence.sync.aligned;" ::: "memory"); }
__device__ __forceinline__ void wg_commit() { asm volatile("wgmma.commit_group.sync.aligned;" ::: "memory"); }
template <int N>
__device__ __forceinline__ void wg_wait() { asm volatile("wgmma.wait_group.sync.aligned %0;" ::"n"(N) : "memory"); }
__device__ __forceinline__ void bar_sync(int id, int n) { asm volatile("bar.sync %0, %1;" ::"r"(id), "r"(n) : "memory"); }
__device__ __forceinline__ void wg_bar(int cw) {
  asm volatile("{\n.reg .pred p;\nsetp.ne.s32 p, %0, 0;\n@p bar.sync 3, 128;\n@!p bar.sync 2, 128;\n}\n" ::"r"(cw) : "memory");
}
__device__ __forceinline__ void cluster_arrive_relaxed() { asm volatile("barrier.cluster.arrive.relaxed.aligned;" ::: "memory"); }
__device__ __forceinline__ void cluster_wait() { asm volatile("barrier.cluster.wait.acquire.aligned;" ::: "memory"); }
__device__ __forceinline__ uint32_t load_epoch(const unsigned* p) {
  uint32_t e;
  asm volatile("ld.relaxed.gpu.global.u32 %0, [%1];" : "=r"(e) : "l"(p) : "memory");
  return e;
}
__device__ __forceinline__ uint32_t pack2(float lo, float hi) {
  uint32_t r;
  asm("cvt.rn.bf16x2.f32 %0, %1, %2;" : "=r"(r) : "f"(hi), "f"(lo));
  return r;
}
__device__ __forceinline__ float bf_lo(uint32_t v) { return __uint_as_float(v << 16); }
__device__ __forceinline__ float bf_hi(uint32_t v) { return __uint_as_float(v & 0xffff0000u); }
__device__ __forceinline__ uint32_t fma_bf2(uint32_t a, uint32_t b, uint32_t c) {
  uint32_t d;
  asm("fma.rn.bf16x2 %0, %1, %2, %3;" : "=r"(d) : "r"(a), "r"(b), "r"(c));
  return d;
}
__device__ __forceinline__ float bf_round(float v) { return __bfloat162float(__float2bfloat16_rn(v)); }
__device__ __forceinline__ float silu_f(float v) { return __fdividef(v, 1.0f + __expf(-v)); }
__device__ __forceinline__ uint4 ldg_nc(const void* p) {
  uint4 v;
  asm volatile("ld.global.nc.L1::no_allocate.v4.u32 {%0, %1, %2, %3}, [%4];" : "=r"(v.x), "=r"(v.y), "=r"(v.z), "=r"(v.w) : "l"(p));
  return v;
}
__device__ __forceinline__ void stmatrix4(uint32_t addr, uint32_t a, uint32_t b, uint32_t c, uint32_t d) {
  asm volatile("stmatrix.sync.aligned.m8n8.x4.shared.b16 [%0], {%1, %2, %3, %4};" ::"r"(addr), "r"(a), "r"(b), "r"(c), "r"(d) : "memory");
}
__device__ __forceinline__ void stmatrix2(uint32_t addr, uint32_t a, uint32_t b) {
  asm volatile("stmatrix.sync.aligned.m8n8.x2.shared.b16 [%0], {%1, %2};" ::"r"(addr), "r"(a), "r"(b) : "memory");
}
__device__ __forceinline__ void stmatrix1(uint32_t addr, uint32_t a) {
  asm volatile("stmatrix.sync.aligned.m8n8.x1.shared.b16 [%0], {%1};" ::"r"(addr), "r"(a) : "memory");
}
__device__ __forceinline__ uint32_t movmatrix(uint32_t a) {
  uint32_t d;
  asm("movmatrix.sync.aligned.m8n8.trans.b16 %0, %1;" : "=r"(d) : "r"(a));
  return d;
}
__device__ __forceinline__ void mma16816(float (&d)[4], uint32_t a0, uint32_t a1, uint32_t a2, uint32_t a3, uint32_t b0, uint32_t b1) {
  asm("mma.sync.aligned.m16n8k16.row.col.f32.bf16.bf16.f32 {%0, %1, %2, %3}, {%4, %5, %6, %7}, {%8, %9}, {%0, %1, %2, %3};"
               : "+f"(d[0]), "+f"(d[1]), "+f"(d[2]), "+f"(d[3]) : "r"(a0), "r"(a1), "r"(a2), "r"(a3), "r"(b0), "r"(b1));
}
__device__ __forceinline__ void mma1688(float (&d)[4], uint32_t a0, uint32_t a1, uint32_t b0) {
  asm("mma.sync.aligned.m16n8k8.row.col.f32.bf16.bf16.f32 {%0, %1, %2, %3}, {%4, %5}, {%6}, {%0, %1, %2, %3};"
               : "+f"(d[0]), "+f"(d[1]), "+f"(d[2]), "+f"(d[3]) : "r"(a0), "r"(a1), "r"(b0));
}
__device__ __forceinline__ void ldmatrix4t(uint32_t (&b)[4], uint32_t addr) {
  asm volatile("ldmatrix.sync.aligned.m8n8.x4.trans.shared.b16 {%0, %1, %2, %3}, [%4];" : "=r"(b[0]), "=r"(b[1]), "=r"(b[2]), "=r"(b[3]) : "r"(addr) : "memory");
}
__device__ __forceinline__ void ldmatrix4(uint32_t& a, uint32_t& b, uint32_t& c, uint32_t& d, uint32_t addr) {
  asm volatile("ldmatrix.sync.aligned.m8n8.x4.shared.b16 {%0, %1, %2, %3}, [%4];" : "=r"(a), "=r"(b), "=r"(c), "=r"(d) : "r"(addr) : "memory");
}
__device__ __forceinline__ void cp_async16(uint32_t dst, const void* src) {
  asm volatile("cp.async.cg.shared.global.L2::cache_hint [%0], [%1], 16, %2;" ::"r"(dst), "l"(src), "l"(POLICY_EVICT_FIRST) : "memory");
}
__device__ __forceinline__ uint32_t lds32(uint32_t addr) {
  uint32_t v;
  asm volatile("ld.shared.u32 %0, [%1];" : "=r"(v) : "r"(addr) : "memory");
  return v;
}
__device__ __forceinline__ void sts64f(uint32_t addr, float a, float b) {
  asm volatile("st.shared.v2.f32 [%0], {%1, %2};" ::"r"(addr), "f"(a), "f"(b) : "memory");
}
constexpr float QK_SCALE = 0.17677669529663687f;
__device__ __forceinline__ float softmax8(float& p0, float& p1) {
  float m = fmaxf(p0, p1);
  m = fmaxf(m, __shfl_xor_sync(~0u, m, 1));
  m = fmaxf(m, __shfl_xor_sync(~0u, m, 2));
  asm("ex2.approx.ftz.f32 %0, %1;" : "=f"(p0) : "f"((p0 - m) * 1.4426950408889634f));
  asm("ex2.approx.ftz.f32 %0, %1;" : "=f"(p1) : "f"((p1 - m) * 1.4426950408889634f));
  float s = p0 + p1;
  s += __shfl_xor_sync(~0u, s, 1);
  s += __shfl_xor_sync(~0u, s, 2);
  float r;
  asm("rcp.approx.ftz.f32 %0, %1;" : "=f"(r) : "f"(s));
  return r;
}
__device__ __forceinline__ void sts128(uint32_t addr, uint32_t a, uint32_t b, uint32_t c, uint32_t d) {
  asm volatile("st.shared.v4.u32 [%0], {%1, %2, %3, %4};" ::"r"(addr), "r"(a), "r"(b), "r"(c), "r"(d) : "memory");
}
__device__ __forceinline__ uint4 lds128(uint32_t addr) {
  uint4 v;
  asm volatile("ld.shared.v4.u32 {%0, %1, %2, %3}, [%4];" : "=r"(v.x), "=r"(v.y), "=r"(v.z), "=r"(v.w) : "r"(addr) : "memory");
  return v;
}
__device__ __forceinline__ float2 lds64f(uint32_t addr) {
  float2 v;
  asm volatile("ld.shared.v2.f32 {%0, %1}, [%2];" : "=f"(v.x), "=f"(v.y) : "r"(addr) : "memory");
  return v;
}
#define PROF_AT(cond, slot) do {} while (0)

constexpr uint32_t SMEM_BASE = 1024;
constexpr uint32_t DESC_A = (1u << 16) | (SMEM_BASE >> 4);
constexpr uint32_t DESC_B = ((8192u >> 4) << 16) | ((SMEM_BASE + 16384) >> 4);

template <int BN> struct Wg;
template <> struct Wg<128> { static __device__ __forceinline__ void mma(float (&d)[64], uint32_t a, uint32_t b, int s) { wgmma_ss_n128(d, a, b, s); } };
template <> struct Wg<192> { static __device__ __forceinline__ void mma(float (&d)[96], uint32_t a, uint32_t b, int s) { wgmma_ss_n192(d, a, b, s); } };
template <> struct Wg<256> { static __device__ __forceinline__ void mma(float (&d)[128], uint32_t a, uint32_t b, int s) { wgmma_ss_n256(d, a, b, s); } };

struct Ring {
  uint32_t full0, rel0;
  int s;
  uint32_t ph;
  bool releaser;
};

template <int N>
__device__ __forceinline__ void fence_regs(float (&a)[N]) {
#pragma unroll
  for (int i = 0; i < N; i++) asm volatile("" : "+f"(a[i])::"memory");
}

template <int BN, int NST, uint32_t STAGE>
__device__ __forceinline__ void kblock(float (&acc)[BN / 2], Ring& g, uint32_t a_addr, bool zero, uint32_t& prev) {
  mbar_wait(g.full0 + 8 * g.s, g.ph);
  const uint32_t da = DESC_A + (a_addr >> 4);
  const uint32_t db = DESC_B + g.s * (STAGE >> 4);
  wg_fence();
#pragma unroll
  for (int k = 0; k < 4; k++) Wg<BN>::mma(acc, da + k * 2, db + k * 128, !(zero && k == 0));
  wg_commit();
  wg_wait<1>();
  if (prev != 0) mbar_arrive_cluster(prev);
  prev = g.releaser ? g.rel0 + 8 * g.s : 0u;
  if (++g.s == NST) { g.s = 0; g.ph ^= 1; }
}
template <int N>
__device__ __forceinline__ void tile_end(float (&acc)[N], uint32_t& prev) {
  wg_wait<0>();
  if (prev != 0) mbar_arrive_cluster(prev);
  prev = 0;
  fence_regs(acc);
}

__device__ __forceinline__ int other_kb(int q, int j) {
  const int ch = q >= 7, jj = q - 7 * ch;
  return 2 * (jj < j ? jj : jj + 1) + ch;
}
__device__ __forceinline__ int own_first(int it, int j) {
  return it >= 16 ? (it & 15) : (it < 2 ? 2 * j + it : other_kb(it - 2, j));
}
__device__ __forceinline__ int qkv_kb(int it, int j) {
  return it < 4 ? 2 * j + (it & 1) : other_kb(it < 18 ? it - 4 : it - 18, j);
}
__device__ __forceinline__ int wo_k(int it, int j) {
  return it < 8 ? it * 128 : (it == 8 ? j : (it - 9 < j ? it - 9 : it - 8)) * 128 + 64;
}
__device__ __forceinline__ int down_k(int it) {
  const int r = (it >> 4) - 1, idx = it & 15;
  return r < 0 ? idx * 64 : (r < 3 ? (idx >> 1) * 448 + r * 128 + (idx & 1) * 64 : idx * 448 + 384);
}
__device__ __forceinline__ void wait_p3_free(uint32_t empty3, int i) {
  mbar_wait(empty3 + 8 * ((i * 2) / 3), 1);
  mbar_wait(empty3 + 8 * ((i * 2 + 1) / 3), 1);
}
__device__ __forceinline__ void wait_p2_free(uint32_t empty2, int i) {
  const int w0 = (i * 3) / 2, w1 = (i * 3 + 2) / 2;
  mbar_wait(empty2 + 8 * w0, w0 < 4 ? 0 : 1);
  mbar_wait(empty2 + 8 * w1, w1 < 4 ? 0 : 1);
}

__device__ __forceinline__ void chan(float& m, float& q, float m2, float q2, float n) {
  const float d = m2 - m;
  m = 0.5f * (m + m2);
  q = q + q2 + d * d * (0.5f * n);
}

template <int N>
__device__ __forceinline__ void row_stats(const uint32_t (&ll)[N], float& mean, float& rstd) {
  float ma = __uint_as_float(ll[0]), qa = __uint_as_float(ll[1]), mb = __uint_as_float(ll[4]), qb = __uint_as_float(ll[5]);
  chan(ma, qa, __uint_as_float(ll[2]), __uint_as_float(ll[3]), 128.f);
  chan(mb, qb, __uint_as_float(ll[6]), __uint_as_float(ll[7]), 128.f);
  chan(ma, qa, mb, qb, 256.f);
  const float mo = __shfl_xor_sync(~0u, ma, 16), qo = __shfl_xor_sync(~0u, qa, 16);
  chan(ma, qa, mo, qo, 512.f);
  mean = ma;
  rstd = rsqrtf(qa * (1.0f / DM) + 1e-5f);
}

__device__ __forceinline__ void publish_stats(const uint32_t (&xl)[16], const uint32_t (&xh)[16], uint4* slot, int lane, uint32_t tag) {
  float ds[4] = {0.f, 0.f, 0.f, 0.f}, dl[4] = {0.f, 0.f, 0.f, 0.f}, dh[4] = {0.f, 0.f, 0.f, 0.f};
#pragma unroll
  for (int q = 0; q < 8; q++) {
    mma16816(ds, xl[2 * q], xh[2 * q], xl[2 * q + 1], xh[2 * q + 1], 0x3f803f80u, 0x3f803f80u);
    mma16816(dl, xl[2 * q], xh[2 * q], xl[2 * q + 1], xh[2 * q + 1], xl[2 * q], xl[2 * q + 1]);
    mma16816(dh, xl[2 * q], xh[2 * q], xl[2 * q + 1], xh[2 * q + 1], xh[2 * q], xh[2 * q + 1]);
  }
  const int r = lane >> 2;
  if ((lane & 3) == (r >> 1)) {
    const float ml = ds[0] * (1.0f / 128), mh = ds[2] * (1.0f / 128);
    const float ql = fmaxf(((r & 1) ? dl[1] : dl[0]) - ds[0] * ml, 0.f), qh = fmaxf(((r & 1) ? dh[3] : dh[2]) - ds[2] * mh, 0.f);
    ll_store(slot + r, __float_as_uint(ml), __float_as_uint(ql), tag);
    ll_store(slot + r + 8, __float_as_uint(mh), __float_as_uint(qh), tag);
  }
  __syncwarp();
}

__device__ __forceinline__ void stage_slab(uint32_t chunk, int warp, int lane, const uint32_t (&lo)[8], const uint32_t (&hi)[8]) {
  const int row = warp * 16 + (lane & 7) + ((lane >> 3) & 1) * 8;
  const uint32_t rbase = chunk + row * 128;
#pragma unroll
  for (int q = 0; q < 4; q++) {
    const int grp = 2 * q + (lane >> 4);
    stmatrix4(rbase + ((grp ^ (row & 7)) << 4), lo[2 * q], hi[2 * q], lo[2 * q + 1], hi[2 * q + 1]);
  }
}
__device__ __forceinline__ float silu_mul(float g, float u) {
  float e, r;
  asm("ex2.approx.ftz.f32 %0, %1;" : "=f"(e) : "f"(g * -1.4426950408889634f));
  asm("rcp.approx.ftz.f32 %0, %1;" : "=f"(r) : "f"(1.0f + e));
  return g * r * u;
}
__device__ __forceinline__ uint32_t swiglu2(uint32_t g2, uint32_t u2) {
  asm volatile("" : "+r"(g2));
  return pack2(silu_mul(bf_lo(g2), bf_lo(u2)), silu_mul(bf_hi(g2), bf_hi(u2)));
}
__device__ __forceinline__ void stage_done(uint32_t bar, int lane) {
  asm volatile("fence.proxy.async.shared::cta;" ::: "memory");
  __syncwarp();
  if (lane == 0) mbar_arrive(bar);
}

__device__ __forceinline__ int fresh_tid() {
  int t;
  asm volatile("mov.u32 %0, %%tid.x;" : "=r"(t));
  return t;
}
#define RING_IDS()                                                                                           \
  const int tid = fresh_tid() - 128;                                                                         \
  const int cw = __shfl_sync(~0u, tid >> 7, 0), warp = __shfl_sync(~0u, (tid >> 5) & 3, 0);                  \
  const bool releaser = (tid & 31) < 2;                                                                      \
  const uint32_t rbars = mapa(bars, tid & 1);                                                                \
  const uint32_t a_base = cw * 8192
#define LANE_IDS()                                                                                           \
  const int lane = fresh_tid() & 31, r = lane >> 2, c = lane & 3;                                            \
  const int srow = warp * 16 + (lane & 7) + ((lane >> 3) & 1) * 8;                                           \
  const uint32_t slab = stg + cw * 8192 + srow * 128, sw0 = (lane >> 4) ^ (srow & 7);                        \
  (void)r; (void)c; (void)slab; (void)sw0

template <int NPRE, bool EAGER, class Step>
__device__ __forceinline__ void attention(float (&acc)[96], const Params& p, int rho, int rb, int cta, int cw, int warp, uint32_t tag,
                                          uint32_t stg, uint32_t bars, uint32_t& prev, Step step) {
  uint32_t ql[8], qh[8], k0[8], k1[8], v0[8], v1[8], hp[16];
  if (EAGER) {
    tile_end(acc, prev);
  } else {
    step();
    fence_regs(acc);
  }
#pragma unroll
  for (int t = 0; t < 8; t++) {
    k0[t] = pack2(acc[4 * (8 + t)], acc[4 * (8 + t) + 1]);
    k1[t] = pack2(acc[4 * (8 + t) + 2], acc[4 * (8 + t) + 3]);
    v0[t] = pack2(acc[4 * (16 + t)], acc[4 * (16 + t) + 1]);
    v1[t] = pack2(acc[4 * (16 + t) + 2], acc[4 * (16 + t) + 3]);
    asm volatile("" : "+r"(k0[t]), "+r"(k1[t]), "+r"(v0[t]), "+r"(v1[t]));
  }
  const int lane = fresh_tid() & 31, r = lane >> 2, c = lane & 3;
#pragma unroll
  for (int t = 0; t < 8; t++) v1[t] = movmatrix(v1[t]);
  mbar_wait(bars + 8 * B_STGE, rho);
  mbar_wait(bars + 8 * (B_STGE + 1), 0);
  const uint32_t xch = stg + 16384 + (cw * 4 + warp) * 2048 + lane * 16;
  if (warp < 3) {
    sts128(xch, k1[0], k1[1], k1[2], k1[3]);
    sts128(xch + 512, k1[4], k1[5], k1[6], k1[7]);
    sts128(xch + 1024, v1[0], v1[1], v1[2], v1[3]);
    sts128(xch + 1536, v1[4], v1[5], v1[6], v1[7]);
  } else if (rb < 15) {
    uint4* dst = p.halo + ((cta * 2 + rho) * 2 + cw) * 256 + lane;
#pragma unroll
    for (int t = 0; t < 4; t++) {
      ll_store(dst + t * 32, k1[2 * t], k1[2 * t + 1], tag);
      ll_store(dst + (4 + t) * 32, v1[2 * t], v1[2 * t + 1], tag);
    }
  }
#pragma unroll
  for (int t = 0; t < 8; t++) {
    v0[t] = movmatrix(v0[t]);
    ql[t] = pack2(acc[4 * t], acc[4 * t + 1]);
    qh[t] = pack2(acc[4 * t + 2], acc[4 * t + 3]);
    asm volatile("" : "+r"(v0[t]), "+r"(ql[t]), "+r"(qh[t]));
  }
#pragma unroll 1
  for (int i = 0; i < NPRE; i++) step();
  const uint4* src = p.halo + (((cta - 8) * 2 + rho) * 2 + cw) * 256 + lane;
  uint4 early[8] = {};
  if (warp == 0 && rb > 0) {
#pragma unroll
    for (int i = 0; i < 8; i++) early[i] = ll_peek(src + i * 32);
  }
  step();
  wg_bar(cw);
  if (warp > 0) {
#pragma unroll
    for (int t = 0; t < 4; t++) {
      const uint4 a = lds128(xch - 2048 + t * 512);
      hp[4 * t] = a.x; hp[4 * t + 1] = a.y; hp[4 * t + 2] = a.z; hp[4 * t + 3] = a.w;
    }
  } else if (rb > 0) {
    uint32_t bad = 0;
#pragma unroll
    for (int i = 0; i < 8; i++) {
      bad |= (early[i].y ^ tag) | (early[i].w ^ tag);
      hp[2 * i] = early[i].x;
      hp[2 * i + 1] = early[i].z;
    }
    if (!__all_sync(~0u, bad == 0)) ll_poll<8>([&](int i) { return src + i * 32; }, tag, hp);
  } else {
#pragma unroll
    for (int t = 0; t < 16; t++) hp[t] = 0;
  }
  wg_wait<0>();
  if (prev != 0) mbar_arrive_cluster(prev);
  prev = 0;
#pragma unroll
  for (int t = 0; t < 8; t++) asm volatile("" : "+r"(ql[t])::"memory");
  const bool up0 = 2 * c > r, up1 = 2 * c + 1 > r;
  const bool first = (rb == 0) && (warp == 0);
  uint32_t a0[2], a2[2], a3[2], a5[2];
  float il[2], ih[2];
#pragma unroll
  for (int h = 0; h < 2; h++) {
    float sp[4] = {0.f, 0.f, 0.f, 0.f}, s0[4] = {0.f, 0.f, 0.f, 0.f}, s1[4] = {0.f, 0.f, 0.f, 0.f};
#pragma unroll
    for (int ks = 0; ks < 2; ks++) {
      const int t = 4 * h + 2 * ks;
      mma16816(sp, ql[t], qh[t], ql[t + 1], qh[t + 1], hp[t], hp[t + 1]);
      mma16816(s0, ql[t], qh[t], ql[t + 1], qh[t + 1], k0[t], k0[t + 1]);
      mma16816(s1, ql[t], qh[t], ql[t + 1], qh[t + 1], k1[t], k1[t + 1]);
    }
    float p0 = (up0 ? sp[0] : s0[0]) * QK_SCALE, p1 = (up1 ? sp[1] : s0[1]) * QK_SCALE;
    float p2 = (up0 ? s0[2] : s1[2]) * QK_SCALE, p3 = (up1 ? s0[3] : s1[3]) * QK_SCALE;
    if (first && up0) p0 = -1000000000.0f;
    if (first && up1) p1 = -1000000000.0f;
    il[h] = softmax8(p0, p1);
    ih[h] = softmax8(p2, p3);
    a0[h] = pack2(up0 ? p0 : 0.f, up1 ? p1 : 0.f);
    a2[h] = pack2(up0 ? 0.f : p0, up1 ? 0.f : p1);
    a3[h] = pack2(up0 ? p2 : 0.f, up1 ? p3 : 0.f);
    a5[h] = pack2(up0 ? 0.f : p2, up1 ? 0.f : p3);
  }
  float o[8][4];
#pragma unroll
  for (int t = 0; t < 8; t++) {
#pragma unroll
    for (int q = 0; q < 4; q++) o[t][q] = 0.f;
    mma1688(o[t], 0u, a5[t >> 2], v1[t]);
    mma16816(o[t], a0[t >> 2], 0u, a2[t >> 2], a3[t >> 2], hp[8 + t], v0[t]);
  }
#pragma unroll
  for (int t = 0; t < 8; t++) fence_regs(o[t]);
  if (!EAGER) step();
  uint32_t ol[8], oh[8];
#pragma unroll
  for (int t = 0; t < 8; t++) {
    ol[t] = pack2(o[t][0] * il[t >> 2], o[t][1] * il[t >> 2]);
    oh[t] = pack2(o[t][2] * ih[t >> 2], o[t][3] * ih[t >> 2]);
  }
  if (!EAGER) step();
  stage_slab(stg + cw * 8192, warp, lane, ol, oh);
  stage_done(bars + 8 * B_STGF, lane);
  if (!EAGER) step();
}

__global__ void __launch_bounds__(384, 1) fused_kernel(const __grid_constant__ Params p) {
  extern __shared__ __align__(1024) uint8_t smem_raw[];
  const uint32_t sm = smem_u32(smem_raw);
  const uint32_t bars = sm + MISC_OFF;
  const uint32_t stg = sm + STG_OFF;
  const int rank = blockIdx.x & 1;
  const int cl = blockIdx.x >> 1;
  if (cl >= NCTA / 2) {
    const int e = blockIdx.x - NCTA, wid = __shfl_sync(~0u, (int)(threadIdx.x >> 5), 0), lane = threadIdx.x & 31;
    if (threadIdx.x == 0) {
      for (int i = 0; i < 6; i++) { mbar_init(bars + 8 * i, 1); mbar_init(bars + 8 * (6 + i), 8); }
      asm volatile("fence.mbarrier_init.release.cluster;" ::: "memory");
    }
    const uint32_t tag = load_epoch(p.epoch) + 1;
    if (threadIdx.x < 256) ll_store(p.modll + 512 + (threadIdx.x >> 6) * 256 + e * 64 + (threadIdx.x & 63), 0u, 0u, 0u);
    for (int i = threadIdx.x; i < 1536; i += 384) {
      uint4 o = make_uint4(0u, 0u, 0u, 0u);
      if (i < 1024 && (i & 63) < 8) {
        const uint4 cv = ldg_nc(p.c + (i >> 6) * 64 + (i & 7) * 8);
        o = make_uint4(pack2(silu_f(bf_lo(cv.x)), silu_f(bf_hi(cv.x))), pack2(silu_f(bf_lo(cv.y)), silu_f(bf_hi(cv.y))),
                       pack2(silu_f(bf_lo(cv.z)), silu_f(bf_hi(cv.z))), pack2(silu_f(bf_lo(cv.w)), silu_f(bf_hi(cv.w))));
      }
      sts128(stg + i * 16, o.x, o.y, o.z, o.w);
    }
    asm volatile("fence.proxy.async.shared::cta;" ::: "memory");
    __syncthreads();
    if (wid == 0) {
      __nanosleep(WMDELAY);
      uint32_t ph = 1;
#pragma unroll 1
      for (int it = 0, s = 0; it < 64; it++) {
        mbar_wait(bars + 8 * (6 + s), ph);
        expect_tx_elect(bars + 8 * s, 32768);
#pragma unroll
        for (int q = 0; q < 4; q++) tma_load_ef(sm + s * 32768 + q * 8192, &p.wm, bars + 8 * s, 2048 + (it >> 4) * 1024 + e * 256 + q * 64, (it & 15) * 64);
        if (++s == 6) { s = 0; ph ^= 1; }
      }
    } else if (wid == 1 && PFW) {
      __nanosleep(PFW);
#pragma unroll 1
      for (int i = 0; i < 64; i++) {
        l2_prefetch_tile(&p.wo, (i & 15) * 64, (e * 4 + (i >> 4)) * 64);
        if (PFP) __nanosleep(PFP);
      }
#pragma unroll 1
      for (int i = 0; i < 128; i++) {
        l2_prefetch_tile((i & 2) ? &p.wu : &p.wg, ((i >> 2) & 7) * 448 + (i & 1) * 64, ((i >> 5) * 4 + e) * 64);
        if (PFP) __nanosleep(PFP);
      }
    } else if (wid >= 4) {
      const int hf = (wid >> 2) - 1;
      uint32_t ph = 0;
      int s = 0;
#pragma unroll 1
      for (int v = 0; v < 4; v++) {
        float acc[64];
#pragma unroll 1
        for (int kb = 0; kb < 16; kb++) {
          mbar_wait_watchdog(bars + 8 * s, ph);
          const uint32_t da = DESC_A + ((STG_OFF + kb * 1024) >> 4), db = DESC_B + ((s * 32768 + hf * 16384) >> 4) - 1024;
          wg_fence();
#pragma unroll
          for (int k = 0; k < 4; k++) wgmma_ss_n128(acc, da + k * 2, db + k * 128, (kb | k) != 0);
          wg_commit();
          wg_wait<0>();
          if (lane == 0) mbar_arrive(bars + 8 * (6 + s));
          if (++s == 6) { s = 0; ph ^= 1; }
        }
        if ((wid & 3) == 0) {
#pragma unroll
          for (int n = 0; n < 16; n++) {
            const uint32_t mine = pack2(acc[4 * n], acc[4 * n + 1]), next = __shfl_down_sync(~0u, mine, 1);
            if (lane < 4 && (lane & 1) == 0) ll_store(p.modll + 512 + v * 256 + e * 64 + hf * 32 + n * 2 + (lane >> 1), mine, next, tag);
          }
        }
      }
    }
    return;
  }
  const int slot = p.slot[cl];
  const int rb = (slot >> 3) * 2 + rank, j = slot & 7;
  const int cta = rb * 8 + j;
  PROF_AT(threadIdx.x == 0, 0);

  if (threadIdx.x < 128) {
    uint32_t tag = load_epoch(p.epoch);
    asm volatile("setmaxnreg.dec.sync.aligned.u32 40;");
    const int warp = __shfl_sync(~0u, (int)(threadIdx.x >> 5), 0), lane = threadIdx.x & 31;
    if (threadIdx.x == 0) {
      if ((sm & 0x3FFFF) != SMEM_BASE) asm volatile("trap;");
      for (int i = 0; i < 4; i++) { mbar_init(bars + 8 * (B_FQ + i), 1); mbar_init(bars + 8 * (B_EQ + i), 16); }
      for (int i = 0; i < 6; i++) { mbar_init(bars + 8 * (B_FW + i), 1); mbar_init(bars + 8 * (B_EW + i), 16); }
      for (int i = 0; i < 4; i++) { mbar_init(bars + 8 * (B_FG + i), 1); mbar_init(bars + 8 * (B_EG + i), 16); }
      for (int i = 0; i < 6; i++) { mbar_init(bars + 8 * (B_FD + i), 1); mbar_init(bars + 8 * (B_ED + i), 16); }
      for (int i = 0; i < 2; i++) { mbar_init(bars + 8 * (B_STGF + i), 8); mbar_init(bars + 8 * (B_STGE + i), 1); }
      mbar_init(bars + 8 * B_MODB, 1);
      mbar_init(bars + 8 * (B_MODB + 1), 1);
      mbar_init(bars + 8 * B_MODA, 1);
      for (int i = 0; i < 8; i++) mbar_init(bars + 8 * (B_RDY + i), 1);
      asm volatile("fence.mbarrier_init.release.cluster;" ::: "memory");
    }
    __syncwarp();
    cluster_arrive_relaxed();
    tag += 1;
    const unsigned target = tag * 8;
    unsigned* cnt = p.cnt + rb * 32;
    cluster_wait();
    if (warp == 0) {
      const CUtensorMap* wgu = rank ? &p.wu : &p.wg;
      uint32_t st = sm + 16384, fb = bars + 8 * B_FQ, ph = 1;
      __nanosleep(BDELAY);
#pragma unroll 1
      for (int it = 0; it < 32; it++) {
        const int kb = qkv_kb(it, j), col = j * 128 + ((it < 4 ? it >= 2 : it >= 18) ? 64 : 0);
        mbar_wait(fb + 8 * (B_EQ - B_FQ), ph);
        expect_tx_elect(fb, it < 4 ? 24576 : 40960);
        tma_load_mc(st + rank * 8192, &p.wqkv, fb, col + rank * 1024, kb * 64);
        tma_load_mc(st + 16384 + rank * 4096, &p.wqkv32, fb, col + 2048, kb * 64 + rank * 32);
        st += 49152; fb += 8;
        if ((it & 3) == 3) { st -= 4 * 49152; fb -= 32; ph ^= 1; }
      }
      fb = bars + 8 * B_FW; ph = 1;
#pragma unroll 1
      for (int it = 0, s = 0; it < 16; it++) {
        if (it < 6) wait_p3_free(bars + 8 * B_EQ, it);
        mbar_wait(fb + 8 * (B_EW - B_FW), ph);
        expect_tx_elect(fb, it == 8 ? 16384 : 32768);
        tma_load_mc(st + rank * 8192, &p.wo, fb, j * 128 + rank * 64, wo_k(it, j));
        st += 32768; fb += 8;
        if (++s == 6) { s = 0; st -= 6 * 32768; fb -= 48; ph ^= 1; }
      }
      st = sm + 16384; fb = bars + 8 * B_FG; ph = 1;
#pragma unroll 1
      for (int it = 0; it < 48; it++) {
        const int kb = own_first(it, j), col = j * 448 + (it >> 4) * 128;
        if (it < 4) wait_p2_free(bars + 8 * B_EW, it);
        mbar_wait(fb + 8 * (B_EG - B_FG), ph);
        expect_tx_elect(fb, it < 2 ? 32768 : 49152);
        tma_load_mc(st + rank * 16384, wgu, fb, col, kb * 64);
        tma_load_mc(st + rank * 16384 + 8192, wgu, fb, col + 64, kb * 64);
        st += 49152; fb += 8;
        if ((it & 3) == 3) { st -= 4 * 49152; fb -= 32; ph ^= 1; }
      }
      fb = bars + 8 * B_FD; ph = 1;
#pragma unroll 1
      for (int it = 0, s = 0; it < 72; it++) {
        if (it < 6) wait_p3_free(bars + 8 * B_EG, it);
        mbar_wait(fb + 8 * (B_ED - B_FD), ph);
        expect_tx_elect(fb, 32768);
        tma_load_mc(st + rank * 8192, it < 16 ? wgu : &p.wd, fb, it < 16 ? j * 448 + 384 : j * 128 + rank * 64, down_k(it));
        st += 32768; fb += 8;
        if (++s == 6) { s = 0; st -= 6 * 32768; fb -= 48; ph ^= 1; }
      }
    } else if (warp == 1) {
      const int arow = rb * 128;
      uint32_t st = sm, fb = bars + 8 * B_FQ, ph = 0;
      cnt_wait(cnt + C_HA, target);
      PROF_AT(lane == 0, 16);
#pragma unroll 1
      for (int it = 4; it < 32; it++) {
        if (it == 11) mbar_wait(bars + 8 * (B_RDY + C_H), 0);
        mbar_wait(fb + 8 * (B_EQ - B_FQ), ph);
        tma_load(st, &p.h, fb, qkv_kb(it, j) * 64, arow);
        st += 49152; fb += 8;
        if ((it & 3) == 3) { st -= 4 * 49152; fb -= 32; ph ^= 1; }
      }
      fb = bars + 8 * B_FW; ph = 1;
#pragma unroll 1
      for (int it = 0, s = 0; it < 16; it++) {
        if (it < 6) wait_p3_free(bars + 8 * B_EQ, it);
        mbar_wait(fb + 8 * (B_EW - B_FW), ph);
        if (it == 0) mbar_wait(bars + 8 * (B_RDY + C_O), 0);
        if (it == 9) cnt_wait(cnt + C_O + 1, target * 8);
        PROF_AT(lane == 0 && (it == 0 || it == 9), 17 + (it >> 3));
        if (it != 8) tma_load(st, &p.o_ld, fb, wo_k(it, j), arow);
        st += 32768; fb += 8;
        if (++s == 6) { s = 0; st -= 6 * 32768; fb -= 48; ph ^= 1; }
      }
      st = sm + 2 * 49152; fb = bars + 8 * (B_FG + 2); ph = 1;
      cnt_wait(cnt + C_H2A, target * 8);
      PROF_AT(lane == 0, 19);
#pragma unroll 1
      for (int it = 2; it < 48; it++) {
        if (it == 9) mbar_wait(bars + 8 * (B_RDY + C_H2), 0);
        mbar_wait(fb + 8 * (B_EG - B_FG), ph);
        tma_load(st, &p.h2, fb, own_first(it, j) * 64, arow);
        st += 49152; fb += 8;
        if ((it & 3) == 3) { st -= 4 * 49152; fb -= 32; ph ^= 1; }
      }
      fb = bars + 8 * B_FD; ph = 1;
#pragma unroll 1
      for (int it = 0, s = 0; it < 72; it++) {
        if (it < 6) wait_p3_free(bars + 8 * B_EG, it);
        mbar_wait(fb + 8 * (B_ED - B_FD), ph);
        if ((it & 15) == 0 && it > 0) { mbar_wait(bars + 8 * (B_RDY + C_ACT - 1 + (it >> 4)), 0); PROF_AT(lane == 0, 19 + (it >> 4)); }
        tma_load(st, it < 16 ? &p.h2 : &p.act, fb, down_k(it), arow);
        st += 32768; fb += 8;
        if (++s == 6) { s = 0; st -= 6 * 32768; fb -= 48; ph ^= 1; }
      }
    } else if (warp == 2) {
      if (lane < 14) prefetch_map(&p.h + lane);
      __syncwarp();
      uint32_t ph1 = 0;
#pragma unroll 1
      for (int n = 0; n < 8; n++) {
        const int nch = (n == 1 || n == 2 || n == 7) ? 1 : 2;
#pragma unroll 1
        for (int ch = 0; ch < nch; ch++) {
          mbar_wait_watchdog(bars + 8 * (B_STGF + ch), ch ? ph1 : (n & 1));
          const uint32_t src = stg + ch * 16384;
          if (n == 2 || n == 3) {
          } else if (n == 1) {
#pragma unroll 1
            for (int q = 0; q < 8; q++) {
              tma_store2(&p.o_st, src + q * 2048, j * 128, rb * 128 + q * 16);
              if (q & 1) store_pause(true);
            }
          } else if (n >= 4 && n < 8) {
#pragma unroll 1
            for (int q = 0; q < 4; q++) {
              tma_store2(&p.act_st, src + q * 4096, j * 448 + (n - 4) * 128 + ch * 64, rb * 128 + q * 32);
              store_pause(true);
            }
          } else {
            tma_store2(&p.h, src, j * 128 + ch * 64, rb * 128);
            asm volatile("cp.async.bulk.commit_group;" ::: "memory");
            if (ch == 1) {
              asm volatile("cp.async.bulk.wait_group 1;" ::: "memory");
              __syncwarp();
              cnt_signal(cnt + C_HA);
            }
          }
          if (n >= 4 && n < 7 && ch == 0) arrive_elect(bars + 8 * B_STGE);
        }
        asm volatile("cp.async.bulk.commit_group;" ::: "memory");
        asm volatile("cp.async.bulk.wait_group 0;" ::: "memory");
        __syncwarp();
        if (n != 2 && n != 3) cnt_signal(cnt + n);
        PROF_AT(lane == 0, n == 0 ? 33 : 23 + n);
        if (n == 0) {
#pragma unroll 1
          for (int t = 0; t < 36; t++) {
            ll_store(t < 32 ? p.halo + cta * 1024 + t * 32 + lane : p.stats2 + cta * 128 + (t - 32) * 32 + lane, 0u, 0u, 0u);
            __nanosleep(40);
          }
          __syncwarp();
        }
        if (!(n >= 4 && n < 7)) arrive_elect(bars + 8 * B_STGE);
        if (nch == 2) { arrive_elect(bars + 8 * (B_STGE + 1)); ph1 ^= 1; }
      }
      mbar_wait_watchdog(bars + 8 * B_STGF, 0);
      PROF_AT(lane == 0, 31);
    } else {
      if (lane < 4) ll_store(p.modll + cta * 4 + lane, 0u, 0u, 0u);
      bar_sync(1, 288);
      {
        const uint4 t4 = lds128(sm + RED_OFF + lane * 16);
        float a[4] = {__uint_as_float(t4.x), __uint_as_float(t4.y), __uint_as_float(t4.z), __uint_as_float(t4.w)};
#pragma unroll
        for (int o = 4; o < 32; o <<= 1)
#pragma unroll
          for (int q = 0; q < 4; q++) a[q] += __shfl_xor_sync(~0u, a[q], o);
        if (lane < 4) ll_store(p.modll + cta * 4 + lane, pack2(a[0], a[1]), pack2(a[2], a[3]), tag);
        PROF_AT(lane == 0, 1);
        uint32_t m[4];
        const uint4* mp = p.modll + j * 32 + lane;
        ll_poll<2>([&](int i) { return mp + i * 256; }, tag, m);
        const uint32_t c0 = pack2(1.0f + bf_lo(m[2]), 1.0f + bf_hi(m[2])), c1 = pack2(1.0f + bf_lo(m[3]), 1.0f + bf_hi(m[3]));
        sts128(sm + MODB_OFF + lane * 16, c0, m[0], c1, m[1]);
        __syncwarp();
        arrive_elect(bars + 8 * B_MODA);
      }
#pragma unroll 1
      for (int n = C_H; n <= C_O; n++) {
        cnt_wait_lazy(cnt + n, target);
        arrive_elect(bars + 8 * (B_RDY + n));
      }
      {
        uint32_t m[6];
        const uint4* src = p.modll + 512 + j * 32 + lane;
        ll_poll<3, 500>([&](int i) { return src + i * 256; }, tag, m);
#pragma unroll
        for (int vec = 0; vec < 3; vec++) {
          const float add = vec == 2 ? 1.0f : 0.0f;
          sts128(sm + MODB_OFF + (vec * 128 + lane * 4) * 4, __float_as_uint(bf_round(bf_lo(m[2 * vec]) + add)), __float_as_uint(bf_round(bf_hi(m[2 * vec]) + add)),
                 __float_as_uint(bf_round(bf_lo(m[2 * vec + 1]) + add)), __float_as_uint(bf_round(bf_hi(m[2 * vec + 1]) + add)));
        }
        __syncwarp();
        if (lane == 0) mbar_arrive(bars + 8 * B_MODB);
        PROF_AT(lane == 0, 15);
      }
      __syncwarp();
#pragma unroll 1
      for (int n = C_H2; n < 8; n++) {
        cnt_wait_lazy(cnt + n, n == C_H2 ? target * 8 : target);
        arrive_elect(bars + 8 * (B_RDY + n));
      }
      {
        uint32_t m[2];
        const uint4* src = p.modll + 512 + 768 + j * 32 + lane;
        ll_poll<1>([&](int) { return src; }, tag, m);
        sts128(sm + MODB_OFF + (384 + lane * 4) * 4, m[0] << 16, m[0] & 0xffff0000u, m[1] << 16, m[1] & 0xffff0000u);
        __syncwarp();
        if (lane == 0) mbar_arrive(bars + 8 * (B_MODB + 1));
      }
    }
  } else {
    uint32_t tag;

    {
      const int tid = threadIdx.x - 128, cw = tid >> 7, warp = (tid >> 5) & 3, lane = tid & 31;
      const int l16 = lane & 15, half = lane >> 4, w8 = cw * 4 + warp;
      const uint32_t cbuf = sm + 3 * 49152 + w8 * 512;
      if (lane <= 16) cp_async16(cbuf + lane * 16, lane < 16 ? (const void*)(p.c + w8 * 128 + lane * 8) : (const void*)p.epoch);
      asm volatile("cp.async.commit_group;" ::: "memory");
      const uint32_t xbuf = sm + 40960 + (cw * 2 + (l16 >> 3)) * 49152 + (warp * 16 + half) * 128;
      {
        const char* xp = (const char*)p.x + (uint32_t)((rb * 128 + (warp * 16 + half) * 2 + cw) * 2048 + j * 256 + l16 * 16);
#pragma unroll
        for (int i = 0; i < 8; i++) cp_async16(xbuf + i * 256 + (((l16 & 7) ^ ((i * 2 + half) & 7)) << 4), xp + i * 8192);
      }
      asm volatile("cp.async.commit_group;" ::: "memory");
      const uint32_t wbuf = sm + cw * 49152 + warp * 4096;
      {
        const char* wp = (const char*)p.wmod + (uint32_t)(cta * 32 + (lane & 1) * 16 + (w8 * 128 + (lane >> 1)) * 12288);
#pragma unroll
        for (int i = 0; i < 8; i++) cp_async16(wbuf + i * 512 + lane * 16, wp + i * 16 * 12288);
      }
      asm volatile("cp.async.commit_group;" ::: "memory");
      PROF_AT(tid == 0, 32);
      uint4* st1 = p.stats1 + (rb * 8 + j) * 128 + cw * 64 + warp * 16;
      if (lane < 16) ll_store(st1 + lane, 0u, 0u, 0u);
      __syncwarp();
      cluster_arrive_relaxed();
      asm volatile("setmaxnreg.inc.sync.aligned.u32 232;");
      uint32_t sa[4][4];
      {
        asm volatile("cp.async.wait_group 2;" ::: "memory");
        __syncwarp();
        tag = lds32(cbuf + 256) + 1;
        const float2 cv = lds64f(cbuf + lane * 8);
        const uint32_t c0 = __float_as_uint(cv.x), c1 = __float_as_uint(cv.y);
        sts64f(cbuf + lane * 8, __uint_as_float(pack2(silu_f(bf_lo(c0)), silu_f(bf_hi(c0)))), __uint_as_float(pack2(silu_f(bf_lo(c1)), silu_f(bf_hi(c1)))));
        __syncwarp();
#pragma unroll
        for (int q = 0; q < 4; q++) ldmatrix4(sa[q][0], sa[q][1], sa[q][2], sa[q][3], cbuf + q * 64 + (lane >> 3) * 16);
      }
      cluster_wait();
      asm volatile("cp.async.wait_group 1;" ::: "memory");
      __syncwarp();
      uint32_t xl[16], xh[16];
      {
        const int srow = warp * 16 + (lane & 15);
#pragma unroll
        for (int q = 0; q < 8; q++)
          ldmatrix4(xl[2 * q], xh[2 * q], xl[2 * q + 1], xh[2 * q + 1],
                    sm + 40960 + (cw * 2 + (q >> 2)) * 49152 + srow * 128 + (((half + (q & 3) * 2) ^ (srow & 7)) << 4));
      }
      publish_stats(xl, xh, st1, lane, tag);
      PROF_AT(tid == 0, 50);
      asm volatile("cp.async.wait_group 0;" ::: "memory");
      __syncwarp();
      PROF_AT(tid == 0, 51);
      {
        uint32_t b[8][4];
#pragma unroll
        for (int ks = 0; ks < 8; ks++) ldmatrix4t(b[ks], wbuf + (ks * 16 + (lane & 15)) * 32 + (lane >> 4) * 16);
        float d0[4] = {0.f, 0.f, 0.f, 0.f}, d1[4] = {0.f, 0.f, 0.f, 0.f}, d2[4] = {0.f, 0.f, 0.f, 0.f}, d3[4] = {0.f, 0.f, 0.f, 0.f};
#pragma unroll
        for (int q = 0; q < 4; q++) {
          mma16816(d0, sa[q][0], sa[q][0], sa[q][1], sa[q][1], b[2 * q][0], b[2 * q][1]);
          mma16816(d1, sa[q][0], sa[q][0], sa[q][1], sa[q][1], b[2 * q][2], b[2 * q][3]);
          mma16816(d2, sa[q][2], sa[q][2], sa[q][3], sa[q][3], b[2 * q + 1][0], b[2 * q + 1][1]);
          mma16816(d3, sa[q][2], sa[q][2], sa[q][3], sa[q][3], b[2 * q + 1][2], b[2 * q + 1][3]);
        }
        d0[0] += d2[0]; d0[1] += d2[1]; d1[0] += d3[0]; d1[1] += d3[1];
        if (lane < 4) {
          sts64f(sm + RED_OFF + (w8 * 16 + lane * 2) * 4, d0[0], d0[1]);
          sts64f(sm + RED_OFF + (w8 * 16 + 8 + lane * 2) * 4, d1[0], d1[1]);
        }
        asm volatile("bar.arrive 1, 288;" ::: "memory");
      }
      {
        const int r = lane >> 2, c = lane & 3;
        uint32_t st[8];
        const uint4* sp = p.stats1 + rb * 1024 + half * 512 + cw * 64 + warp * 16 + l16;
        ll_poll<4>([&](int i) { return sp + i * 128; }, tag, st);
        float mu, rstd;
        row_stats(st, mu, rstd);
        mu *= -rstd;
        const float n0 = __shfl_sync(~0u, mu, r), r0 = __shfl_sync(~0u, rstd, r), n1 = __shfl_sync(~0u, mu, r + 8), r1 = __shfl_sync(~0u, rstd, r + 8);
#pragma unroll
        for (int n = 0; n < 16; n++) {
          xl[n] = pack2(bf_lo(xl[n]) * r0 + n0, bf_hi(xl[n]) * r0 + n0);
          xh[n] = pack2(bf_lo(xh[n]) * r1 + n1, bf_hi(xh[n]) * r1 + n1);
        }
        const int srow = warp * 16 + l16;
        const uint32_t slab = stg + cw * 8192 + srow * 128;
#pragma unroll
        for (int q = 0; q < 8; q++)
          stmatrix4(slab + (q >> 2) * 16384 + (((half + (q & 3) * 2) ^ (srow & 7)) << 4), xl[2 * q], xh[2 * q], xl[2 * q + 1], xh[2 * q + 1]);
        PROF_AT(tid == 0, 52);
        mbar_wait(bars + 8 * B_MODA, 0);
        PROF_AT(tid == 0, 2);
#pragma unroll
        for (int q = 0; q < 8; q++) {
          const float2 m0 = lds64f(sm + MODB_OFF + (8 * q + c) * 8), m1 = lds64f(sm + MODB_OFF + (8 * q + 4 + c) * 8);
          const uint32_t c0 = __float_as_uint(m0.x), s0 = __float_as_uint(m0.y), c1 = __float_as_uint(m1.x), s1 = __float_as_uint(m1.y);
          stmatrix4(slab + (q >> 2) * 16384 + (((half + (q & 3) * 2) ^ (srow & 7)) << 4), fma_bf2(xl[2 * q], c0, s0), fma_bf2(xh[2 * q], c0, s0),
                    fma_bf2(xl[2 * q + 1], c1, s1), fma_bf2(xh[2 * q + 1], c1, s1));
          if ((q & 3) == 3) stage_done(bars + 8 * (B_STGF + (q >> 2)), lane);
        }
        wg_bar(cw);
      }
      PROF_AT(tid == 0, 3);
    }

    uint32_t xl[16], xh[16];
    {
      RING_IDS();
      uint32_t prev = 0;
      float acc1[96];
      {
        Ring g{bars + 8 * B_FQ, rbars + 8 * B_EQ, 0, 0u, releaser TR(0)};
        float acc0[96];
#pragma unroll 1
        for (int kb = 0; kb < 2; kb++) kblock<192, 4, 49152>(acc0, g, a_base + STG_OFF + kb * 16384, kb == 0, prev);
#pragma unroll 1
        for (int kb = 0; kb < 2; kb++) kblock<192, 4, 49152>(acc1, g, a_base + STG_OFF + kb * 16384, kb == 0, prev);
#pragma unroll 1
        for (int kb = 0; kb < 14; kb++) kblock<192, 4, 49152>(acc0, g, a_base + g.s * 49152, false, prev);
        PROF_AT(tid == 0, 4);
        attention<NPRE0, false>(acc0, p, 0, rb, cta, cw, warp, tag, stg, bars, prev, [&]() { kblock<192, 4, 49152>(acc1, g, a_base + g.s * 49152, false, prev); });
        PROF_AT(tid == 0, 5);
        {
          LANE_IDS();
#pragma unroll
          for (int q = 0; q < 8; q++)
            ldmatrix4(xl[2 * q], xh[2 * q], xl[2 * q + 1], xh[2 * q + 1], sm + 40960 + (cw * 2 + (q >> 2)) * 49152 + srow * 128 + ((sw0 ^ ((q & 3) * 2)) << 4));
#pragma unroll
          for (int q = 0; q < 16; q++) asm volatile("" : "+r"(xl[q]), "+r"(xh[q])::"memory");
        }
#pragma unroll 1
        for (int kb = 5 + NPRE0; kb < 14; kb++) kblock<192, 4, 49152>(acc1, g, a_base + g.s * 49152, false, prev);
        PROF_AT(tid == 0, 6);
      }
      float acc[64];
      Ring g{bars + 8 * B_FW, rbars + 8 * B_EW, 0, 0u, releaser TR(32)};
      attention<NPRE1, true>(acc1, p, 1, rb, cta, cw, warp, tag, stg, bars, prev, [&]() { kblock<128, 6, 32768>(acc, g, a_base + g.s * 32768, g.s == 0, prev); });
      PROF_AT(tid == 0, 7);
      LANE_IDS();
      unsigned* cnt = p.cnt + rb * 32;
      tma_store2(&p.o_st, stg + cw * 8192 + warp * 2048, j * 128 + 64, rb * 128 + cw * 64 + warp * 16);
      asm volatile("cp.async.bulk.commit_group;" ::: "memory");
#pragma unroll 1
      for (int kb = 1 + NPRE1; kb < 16; kb++) {
        if (kb == 8) wg_bar(cw);
        kblock<128, 6, 32768>(acc, g, a_base + (kb == 8 ? STG_OFF : g.s * 32768), false, prev);
        if (kb == OSIG + NPRE1) {
          asm volatile("cp.async.bulk.wait_group 0;" ::: "memory");
          __syncwarp();
          cnt_signal(cnt + C_O + 1);
        }
      }
      mbar_wait(bars + 8 * B_MODB, 0);
      float2 ga[16];
#pragma unroll
      for (int n = 0; n < 16; n++) ga[n] = lds64f(sm + MODB_OFF + (8 * n + 2 * c) * 4);
      tile_end(acc, prev);
      PROF_AT(tid == 0, 8);
      uint4* st2 = p.stats2 + (rb * 8 + j) * 128 + cw * 64 + warp * 16 + r + (c & 1) * 8;
      float sl[2] = {0.f, 0.f}, sh[2] = {0.f, 0.f}, ql[2] = {0.f, 0.f}, qh[2] = {0.f, 0.f};
#pragma unroll
      for (int n = 0; n < 16; n++) {
        acc[4 * n] = ga[n].x * acc[4 * n] + bf_lo(xl[n]); acc[4 * n + 1] = ga[n].y * acc[4 * n + 1] + bf_hi(xl[n]);
        acc[4 * n + 2] = ga[n].x * acc[4 * n + 2] + bf_lo(xh[n]); acc[4 * n + 3] = ga[n].y * acc[4 * n + 3] + bf_hi(xh[n]);
        sl[0] += acc[4 * n]; sl[1] += acc[4 * n + 1]; sh[0] += acc[4 * n + 2]; sh[1] += acc[4 * n + 3];
        ql[0] += acc[4 * n] * acc[4 * n]; ql[1] += acc[4 * n + 1] * acc[4 * n + 1];
        qh[0] += acc[4 * n + 2] * acc[4 * n + 2]; qh[1] += acc[4 * n + 3] * acc[4 * n + 3];
      }
      {
        const float ml = (sl[0] + sl[1]) * (1.0f / 32), mh = (sh[0] + sh[1]) * (1.0f / 32);
        const float vl = (ql[0] + ql[1]) - 32.0f * ml * ml, vh = (qh[0] + qh[1]) - 32.0f * mh * mh;
        const bool b0 = c & 1;
        float m = b0 ? mh : ml, q = b0 ? vh : vl;
        chan(m, q, __shfl_xor_sync(~0u, b0 ? ml : mh, 1), __shfl_xor_sync(~0u, b0 ? vl : vh, 1), 32.f);
        chan(m, q, __shfl_xor_sync(~0u, m, 2), __shfl_xor_sync(~0u, q, 2), 64.f);
        if (c < 2) ll_store(st2, __float_as_uint(m), __float_as_uint(fmaxf(q, 0.f)), tag);
        __syncwarp();
      }
      PROF_AT(tid == 0, 48);
      float2 sb[16], cb[16];
#pragma unroll
      for (int n = 0; n < 16; n++) {
        sb[n] = lds64f(sm + MODB_OFF + (128 + 8 * n + 2 * c) * 4);
        cb[n] = lds64f(sm + MODB_OFF + (256 + 8 * n + 2 * c) * 4);
        xl[n] = pack2(acc[4 * n], acc[4 * n + 1]);
        xh[n] = pack2(acc[4 * n + 2], acc[4 * n + 3]);
      }
      mbar_wait(bars + 8 * B_STGE, 0);
      PROF_AT(tid == 0, 49);
      float nb[2], rstd[2];
      {
        uint32_t st[8];
        const uint4* sp = p.stats2 + (rb * 8 + (lane >> 4) * 4) * 128 + cw * 64 + warp * 16 + (lane & 15);
        ll_poll<4>([&](int i) { return sp + i * 128; }, tag, st);
        float mu, rs;
        row_stats(st, mu, rs);
        mu *= -rs;
        nb[0] = __shfl_sync(~0u, mu, r); rstd[0] = __shfl_sync(~0u, rs, r);
        nb[1] = __shfl_sync(~0u, mu, r + 8); rstd[1] = __shfl_sync(~0u, rs, r + 8);
      }
      PROF_AT(tid == 0, 9);
#pragma unroll
      for (int ch = 0; ch < 2; ch++) {
        uint32_t lo[8], hi[8];
#pragma unroll
        for (int t = 0; t < 8; t++) {
          const int n = ch * 8 + t;
          lo[t] = pack2((acc[4 * n] * rstd[0] + nb[0]) * cb[n].x + sb[n].x, (acc[4 * n + 1] * rstd[0] + nb[0]) * cb[n].y + sb[n].y);
          hi[t] = pack2((acc[4 * n + 2] * rstd[1] + nb[1]) * cb[n].x + sb[n].x, (acc[4 * n + 3] * rstd[1] + nb[1]) * cb[n].y + sb[n].y);
        }
        stage_slab(stg + ch * 16384 + cw * 8192, warp, lane, lo, hi);
        stage_done(bars + 8 * (B_STGF + ch), lane);
        tma_store2(&p.h2_st, stg + ch * 16384 + cw * 8192 + warp * 2048, j * 128 + ch * 64, rb * 128 + cw * 64 + warp * 16);
        asm volatile("cp.async.bulk.commit_group;" ::: "memory");
      }
      wg_bar(cw);
      PROF_AT(tid == 0, 10);
    }

    uint32_t pg[32], pu[32];
    {
      RING_IDS();
      LANE_IDS();
      Ring g{bars + 8 * B_FG, rbars + 8 * B_EG, 0, 0u, releaser TR(48)};
      float acc[128];
      {
        uint32_t prev = 0;
        uint4* x1p = p.x1 + (size_t)(rb * 128 + (warp * 16 + (lane >> 4)) * 2 + cw) * 128 + j * 16 + (lane & 15);
#pragma unroll 1
        for (int kb = 0; kb < 16; kb++) {
          kblock<256, 4, 49152>(acc, g, a_base + (kb < 2 ? STG_OFF + kb * 16384 : g.s * 49152), kb == 0, prev);
          if (kb == 0) {
            asm volatile("cp.async.bulk.wait_group 1;" ::: "memory");
            __syncwarp();
            cnt_signal(p.cnt + rb * 32 + C_H2A);
          }
          if (kb == 1) {
            asm volatile("cp.async.bulk.wait_group 0;" ::: "memory");
            __syncwarp();
            cnt_signal(p.cnt + rb * 32 + C_H2);
          }
          if (kb == 5) {
#pragma unroll
            for (int q = 0; q < 4; q++) x1p[q * 512] = make_uint4(xl[4 * q], xl[4 * q + 1], xl[4 * q + 2], xl[4 * q + 3]);
          }
          if (kb == 8) {
#pragma unroll
            for (int q = 0; q < 4; q++) x1p[(4 + q) * 512] = make_uint4(xh[4 * q], xh[4 * q + 1], xh[4 * q + 2], xh[4 * q + 3]);
          }
        }
        tile_end(acc, prev);
      }
      PROF_AT(tid == 0, 36);
#pragma unroll 1
      for (int t = 1; t < 3; t++) {
#pragma unroll
        for (int q = 0; q < 32; q++) {
          pg[q] = pack2(acc[2 * q], acc[2 * q + 1]);
          pu[q] = pack2(acc[64 + 2 * q], acc[64 + 2 * q + 1]);
        }
        uint32_t prev = 0;
#pragma unroll 1
        for (int blk = 0; blk < 4; blk++) {
          g.s = 0;
#pragma unroll
          for (int i = 0; i < 4; i++) {
            kblock<256, 4, 49152>(acc, g, a_base + i * 49152, blk == 0 && i == 0, prev);
            if ((blk & 1) == 0 && i == 0) mbar_wait(bars + 8 * (B_STGE + (blk >> 1)), t & 1);
            stmatrix2(slab + (blk >> 1) * 16384 + (((srow & 7) ^ ((blk & 1) * 4 + i)) << 4), swiglu2(pg[2 * i], pu[2 * i]), swiglu2(pg[2 * i + 1], pu[2 * i + 1]));
          }
#pragma unroll
          for (int q = 0; q < 24; q++) { pg[q] = pg[q + 8]; pu[q] = pu[q + 8]; }
          if (blk & 1) stage_done(bars + 8 * (B_STGF + (blk >> 1)), lane);
        }
        tile_end(acc, prev);
        PROF_AT(tid == 0, 36 + t);
      }
#pragma unroll
      for (int q = 0; q < 32; q++) {
        pg[q] = pack2(acc[2 * q], acc[2 * q + 1]);
        pu[q] = pack2(acc[64 + 2 * q], acc[64 + 2 * q + 1]);
      }
      PROF_AT(tid == 0, 11);
    }

    {
      RING_IDS();
      LANE_IDS();
      Ring g{bars + 8 * B_FD, rbars + 8 * B_ED, 0, 0u, releaser TR(96)};
      float acc[64];
      uint32_t prev = 0;
#pragma unroll 1
      for (int blk = 0; blk < 6; blk++) {
#pragma unroll
        for (int i = 0; i < 8; i++) {
          kblock<128, 6, 32768>(acc, g, a_base + g.s * 32768, (blk & ~2) == 0 && i == 0, prev);
          if ((blk & 1) == 0 && i == 0) mbar_wait(bars + 8 * (B_STGE + ((blk >> 1) & 1)), blk < 4);
          stmatrix1(slab + ((blk >> 1) & 1) * 16384 + (i & 1) * 1024 + (((srow & 7) ^ ((blk & 1) * 4 + (i >> 1))) << 4), swiglu2(pg[i], pu[i]));
        }
#pragma unroll
        for (int q = 0; q < 24; q++) { pg[q] = pg[q + 8]; pu[q] = pu[q + 8]; }
        if (blk & 1) stage_done(bars + 8 * (B_STGF + ((blk >> 1) & 1)), lane);
        if (blk == 1) {
          tile_end(acc, prev);
          PROF_AT(tid == 0, 39);
#pragma unroll
          for (int q = 0; q < 16; q++) {
            pg[16 + q] = pack2(acc[2 * q], acc[2 * q + 1]);
            pu[16 + q] = pack2(acc[32 + 2 * q], acc[32 + 2 * q + 1]);
          }
          PROF_AT(tid == 0, 12);
        }
      }
      uint4 x1[8];
      const int fl = fresh_tid() & 31;
      const uint4* x1p = p.x1 + (size_t)(rb * 128 + (warp * 16 + (fl >> 4)) * 2 + cw) * 128 + j * 16 + (fl & 15);
#pragma unroll
      for (int q = 0; q < 2; q++) {
#pragma unroll
        for (int e = 0; e < 4; e++) x1[4 * q + e] = ll_peek(x1p + (4 * q + e) * 512);
#pragma unroll 1
        for (int kb = 0; kb < 12; kb++) {
          if (q == 1 && kb == 6) g.releaser = false;
          kblock<128, 6, 32768>(acc, g, a_base + g.s * 32768, false, prev);
        }
      }
      mbar_wait(bars + 8 * (B_MODB + 1), 0);
      mbar_wait(bars + 8 * B_STGE, 1);
      mbar_wait(bars + 8 * (B_STGE + 1), 0);
      float2 gbv[16];
#pragma unroll
      for (int n = 0; n < 16; n++) gbv[n] = lds64f(sm + MODB_OFF + (384 + 8 * n + 2 * c) * 4);
      tile_end(acc, prev);
      PROF_AT(tid == 0, 13);
#pragma unroll
      for (int ch = 0; ch < 2; ch++) {
        uint32_t lo[8], hi[8];
#pragma unroll
        for (int t = 0; t < 8; t++) {
          const int n = ch * 8 + t;
          const float2 gb = gbv[n];
          const uint4 a = x1[n >> 2], b = x1[4 + (n >> 2)];
          const uint32_t xl = (n & 3) == 0 ? a.x : (n & 3) == 1 ? a.y : (n & 3) == 2 ? a.z : a.w;
          const uint32_t xh = (n & 3) == 0 ? b.x : (n & 3) == 1 ? b.y : (n & 3) == 2 ? b.z : b.w;
          lo[t] = pack2(bf_lo(xl) + gb.x * acc[4 * n], bf_hi(xl) + gb.y * acc[4 * n + 1]);
          hi[t] = pack2(bf_lo(xh) + gb.x * acc[4 * n + 2], bf_hi(xh) + gb.y * acc[4 * n + 3]);
        }
        stage_slab(stg + ch * 16384 + cw * 8192, warp, lane, lo, hi);
        asm volatile("fence.proxy.async.shared::cta;" ::: "memory");
        __syncwarp();
        tma_store3(&p.out, stg + ch * 16384 + cw * 8192 + warp * 2048, j * 128 + ch * 64, rb * 64 + warp * 16, cw);
      }
      asm volatile("cp.async.bulk.commit_group;" ::: "memory");
      if (lane == 0) mbar_arrive(bars + 8 * B_STGF);
      asm volatile("cp.async.bulk.wait_group.read 0;" ::: "memory");
      PROF_AT(tid == 0, 14);
    }
    if (blockIdx.x == 0 && threadIdx.x == 128) asm volatile("st.relaxed.gpu.global.u32 [%0], %1;" ::"l"(p.epoch), "r"(tag) : "memory");
  }
}

typedef CUresult (*EncodeFn)(CUtensorMap*, CUtensorMapDataType, cuuint32_t, void*, const cuuint64_t*, const cuuint64_t*,
                             const cuuint32_t*, const cuuint32_t*, CUtensorMapInterleave, CUtensorMapSwizzle,
                             CUtensorMapL2promotion, CUtensorMapFloatOOBfill);

void encode2d(EncodeFn fn, CUtensorMap* m, const void* ptr, uint64_t cols, uint64_t rows, uint32_t box_rows) {
  cuuint64_t dims[2] = {cols, rows};
  cuuint64_t strides[1] = {cols * 2};
  cuuint32_t box[2] = {64, box_rows};
  cuuint32_t es[2] = {1, 1};
  fn(m, CU_TENSOR_MAP_DATA_TYPE_BFLOAT16, 2, (void*)ptr, dims, strides, box, es, CU_TENSOR_MAP_INTERLEAVE_NONE,
     CU_TENSOR_MAP_SWIZZLE_128B, CU_TENSOR_MAP_L2_PROMOTION_L2_128B, CU_TENSOR_MAP_FLOAT_OOB_FILL_NONE);
}

}

extern "C" void kernel_launch(void* const* d_in, const int* in_sizes, int n_in, void* d_out, int out_size) {
  (void)in_sizes; (void)n_in; (void)out_size;
  void* fp = nullptr;
  cudaDriverEntryPointQueryResult qr;
  cudaGetDriverEntryPoint("cuTensorMapEncodeTiled", &fp, cudaEnableDefault, &qr);
  EncodeFn fn = (EncodeFn)fp;
  void *ph, *po, *ph2, *pact;
  cudaGetSymbolAddress(&ph, g_h);
  cudaGetSymbolAddress(&po, g_o);
  ph2 = ph;
  cudaGetSymbolAddress(&pact, g_act);
  Params p;
  encode2d(fn, &p.h, ph, DM, SEQ, 128);
  encode2d(fn, &p.o_ld, po, DM, SEQ, 128);
  encode2d(fn, &p.h2, ph2, DM, SEQ, 128);
  encode2d(fn, &p.act, pact, FF, SEQ, 128);
  encode2d(fn, &p.act_st, pact, FF, SEQ, 32);
  encode2d(fn, &p.wm, d_in[8], 6 * DM, DM, 64);
  encode2d(fn, &p.o_st, po, DM, SEQ, 16);
  encode2d(fn, &p.h2_st, ph2, DM, SEQ, 16);
  encode2d(fn, &p.wqkv, d_in[1], 3 * DM, DM, 64);
  encode2d(fn, &p.wqkv32, d_in[1], 3 * DM, DM, 32);
  encode2d(fn, &p.wo, d_in[2], DM, DM, 64);
  encode2d(fn, &p.wg, d_in[4], FF, DM, 64);
  encode2d(fn, &p.wu, d_in[5], FF, DM, 64);
  encode2d(fn, &p.wd, d_in[6], DM, FF, 64);
  {
    cuuint64_t dims[3] = {DM, SEQ / 2, 2};
    cuuint64_t strides[2] = {DM * 4, DM * 2};
    cuuint32_t box[3] = {64, 16, 1};
    cuuint32_t es[3] = {1, 1, 1};
    fn(&p.out, CU_TENSOR_MAP_DATA_TYPE_BFLOAT16, 3, d_out, dims, strides, box, es, CU_TENSOR_MAP_INTERLEAVE_NONE,
       CU_TENSOR_MAP_SWIZZLE_128B, CU_TENSOR_MAP_L2_PROMOTION_L2_128B, CU_TENSOR_MAP_FLOAT_OOB_FILL_NONE);
  }
  p.x = (const bf16*)d_in[0];
  p.c = (const bf16*)d_in[7];
  p.wmod = (const bf16*)d_in[8];
  for (int cl = 0; cl < 64; cl++) {
    const int grp = cl < 4 ? 0 : (cl < 36 ? (cl - 4) & 7 : 1 + (cl - 36) % 7);
    const int j = cl < 4 ? 4 + cl : (cl < 36 ? (cl - 4) >> 3 : 4 + (cl - 36) / 7);
    p.slot[cl] = (uint8_t)(grp * 8 + j);
  }
  void* q;
  p.x1 = (uint4*)d_out;
  cudaGetSymbolAddress(&q, g_modll); p.modll = (uint4*)q;
  cudaGetSymbolAddress(&q, g_halo); p.halo = (uint4*)q;
  cudaGetSymbolAddress(&q, g_stats); p.stats1 = (uint4*)q; p.stats2 = p.stats1 + SEQ * 8;
  cudaGetSymbolAddress(&q, g_cnt); p.cnt = (unsigned*)q;
  cudaGetSymbolAddress(&q, g_epoch); p.epoch = (unsigned*)q;

  cudaFuncSetAttribute(fused_kernel, cudaFuncAttributeMaxDynamicSharedMemorySize, SMEM_BYTES);
  cudaLaunchConfig_t cfg = {};
  cfg.gridDim = dim3(NCTA + 4);
  cfg.blockDim = dim3(384);
  cfg.dynamicSmemBytes = SMEM_BYTES;
  cfg.stream = cudaStreamPerThread;
  cudaLaunchAttribute at[1];
  at[0].id = cudaLaunchAttributeClusterDimension;
  at[0].val.clusterDim.x = 2; at[0].val.clusterDim.y = 1; at[0].val.clusterDim.z = 1;
  cfg.attrs = at;
  cfg.numAttrs = 1;
  cudaLaunchKernelEx(&cfg, fused_kernel, p);
}
```

```cpp
#include <cuda_runtime.h>
#include <cuda_bf16.h>
#include <cuda.h>
#include <stdint.h>

typedef __nv_bfloat16 bf16;

#define PAUSE 200
#define WMDELAY 2000
#define BDELAY 1500
#define NPRE0 3
#define NPRE1 1
#define ALIAS 1

#define PFW 8000
#define PFP 0

#define OSIG 3

__device__ __forceinline__ void wgmma_ss_n128(float (&d)[64], uint32_t da, uint32_t db, int scale_d) {
  asm volatile("{\n.reg .pred p;\n.reg .b64 da, db;\nsetp.ne.b32 p, %66, 0;\n"
    "mov.b64 da, {%64, 0x40000040};\nmov.b64 db, {%65, 0x40000040};\n"
    "wgmma.mma_async.sync.aligned.m64n128k16.f32.bf16.bf16 "
    "{%0, %1, %2, %3, %4, %5, %6, %7, %8, %9, %10, %11, %12, %13, %14, %15, "
    "%16, %17, %18, %19, %20, %21, %22, %23, %24, %25, %26, %27, %28, %29, %30, %31, "
    "%32, %33, %34, %35, %36, %37, %38, %39, %40, %41, %42, %43, %44, %45, %46, %47, "
    "%48, %49, %50, %51, %52, %53, %54, %55, %56, %57, %58, %59, %60, %61, %62, %63}, "
    "da, db, p, 1, 1, 0, 1;\n}\n"
    : "+f"(d[0]), "+f"(d[1]), "+f"(d[2]), "+f"(d[3]), "+f"(d[4]), "+f"(d[5]), "+f"(d[6]), "+f"(d[7]),
      "+f"(d[8]), "+f"(d[9]), "+f"(d[10]), "+f"(d[11]), "+f"(d[12]), "+f"(d[13]), "+f"(d[14]), "+f"(d[15]),
      "+f"(d[16]), "+f"(d[17]), "+f"(d[18]), "+f"(d[19]), "+f"(d[20]), "+f"(d[21]), "+f"(d[22]), "+f"(d[23]),
      "+f"(d[24]), "+f"(d[25]), "+f"(d[26]), "+f"(d[27]), "+f"(d[28]), "+f"(d[29]), "+f"(d[30]), "+f"(d[31]),
      "+f"(d[32]), "+f"(d[33]), "+f"(d[34]), "+f"(d[35]), "+f"(d[36]), "+f"(d[37]), "+f"(d[38]), "+f"(d[39]),
      "+f"(d[40]), "+f"(d[41]), "+f"(d[42]), "+f"(d[43]), "+f"(d[44]), "+f"(d[45]), "+f"(d[46]), "+f"(d[47]),
      "+f"(d[48]), "+f"(d[49]), "+f"(d[50]), "+f"(d[51]), "+f"(d[52]), "+f"(d[53]), "+f"(d[54]), "+f"(d[55]),
      "+f"(d[56]), "+f"(d[57]), "+f"(d[58]), "+f"(d[59]), "+f"(d[60]), "+f"(d[61]), "+f"(d[62]), "+f"(d[63])
    : "r"(da), "r"(db), "r"(scale_d));
}

__device__ __forceinline__ void wgmma_ss_n192(float (&d)[96], uint32_t da, uint32_t db, int scale_d) {
  asm volatile("{\n.reg .pred p;\n.reg .b64 da, db;\nsetp.ne.b32 p, %98, 0;\n"
    "mov.b64 da, {%96, 0x40000040};\nmov.b64 db, {%97, 0x40000040};\n"
    "wgmma.mma_async.sync.aligned.m64n192k16.f32.bf16.bf16 "
    "{%0, %1, %2, %3, %4, %5, %6, %7, %8, %9, %10, %11, %12, %13, %14, %15, "
    "%16, %17, %18, %19, %20, %21, %22, %23, %24, %25, %26, %27, %28, %29, %30, %31, "
    "%32, %33, %34, %35, %36, %37, %38, %39, %40, %41, %42, %43, %44, %45, %46, %47, "
    "%48, %49, %50, %51, %52, %53, %54, %55, %56, %57, %58, %59, %60, %61, %62, %63, "
    "%64, %65, %66, %67, %68, %69, %70, %71, %72, %73, %74, %75, %76, %77, %78, %79, "
    "%80, %81, %82, %83, %84, %85, %86, %87, %88, %89, %90, %91, %92, %93, %94, %95}, "
    "da, db, p, 1, 1, 0, 1;\n}\n"
    : "+f"(d[0]), "+f"(d[1]), "+f"(d[2]), "+f"(d[3]), "+f"(d[4]), "+f"(d[5]), "+f"(d[6]), "+f"(d[7]),
      "+f"(d[8]), "+f"(d[9]), "+f"(d[10]), "+f"(d[11]), "+f"(d[12]), "+f"(d[13]), "+f"(d[14]), "+f"(d[15]),
      "+f"(d[16]), "+f"(d[17]), "+f"(d[18]), "+f"(d[19]), "+f"(d[20]), "+f"(d[21]), "+f"(d[22]), "+f"(d[23]),
      "+f"(d[24]), "+f"(d[25]), "+f"(d[26]), "+f"(d[27]), "+f"(d[28]), "+f"(d[29]), "+f"(d[30]), "+f"(d[31]),
      "+f"(d[32]), "+f"(d[33]), "+f"(d[34]), "+f"(d[35]), "+f"(d[36]), "+f"(d[37]), "+f"(d[38]), "+f"(d[39]),
      "+f"(d[40]), "+f"(d[41]), "+f"(d[42]), "+f"(d[43]), "+f"(d[44]), "+f"(d[45]), "+f"(d[46]), "+f"(d[47]),
      "+f"(d[48]), "+f"(d[49]), "+f"(d[50]), "+f"(d[51]), "+f"(d[52]), "+f"(d[53]), "+f"(d[54]), "+f"(d[55]),
      "+f"(d[56]), "+f"(d[57]), "+f"(d[58]), "+f"(d[59]), "+f"(d[60]), "+f"(d[61]), "+f"(d[62]), "+f"(d[63]),
      "+f"(d[64]), "+f"(d[65]), "+f"(d[66]), "+f"(d[67]), "+f"(d[68]), "+f"(d[69]), "+f"(d[70]), "+f"(d[71]),
      "+f"(d[72]), "+f"(d[73]), "+f"(d[74]), "+f"(d[75]), "+f"(d[76]), "+f"(d[77]), "+f"(d[78]), "+f"(d[79]),
      "+f"(d[80]), "+f"(d[81]), "+f"(d[82]), "+f"(d[83]), "+f"(d[84]), "+f"(d[85]), "+f"(d[86]), "+f"(d[87]),
      "+f"(d[88]), "+f"(d[89]), "+f"(d[90]), "+f"(d[91]), "+f"(d[92]), "+f"(d[93]), "+f"(d[94]), "+f"(d[95])
    : "r"(da), "r"(db), "r"(scale_d));
}

__device__ __forceinline__ void wgmma_ss_n256(float (&d)[128], uint32_t da, uint32_t db, int scale_d) {
  asm volatile("{\n.reg .pred p;\n.reg .b64 da, db;\nsetp.ne.b32 p, %130, 0;\n"
    "mov.b64 da, {%128, 0x40000040};\nmov.b64 db, {%129, 0x40000040};\n"
    "wgmma.mma_async.sync.aligned.m64n256k16.f32.bf16.bf16 "
    "{%0, %1, %2, %3, %4, %5, %6, %7, %8, %9, %10, %11, %12, %13, %14, %15, "
    "%16, %17, %18, %19, %20, %21, %22, %23, %24, %25, %26, %27, %28, %29, %30, %31, "
    "%32, %33, %34, %35, %36, %37, %38, %39, %40, %41, %42, %43, %44, %45, %46, %47, "
    "%48, %49, %50, %51, %52, %53, %54, %55, %56, %57, %58, %59, %60, %61, %62, %63, "
    "%64, %65, %66, %67, %68, %69, %70, %71, %72, %73, %74, %75, %76, %77, %78, %79, "
    "%80, %81, %82, %83, %84, %85, %86, %87, %88, %89, %90, %91, %92, %93, %94, %95, "
    "%96, %97, %98, %99, %100, %101, %102, %103, %104, %105, %106, %107, %108, %109, %110, %111, "
    "%112, %113, %114, %115, %116, %117, %118, %119, %120, %121, %122, %123, %124, %125, %126, %127}, "
    "da, db, p, 1, 1, 0, 1;\n}\n"
    : "+f"(d[0]), "+f"(d[1]), "+f"(d[2]), "+f"(d[3]), "+f"(d[4]), "+f"(d[5]), "+f"(d[6]), "+f"(d[7]),
      "+f"(d[8]), "+f"(d[9]), "+f"(d[10]), "+f"(d[11]), "+f"(d[12]), "+f"(d[13]), "+f"(d[14]), "+f"(d[15]),
      "+f"(d[16]), "+f"(d[17]), "+f"(d[18]), "+f"(d[19]), "+f"(d[20]), "+f"(d[21]), "+f"(d[22]), "+f"(d[23]),
      "+f"(d[24]), "+f"(d[25]), "+f"(d[26]), "+f"(d[27]), "+f"(d[28]), "+f"(d[29]), "+f"(d[30]), "+f"(d[31]),
      "+f"(d[32]), "+f"(d[33]), "+f"(d[34]), "+f"(d[35]), "+f"(d[36]), "+f"(d[37]), "+f"(d[38]), "+f"(d[39]),
      "+f"(d[40]), "+f"(d[41]), "+f"(d[42]), "+f"(d[43]), "+f"(d[44]), "+f"(d[45]), "+f"(d[46]), "+f"(d[47]),
      "+f"(d[48]), "+f"(d[49]), "+f"(d[50]), "+f"(d[51]), "+f"(d[52]), "+f"(d[53]), "+f"(d[54]), "+f"(d[55]),
      "+f"(d[56]), "+f"(d[57]), "+f"(d[58]), "+f"(d[59]), "+f"(d[60]), "+f"(d[61]), "+f"(d[62]), "+f"(d[63]),
      "+f"(d[64]), "+f"(d[65]), "+f"(d[66]), "+f"(d[67]), "+f"(d[68]), "+f"(d[69]), "+f"(d[70]), "+f"(d[71]),
      "+f"(d[72]), "+f"(d[73]), "+f"(d[74]), "+f"(d[75]), "+f"(d[76]), "+f"(d[77]), "+f"(d[78]), "+f"(d[79]),
      "+f"(d[80]), "+f"(d[81]), "+f"(d[82]), "+f"(d[83]), "+f"(d[84]), "+f"(d[85]), "+f"(d[86]), "+f"(d[87]),
      "+f"(d[88]), "+f"(d[89]), "+f"(d[90]), "+f"(d[91]), "+f"(d[92]), "+f"(d[93]), "+f"(d[94]), "+f"(d[95]),
      "+f"(d[96]), "+f"(d[97]), "+f"(d[98]), "+f"(d[99]), "+f"(d[100]), "+f"(d[101]), "+f"(d[102]), "+f"(d[103]),
      "+f"(d[104]), "+f"(d[105]), "+f"(d[106]), "+f"(d[107]), "+f"(d[108]), "+f"(d[109]), "+f"(d[110]), "+f"(d[111]),
      "+f"(d[112]), "+f"(d[113]), "+f"(d[114]), "+f"(d[115]), "+f"(d[116]), "+f"(d[117]), "+f"(d[118]), "+f"(d[119]),
      "+f"(d[120]), "+f"(d[121]), "+f"(d[122]), "+f"(d[123]), "+f"(d[124]), "+f"(d[125]), "+f"(d[126]), "+f"(d[127])
    : "r"(da), "r"(db), "r"(scale_d));
}

namespace {

constexpr int SEQ = 2048, DM = 1024, FF = 3584;
constexpr int NCTA = 128;

constexpr uint32_t STG_OFF = 196608;
constexpr uint32_t MISC_OFF = STG_OFF + 32768;
constexpr uint32_t SMEM_BYTES = MISC_OFF + 3072;
constexpr uint32_t RED_OFF = 2 * 49152;
constexpr uint32_t MODB_OFF = MISC_OFF + 512;

enum { B_FQ = 0, B_EQ = 4, B_FW = 8, B_EW = 14, B_FG = 20, B_EG = 24, B_FD = 28, B_ED = 34,
       B_STGF = 40, B_MODB = 42, B_MODA = 45, B_RDY = 48, B_STGE = 56, B_COUNT = 58 };
enum { C_H = 0, C_O = 1, C_H2 = 3, C_ACT = 4, C_HA = 8, C_H2A = 9 };

struct Params {
  CUtensorMap h, o_ld, o_st, h2, act, out, wqkv, wqkv32, wo, wg, wu, wd, act_st, h2_st, wm;
  const bf16* x;
  const bf16* c;
  const bf16* wmod;
  uint4* x1;
  uint4* modll;
  uint4* halo;
  uint2* stats1;
  uint2* stats2;
  unsigned* cnt;
  unsigned* epoch;
  uint8_t slot[64];
};

__device__ __align__(1024) bf16 g_h[SEQ * DM];
__device__ __align__(1024) bf16 g_o[SEQ * DM];
__device__ __align__(1024) bf16 g_act[SEQ * FF];
__device__ __align__(1024) uint4 g_modll[3072 / 2];
__device__ __align__(1024) uint4 g_halo[16 * 8 * 2 * 2 * 8 * 32];
__device__ __align__(1024) uint2 g_stats[2 * SEQ * 8];
__device__ __align__(1024) unsigned g_cnt[16 * 32];
__device__ uint4 g_epoch;
#define TR(off)

__device__ __forceinline__ uint32_t smem_u32(const void* p) { return (uint32_t)__cvta_generic_to_shared(p); }
__device__ __forceinline__ void mbar_init(uint32_t bar, uint32_t count) {
  asm volatile("mbarrier.init.shared::cta.b64 [%0], %1;" ::"r"(bar), "r"(count));
}
__device__ __forceinline__ void mbar_arrive(uint32_t bar) {
  asm volatile("mbarrier.arrive.shared::cta.b64 _, [%0];" ::"r"(bar) : "memory");
}
__device__ __forceinline__ void mbar_arrive_cluster(uint32_t cluster_addr) {
  asm volatile("mbarrier.arrive.shared::cluster.b64 _, [%0];" ::"r"(cluster_addr) : "memory");
}
__device__ __forceinline__ uint32_t mapa(uint32_t addr, uint32_t cta) {
  uint32_t r;
  asm volatile("mapa.shared::cluster.u32 %0, %1, %2;" : "=r"(r) : "r"(addr), "r"(cta));
  return r;
}
__device__ __forceinline__ void mbar_wait(uint32_t bar, uint32_t parity) {
  asm volatile(
      "{\n.reg .pred p;\n"
      "WAIT_%=:\n"
      "mbarrier.try_wait.parity.shared::cta.b64 p, [%0], %1;\n"
      "@!p bra WAIT_%=;\n}\n" ::"r"(bar), "r"(parity) : "memory");
}
__device__ __forceinline__ void mbar_wait_watchdog(uint32_t bar, uint32_t parity) {
  asm volatile(
      "{\n.reg .pred p;\n.reg .u64 t0, t1;\nmov.u64 t0, %%globaltimer;\n"
      "WAIT_%=:\n"
      "mbarrier.try_wait.parity.shared::cta.b64 p, [%0], %1;\n"
      "@p bra DONE_%=;\n"
      "mov.u64 t1, %%globaltimer;\n"
      "sub.u64 t1, t1, t0;\n"
      "setp.lt.u64 p, t1, 2000000000;\n"
      "@p bra WAIT_%=;\n"
      "trap;\n"
      "DONE_%=:\n}\n" ::"r"(bar), "r"(parity) : "memory");
}
__device__ __forceinline__ void cnt_wait(const unsigned* p, unsigned target) {
  asm volatile(
      "{\n.reg .pred p;\n.reg .u32 v;\n.reg .s32 d;\n"
      "WAIT_%=:\n"
      "ld.relaxed.gpu.global.u32 v, [%0];\n"
      "sub.s32 d, v, %1;\n"
      "setp.lt.s32 p, d, 0;\n"
      "@p bra WAIT_%=;\n"
      "fence.proxy.async.global;\n"
      "}\n" ::"l"(p), "r"(target) : "memory");
}
__device__ __forceinline__ void cnt_wait_lazy(const unsigned* p, unsigned target) {
  asm volatile(
      "{\n.reg .pred p;\n.reg .u32 v;\n.reg .s32 d;\n"
      "WAIT_%=:\n"
      "nanosleep.u32 400;\n"
      "ld.relaxed.gpu.global.u32 v, [%0];\n"
      "sub.s32 d, v, %1;\n"
      "setp.lt.s32 p, d, 0;\n"
      "@p bra WAIT_%=;\n"
      "fence.proxy.async.global;\n"
      "}\n" ::"l"(p), "r"(target) : "memory");
}
__device__ __forceinline__ void cnt_signal(unsigned* p) {
  asm volatile("{\n.reg .pred p;\nelect.sync _|p, 0xffffffff;\n@p red.relaxed.gpu.global.add.u32 [%0], 1;\n}\n" ::"l"(p) : "memory");
}
__device__ __forceinline__ void ll_store(uint4* p, uint32_t a, uint32_t b, uint32_t tag) {
  asm volatile("st.relaxed.gpu.global.v2.b64 [%0], {%1, %2};" ::"l"(p), "l"((uint64_t)a | ((uint64_t)tag << 32)),
               "l"((uint64_t)b | ((uint64_t)tag << 32)) : "memory");
}
__device__ __forceinline__ uint4 ll_peek(const uint4* p) {
  uint4 v;
  asm volatile("ld.relaxed.gpu.global.v4.u32 {%0, %1, %2, %3}, [%4];" : "=r"(v.x), "=r"(v.y), "=r"(v.z), "=r"(v.w) : "l"(p) : "memory");
  return v;
}
template <int N, int SLEEP = 0, class F>
__device__ __forceinline__ void ll_poll(F addr, uint32_t tag, uint32_t (&out)[2 * N]) {
  for (;;) {
    uint4 v[N];
#pragma unroll
    for (int i = 0; i < N; i++) v[i] = ll_peek(addr(i));
    uint32_t bad = 0;
#pragma unroll
    for (int i = 0; i < N; i++) {
      bad |= (v[i].y ^ tag) | (v[i].w ^ tag);
      out[2 * i] = v[i].x;
      out[2 * i + 1] = v[i].z;
    }
    if (__all_sync(~0u, bad == 0)) break;
    if (SLEEP) __nanosleep(SLEEP);
  }
}
constexpr uint64_t POLICY_EVICT_FIRST = 0x12F0000000000000ull;
__device__ __forceinline__ void expect_tx_elect(uint32_t bar, uint32_t bytes) {
  asm volatile("{\n.reg .pred p;\nelect.sync _|p, 0xffffffff;\n@p mbarrier.arrive.expect_tx.shared::cta.b64 _, [%0], %1;\n}\n" ::"r"(bar), "r"(bytes) : "memory");
}
__device__ __forceinline__ void arrive_elect(uint32_t bar) {
  asm volatile("{\n.reg .pred p;\nelect.sync _|p, 0xffffffff;\n@p mbarrier.arrive.shared::cta.b64 _, [%0];\n}\n" ::"r"(bar) : "memory");
}
__device__ __forceinline__ void tma_load(uint32_t dst, const CUtensorMap* m, uint32_t bar, int c0, int c1) {
  asm volatile("{\n.reg .pred p;\nelect.sync _|p, 0xffffffff;\n"
               "@p cp.async.bulk.tensor.2d.shared::cluster.global.mbarrier::complete_tx::bytes [%0], [%1, {%3, %4}], [%2];\n}\n"
               ::"r"(dst), "l"(m), "r"(bar), "r"(c0), "r"(c1) : "memory");
}
__device__ __forceinline__ void tma_load_mc(uint32_t dst, const CUtensorMap* m, uint32_t bar, int c0, int c1) {
  asm volatile("{\n.reg .pred p;\nelect.sync _|p, 0xffffffff;\n"
               "@p cp.async.bulk.tensor.2d.shared::cluster.global.mbarrier::complete_tx::bytes.multicast::cluster.L2::cache_hint [%0], [%1, {%3, %4}], [%2], %5, %6;\n}\n"
               ::"r"(dst), "l"(m), "r"(bar), "r"(c0), "r"(c1), "h"((uint16_t)3), "l"(POLICY_EVICT_FIRST) : "memory");
}
__device__ __forceinline__ void tma_load_ef(uint32_t dst, const CUtensorMap* m, uint32_t bar, int c0, int c1) {
  asm volatile("{\n.reg .pred p;\nelect.sync _|p, 0xffffffff;\n"
               "@p cp.async.bulk.tensor.2d.shared::cluster.global.mbarrier::complete_tx::bytes.L2::cache_hint [%0], [%1, {%3, %4}], [%2], %5;\n}\n"
               ::"r"(dst), "l"(m), "r"(bar), "r"(c0), "r"(c1), "l"(POLICY_EVICT_FIRST) : "memory");
}
__device__ __forceinline__ void tma_store2(const CUtensorMap* m, uint32_t src, int c0, int c1) {
  asm volatile("{\n.reg .pred p;\nelect.sync _|p, 0xffffffff;\n"
               "@p cp.async.bulk.tensor.2d.global.shared::cta.bulk_group [%0, {%2, %3}], [%1];\n}\n"
               ::"l"(m), "r"(src), "r"(c0), "r"(c1) : "memory");
}
__device__ __forceinline__ void tma_store3(const CUtensorMap* m, uint32_t src, int c0, int c1, int c2) {
  asm volatile("{\n.reg .pred p;\nelect.sync _|p, 0xffffffff;\n"
               "@p cp.async.bulk.tensor.3d.global.shared::cta.bulk_group [%0, {%2, %3, %4}], [%1];\n}\n"
               ::"l"(m), "r"(src), "r"(c0), "r"(c1), "r"(c2) : "memory");
}
__device__ __forceinline__ void store_pause(bool sleep) {
  asm volatile("cp.async.bulk.commit_group;" ::: "memory");
  asm volatile("cp.async.bulk.wait_group.read 0;" ::: "memory");
  if (sleep) __nanosleep(PAUSE);
}
__device__ __forceinline__ void l2_prefetch_tile(const CUtensorMap* m, int c0, int c1) {
  asm volatile("{\n.reg .pred p;\nelect.sync _|p, 0xffffffff;\n@p cp.async.bulk.prefetch.tensor.2d.L2.global [%0, {%1, %2}];\n}\n"
               ::"l"(m), "r"(c0), "r"(c1) : "memory");
}
__device__ __forceinline__ void prefetch_map(const CUtensorMap* m) {
  asm volatile("prefetch.tensormap [%0];" ::"l"(m) : "memory");
}
__device__ __forceinline__ void wg_fence() { asm volatile("wgmma.fence.sync.aligned;" ::: "memory"); }
__device__ __forceinline__ void wg_commit() { asm volatile("wgmma.commit_group.sync.aligned;" ::: "memory"); }
template <int N>
__device__ __forceinline__ void wg_wait() { asm volatile("wgmma.wait_group.sync.aligned %0;" ::"n"(N) : "memory"); }
__device__ __forceinline__ void bar_sync(int id, int n) { asm volatile("bar.sync %0, %1;" ::"r"(id), "r"(n) : "memory"); }
__device__ __forceinline__ void wg_bar(int cw) {
  asm volatile("{\n.reg .pred p;\nsetp.ne.s32 p, %0, 0;\n@p bar.sync 3, 128;\n@!p bar.sync 2, 128;\n}\n" ::"r"(cw) : "memory");
}
__device__ __forceinline__ void cluster_arrive_relaxed() { asm volatile("barrier.cluster.arrive.relaxed.aligned;" ::: "memory"); }
__device__ __forceinline__ void cluster_wait() { asm volatile("barrier.cluster.wait.acquire.aligned;" ::: "memory"); }
__device__ __forceinline__ uint32_t load_epoch(const unsigned* p) {
  uint32_t e;
  asm volatile("ld.relaxed.gpu.global.u32 %0, [%1];" : "=r"(e) : "l"(p) : "memory");
  return e;
}
__device__ __forceinline__ uint32_t pack2(float lo, float hi) {
  uint32_t r;
  asm("cvt.rn.bf16x2.f32 %0, %1, %2;" : "=r"(r) : "f"(hi), "f"(lo));
  return r;
}
__device__ __forceinline__ float bf_lo(uint32_t v) { return __uint_as_float(v << 16); }
__device__ __forceinline__ float bf_hi(uint32_t v) { return __uint_as_float(v & 0xffff0000u); }
__device__ __forceinline__ uint32_t fma_bf2(uint32_t a, uint32_t b, uint32_t c) {
  uint32_t d;
  asm("fma.rn.bf16x2 %0, %1, %2, %3;" : "=r"(d) : "r"(a), "r"(b), "r"(c));
  return d;
}
__device__ __forceinline__ float bf_round(float v) { return __bfloat162float(__float2bfloat16_rn(v)); }
__device__ __forceinline__ float silu_f(float v) { return __fdividef(v, 1.0f + __expf(-v)); }
__device__ __forceinline__ uint4 ldg_nc(const void* p) {
  uint4 v;
  asm volatile("ld.global.nc.L1::no_allocate.v4.u32 {%0, %1, %2, %3}, [%4];" : "=r"(v.x), "=r"(v.y), "=r"(v.z), "=r"(v.w) : "l"(p));
  return v;
}
__device__ __forceinline__ void stmatrix4(uint32_t addr, uint32_t a, uint32_t b, uint32_t c, uint32_t d) {
  asm volatile("stmatrix.sync.aligned.m8n8.x4.shared.b16 [%0], {%1, %2, %3, %4};" ::"r"(addr), "r"(a), "r"(b), "r"(c), "r"(d) : "memory");
}
__device__ __forceinline__ void stmatrix2(uint32_t addr, uint32_t a, uint32_t b) {
  asm volatile("stmatrix.sync.aligned.m8n8.x2.shared.b16 [%0], {%1, %2};" ::"r"(addr), "r"(a), "r"(b) : "memory");
}
__device__ __forceinline__ void stmatrix1(uint32_t addr, uint32_t a) {
  asm volatile("stmatrix.sync.aligned.m8n8.x1.shared.b16 [%0], {%1};" ::"r"(addr), "r"(a) : "memory");
}
__device__ __forceinline__ uint32_t movmatrix(uint32_t a) {
  uint32_t d;
  asm("movmatrix.sync.aligned.m8n8.trans.b16 %0, %1;" : "=r"(d) : "r"(a));
  return d;
}
__device__ __forceinline__ void mma16816(float (&d)[4], uint32_t a0, uint32_t a1, uint32_t a2, uint32_t a3, uint32_t b0, uint32_t b1) {
  asm("mma.sync.aligned.m16n8k16.row.col.f32.bf16.bf16.f32 {%0, %1, %2, %3}, {%4, %5, %6, %7}, {%8, %9}, {%0, %1, %2, %3};"
               : "+f"(d[0]), "+f"(d[1]), "+f"(d[2]), "+f"(d[3]) : "r"(a0), "r"(a1), "r"(a2), "r"(a3), "r"(b0), "r"(b1));
}
__device__ __forceinline__ void mma1688(float (&d)[4], uint32_t a0, uint32_t a1, uint32_t b0) {
  asm("mma.sync.aligned.m16n8k8.row.col.f32.bf16.bf16.f32 {%0, %1, %2, %3}, {%4, %5}, {%6}, {%0, %1, %2, %3};"
               : "+f"(d[0]), "+f"(d[1]), "+f"(d[2]), "+f"(d[3]) : "r"(a0), "r"(a1), "r"(b0));
}
__device__ __forceinline__ void ldmatrix4t(uint32_t (&b)[4], uint32_t addr) {
  asm volatile("ldmatrix.sync.aligned.m8n8.x4.trans.shared.b16 {%0, %1, %2, %3}, [%4];" : "=r"(b[0]), "=r"(b[1]), "=r"(b[2]), "=r"(b[3]) : "r"(addr) : "memory");
}
__device__ __forceinline__ void ldmatrix4(uint32_t& a, uint32_t& b, uint32_t& c, uint32_t& d, uint32_t addr) {
  asm volatile("ldmatrix.sync.aligned.m8n8.x4.shared.b16 {%0, %1, %2, %3}, [%4];" : "=r"(a), "=r"(b), "=r"(c), "=r"(d) : "r"(addr) : "memory");
}
__device__ __forceinline__ void cp_async16(uint32_t dst, const void* src) {
  asm volatile("cp.async.cg.shared.global.L2::cache_hint [%0], [%1], 16, %2;" ::"r"(dst), "l"(src), "l"(POLICY_EVICT_FIRST) : "memory");
}
__device__ __forceinline__ uint32_t lds32(uint32_t addr) {
  uint32_t v;
  asm volatile("ld.shared.u32 %0, [%1];" : "=r"(v) : "r"(addr) : "memory");
  return v;
}
__device__ __forceinline__ void sts64f(uint32_t addr, float a, float b) {
  asm volatile("st.shared.v2.f32 [%0], {%1, %2};" ::"r"(addr), "f"(a), "f"(b) : "memory");
}
constexpr float QK_SCALE = 0.17677669529663687f;
__device__ __forceinline__ float softmax8(float& p0, float& p1) {
  float m = fmaxf(p0, p1);
  m = fmaxf(m, __shfl_xor_sync(~0u, m, 1));
  m = fmaxf(m, __shfl_xor_sync(~0u, m, 2));
  asm("ex2.approx.ftz.f32 %0, %1;" : "=f"(p0) : "f"((p0 - m) * 1.4426950408889634f));
  asm("ex2.approx.ftz.f32 %0, %1;" : "=f"(p1) : "f"((p1 - m) * 1.4426950408889634f));
  float s = p0 + p1;
  s += __shfl_xor_sync(~0u, s, 1);
  s += __shfl_xor_sync(~0u, s, 2);
  float r;
  asm("rcp.approx.ftz.f32 %0, %1;" : "=f"(r) : "f"(s));
  return r;
}
__device__ __forceinline__ void sts128(uint32_t addr, uint32_t a, uint32_t b, uint32_t c, uint32_t d) {
  asm volatile("st.shared.v4.u32 [%0], {%1, %2, %3, %4};" ::"r"(addr), "r"(a), "r"(b), "r"(c), "r"(d) : "memory");
}
__device__ __forceinline__ uint4 lds128(uint32_t addr) {
  uint4 v;
  asm volatile("ld.shared.v4.u32 {%0, %1, %2, %3}, [%4];" : "=r"(v.x), "=r"(v.y), "=r"(v.z), "=r"(v.w) : "r"(addr) : "memory");
  return v;
}
__device__ __forceinline__ float2 lds64f(uint32_t addr) {
  float2 v;
  asm volatile("ld.shared.v2.f32 {%0, %1}, [%2];" : "=f"(v.x), "=f"(v.y) : "r"(addr) : "memory");
  return v;
}
#define PROF_AT(cond, slot) do {} while (0)

constexpr uint32_t SMEM_BASE = 1024;
constexpr uint32_t DESC_A = (1u << 16) | (SMEM_BASE >> 4);
constexpr uint32_t DESC_B = ((8192u >> 4) << 16) | ((SMEM_BASE + 16384) >> 4);

template <int BN> struct Wg;
template <> struct Wg<128> { static __device__ __forceinline__ void mma(float (&d)[64], uint32_t a, uint32_t b, int s) { wgmma_ss_n128(d, a, b, s); } };
template <> struct Wg<192> { static __device__ __forceinline__ void mma(float (&d)[96], uint32_t a, uint32_t b, int s) { wgmma_ss_n192(d, a, b, s); } };
template <> struct Wg<256> { static __device__ __forceinline__ void mma(float (&d)[128], uint32_t a, uint32_t b, int s) { wgmma_ss_n256(d, a, b, s); } };

struct Ring {
  uint32_t full0, rel0;
  int s;
  uint32_t ph;
  bool releaser;
};

template <int N>
__device__ __forceinline__ void fence_regs(float (&a)[N]) {
#pragma unroll
  for (int i = 0; i < N; i++) asm volatile("" : "+f"(a[i])::"memory");
}

template <int BN, int NST, uint32_t STAGE>
__device__ __forceinline__ void kblock(float (&acc)[BN / 2], Ring& g, uint32_t a_addr, bool zero, uint32_t& prev) {
  mbar_wait(g.full0 + 8 * g.s, g.ph);
  const uint32_t da = DESC_A + (a_addr >> 4);
  const uint32_t db = DESC_B + g.s * (STAGE >> 4);
  wg_fence();
#pragma unroll
  for (int k = 0; k < 4; k++) Wg<BN>::mma(acc, da + k * 2, db + k * 128, !(zero && k == 0));
  wg_commit();
  wg_wait<1>();
  if (prev != 0) mbar_arrive_cluster(prev);
  prev = g.releaser ? g.rel0 + 8 * g.s : 0u;
  if (++g.s == NST) { g.s = 0; g.ph ^= 1; }
}
template <int N>
__device__ __forceinline__ void tile_end(float (&acc)[N], uint32_t& prev) {
  wg_wait<0>();
  if (prev != 0) mbar_arrive_cluster(prev);
  prev = 0;
  fence_regs(acc);
}

__device__ __forceinline__ int other_kb(int q, int j) {
  const int ch = q >= 7, jj = q - 7 * ch;
  return 2 * (jj < j ? jj : jj + 1) + ch;
}
__device__ __forceinline__ int own_first(int it, int j) {
  return it >= 16 ? (it & 15) : (it < 2 ? 2 * j + it : other_kb(it - 2, j));
}
__device__ __forceinline__ int qkv_kb(int it, int j) {
  return it < 4 ? 2 * j + (it & 1) : other_kb(it < 18 ? it - 4 : it - 18, j);
}
__device__ __forceinline__ int wo_k(int it, int j) {
  return it < 8 ? it * 128 : (it == 8 ? j : (it - 9 < j ? it - 9 : it - 8)) * 128 + 64;
}
__device__ __forceinline__ int down_k(int it) {
  const int r = (it >> 4) - 1, idx = it & 15;
  return r < 0 ? idx * 64 : (r < 3 ? (idx >> 1) * 448 + r * 128 + (idx & 1) * 64 : idx * 448 + 384);
}
__device__ __forceinline__ void wait_p3_free(uint32_t empty3, int i) {
  mbar_wait(empty3 + 8 * ((i * 2) / 3), 1);
  mbar_wait(empty3 + 8 * ((i * 2 + 1) / 3), 1);
}
__device__ __forceinline__ void wait_p2_free(uint32_t empty2, int i) {
  const int w0 = (i * 3) / 2, w1 = (i * 3 + 2) / 2;
  mbar_wait(empty2 + 8 * w0, w0 < 4 ? 0 : 1);
  mbar_wait(empty2 + 8 * w1, w1 < 4 ? 0 : 1);
}

__device__ __forceinline__ void chan(float& m, float& q, float m2, float q2, float n) {
  const float d = m2 - m;
  m = 0.5f * (m + m2);
  q = q + q2 + d * d * (0.5f * n);
}

__device__ __forceinline__ uint32_t tag16(uint32_t tag) { return tag % 65535u + 1u; }
__device__ __forceinline__ void stat_store(uint2* slot, float m, float q, uint32_t t16) {
  const uint32_t a = ((__float_as_uint(m) + 0x80u) & 0xffffff00u) | (t16 & 0xffu), b = ((__float_as_uint(q) + 0x80u) & 0xffffff00u) | (t16 >> 8);
  asm volatile("st.relaxed.gpu.global.b64 [%0], %1;" ::"l"(slot), "l"((uint64_t)a | ((uint64_t)b << 32)) : "memory");
}
__device__ __forceinline__ void stat_gather(const uint2* rows, uint32_t t16, int lane, float (&rs)[2], float (&nb)[2]) {
  const uint4* sp = (const uint4*)(rows + (lane >> 3) * 128) + (lane & 7);
  const uint32_t want = (t16 & 0xffu) | ((t16 >> 8) << 8);
  uint4 a, b;
  for (;;) {
    a = ll_peek(sp);
    b = ll_peek(sp + 256);
    const uint32_t bad = (__byte_perm(a.x, a.y, 0x40) ^ want) | (__byte_perm(a.z, a.w, 0x40) ^ want) | (__byte_perm(b.x, b.y, 0x40) ^ want) |
                         (__byte_perm(b.z, b.w, 0x40) ^ want);
    if (__all_sync(~0u, (bad & 0xffffu) == 0)) break;
  }
  float m0 = __uint_as_float(a.x & 0xffffff00u), q0 = __uint_as_float(a.y & 0xffffff00u);
  float m1 = __uint_as_float(a.z & 0xffffff00u), q1 = __uint_as_float(a.w & 0xffffff00u);
  chan(m0, q0, __uint_as_float(b.x & 0xffffff00u), __uint_as_float(b.y & 0xffffff00u), 128.f);
  chan(m1, q1, __uint_as_float(b.z & 0xffffff00u), __uint_as_float(b.w & 0xffffff00u), 128.f);
  const bool hi = lane & 8;
  float m = hi ? m1 : m0, q = hi ? q1 : q0;
  chan(m, q, __shfl_xor_sync(~0u, hi ? m0 : m1, 8), __shfl_xor_sync(~0u, hi ? q0 : q1, 8), 256.f);
  chan(m, q, __shfl_xor_sync(~0u, m, 16), __shfl_xor_sync(~0u, q, 16), 512.f);
  const float rstd = rsqrtf(q * (1.0f / DM) + 1e-5f), nmr = -m * rstd;
  const int r = lane >> 2, src = (r >> 1) + (r & 1) * 8;
  rs[0] = __shfl_sync(~0u, rstd, src); nb[0] = __shfl_sync(~0u, nmr, src);
  rs[1] = __shfl_sync(~0u, rstd, src + 4); nb[1] = __shfl_sync(~0u, nmr, src + 4);
}

__device__ __forceinline__ void publish_stats(const uint32_t (&xl)[16], const uint32_t (&xh)[16], uint2* slot, int lane, uint32_t t16) {
  float ds[4] = {0.f, 0.f, 0.f, 0.f}, dl[4] = {0.f, 0.f, 0.f, 0.f}, dh[4] = {0.f, 0.f, 0.f, 0.f};
#pragma unroll
  for (int q = 0; q < 8; q++) {
    mma16816(ds, xl[2 * q], xh[2 * q], xl[2 * q + 1], xh[2 * q + 1], 0x3f803f80u, 0x3f803f80u);
    mma16816(dl, xl[2 * q], xh[2 * q], xl[2 * q + 1], xh[2 * q + 1], xl[2 * q], xl[2 * q + 1]);
    mma16816(dh, xl[2 * q], xh[2 * q], xl[2 * q + 1], xh[2 * q + 1], xh[2 * q], xh[2 * q + 1]);
  }
  const int r = lane >> 2;
  if ((lane & 3) == (r >> 1)) {
    const float ml = ds[0] * (1.0f / 128), mh = ds[2] * (1.0f / 128);
    const float ql = fmaxf(((r & 1) ? dl[1] : dl[0]) - ds[0] * ml, 0.f), qh = fmaxf(((r & 1) ? dh[3] : dh[2]) - ds[2] * mh, 0.f);
    stat_store(slot + r, ml, ql, t16);
    stat_store(slot + r + 8, mh, qh, t16);
  }
  __syncwarp();
}

__device__ __forceinline__ void stage_slab(uint32_t chunk, int warp, int lane, const uint32_t (&lo)[8], const uint32_t (&hi)[8]) {
  const int row = warp * 16 + (lane & 7) + ((lane >> 3) & 1) * 8;
  const uint32_t rbase = chunk + row * 128;
#pragma unroll
  for (int q = 0; q < 4; q++) {
    const int grp = 2 * q + (lane >> 4);
    stmatrix4(rbase + ((grp ^ (row & 7)) << 4), lo[2 * q], hi[2 * q], lo[2 * q + 1], hi[2 * q + 1]);
  }
}
__device__ __forceinline__ float silu_mul(float g, float u) {
  float e, r;
  asm("ex2.approx.ftz.f32 %0, %1;" : "=f"(e) : "f"(g * -1.4426950408889634f));
  asm("rcp.approx.ftz.f32 %0, %1;" : "=f"(r) : "f"(1.0f + e));
  return g * r * u;
}
__device__ __forceinline__ uint32_t swiglu2(uint32_t g2, uint32_t u2) {
  asm volatile("" : "+r"(g2));
  return pack2(silu_mul(bf_lo(g2), bf_lo(u2)), silu_mul(bf_hi(g2), bf_hi(u2)));
}
__device__ __forceinline__ void stage_done(uint32_t bar, int lane) {
  asm volatile("fence.proxy.async.shared::cta;" ::: "memory");
  __syncwarp();
  if (lane == 0) mbar_arrive(bar);
}

__device__ __forceinline__ int fresh_tid() {
  int t;
  asm volatile("mov.u32 %0, %%tid.x;" : "=r"(t));
  return t;
}
#define RING_IDS()                                                                                           \
  const int tid = fresh_tid() - 128;                                                                         \
  const int cw = __shfl_sync(~0u, tid >> 7, 0), warp = __shfl_sync(~0u, (tid >> 5) & 3, 0);                  \
  const bool releaser = (tid & 31) < 2;                                                                      \
  const uint32_t rbars = mapa(bars, tid & 1);                                                                \
  const uint32_t a_base = cw * 8192
#define LANE_IDS()                                                                                           \
  const int lane = fresh_tid() & 31, r = lane >> 2, c = lane & 3;                                            \
  const int srow = warp * 16 + (lane & 7) + ((lane >> 3) & 1) * 8;                                           \
  const uint32_t slab = stg + cw * 8192 + srow * 128, sw0 = (lane >> 4) ^ (srow & 7);                        \
  (void)r; (void)c; (void)slab; (void)sw0

template <int NPRE, bool EAGER, class Step>
__device__ __forceinline__ void attention(float (&acc)[96], const Params& p, int rho, int rb, int cta, int cw, int warp, uint32_t tag,
                                          uint32_t stg, uint32_t bars, uint32_t& prev, Step step) {
  uint32_t ql[8], qh[8], k0[8], k1[8], v0[8], v1[8], hp[16];
  if (EAGER) {
    tile_end(acc, prev);
  } else {
    step();
    fence_regs(acc);
  }
#pragma unroll
  for (int t = 0; t < 8; t++) {
    k0[t] = pack2(acc[4 * (8 + t)], acc[4 * (8 + t) + 1]);
    k1[t] = pack2(acc[4 * (8 + t) + 2], acc[4 * (8 + t) + 3]);
    v0[t] = pack2(acc[4 * (16 + t)], acc[4 * (16 + t) + 1]);
    v1[t] = pack2(acc[4 * (16 + t) + 2], acc[4 * (16 + t) + 3]);
    asm volatile("" : "+r"(k0[t]), "+r"(k1[t]), "+r"(v0[t]), "+r"(v1[t]));
  }
  const int lane = fresh_tid() & 31, r = lane >> 2, c = lane & 3;
#pragma unroll
  for (int t = 0; t < 8; t++) v1[t] = movmatrix(v1[t]);
  mbar_wait(bars + 8 * B_STGE, rho);
  mbar_wait(bars + 8 * (B_STGE + 1), 0);
  const uint32_t xch = stg + 16384 + (cw * 4 + warp) * 2048 + lane * 16;
  if (warp < 3) {
    sts128(xch, k1[0], k1[1], k1[2], k1[3]);
    sts128(xch + 512, k1[4], k1[5], k1[6], k1[7]);
    sts128(xch + 1024, v1[0], v1[1], v1[2], v1[3]);
    sts128(xch + 1536, v1[4], v1[5], v1[6], v1[7]);
  } else if (rb < 15) {
    uint4* dst = p.halo + ((cta * 2 + rho) * 2 + cw) * 256 + lane;
#pragma unroll
    for (int t = 0; t < 4; t++) {
      ll_store(dst + t * 32, k1[2 * t], k1[2 * t + 1], tag);
      ll_store(dst + (4 + t) * 32, v1[2 * t], v1[2 * t + 1], tag);
    }
  }
#pragma unroll
  for (int t = 0; t < 8; t++) {
    v0[t] = movmatrix(v0[t]);
    ql[t] = pack2(acc[4 * t], acc[4 * t + 1]);
    qh[t] = pack2(acc[4 * t + 2], acc[4 * t + 3]);
    asm volatile("" : "+r"(v0[t]), "+r"(ql[t]), "+r"(qh[t]));
  }
#pragma unroll 1
  for (int i = 0; i < NPRE; i++) step();
  const uint4* src = p.halo + (((cta - 8) * 2 + rho) * 2 + cw) * 256 + lane;
  uint4 early[8] = {};
  if (warp == 0 && rb > 0) {
#pragma unroll
    for (int i = 0; i < 8; i++) early[i] = ll_peek(src + i * 32);
  }
  step();
  wg_bar(cw);
  if (warp > 0) {
#pragma unroll
    for (int t = 0; t < 4; t++) {
      const uint4 a = lds128(xch - 2048 + t * 512);
      hp[4 * t] = a.x; hp[4 * t + 1] = a.y; hp[4 * t + 2] = a.z; hp[4 * t + 3] = a.w;
    }
  } else if (rb > 0) {
    uint32_t bad = 0;
#pragma unroll
    for (int i = 0; i < 8; i++) {
      bad |= (early[i].y ^ tag) | (early[i].w ^ tag);
      hp[2 * i] = early[i].x;
      hp[2 * i + 1] = early[i].z;
    }
    if (!__all_sync(~0u, bad == 0)) ll_poll<8>([&](int i) { return src + i * 32; }, tag, hp);
  } else {
#pragma unroll
    for (int t = 0; t < 16; t++) hp[t] = 0;
  }
  wg_wait<0>();
  if (prev != 0) mbar_arrive_cluster(prev);
  prev = 0;
#pragma unroll
  for (int t = 0; t < 8; t++) asm volatile("" : "+r"(ql[t])::"memory");
  const bool up0 = 2 * c > r, up1 = 2 * c + 1 > r;
  const bool first = (rb == 0) && (warp == 0);
  uint32_t a0[2], a2[2], a3[2], a5[2];
  float il[2], ih[2];
#pragma unroll
  for (int h = 0; h < 2; h++) {
    float sp[4] = {0.f, 0.f, 0.f, 0.f}, s0[4] = {0.f, 0.f, 0.f, 0.f}, s1[4] = {0.f, 0.f, 0.f, 0.f};
#pragma unroll
    for (int ks = 0; ks < 2; ks++) {
      const int t = 4 * h + 2 * ks;
      mma16816(sp, ql[t], qh[t], ql[t + 1], qh[t + 1], hp[t], hp[t + 1]);
      mma16816(s0, ql[t], qh[t], ql[t + 1], qh[t + 1], k0[t], k0[t + 1]);
      mma16816(s1, ql[t], qh[t], ql[t + 1], qh[t + 1], k1[t], k1[t + 1]);
    }
    float p0 = (up0 ? sp[0] : s0[0]) * QK_SCALE, p1 = (up1 ? sp[1] : s0[1]) * QK_SCALE;
    float p2 = (up0 ? s0[2] : s1[2]) * QK_SCALE, p3 = (up1 ? s0[3] : s1[3]) * QK_SCALE;
    if (first && up0) p0 = -1000000000.0f;
    if (first && up1) p1 = -1000000000.0f;
    il[h] = softmax8(p0, p1);
    ih[h] = softmax8(p2, p3);
    a0[h] = pack2(up0 ? p0 : 0.f, up1 ? p1 : 0.f);
    a2[h] = pack2(up0 ? 0.f : p0, up1 ? 0.f : p1);
    a3[h] = pack2(up0 ? p2 : 0.f, up1 ? p3 : 0.f);
    a5[h] = pack2(up0 ? 0.f : p2, up1 ? 0.f : p3);
  }
  float o[8][4];
#pragma unroll
  for (int t = 0; t < 8; t++) {
#pragma unroll
    for (int q = 0; q < 4; q++) o[t][q] = 0.f;
    mma1688(o[t], 0u, a5[t >> 2], v1[t]);
    mma16816(o[t], a0[t >> 2], 0u, a2[t >> 2], a3[t >> 2], hp[8 + t], v0[t]);
  }
#pragma unroll
  for (int t = 0; t < 8; t++) fence_regs(o[t]);
  if (!EAGER) step();
  uint32_t ol[8], oh[8];
#pragma unroll
  for (int t = 0; t < 8; t++) {
    ol[t] = pack2(o[t][0] * il[t >> 2], o[t][1] * il[t >> 2]);
    oh[t] = pack2(o[t][2] * ih[t >> 2], o[t][3] * ih[t >> 2]);
  }
  if (!EAGER) step();
  stage_slab(stg + cw * 8192, warp, lane, ol, oh);
  stage_done(bars + 8 * B_STGF, lane);
  if (!EAGER) step();
}

__global__ void __launch_bounds__(384, 1) fused_kernel(const __grid_constant__ Params p) {
  extern __shared__ __align__(1024) uint8_t smem_raw[];
  const uint32_t sm = smem_u32(smem_raw);
  const uint32_t bars = sm + MISC_OFF;
  const uint32_t stg = sm + STG_OFF;
  const int rank = blockIdx.x & 1;
  const int cl = blockIdx.x >> 1;
  if (cl >= NCTA / 2) {
    const int e = blockIdx.x - NCTA, wid = __shfl_sync(~0u, (int)(threadIdx.x >> 5), 0), lane = threadIdx.x & 31;
    if (threadIdx.x == 0) {
      for (int i = 0; i < 6; i++) { mbar_init(bars + 8 * i, 1); mbar_init(bars + 8 * (6 + i), 8); }
      asm volatile("fence.mbarrier_init.release.cluster;" ::: "memory");
    }
    const uint32_t tag = load_epoch(p.epoch) + 1;
    if (threadIdx.x < 256) ll_store(p.modll + 512 + (threadIdx.x >> 6) * 256 + e * 64 + (threadIdx.x & 63), 0u, 0u, 0u);
    for (int i = threadIdx.x; i < 1536; i += 384) {
      uint4 o = make_uint4(0u, 0u, 0u, 0u);
      if (i < 1024 && (i & 63) < 8) {
        const uint4 cv = ldg_nc(p.c + (i >> 6) * 64 + (i & 7) * 8);
        o = make_uint4(pack2(silu_f(bf_lo(cv.x)), silu_f(bf_hi(cv.x))), pack2(silu_f(bf_lo(cv.y)), silu_f(bf_hi(cv.y))),
                       pack2(silu_f(bf_lo(cv.z)), silu_f(bf_hi(cv.z))), pack2(silu_f(bf_lo(cv.w)), silu_f(bf_hi(cv.w))));
      }
      sts128(stg + i * 16, o.x, o.y, o.z, o.w);
    }
    asm volatile("fence.proxy.async.shared::cta;" ::: "memory");
    __syncthreads();
    if (wid == 0) {
      __nanosleep(WMDELAY);
      uint32_t ph = 1;
#pragma unroll 1
      for (int it = 0, s = 0; it < 64; it++) {
        mbar_wait(bars + 8 * (6 + s), ph);
        expect_tx_elect(bars + 8 * s, 32768);
#pragma unroll
        for (int q = 0; q < 4; q++) tma_load_ef(sm + s * 32768 + q * 8192, &p.wm, bars + 8 * s, 2048 + (it >> 4) * 1024 + e * 256 + q * 64, (it & 15) * 64);
        if (++s == 6) { s = 0; ph ^= 1; }
      }
    } else if (wid == 1 && PFW) {
      __nanosleep(PFW);
#pragma unroll 1
      for (int i = 0; i < 64; i++) {
        l2_prefetch_tile(&p.wo, (i & 15) * 64, (e * 4 + (i >> 4)) * 64);
        if (PFP) __nanosleep(PFP);
      }
#pragma unroll 1
      for (int i = 0; i < 128; i++) {
        l2_prefetch_tile((i & 2) ? &p.wu : &p.wg, ((i >> 2) & 7) * 448 + (i & 1) * 64, ((i >> 5) * 4 + e) * 64);
        if (PFP) __nanosleep(PFP);
      }
    } else if (wid >= 4) {
      const int hf = (wid >> 2) - 1;
      uint32_t ph = 0;
      int s = 0;
#pragma unroll 1
      for (int v = 0; v < 4; v++) {
        float acc[64];
#pragma unroll 1
        for (int kb = 0; kb < 16; kb++) {
          mbar_wait_watchdog(bars + 8 * s, ph);
          const uint32_t da = DESC_A + ((STG_OFF + kb * 1024) >> 4), db = DESC_B + ((s * 32768 + hf * 16384) >> 4) - 1024;
          wg_fence();
#pragma unroll
          for (int k = 0; k < 4; k++) wgmma_ss_n128(acc, da + k * 2, db + k * 128, (kb | k) != 0);
          wg_commit();
          wg_wait<0>();
          if (lane == 0) mbar_arrive(bars + 8 * (6 + s));
          if (++s == 6) { s = 0; ph ^= 1; }
        }
        if ((wid & 3) == 0) {
#pragma unroll
          for (int n = 0; n < 16; n++) {
            const uint32_t mine = pack2(acc[4 * n], acc[4 * n + 1]), next = __shfl_down_sync(~0u, mine, 1);
            if (lane < 4 && (lane & 1) == 0) ll_store(p.modll + 512 + v * 256 + e * 64 + hf * 32 + n * 2 + (lane >> 1), mine, next, tag);
          }
        }
      }
    }
    return;
  }
  const int slot = p.slot[cl];
  const int rb = (slot >> 3) * 2 + rank, j = slot & 7;
  const int cta = rb * 8 + j;
  PROF_AT(threadIdx.x == 0, 0);

  if (threadIdx.x < 128) {
    uint32_t tag = load_epoch(p.epoch);
    asm volatile("setmaxnreg.dec.sync.aligned.u32 40;");
    const int warp = __shfl_sync(~0u, (int)(threadIdx.x >> 5), 0), lane = threadIdx.x & 31;
    if (threadIdx.x == 0) {
      if ((sm & 0x3FFFF) != SMEM_BASE) asm volatile("trap;");
      for (int i = 0; i < 4; i++) { mbar_init(bars + 8 * (B_FQ + i), 1); mbar_init(bars + 8 * (B_EQ + i), 16); }
      for (int i = 0; i < 6; i++) { mbar_init(bars + 8 * (B_FW + i), 1); mbar_init(bars + 8 * (B_EW + i), 16); }
      for (int i = 0; i < 4; i++) { mbar_init(bars + 8 * (B_FG + i), 1); mbar_init(bars + 8 * (B_EG + i), 16); }
      for (int i = 0; i < 6; i++) { mbar_init(bars + 8 * (B_FD + i), 1); mbar_init(bars + 8 * (B_ED + i), 16); }
      for (int i = 0; i < 2; i++) { mbar_init(bars + 8 * (B_STGF + i), 8); mbar_init(bars + 8 * (B_STGE + i), 1); }
      mbar_init(bars + 8 * B_MODB, 1);
      mbar_init(bars + 8 * (B_MODB + 1), 1);
      mbar_init(bars + 8 * B_MODA, 1);
      for (int i = 0; i < 8; i++) mbar_init(bars + 8 * (B_RDY + i), 1);
      asm volatile("fence.mbarrier_init.release.cluster;" ::: "memory");
    }
    __syncwarp();
    cluster_arrive_relaxed();
    tag += 1;
    const unsigned target = tag * 8;
    unsigned* cnt = p.cnt + rb * 32;
    cluster_wait();
    if (warp == 0) {
      const CUtensorMap* wgu = rank ? &p.wu : &p.wg;
      uint32_t st = sm + 16384, fb = bars + 8 * B_FQ, ph = 1;
      __nanosleep(BDELAY);
#pragma unroll 1
      for (int it = 0; it < 32; it++) {
        const int kb = qkv_kb(it, j), col = j * 128 + ((it < 4 ? it >= 2 : it >= 18) ? 64 : 0);
        mbar_wait(fb + 8 * (B_EQ - B_FQ), ph);
        expect_tx_elect(fb, it < 4 ? 24576 : 40960);
        tma_load_mc(st + rank * 8192, &p.wqkv, fb, col + rank * 1024, kb * 64);
        tma_load_mc(st + 16384 + rank * 4096, &p.wqkv32, fb, col + 2048, kb * 64 + rank * 32);
        st += 49152; fb += 8;
        if ((it & 3) == 3) { st -= 4 * 49152; fb -= 32; ph ^= 1; }
      }
      fb = bars + 8 * B_FW; ph = 1;
#pragma unroll 1
      for (int it = 0, s = 0; it < 16; it++) {
        if (it < 6) wait_p3_free(bars + 8 * B_EQ, it);
        mbar_wait(fb + 8 * (B_EW - B_FW), ph);
        expect_tx_elect(fb, it == 8 ? 16384 : 32768);
        tma_load_mc(st + rank * 8192, &p.wo, fb, j * 128 + rank * 64, wo_k(it, j));
        st += 32768; fb += 8;
        if (++s == 6) { s = 0; st -= 6 * 32768; fb -= 48; ph ^= 1; }
      }
      st = sm + 16384; fb = bars + 8 * B_FG; ph = 1;
#pragma unroll 1
      for (int it = 0; it < 48; it++) {
        const int kb = own_first(it, j), col = j * 448 + (it >> 4) * 128;
        if (it < 4) wait_p2_free(bars + 8 * B_EW, it);
        mbar_wait(fb + 8 * (B_EG - B_FG), ph);
        expect_tx_elect(fb, it < 2 ? 32768 : 49152);
        tma_load_mc(st + rank * 16384, wgu, fb, col, kb * 64);
        tma_load_mc(st + rank * 16384 + 8192, wgu, fb, col + 64, kb * 64);
        st += 49152; fb += 8;
        if ((it & 3) == 3) { st -= 4 * 49152; fb -= 32; ph ^= 1; }
      }
      fb = bars + 8 * B_FD; ph = 1;
#pragma unroll 1
      for (int it = 0, s = 0; it < 72; it++) {
        if (it < 6) wait_p3_free(bars + 8 * B_EG, it);
        mbar_wait(fb + 8 * (B_ED - B_FD), ph);
        expect_tx_elect(fb, 32768);
        tma_load_mc(st + rank * 8192, it < 16 ? wgu : &p.wd, fb, it < 16 ? j * 448 + 384 : j * 128 + rank * 64, down_k(it));
        st += 32768; fb += 8;
        if (++s == 6) { s = 0; st -= 6 * 32768; fb -= 48; ph ^= 1; }
      }
    } else if (warp == 1) {
      const int arow = rb * 128;
      uint32_t st = sm, fb = bars + 8 * B_FQ, ph = 0;
      cnt_wait(cnt + C_HA, target);
      PROF_AT(lane == 0, 16);
#pragma unroll 1
      for (int it = 4; it < 32; it++) {
        if (it == 11) mbar_wait(bars + 8 * (B_RDY + C_H), 0);
        mbar_wait(fb + 8 * (B_EQ - B_FQ), ph);
        tma_load(st, &p.h, fb, qkv_kb(it, j) * 64, arow);
        st += 49152; fb += 8;
        if ((it & 3) == 3) { st -= 4 * 49152; fb -= 32; ph ^= 1; }
      }
      fb = bars + 8 * B_FW; ph = 1;
#pragma unroll 1
      for (int it = 0, s = 0; it < 16; it++) {
        if (it < 6) wait_p3_free(bars + 8 * B_EQ, it);
        mbar_wait(fb + 8 * (B_EW - B_FW), ph);
        if (it == 0) mbar_wait(bars + 8 * (B_RDY + C_O), 0);
        if (it == 9) cnt_wait(cnt + C_O + 1, target * 8);
        PROF_AT(lane == 0 && (it == 0 || it == 9), 17 + (it >> 3));
        if (it != 8) tma_load(st, &p.o_ld, fb, wo_k(it, j), arow);
        st += 32768; fb += 8;
        if (++s == 6) { s = 0; st -= 6 * 32768; fb -= 48; ph ^= 1; }
      }
      st = sm + 2 * 49152; fb = bars + 8 * (B_FG + 2); ph = 1;
      cnt_wait(cnt + C_H2A, target * 8);
      PROF_AT(lane == 0, 19);
#pragma unroll 1
      for (int it = 2; it < 48; it++) {
        if (it == 9) mbar_wait(bars + 8 * (B_RDY + C_H2), 0);
        mbar_wait(fb + 8 * (B_EG - B_FG), ph);
        tma_load(st, &p.h2, fb, own_first(it, j) * 64, arow);
        st += 49152; fb += 8;
        if ((it & 3) == 3) { st -= 4 * 49152; fb -= 32; ph ^= 1; }
      }
      fb = bars + 8 * B_FD; ph = 1;
#pragma unroll 1
      for (int it = 0, s = 0; it < 72; it++) {
        if (it < 6) wait_p3_free(bars + 8 * B_EG, it);
        mbar_wait(fb + 8 * (B_ED - B_FD), ph);
        if ((it & 15) == 0 && it > 0) { mbar_wait(bars + 8 * (B_RDY + C_ACT - 1 + (it >> 4)), 0); PROF_AT(lane == 0, 19 + (it >> 4)); }
        tma_load(st, it < 16 ? &p.h2 : &p.act, fb, down_k(it), arow);
        st += 32768; fb += 8;
        if (++s == 6) { s = 0; st -= 6 * 32768; fb -= 48; ph ^= 1; }
      }
    } else if (warp == 2) {
      if (lane < 14) prefetch_map(&p.h + lane);
      __syncwarp();
      uint32_t ph1 = 0;
#pragma unroll 1
      for (int n = 0; n < 8; n++) {
        const int nch = (n == 1 || n == 2 || n == 7) ? 1 : 2;
#pragma unroll 1
        for (int ch = 0; ch < nch; ch++) {
          mbar_wait_watchdog(bars + 8 * (B_STGF + ch), ch ? ph1 : (n & 1));
          const uint32_t src = stg + ch * 16384;
          if (n == 2 || n == 3) {
          } else if (n == 1) {
#pragma unroll 1
            for (int q = 0; q < 8; q++) {
              tma_store2(&p.o_st, src + q * 2048, j * 128, rb * 128 + q * 16);
              if (q & 1) store_pause(true);
            }
          } else if (n >= 4 && n < 8) {
#pragma unroll 1
            for (int q = 0; q < 4; q++) {
              tma_store2(&p.act_st, src + q * 4096, j * 448 + (n - 4) * 128 + ch * 64, rb * 128 + q * 32);
              store_pause(true);
            }
          } else {
            tma_store2(&p.h, src, j * 128 + ch * 64, rb * 128);
            asm volatile("cp.async.bulk.commit_group;" ::: "memory");
            if (ch == 1) {
              asm volatile("cp.async.bulk.wait_group 1;" ::: "memory");
              __syncwarp();
              cnt_signal(cnt + C_HA);
            }
          }
          if (n >= 4 && n < 7 && ch == 0) arrive_elect(bars + 8 * B_STGE);
        }
        asm volatile("cp.async.bulk.commit_group;" ::: "memory");
        asm volatile("cp.async.bulk.wait_group 0;" ::: "memory");
        __syncwarp();
        if (n != 2 && n != 3) cnt_signal(cnt + n);
        PROF_AT(lane == 0, n == 0 ? 33 : 23 + n);
        if (n == 0) {
#pragma unroll 1
          for (int t = 0; t < 34; t++) {
            ll_store(t < 32 ? p.halo + cta * 1024 + t * 32 + lane : (uint4*)(p.stats2 + cta * 128) + (t - 32) * 32 + lane, 0u, 0u, 0u);
            __nanosleep(40);
          }
          __syncwarp();
        }
        if (!(n >= 4 && n < 7)) arrive_elect(bars + 8 * B_STGE);
        if (nch == 2) { arrive_elect(bars + 8 * (B_STGE + 1)); ph1 ^= 1; }
      }
      mbar_wait_watchdog(bars + 8 * B_STGF, 0);
      PROF_AT(lane == 0, 31);
    } else {
      if (lane < 4) ll_store(p.modll + cta * 4 + lane, 0u, 0u, 0u);
      bar_sync(1, 288);
      {
        const uint4 t4 = lds128(sm + RED_OFF + lane * 16);
        float a[4] = {__uint_as_float(t4.x), __uint_as_float(t4.y), __uint_as_float(t4.z), __uint_as_float(t4.w)};
#pragma unroll
        for (int o = 4; o < 32; o <<= 1)
#pragma unroll
          for (int q = 0; q < 4; q++) a[q] += __shfl_xor_sync(~0u, a[q], o);
        if (lane < 4) ll_store(p.modll + cta * 4 + lane, pack2(a[0], a[1]), pack2(a[2], a[3]), tag);
        PROF_AT(lane == 0, 1);
        uint32_t m[4];
        const uint4* mp = p.modll + j * 32 + lane;
        ll_poll<2>([&](int i) { return mp + i * 256; }, tag, m);
        const uint32_t c0 = pack2(1.0f + bf_lo(m[2]), 1.0f + bf_hi(m[2])), c1 = pack2(1.0f + bf_lo(m[3]), 1.0f + bf_hi(m[3]));
        sts128(sm + MODB_OFF + lane * 16, c0, m[0], c1, m[1]);
        __syncwarp();
        arrive_elect(bars + 8 * B_MODA);
      }
#pragma unroll 1
      for (int n = C_H; n <= C_O; n++) {
        cnt_wait_lazy(cnt + n, target);
        arrive_elect(bars + 8 * (B_RDY + n));
      }
      {
        uint32_t m[6];
        const uint4* src = p.modll + 512 + j * 32 + lane;
        ll_poll<3, 500>([&](int i) { return src + i * 256; }, tag, m);
#pragma unroll
        for (int vec = 0; vec < 3; vec++) {
          const float add = vec == 2 ? 1.0f : 0.0f;
          sts128(sm + MODB_OFF + (vec * 128 + lane * 4) * 4, __float_as_uint(bf_round(bf_lo(m[2 * vec]) + add)), __float_as_uint(bf_round(bf_hi(m[2 * vec]) + add)),
                 __float_as_uint(bf_round(bf_lo(m[2 * vec + 1]) + add)), __float_as_uint(bf_round(bf_hi(m[2 * vec + 1]) + add)));
        }
        __syncwarp();
        if (lane == 0) mbar_arrive(bars + 8 * B_MODB);
        PROF_AT(lane == 0, 15);
      }
      __syncwarp();
#pragma unroll 1
      for (int n = C_H2; n < 8; n++) {
        cnt_wait_lazy(cnt + n, n == C_H2 ? target * 8 : target);
        arrive_elect(bars + 8 * (B_RDY + n));
      }
      {
        uint32_t m[2];
        const uint4* src = p.modll + 512 + 768 + j * 32 + lane;
        ll_poll<1>([&](int) { return src; }, tag, m);
        sts128(sm + MODB_OFF + (384 + lane * 4) * 4, m[0] << 16, m[0] & 0xffff0000u, m[1] << 16, m[1] & 0xffff0000u);
        __syncwarp();
        if (lane == 0) mbar_arrive(bars + 8 * (B_MODB + 1));
      }
    }
  } else {
    uint32_t tag;

    {
      const int tid = threadIdx.x - 128, cw = tid >> 7, warp = (tid >> 5) & 3, lane = tid & 31;
      const int l16 = lane & 15, half = lane >> 4, w8 = cw * 4 + warp;
      const uint32_t cbuf = sm + 3 * 49152 + w8 * 512;
      if (lane <= 16) cp_async16(cbuf + lane * 16, lane < 16 ? (const void*)(p.c + w8 * 128 + lane * 8) : (const void*)p.epoch);
      asm volatile("cp.async.commit_group;" ::: "memory");
      const uint32_t xbuf = sm + 40960 + (cw * 2 + (l16 >> 3)) * 49152 + (warp * 16 + half) * 128;
      {
        const char* xp = (const char*)p.x + (uint32_t)((rb * 128 + (warp * 16 + half) * 2 + cw) * 2048 + j * 256 + l16 * 16);
#pragma unroll
        for (int i = 0; i < 8; i++) cp_async16(xbuf + i * 256 + (((l16 & 7) ^ ((i * 2 + half) & 7)) << 4), xp + i * 8192);
      }
      asm volatile("cp.async.commit_group;" ::: "memory");
      const uint32_t wbuf = sm + cw * 49152 + warp * 4096;
      {
        const char* wp = (const char*)p.wmod + (uint32_t)(cta * 32 + (lane & 1) * 16 + (w8 * 128 + (lane >> 1)) * 12288);
#pragma unroll
        for (int i = 0; i < 8; i++) cp_async16(wbuf + i * 512 + lane * 16, wp + i * 16 * 12288);
      }
      asm volatile("cp.async.commit_group;" ::: "memory");
      PROF_AT(tid == 0, 32);
      uint2* st1 = p.stats1 + (rb * 8 + j) * 128 + cw * 64 + warp * 16;
      if (lane < 8) ll_store((uint4*)st1 + lane, 0u, 0u, 0u);
      __syncwarp();
      cluster_arrive_relaxed();
      asm volatile("setmaxnreg.inc.sync.aligned.u32 232;");
      uint32_t sa[4][4];
      {
        asm volatile("cp.async.wait_group 2;" ::: "memory");
        __syncwarp();
        tag = lds32(cbuf + 256) + 1;
        const float2 cv = lds64f(cbuf + lane * 8);
        const uint32_t c0 = __float_as_uint(cv.x), c1 = __float_as_uint(cv.y);
        sts64f(cbuf + lane * 8, __uint_as_float(pack2(silu_f(bf_lo(c0)), silu_f(bf_hi(c0)))), __uint_as_float(pack2(silu_f(bf_lo(c1)), silu_f(bf_hi(c1)))));
        __syncwarp();
#pragma unroll
        for (int q = 0; q < 4; q++) ldmatrix4(sa[q][0], sa[q][1], sa[q][2], sa[q][3], cbuf + q * 64 + (lane >> 3) * 16);
      }
      cluster_wait();
      asm volatile("cp.async.wait_group 1;" ::: "memory");
      __syncwarp();
      uint32_t xl[16], xh[16];
      {
        const int srow = warp * 16 + (lane & 15);
#pragma unroll
        for (int q = 0; q < 8; q++)
          ldmatrix4(xl[2 * q], xh[2 * q], xl[2 * q + 1], xh[2 * q + 1],
                    sm + 40960 + (cw * 2 + (q >> 2)) * 49152 + srow * 128 + (((half + (q & 3) * 2) ^ (srow & 7)) << 4));
      }
      publish_stats(xl, xh, st1, lane, tag16(tag));
      PROF_AT(tid == 0, 50);
      asm volatile("cp.async.wait_group 0;" ::: "memory");
      __syncwarp();
      PROF_AT(tid == 0, 51);
      {
        uint32_t b[8][4];
#pragma unroll
        for (int ks = 0; ks < 8; ks++) ldmatrix4t(b[ks], wbuf + (ks * 16 + (lane & 15)) * 32 + (lane >> 4) * 16);
        float d0[4] = {0.f, 0.f, 0.f, 0.f}, d1[4] = {0.f, 0.f, 0.f, 0.f}, d2[4] = {0.f, 0.f, 0.f, 0.f}, d3[4] = {0.f, 0.f, 0.f, 0.f};
#pragma unroll
        for (int q = 0; q < 4; q++) {
          mma16816(d0, sa[q][0], sa[q][0], sa[q][1], sa[q][1], b[2 * q][0], b[2 * q][1]);
          mma16816(d1, sa[q][0], sa[q][0], sa[q][1], sa[q][1], b[2 * q][2], b[2 * q][3]);
          mma16816(d2, sa[q][2], sa[q][2], sa[q][3], sa[q][3], b[2 * q + 1][0], b[2 * q + 1][1]);
          mma16816(d3, sa[q][2], sa[q][2], sa[q][3], sa[q][3], b[2 * q + 1][2], b[2 * q + 1][3]);
        }
        d0[0] += d2[0]; d0[1] += d2[1]; d1[0] += d3[0]; d1[1] += d3[1];
        if (lane < 4) {
          sts64f(sm + RED_OFF + (w8 * 16 + lane * 2) * 4, d0[0], d0[1]);
          sts64f(sm + RED_OFF + (w8 * 16 + 8 + lane * 2) * 4, d1[0], d1[1]);
        }
        asm volatile("bar.arrive 1, 288;" ::: "memory");
      }
      {
        const int c = lane & 3;
        float rs[2], nb[2];
        stat_gather(p.stats1 + rb * 1024 + cw * 64 + warp * 16, tag16(tag), lane, rs, nb);
#pragma unroll
        for (int n = 0; n < 16; n++) {
          xl[n] = pack2(bf_lo(xl[n]) * rs[0] + nb[0], bf_hi(xl[n]) * rs[0] + nb[0]);
          xh[n] = pack2(bf_lo(xh[n]) * rs[1] + nb[1], bf_hi(xh[n]) * rs[1] + nb[1]);
        }
        const int srow = warp * 16 + l16;
        const uint32_t slab = stg + cw * 8192 + srow * 128;
#pragma unroll
        for (int q = 0; q < 8; q++)
          stmatrix4(slab + (q >> 2) * 16384 + (((half + (q & 3) * 2) ^ (srow & 7)) << 4), xl[2 * q], xh[2 * q], xl[2 * q + 1], xh[2 * q + 1]);
        PROF_AT(tid == 0, 52);
        mbar_wait(bars + 8 * B_MODA, 0);
        PROF_AT(tid == 0, 2);
#pragma unroll
        for (int q = 0; q < 8; q++) {
          const float2 m0 = lds64f(sm + MODB_OFF + (8 * q + c) * 8), m1 = lds64f(sm + MODB_OFF + (8 * q + 4 + c) * 8);
          const uint32_t c0 = __float_as_uint(m0.x), s0 = __float_as_uint(m0.y), c1 = __float_as_uint(m1.x), s1 = __float_as_uint(m1.y);
          stmatrix4(slab + (q >> 2) * 16384 + (((half + (q & 3) * 2) ^ (srow & 7)) << 4), fma_bf2(xl[2 * q], c0, s0), fma_bf2(xh[2 * q], c0, s0),
                    fma_bf2(xl[2 * q + 1], c1, s1), fma_bf2(xh[2 * q + 1], c1, s1));
          if ((q & 3) == 3) stage_done(bars + 8 * (B_STGF + (q >> 2)), lane);
        }
        wg_bar(cw);
      }
      PROF_AT(tid == 0, 3);
    }

    uint32_t xl[16], xh[16];
    {
      RING_IDS();
      uint32_t prev = 0;
      float acc1[96];
      {
        Ring g{bars + 8 * B_FQ, rbars + 8 * B_EQ, 0, 0u, releaser TR(0)};
        float acc0[96];
#pragma unroll 1
        for (int kb = 0; kb < 2; kb++) kblock<192, 4, 49152>(acc0, g, a_base + STG_OFF + kb * 16384, kb == 0, prev);
#pragma unroll 1
        for (int kb = 0; kb < 2; kb++) kblock<192, 4, 49152>(acc1, g, a_base + STG_OFF + kb * 16384, kb == 0, prev);
#pragma unroll 1
        for (int kb = 0; kb < 14; kb++) kblock<192, 4, 49152>(acc0, g, a_base + g.s * 49152, false, prev);
        PROF_AT(tid == 0, 4);
        attention<NPRE0, false>(acc0, p, 0, rb, cta, cw, warp, tag, stg, bars, prev, [&]() { kblock<192, 4, 49152>(acc1, g, a_base + g.s * 49152, false, prev); });
        PROF_AT(tid == 0, 5);
        {
          LANE_IDS();
#pragma unroll
          for (int q = 0; q < 8; q++)
            ldmatrix4(xl[2 * q], xh[2 * q], xl[2 * q + 1], xh[2 * q + 1], sm + 40960 + (cw * 2 + (q >> 2)) * 49152 + srow * 128 + ((sw0 ^ ((q & 3) * 2)) << 4));
#pragma unroll
          for (int q = 0; q < 16; q++) asm volatile("" : "+r"(xl[q]), "+r"(xh[q])::"memory");
        }
#pragma unroll 1
        for (int kb = 5 + NPRE0; kb < 14; kb++) kblock<192, 4, 49152>(acc1, g, a_base + g.s * 49152, false, prev);
        PROF_AT(tid == 0, 6);
      }
      float acc[64];
      Ring g{bars + 8 * B_FW, rbars + 8 * B_EW, 0, 0u, releaser TR(32)};
      attention<NPRE1, true>(acc1, p, 1, rb, cta, cw, warp, tag, stg, bars, prev, [&]() { kblock<128, 6, 32768>(acc, g, a_base + g.s * 32768, g.s == 0, prev); });
      PROF_AT(tid == 0, 7);
      LANE_IDS();
      unsigned* cnt = p.cnt + rb * 32;
      tma_store2(&p.o_st, stg + cw * 8192 + warp * 2048, j * 128 + 64, rb * 128 + cw * 64 + warp * 16);
      asm volatile("cp.async.bulk.commit_group;" ::: "memory");
#pragma unroll 1
      for (int kb = 1 + NPRE1; kb < 16; kb++) {
        if (kb == 8) wg_bar(cw);
        kblock<128, 6, 32768>(acc, g, a_base + (kb == 8 ? STG_OFF : g.s * 32768), false, prev);
        if (kb == OSIG + NPRE1) {
          asm volatile("cp.async.bulk.wait_group 0;" ::: "memory");
          __syncwarp();
          cnt_signal(cnt + C_O + 1);
        }
      }
      mbar_wait(bars + 8 * B_MODB, 0);
      float2 ga[16];
#pragma unroll
      for (int n = 0; n < 16; n++) ga[n] = lds64f(sm + MODB_OFF + (8 * n + 2 * c) * 4);
      tile_end(acc, prev);
      PROF_AT(tid == 0, 8);
      uint2* st2 = p.stats2 + (rb * 8 + j) * 128 + cw * 64 + warp * 16 + r + (c & 1) * 8;
      float sl[2] = {0.f, 0.f}, sh[2] = {0.f, 0.f}, ql[2] = {0.f, 0.f}, qh[2] = {0.f, 0.f};
#pragma unroll
      for (int n = 0; n < 16; n++) {
        acc[4 * n] = ga[n].x * acc[4 * n] + bf_lo(xl[n]); acc[4 * n + 1] = ga[n].y * acc[4 * n + 1] + bf_hi(xl[n]);
        acc[4 * n + 2] = ga[n].x * acc[4 * n + 2] + bf_lo(xh[n]); acc[4 * n + 3] = ga[n].y * acc[4 * n + 3] + bf_hi(xh[n]);
        sl[0] += acc[4 * n]; sl[1] += acc[4 * n + 1]; sh[0] += acc[4 * n + 2]; sh[1] += acc[4 * n + 3];
        ql[0] += acc[4 * n] * acc[4 * n]; ql[1] += acc[4 * n + 1] * acc[4 * n + 1];
        qh[0] += acc[4 * n + 2] * acc[4 * n + 2]; qh[1] += acc[4 * n + 3] * acc[4 * n + 3];
      }
      {
        const float ml = (sl[0] + sl[1]) * (1.0f / 32), mh = (sh[0] + sh[1]) * (1.0f / 32);
        const float vl = (ql[0] + ql[1]) - 32.0f * ml * ml, vh = (qh[0] + qh[1]) - 32.0f * mh * mh;
        const bool b0 = c & 1;
        float m = b0 ? mh : ml, q = b0 ? vh : vl;
        chan(m, q, __shfl_xor_sync(~0u, b0 ? ml : mh, 1), __shfl_xor_sync(~0u, b0 ? vl : vh, 1), 32.f);
        chan(m, q, __shfl_xor_sync(~0u, m, 2), __shfl_xor_sync(~0u, q, 2), 64.f);
        if (c < 2) stat_store(st2, m, fmaxf(q, 0.f), tag16(tag));
        __syncwarp();
      }
      PROF_AT(tid == 0, 48);
      float2 sb[16], cb[16];
#pragma unroll
      for (int n = 0; n < 16; n++) {
        sb[n] = lds64f(sm + MODB_OFF + (128 + 8 * n + 2 * c) * 4);
        cb[n] = lds64f(sm + MODB_OFF + (256 + 8 * n + 2 * c) * 4);
        xl[n] = pack2(acc[4 * n], acc[4 * n + 1]);
        xh[n] = pack2(acc[4 * n + 2], acc[4 * n + 3]);
      }
      mbar_wait(bars + 8 * B_STGE, 0);
      PROF_AT(tid == 0, 49);
      float nb[2], rstd[2];
      stat_gather(p.stats2 + rb * 1024 + cw * 64 + warp * 16, tag16(tag), lane, rstd, nb);
      PROF_AT(tid == 0, 9);
#pragma unroll
      for (int ch = 0; ch < 2; ch++) {
        uint32_t lo[8], hi[8];
#pragma unroll
        for (int t = 0; t < 8; t++) {
          const int n = ch * 8 + t;
          lo[t] = pack2((acc[4 * n] * rstd[0] + nb[0]) * cb[n].x + sb[n].x, (acc[4 * n + 1] * rstd[0] + nb[0]) * cb[n].y + sb[n].y);
          hi[t] = pack2((acc[4 * n + 2] * rstd[1] + nb[1]) * cb[n].x + sb[n].x, (acc[4 * n + 3] * rstd[1] + nb[1]) * cb[n].y + sb[n].y);
        }
        stage_slab(stg + ch * 16384 + cw * 8192, warp, lane, lo, hi);
        stage_done(bars + 8 * (B_STGF + ch), lane);
        tma_store2(&p.h2_st, stg + ch * 16384 + cw * 8192 + warp * 2048, j * 128 + ch * 64, rb * 128 + cw * 64 + warp * 16);
        asm volatile("cp.async.bulk.commit_group;" ::: "memory");
      }
      wg_bar(cw);
      PROF_AT(tid == 0, 10);
    }

    uint32_t pg[32], pu[32];
    {
      RING_IDS();
      LANE_IDS();
      Ring g{bars + 8 * B_FG, rbars + 8 * B_EG, 0, 0u, releaser TR(48)};
      float acc[128];
      {
        uint32_t prev = 0;
        uint4* x1p = p.x1 + (size_t)(rb * 128 + (warp * 16 + (lane >> 4)) * 2 + cw) * 128 + j * 16 + (lane & 15);
#pragma unroll 1
        for (int kb = 0; kb < 16; kb++) {
          kblock<256, 4, 49152>(acc, g, a_base + (kb < 2 ? STG_OFF + kb * 16384 : g.s * 49152), kb == 0, prev);
          if (kb == 0) {
            asm volatile("cp.async.bulk.wait_group 1;" ::: "memory");
            __syncwarp();
            cnt_signal(p.cnt + rb * 32 + C_H2A);
          }
          if (kb == 1) {
            asm volatile("cp.async.bulk.wait_group 0;" ::: "memory");
            __syncwarp();
            cnt_signal(p.cnt + rb * 32 + C_H2);
          }
          if (kb == 5) {
#pragma unroll
            for (int q = 0; q < 4; q++) x1p[q * 512] = make_uint4(xl[4 * q], xl[4 * q + 1], xl[4 * q + 2], xl[4 * q + 3]);
          }
          if (kb == 8) {
#pragma unroll
            for (int q = 0; q < 4; q++) x1p[(4 + q) * 512] = make_uint4(xh[4 * q], xh[4 * q + 1], xh[4 * q + 2], xh[4 * q + 3]);
          }
        }
        tile_end(acc, prev);
      }
      PROF_AT(tid == 0, 36);
#pragma unroll 1
      for (int t = 1; t < 3; t++) {
#pragma unroll
        for (int q = 0; q < 32; q++) {
          pg[q] = pack2(acc[2 * q], acc[2 * q + 1]);
          pu[q] = pack2(acc[64 + 2 * q], acc[64 + 2 * q + 1]);
        }
        uint32_t prev = 0;
#pragma unroll 1
        for (int blk = 0; blk < 4; blk++) {
          g.s = 0;
#pragma unroll
          for (int i = 0; i < 4; i++) {
            kblock<256, 4, 49152>(acc, g, a_base + i * 49152, blk == 0 && i == 0, prev);
            if ((blk & 1) == 0 && i == 0) mbar_wait(bars + 8 * (B_STGE + (blk >> 1)), t & 1);
            stmatrix2(slab + (blk >> 1) * 16384 + (((srow & 7) ^ ((blk & 1) * 4 + i)) << 4), swiglu2(pg[2 * i], pu[2 * i]), swiglu2(pg[2 * i + 1], pu[2 * i + 1]));
          }
#pragma unroll
          for (int q = 0; q < 24; q++) { pg[q] = pg[q + 8]; pu[q] = pu[q + 8]; }
          if (blk & 1) stage_done(bars + 8 * (B_STGF + (blk >> 1)), lane);
        }
        tile_end(acc, prev);
        PROF_AT(tid == 0, 36 + t);
      }
#pragma unroll
      for (int q = 0; q < 32; q++) {
        pg[q] = pack2(acc[2 * q], acc[2 * q + 1]);
        pu[q] = pack2(acc[64 + 2 * q], acc[64 + 2 * q + 1]);
      }
      PROF_AT(tid == 0, 11);
    }

    {
      RING_IDS();
      LANE_IDS();
      Ring g{bars + 8 * B_FD, rbars + 8 * B_ED, 0, 0u, releaser TR(96)};
      float acc[64];
      uint32_t prev = 0;
#pragma unroll 1
      for (int blk = 0; blk < 6; blk++) {
#pragma unroll
        for (int i = 0; i < 8; i++) {
          kblock<128, 6, 32768>(acc, g, a_base + g.s * 32768, (blk & ~2) == 0 && i == 0, prev);
          if ((blk & 1) == 0 && i == 0) mbar_wait(bars + 8 * (B_STGE + ((blk >> 1) & 1)), blk < 4);
          stmatrix1(slab + ((blk >> 1) & 1) * 16384 + (i & 1) * 1024 + (((srow & 7) ^ ((blk & 1) * 4 + (i >> 1))) << 4), swiglu2(pg[i], pu[i]));
        }
#pragma unroll
        for (int q = 0; q < 24; q++) { pg[q] = pg[q + 8]; pu[q] = pu[q + 8]; }
        if (blk & 1) stage_done(bars + 8 * (B_STGF + ((blk >> 1) & 1)), lane);
        if (blk == 1) {
          tile_end(acc, prev);
          PROF_AT(tid == 0, 39);
#pragma unroll
          for (int q = 0; q < 16; q++) {
            pg[16 + q] = pack2(acc[2 * q], acc[2 * q + 1]);
            pu[16 + q] = pack2(acc[32 + 2 * q], acc[32 + 2 * q + 1]);
          }
          PROF_AT(tid == 0, 12);
        }
      }
      uint4 x1[8];
      const int fl = fresh_tid() & 31;
      const uint4* x1p = p.x1 + (size_t)(rb * 128 + (warp * 16 + (fl >> 4)) * 2 + cw) * 128 + j * 16 + (fl & 15);
#pragma unroll
      for (int q = 0; q < 2; q++) {
#pragma unroll
        for (int e = 0; e < 4; e++) x1[4 * q + e] = ll_peek(x1p + (4 * q + e) * 512);
#pragma unroll 1
        for (int kb = 0; kb < 12; kb++) {
          if (q == 1 && kb == 6) g.releaser = false;
          kblock<128, 6, 32768>(acc, g, a_base + g.s * 32768, false, prev);
        }
      }
      mbar_wait(bars + 8 * (B_MODB + 1), 0);
      mbar_wait(bars + 8 * B_STGE, 1);
      mbar_wait(bars + 8 * (B_STGE + 1), 0);
      float2 gbv[16];
#pragma unroll
      for (int n = 0; n < 16; n++) gbv[n] = lds64f(sm + MODB_OFF + (384 + 8 * n + 2 * c) * 4);
      tile_end(acc, prev);
      PROF_AT(tid == 0, 13);
#pragma unroll
      for (int ch = 0; ch < 2; ch++) {
        uint32_t lo[8], hi[8];
#pragma unroll
        for (int t = 0; t < 8; t++) {
          const int n = ch * 8 + t;
          const float2 gb = gbv[n];
          const uint4 a = x1[n >> 2], b = x1[4 + (n >> 2)];
          const uint32_t xl = (n & 3) == 0 ? a.x : (n & 3) == 1 ? a.y : (n & 3) == 2 ? a.z : a.w;
          const uint32_t xh = (n & 3) == 0 ? b.x : (n & 3) == 1 ? b.y : (n & 3) == 2 ? b.z : b.w;
          lo[t] = pack2(bf_lo(xl) + gb.x * acc[4 * n], bf_hi(xl) + gb.y * acc[4 * n + 1]);
          hi[t] = pack2(bf_lo(xh) + gb.x * acc[4 * n + 2], bf_hi(xh) + gb.y * acc[4 * n + 3]);
        }
        stage_slab(stg + ch * 16384 + cw * 8192, warp, lane, lo, hi);
        asm volatile("fence.proxy.async.shared::cta;" ::: "memory");
        __syncwarp();
        tma_store3(&p.out, stg + ch * 16384 + cw * 8192 + warp * 2048, j * 128 + ch * 64, rb * 64 + warp * 16, cw);
      }
      asm volatile("cp.async.bulk.commit_group;" ::: "memory");
      if (lane == 0) mbar_arrive(bars + 8 * B_STGF);
      asm volatile("cp.async.bulk.wait_group.read 0;" ::: "memory");
      PROF_AT(tid == 0, 14);
    }
    if (blockIdx.x == 0 && threadIdx.x == 128) asm volatile("st.relaxed.gpu.global.u32 [%0], %1;" ::"l"(p.epoch), "r"(tag) : "memory");
  }
}

typedef CUresult (*EncodeFn)(CUtensorMap*, CUtensorMapDataType, cuuint32_t, void*, const cuuint64_t*, const cuuint64_t*,
                             const cuuint32_t*, const cuuint32_t*, CUtensorMapInterleave, CUtensorMapSwizzle,
                             CUtensorMapL2promotion, CUtensorMapFloatOOBfill);

void encode2d(EncodeFn fn, CUtensorMap* m, const void* ptr, uint64_t cols, uint64_t rows, uint32_t box_rows) {
  cuuint64_t dims[2] = {cols, rows};
  cuuint64_t strides[1] = {cols * 2};
  cuuint32_t box[2] = {64, box_rows};
  cuuint32_t es[2] = {1, 1};
  fn(m, CU_TENSOR_MAP_DATA_TYPE_BFLOAT16, 2, (void*)ptr, dims, strides, box, es, CU_TENSOR_MAP_INTERLEAVE_NONE,
     CU_TENSOR_MAP_SWIZZLE_128B, CU_TENSOR_MAP_L2_PROMOTION_L2_128B, CU_TENSOR_MAP_FLOAT_OOB_FILL_NONE);
}

}

extern "C" void kernel_launch(void* const* d_in, const int* in_sizes, int n_in, void* d_out, int out_size) {
  (void)in_sizes; (void)n_in; (void)out_size;
  void* fp = nullptr;
  cudaDriverEntryPointQueryResult qr;
  cudaGetDriverEntryPoint("cuTensorMapEncodeTiled", &fp, cudaEnableDefault, &qr);
  EncodeFn fn = (EncodeFn)fp;
  void *ph, *po, *ph2, *pact;
  cudaGetSymbolAddress(&ph, g_h);
  cudaGetSymbolAddress(&po, g_o);
  ph2 = ph;
  cudaGetSymbolAddress(&pact, g_act);
  Params p;
  encode2d(fn, &p.h, ph, DM, SEQ, 128);
  encode2d(fn, &p.o_ld, po, DM, SEQ, 128);
  encode2d(fn, &p.h2, ph2, DM, SEQ, 128);
  encode2d(fn, &p.act, pact, FF, SEQ, 128);
  encode2d(fn, &p.act_st, pact, FF, SEQ, 32);
  encode2d(fn, &p.wm, d_in[8], 6 * DM, DM, 64);
  encode2d(fn, &p.o_st, po, DM, SEQ, 16);
  encode2d(fn, &p.h2_st, ph2, DM, SEQ, 16);
  encode2d(fn, &p.wqkv, d_in[1], 3 * DM, DM, 64);
  encode2d(fn, &p.wqkv32, d_in[1], 3 * DM, DM, 32);
  encode2d(fn, &p.wo, d_in[2], DM, DM, 64);
  encode2d(fn, &p.wg, d_in[4], FF, DM, 64);
  encode2d(fn, &p.wu, d_in[5], FF, DM, 64);
  encode2d(fn, &p.wd, d_in[6], DM, FF, 64);
  {
    cuuint64_t dims[3] = {DM, SEQ / 2, 2};
    cuuint64_t strides[2] = {DM * 4, DM * 2};
    cuuint32_t box[3] = {64, 16, 1};
    cuuint32_t es[3] = {1, 1, 1};
    fn(&p.out, CU_TENSOR_MAP_DATA_TYPE_BFLOAT16, 3, d_out, dims, strides, box, es, CU_TENSOR_MAP_INTERLEAVE_NONE,
       CU_TENSOR_MAP_SWIZZLE_128B, CU_TENSOR_MAP_L2_PROMOTION_L2_128B, CU_TENSOR_MAP_FLOAT_OOB_FILL_NONE);
  }
  p.x = (const bf16*)d_in[0];
  p.c = (const bf16*)d_in[7];
  p.wmod = (const bf16*)d_in[8];
  for (int cl = 0; cl < 64; cl++) {
    const int grp = cl < 4 ? 0 : (cl < 36 ? (cl - 4) & 7 : 1 + (cl - 36) % 7);
    const int j = cl < 4 ? 4 + cl : (cl < 36 ? (cl - 4) >> 3 : 4 + (cl - 36) / 7);
    p.slot[cl] = (uint8_t)(grp * 8 + j);
  }
  void* q;
  p.x1 = (uint4*)d_out;
  cudaGetSymbolAddress(&q, g_modll); p.modll = (uint4*)q;
  cudaGetSymbolAddress(&q, g_halo); p.halo = (uint4*)q;
  cudaGetSymbolAddress(&q, g_stats); p.stats1 = (uint2*)q; p.stats2 = p.stats1 + SEQ * 8;
  cudaGetSymbolAddress(&q, g_cnt); p.cnt = (unsigned*)q;
  cudaGetSymbolAddress(&q, g_epoch); p.epoch = (unsigned*)q;

  cudaFuncSetAttribute(fused_kernel, cudaFuncAttributeMaxDynamicSharedMemorySize, SMEM_BYTES);
  cudaLaunchConfig_t cfg = {};
  cfg.gridDim = dim3(NCTA + 4);
  cfg.blockDim = dim3(384);
  cfg.dynamicSmemBytes = SMEM_BYTES;
  cfg.stream = cudaStreamPerThread;
  cudaLaunchAttribute at[1];
  at[0].id = cudaLaunchAttributeClusterDimension;
  at[0].val.clusterDim.x = 2; at[0].val.clusterDim.y = 1; at[0].val.clusterDim.z = 1;
  cfg.attrs = at;
  cfg.numAttrs = 1;
  cudaLaunchKernelEx(&cfg, fused_kernel, p);
}
```

```cpp
#include <cuda_runtime.h>
#include <cuda_bf16.h>
#include <cuda.h>
#include <stdint.h>

typedef __nv_bfloat16 bf16;

#define PAUSE 200
#define WMDELAY 2000
#define BDELAY 1500
#define NPRE0 3
#define NPRE1 1
#define ALIAS 1

#define PFW 8000
#define PFP 0

#define OSIG 3

__device__ __forceinline__ void wgmma_ss_n128(float (&d)[64], uint32_t da, uint32_t db, int scale_d) {
  asm volatile("{\n.reg .pred p;\n.reg .b64 da, db;\nsetp.ne.b32 p, %66, 0;\n"
    "mov.b64 da, {%64, 0x40000040};\nmov.b64 db, {%65, 0x40000040};\n"
    "wgmma.mma_async.sync.aligned.m64n128k16.f32.bf16.bf16 "
    "{%0, %1, %2, %3, %4, %5, %6, %7, %8, %9, %10, %11, %12, %13, %14, %15, "
    "%16, %17, %18, %19, %20, %21, %22, %23, %24, %25, %26, %27, %28, %29, %30, %31, "
    "%32, %33, %34, %35, %36, %37, %38, %39, %40, %41, %42, %43, %44, %45, %46, %47, "
    "%48, %49, %50, %51, %52, %53, %54, %55, %56, %57, %58, %59, %60, %61, %62, %63}, "
    "da, db, p, 1, 1, 0, 1;\n}\n"
    : "+f"(d[0]), "+f"(d[1]), "+f"(d[2]), "+f"(d[3]), "+f"(d[4]), "+f"(d[5]), "+f"(d[6]), "+f"(d[7]),
      "+f"(d[8]), "+f"(d[9]), "+f"(d[10]), "+f"(d[11]), "+f"(d[12]), "+f"(d[13]), "+f"(d[14]), "+f"(d[15]),
      "+f"(d[16]), "+f"(d[17]), "+f"(d[18]), "+f"(d[19]), "+f"(d[20]), "+f"(d[21]), "+f"(d[22]), "+f"(d[23]),
      "+f"(d[24]), "+f"(d[25]), "+f"(d[26]), "+f"(d[27]), "+f"(d[28]), "+f"(d[29]), "+f"(d[30]), "+f"(d[31]),
      "+f"(d[32]), "+f"(d[33]), "+f"(d[34]), "+f"(d[35]), "+f"(d[36]), "+f"(d[37]), "+f"(d[38]), "+f"(d[39]),
      "+f"(d[40]), "+f"(d[41]), "+f"(d[42]), "+f"(d[43]), "+f"(d[44]), "+f"(d[45]), "+f"(d[46]), "+f"(d[47]),
      "+f"(d[48]), "+f"(d[49]), "+f"(d[50]), "+f"(d[51]), "+f"(d[52]), "+f"(d[53]), "+f"(d[54]), "+f"(d[55]),
      "+f"(d[56]), "+f"(d[57]), "+f"(d[58]), "+f"(d[59]), "+f"(d[60]), "+f"(d[61]), "+f"(d[62]), "+f"(d[63])
    : "r"(da), "r"(db), "r"(scale_d));
}

__device__ __forceinline__ void wgmma_ss_n192(float (&d)[96], uint32_t da, uint32_t db, int scale_d) {
  asm volatile("{\n.reg .pred p;\n.reg .b64 da, db;\nsetp.ne.b32 p, %98, 0;\n"
    "mov.b64 da, {%96, 0x40000040};\nmov.b64 db, {%97, 0x40000040};\n"
    "wgmma.mma_async.sync.aligned.m64n192k16.f32.bf16.bf16 "
    "{%0, %1, %2, %3, %4, %5, %6, %7, %8, %9, %10, %11, %12, %13, %14, %15, "
    "%16, %17, %18, %19, %20, %21, %22, %23, %24, %25, %26, %27, %28, %29, %30, %31, "
    "%32, %33, %34, %35, %36, %37, %38, %39, %40, %41, %42, %43, %44, %45, %46, %47, "
    "%48, %49, %50, %51, %52, %53, %54, %55, %56, %57, %58, %59, %60, %61, %62, %63, "
    "%64, %65, %66, %67, %68, %69, %70, %71, %72, %73, %74, %75, %76, %77, %78, %79, "
    "%80, %81, %82, %83, %84, %85, %86, %87, %88, %89, %90, %91, %92, %93, %94, %95}, "
    "da, db, p, 1, 1, 0, 1;\n}\n"
    : "+f"(d[0]), "+f"(d[1]), "+f"(d[2]), "+f"(d[3]), "+f"(d[4]), "+f"(d[5]), "+f"(d[6]), "+f"(d[7]),
      "+f"(d[8]), "+f"(d[9]), "+f"(d[10]), "+f"(d[11]), "+f"(d[12]), "+f"(d[13]), "+f"(d[14]), "+f"(d[15]),
      "+f"(d[16]), "+f"(d[17]), "+f"(d[18]), "+f"(d[19]), "+f"(d[20]), "+f"(d[21]), "+f"(d[22]), "+f"(d[23]),
      "+f"(d[24]), "+f"(d[25]), "+f"(d[26]), "+f"(d[27]), "+f"(d[28]), "+f"(d[29]), "+f"(d[30]), "+f"(d[31]),
      "+f"(d[32]), "+f"(d[33]), "+f"(d[34]), "+f"(d[35]), "+f"(d[36]), "+f"(d[37]), "+f"(d[38]), "+f"(d[39]),
      "+f"(d[40]), "+f"(d[41]), "+f"(d[42]), "+f"(d[43]), "+f"(d[44]), "+f"(d[45]), "+f"(d[46]), "+f"(d[47]),
      "+f"(d[48]), "+f"(d[49]), "+f"(d[50]), "+f"(d[51]), "+f"(d[52]), "+f"(d[53]), "+f"(d[54]), "+f"(d[55]),
      "+f"(d[56]), "+f"(d[57]), "+f"(d[58]), "+f"(d[59]), "+f"(d[60]), "+f"(d[61]), "+f"(d[62]), "+f"(d[63]),
      "+f"(d[64]), "+f"(d[65]), "+f"(d[66]), "+f"(d[67]), "+f"(d[68]), "+f"(d[69]), "+f"(d[70]), "+f"(d[71]),
      "+f"(d[72]), "+f"(d[73]), "+f"(d[74]), "+f"(d[75]), "+f"(d[76]), "+f"(d[77]), "+f"(d[78]), "+f"(d[79]),
      "+f"(d[80]), "+f"(d[81]), "+f"(d[82]), "+f"(d[83]), "+f"(d[84]), "+f"(d[85]), "+f"(d[86]), "+f"(d[87]),
      "+f"(d[88]), "+f"(d[89]), "+f"(d[90]), "+f"(d[91]), "+f"(d[92]), "+f"(d[93]), "+f"(d[94]), "+f"(d[95])
    : "r"(da), "r"(db), "r"(scale_d));
}

__device__ __forceinline__ void wgmma_ss_n256(float (&d)[128], uint32_t da, uint32_t db, int scale_d) {
  asm volatile("{\n.reg .pred p;\n.reg .b64 da, db;\nsetp.ne.b32 p, %130, 0;\n"
    "mov.b64 da, {%128, 0x40000040};\nmov.b64 db, {%129, 0x40000040};\n"
    "wgmma.mma_async.sync.aligned.m64n256k16.f32.bf16.bf16 "
    "{%0, %1, %2, %3, %4, %5, %6, %7, %8, %9, %10, %11, %12, %13, %14, %15, "
    "%16, %17, %18, %19, %20, %21, %22, %23, %24, %25, %26, %27, %28, %29, %30, %31, "
    "%32, %33, %34, %35, %36, %37, %38, %39, %40, %41, %42, %43, %44, %45, %46, %47, "
    "%48, %49, %50, %51, %52, %53, %54, %55, %56, %57, %58, %59, %60, %61, %62, %63, "
    "%64, %65, %66, %67, %68, %69, %70, %71, %72, %73, %74, %75, %76, %77, %78, %79, "
    "%80, %81, %82, %83, %84, %85, %86, %87, %88, %89, %90, %91, %92, %93, %94, %95, "
    "%96, %97, %98, %99, %100, %101, %102, %103, %104, %105, %106, %107, %108, %109, %110, %111, "
    "%112, %113, %114, %115, %116, %117, %118, %119, %120, %121, %122, %123, %124, %125, %126, %127}, "
    "da, db, p, 1, 1, 0, 1;\n}\n"
    : "+f"(d[0]), "+f"(d[1]), "+f"(d[2]), "+f"(d[3]), "+f"(d[4]), "+f"(d[5]), "+f"(d[6]), "+f"(d[7]),
      "+f"(d[8]), "+f"(d[9]), "+f"(d[10]), "+f"(d[11]), "+f"(d[12]), "+f"(d[13]), "+f"(d[14]), "+f"(d[15]),
      "+f"(d[16]), "+f"(d[17]), "+f"(d[18]), "+f"(d[19]), "+f"(d[20]), "+f"(d[21]), "+f"(d[22]), "+f"(d[23]),
      "+f"(d[24]), "+f"(d[25]), "+f"(d[26]), "+f"(d[27]), "+f"(d[28]), "+f"(d[29]), "+f"(d[30]), "+f"(d[31]),
      "+f"(d[32]), "+f"(d[33]), "+f"(d[34]), "+f"(d[35]), "+f"(d[36]), "+f"(d[37]), "+f"(d[38]), "+f"(d[39]),
      "+f"(d[40]), "+f"(d[41]), "+f"(d[42]), "+f"(d[43]), "+f"(d[44]), "+f"(d[45]), "+f"(d[46]), "+f"(d[47]),
      "+f"(d[48]), "+f"(d[49]), "+f"(d[50]), "+f"(d[51]), "+f"(d[52]), "+f"(d[53]), "+f"(d[54]), "+f"(d[55]),
      "+f"(d[56]), "+f"(d[57]), "+f"(d[58]), "+f"(d[59]), "+f"(d[60]), "+f"(d[61]), "+f"(d[62]), "+f"(d[63]),
      "+f"(d[64]), "+f"(d[65]), "+f"(d[66]), "+f"(d[67]), "+f"(d[68]), "+f"(d[69]), "+f"(d[70]), "+f"(d[71]),
      "+f"(d[72]), "+f"(d[73]), "+f"(d[74]), "+f"(d[75]), "+f"(d[76]), "+f"(d[77]), "+f"(d[78]), "+f"(d[79]),
      "+f"(d[80]), "+f"(d[81]), "+f"(d[82]), "+f"(d[83]), "+f"(d[84]), "+f"(d[85]), "+f"(d[86]), "+f"(d[87]),
      "+f"(d[88]), "+f"(d[89]), "+f"(d[90]), "+f"(d[91]), "+f"(d[92]), "+f"(d[93]), "+f"(d[94]), "+f"(d[95]),
      "+f"(d[96]), "+f"(d[97]), "+f"(d[98]), "+f"(d[99]), "+f"(d[100]), "+f"(d[101]), "+f"(d[102]), "+f"(d[103]),
      "+f"(d[104]), "+f"(d[105]), "+f"(d[106]), "+f"(d[107]), "+f"(d[108]), "+f"(d[109]), "+f"(d[110]), "+f"(d[111]),
      "+f"(d[112]), "+f"(d[113]), "+f"(d[114]), "+f"(d[115]), "+f"(d[116]), "+f"(d[117]), "+f"(d[118]), "+f"(d[119]),
      "+f"(d[120]), "+f"(d[121]), "+f"(d[122]), "+f"(d[123]), "+f"(d[124]), "+f"(d[125]), "+f"(d[126]), "+f"(d[127])
    : "r"(da), "r"(db), "r"(scale_d));
}

namespace {

constexpr int SEQ = 2048, DM = 1024, FF = 3584;
constexpr int NCTA = 128;

constexpr uint32_t STG_OFF = 196608;
constexpr uint32_t MISC_OFF = STG_OFF + 32768;
constexpr uint32_t SMEM_BYTES = MISC_OFF + 3072;
constexpr uint32_t RED_OFF = 2 * 49152;
constexpr uint32_t MODB_OFF = MISC_OFF + 512;

enum { B_FQ = 0, B_EQ = 4, B_FW = 8, B_EW = 14, B_FG = 20, B_EG = 24, B_FD = 28, B_ED = 34,
       B_STGF = 40, B_MODB = 42, B_MODA = 45, B_RDY = 48, B_STGE = 56, B_COUNT = 58 };
enum { C_H = 0, C_O = 1, C_H2 = 3, C_ACT = 4, C_HA = 8, C_H2A = 9 };

struct Params {
  CUtensorMap h, o_ld, o_st, h2, act, out, wqkv, wqkv32, wo, wg, wu, wd, act_st, h2_st, wm;
  const bf16* x;
  const bf16* c;
  const bf16* wmod;
  uint4* modll;
  uint4* halo;
  uint2* stats1;
  uint2* stats2;
  unsigned* cnt;
  unsigned* epoch;
  uint8_t slot[64];
};

__device__ __align__(1024) bf16 g_h[SEQ * DM];
__device__ __align__(1024) bf16 g_o[SEQ * DM];
__device__ __align__(1024) bf16 g_act[SEQ * FF];
__device__ __align__(1024) uint4 g_modll[3072 / 2];
__device__ __align__(1024) uint4 g_halo[16 * 8 * 2 * 2 * 8 * 32];
__device__ __align__(1024) uint2 g_stats[2 * SEQ * 8];
__device__ __align__(1024) unsigned g_cnt[16 * 32];
__device__ uint4 g_epoch;
#define TR(off)

__device__ __forceinline__ uint32_t smem_u32(const void* p) { return (uint32_t)__cvta_generic_to_shared(p); }
__device__ __forceinline__ void mbar_init(uint32_t bar, uint32_t count) {
  asm volatile("mbarrier.init.shared::cta.b64 [%0], %1;" ::"r"(bar), "r"(count));
}
__device__ __forceinline__ void mbar_arrive(uint32_t bar) {
  asm volatile("mbarrier.arrive.shared::cta.b64 _, [%0];" ::"r"(bar) : "memory");
}
__device__ __forceinline__ void mbar_arrive_cluster(uint32_t cluster_addr) {
  asm volatile("mbarrier.arrive.shared::cluster.b64 _, [%0];" ::"r"(cluster_addr) : "memory");
}
__device__ __forceinline__ uint32_t mapa(uint32_t addr, uint32_t cta) {
  uint32_t r;
  asm volatile("mapa.shared::cluster.u32 %0, %1, %2;" : "=r"(r) : "r"(addr), "r"(cta));
  return r;
}
__device__ __forceinline__ void mbar_wait(uint32_t bar, uint32_t parity) {
  asm volatile(
      "{\n.reg .pred p;\n"
      "WAIT_%=:\n"
      "mbarrier.try_wait.parity.shared::cta.b64 p, [%0], %1;\n"
      "@!p bra WAIT_%=;\n}\n" ::"r"(bar), "r"(parity) : "memory");
}
__device__ __forceinline__ void mbar_wait_watchdog(uint32_t bar, uint32_t parity) {
  asm volatile(
      "{\n.reg .pred p;\n.reg .u64 t0, t1;\nmov.u64 t0, %%globaltimer;\n"
      "WAIT_%=:\n"
      "mbarrier.try_wait.parity.shared::cta.b64 p, [%0], %1;\n"
      "@p bra DONE_%=;\n"
      "mov.u64 t1, %%globaltimer;\n"
      "sub.u64 t1, t1, t0;\n"
      "setp.lt.u64 p, t1, 2000000000;\n"
      "@p bra WAIT_%=;\n"
      "trap;\n"
      "DONE_%=:\n}\n" ::"r"(bar), "r"(parity) : "memory");
}
__device__ __forceinline__ void cnt_wait(const unsigned* p, unsigned target) {
  asm volatile(
      "{\n.reg .pred p;\n.reg .u32 v;\n.reg .s32 d;\n"
      "WAIT_%=:\n"
      "ld.relaxed.gpu.global.u32 v, [%0];\n"
      "sub.s32 d, v, %1;\n"
      "setp.lt.s32 p, d, 0;\n"
      "@p bra WAIT_%=;\n"
      "fence.proxy.async.global;\n"
      "}\n" ::"l"(p), "r"(target) : "memory");
}
__device__ __forceinline__ void cnt_wait_lazy(const unsigned* p, unsigned target) {
  asm volatile(
      "{\n.reg .pred p;\n.reg .u32 v;\n.reg .s32 d;\n"
      "WAIT_%=:\n"
      "nanosleep.u32 400;\n"
      "ld.relaxed.gpu.global.u32 v, [%0];\n"
      "sub.s32 d, v, %1;\n"
      "setp.lt.s32 p, d, 0;\n"
      "@p bra WAIT_%=;\n"
      "fence.proxy.async.global;\n"
      "}\n" ::"l"(p), "r"(target) : "memory");
}
__device__ __forceinline__ void cnt_signal(unsigned* p) {
  asm volatile("{\n.reg .pred p;\nelect.sync _|p, 0xffffffff;\n@p red.relaxed.gpu.global.add.u32 [%0], 1;\n}\n" ::"l"(p) : "memory");
}
__device__ __forceinline__ void ll_store(uint4* p, uint32_t a, uint32_t b, uint32_t tag) {
  asm volatile("st.relaxed.gpu.global.v2.b64 [%0], {%1, %2};" ::"l"(p), "l"((uint64_t)a | ((uint64_t)tag << 32)),
               "l"((uint64_t)b | ((uint64_t)tag << 32)) : "memory");
}
__device__ __forceinline__ uint4 ll_peek(const uint4* p) {
  uint4 v;
  asm volatile("ld.relaxed.gpu.global.v4.u32 {%0, %1, %2, %3}, [%4];" : "=r"(v.x), "=r"(v.y), "=r"(v.z), "=r"(v.w) : "l"(p) : "memory");
  return v;
}
template <int N, int SLEEP = 0, class F>
__device__ __forceinline__ void ll_poll(F addr, uint32_t tag, uint32_t (&out)[2 * N]) {
  for (;;) {
    uint4 v[N];
#pragma unroll
    for (int i = 0; i < N; i++) v[i] = ll_peek(addr(i));
    uint32_t bad = 0;
#pragma unroll
    for (int i = 0; i < N; i++) {
      bad |= (v[i].y ^ tag) | (v[i].w ^ tag);
      out[2 * i] = v[i].x;
      out[2 * i + 1] = v[i].z;
    }
    if (__all_sync(~0u, bad == 0)) break;
    if (SLEEP) __nanosleep(SLEEP);
  }
}
constexpr uint64_t POLICY_EVICT_FIRST = 0x12F0000000000000ull;
__device__ __forceinline__ void expect_tx_elect(uint32_t bar, uint32_t bytes) {
  asm volatile("{\n.reg .pred p;\nelect.sync _|p, 0xffffffff;\n@p mbarrier.arrive.expect_tx.shared::cta.b64 _, [%0], %1;\n}\n" ::"r"(bar), "r"(bytes) : "memory");
}
__device__ __forceinline__ void arrive_elect(uint32_t bar) {
  asm volatile("{\n.reg .pred p;\nelect.sync _|p, 0xffffffff;\n@p mbarrier.arrive.shared::cta.b64 _, [%0];\n}\n" ::"r"(bar) : "memory");
}
__device__ __forceinline__ void tma_load(uint32_t dst, const CUtensorMap* m, uint32_t bar, int c0, int c1) {
  asm volatile("{\n.reg .pred p;\nelect.sync _|p, 0xffffffff;\n"
               "@p cp.async.bulk.tensor.2d.shared::cluster.global.mbarrier::complete_tx::bytes [%0], [%1, {%3, %4}], [%2];\n}\n"
               ::"r"(dst), "l"(m), "r"(bar), "r"(c0), "r"(c1) : "memory");
}
__device__ __forceinline__ void tma_load_mc(uint32_t dst, const CUtensorMap* m, uint32_t bar, int c0, int c1) {
  asm volatile("{\n.reg .pred p;\nelect.sync _|p, 0xffffffff;\n"
               "@p cp.async.bulk.tensor.2d.shared::cluster.global.mbarrier::complete_tx::bytes.multicast::cluster.L2::cache_hint [%0], [%1, {%3, %4}], [%2], %5, %6;\n}\n"
               ::"r"(dst), "l"(m), "r"(bar), "r"(c0), "r"(c1), "h"((uint16_t)3), "l"(POLICY_EVICT_FIRST) : "memory");
}
__device__ __forceinline__ void tma_load_ef(uint32_t dst, const CUtensorMap* m, uint32_t bar, int c0, int c1) {
  asm volatile("{\n.reg .pred p;\nelect.sync _|p, 0xffffffff;\n"
               "@p cp.async.bulk.tensor.2d.shared::cluster.global.mbarrier::complete_tx::bytes.L2::cache_hint [%0], [%1, {%3, %4}], [%2], %5;\n}\n"
               ::"r"(dst), "l"(m), "r"(bar), "r"(c0), "r"(c1), "l"(POLICY_EVICT_FIRST) : "memory");
}
__device__ __forceinline__ void tma_store2(const CUtensorMap* m, uint32_t src, int c0, int c1) {
  asm volatile("{\n.reg .pred p;\nelect.sync _|p, 0xffffffff;\n"
               "@p cp.async.bulk.tensor.2d.global.shared::cta.bulk_group [%0, {%2, %3}], [%1];\n}\n"
               ::"l"(m), "r"(src), "r"(c0), "r"(c1) : "memory");
}
__device__ __forceinline__ void tma_store3(const CUtensorMap* m, uint32_t src, int c0, int c1, int c2) {
  asm volatile("{\n.reg .pred p;\nelect.sync _|p, 0xffffffff;\n"
               "@p cp.async.bulk.tensor.3d.global.shared::cta.bulk_group [%0, {%2, %3, %4}], [%1];\n}\n"
               ::"l"(m), "r"(src), "r"(c0), "r"(c1), "r"(c2) : "memory");
}
__device__ __forceinline__ void tma_add3(const CUtensorMap* m, uint32_t src, int c0, int c1, int c2) {
  asm volatile("{\n.reg .pred p;\nelect.sync _|p, 0xffffffff;\n"
               "@p cp.reduce.async.bulk.tensor.3d.global.shared::cta.add.bulk_group [%0, {%2, %3, %4}], [%1];\n}\n"
               ::"l"(m), "r"(src), "r"(c0), "r"(c1), "r"(c2) : "memory");
}
__device__ __forceinline__ void store_pause(bool sleep) {
  asm volatile("cp.async.bulk.commit_group;" ::: "memory");
  asm volatile("cp.async.bulk.wait_group.read 0;" ::: "memory");
  if (sleep) __nanosleep(PAUSE);
}
__device__ __forceinline__ void l2_prefetch_tile(const CUtensorMap* m, int c0, int c1) {
  asm volatile("{\n.reg .pred p;\nelect.sync _|p, 0xffffffff;\n@p cp.async.bulk.prefetch.tensor.2d.L2.global [%0, {%1, %2}];\n}\n"
               ::"l"(m), "r"(c0), "r"(c1) : "memory");
}
__device__ __forceinline__ void prefetch_map(const CUtensorMap* m) {
  asm volatile("prefetch.tensormap [%0];" ::"l"(m) : "memory");
}
__device__ __forceinline__ void wg_fence() { asm volatile("wgmma.fence.sync.aligned;" ::: "memory"); }
__device__ __forceinline__ void wg_commit() { asm volatile("wgmma.commit_group.sync.aligned;" ::: "memory"); }
template <int N>
__device__ __forceinline__ void wg_wait() { asm volatile("wgmma.wait_group.sync.aligned %0;" ::"n"(N) : "memory"); }
__device__ __forceinline__ void bar_sync(int id, int n) { asm volatile("bar.sync %0, %1;" ::"r"(id), "r"(n) : "memory"); }
__device__ __forceinline__ void wg_bar(int cw) {
  asm volatile("{\n.reg .pred p;\nsetp.ne.s32 p, %0, 0;\n@p bar.sync 3, 128;\n@!p bar.sync 2, 128;\n}\n" ::"r"(cw) : "memory");
}
__device__ __forceinline__ void cluster_arrive_relaxed() { asm volatile("barrier.cluster.arrive.relaxed.aligned;" ::: "memory"); }
__device__ __forceinline__ void cluster_wait() { asm volatile("barrier.cluster.wait.acquire.aligned;" ::: "memory"); }
__device__ __forceinline__ uint32_t load_epoch(const unsigned* p) {
  uint32_t e;
  asm volatile("ld.relaxed.gpu.global.u32 %0, [%1];" : "=r"(e) : "l"(p) : "memory");
  return e;
}
__device__ __forceinline__ uint32_t pack2(float lo, float hi) {
  uint32_t r;
  asm("cvt.rn.bf16x2.f32 %0, %1, %2;" : "=r"(r) : "f"(hi), "f"(lo));
  return r;
}
__device__ __forceinline__ float bf_lo(uint32_t v) { return __uint_as_float(v << 16); }
__device__ __forceinline__ float bf_hi(uint32_t v) { return __uint_as_float(v & 0xffff0000u); }
__device__ __forceinline__ uint32_t fma_bf2(uint32_t a, uint32_t b, uint32_t c) {
  uint32_t d;
  asm("fma.rn.bf16x2 %0, %1, %2, %3;" : "=r"(d) : "r"(a), "r"(b), "r"(c));
  return d;
}
__device__ __forceinline__ float bf_round(float v) { return __bfloat162float(__float2bfloat16_rn(v)); }
__device__ __forceinline__ float silu_f(float v) { return __fdividef(v, 1.0f + __expf(-v)); }
__device__ __forceinline__ uint4 ldg_nc(const void* p) {
  uint4 v;
  asm volatile("ld.global.nc.L1::no_allocate.v4.u32 {%0, %1, %2, %3}, [%4];" : "=r"(v.x), "=r"(v.y), "=r"(v.z), "=r"(v.w) : "l"(p));
  return v;
}
__device__ __forceinline__ void stmatrix4(uint32_t addr, uint32_t a, uint32_t b, uint32_t c, uint32_t d) {
  asm volatile("stmatrix.sync.aligned.m8n8.x4.shared.b16 [%0], {%1, %2, %3, %4};" ::"r"(addr), "r"(a), "r"(b), "r"(c), "r"(d) : "memory");
}
__device__ __forceinline__ void stmatrix2(uint32_t addr, uint32_t a, uint32_t b) {
  asm volatile("stmatrix.sync.aligned.m8n8.x2.shared.b16 [%0], {%1, %2};" ::"r"(addr), "r"(a), "r"(b) : "memory");
}
__device__ __forceinline__ void stmatrix1(uint32_t addr, uint32_t a) {
  asm volatile("stmatrix.sync.aligned.m8n8.x1.shared.b16 [%0], {%1};" ::"r"(addr), "r"(a) : "memory");
}
__device__ __forceinline__ uint32_t movmatrix(uint32_t a) {
  uint32_t d;
  asm("movmatrix.sync.aligned.m8n8.trans.b16 %0, %1;" : "=r"(d) : "r"(a));
  return d;
}
__device__ __forceinline__ void mma16816(float (&d)[4], uint32_t a0, uint32_t a1, uint32_t a2, uint32_t a3, uint32_t b0, uint32_t b1) {
  asm("mma.sync.aligned.m16n8k16.row.col.f32.bf16.bf16.f32 {%0, %1, %2, %3}, {%4, %5, %6, %7}, {%8, %9}, {%0, %1, %2, %3};"
               : "+f"(d[0]), "+f"(d[1]), "+f"(d[2]), "+f"(d[3]) : "r"(a0), "r"(a1), "r"(a2), "r"(a3), "r"(b0), "r"(b1));
}
__device__ __forceinline__ void mma1688(float (&d)[4], uint32_t a0, uint32_t a1, uint32_t b0) {
  asm("mma.sync.aligned.m16n8k8.row.col.f32.bf16.bf16.f32 {%0, %1, %2, %3}, {%4, %5}, {%6}, {%0, %1, %2, %3};"
               : "+f"(d[0]), "+f"(d[1]), "+f"(d[2]), "+f"(d[3]) : "r"(a0), "r"(a1), "r"(b0));
}
__device__ __forceinline__ void ldmatrix4t(uint32_t (&b)[4], uint32_t addr) {
  asm volatile("ldmatrix.sync.aligned.m8n8.x4.trans.shared.b16 {%0, %1, %2, %3}, [%4];" : "=r"(b[0]), "=r"(b[1]), "=r"(b[2]), "=r"(b[3]) : "r"(addr) : "memory");
}
__device__ __forceinline__ void ldmatrix4(uint32_t& a, uint32_t& b, uint32_t& c, uint32_t& d, uint32_t addr) {
  asm volatile("ldmatrix.sync.aligned.m8n8.x4.shared.b16 {%0, %1, %2, %3}, [%4];" : "=r"(a), "=r"(b), "=r"(c), "=r"(d) : "r"(addr) : "memory");
}
__device__ __forceinline__ void cp_async16(uint32_t dst, const void* src) {
  asm volatile("cp.async.cg.shared.global.L2::cache_hint [%0], [%1], 16, %2;" ::"r"(dst), "l"(src), "l"(POLICY_EVICT_FIRST) : "memory");
}
__device__ __forceinline__ uint32_t lds32(uint32_t addr) {
  uint32_t v;
  asm volatile("ld.shared.u32 %0, [%1];" : "=r"(v) : "r"(addr) : "memory");
  return v;
}
__device__ __forceinline__ void sts64f(uint32_t addr, float a, float b) {
  asm volatile("st.shared.v2.f32 [%0], {%1, %2};" ::"r"(addr), "f"(a), "f"(b) : "memory");
}
constexpr float QK_SCALE = 0.17677669529663687f;
__device__ __forceinline__ float softmax8(float& p0, float& p1) {
  float m = fmaxf(p0, p1);
  m = fmaxf(m, __shfl_xor_sync(~0u, m, 1));
  m = fmaxf(m, __shfl_xor_sync(~0u, m, 2));
  asm("ex2.approx.ftz.f32 %0, %1;" : "=f"(p0) : "f"((p0 - m) * 1.4426950408889634f));
  asm("ex2.approx.ftz.f32 %0, %1;" : "=f"(p1) : "f"((p1 - m) * 1.4426950408889634f));
  float s = p0 + p1;
  s += __shfl_xor_sync(~0u, s, 1);
  s += __shfl_xor_sync(~0u, s, 2);
  float r;
  asm("rcp.approx.ftz.f32 %0, %1;" : "=f"(r) : "f"(s));
  return r;
}
__device__ __forceinline__ void sts128(uint32_t addr, uint32_t a, uint32_t b, uint32_t c, uint32_t d) {
  asm volatile("st.shared.v4.u32 [%0], {%1, %2, %3, %4};" ::"r"(addr), "r"(a), "r"(b), "r"(c), "r"(d) : "memory");
}
__device__ __forceinline__ uint4 lds128(uint32_t addr) {
  uint4 v;
  asm volatile("ld.shared.v4.u32 {%0, %1, %2, %3}, [%4];" : "=r"(v.x), "=r"(v.y), "=r"(v.z), "=r"(v.w) : "r"(addr) : "memory");
  return v;
}
__device__ __forceinline__ float2 lds64f(uint32_t addr) {
  float2 v;
  asm volatile("ld.shared.v2.f32 {%0, %1}, [%2];" : "=f"(v.x), "=f"(v.y) : "r"(addr) : "memory");
  return v;
}
#define PROF_AT(cond, slot) do {} while (0)

constexpr uint32_t SMEM_BASE = 1024;
constexpr uint32_t DESC_A = (1u << 16) | (SMEM_BASE >> 4);
constexpr uint32_t DESC_B = ((8192u >> 4) << 16) | ((SMEM_BASE + 16384) >> 4);

template <int BN> struct Wg;
template <> struct Wg<128> { static __device__ __forceinline__ void mma(float (&d)[64], uint32_t a, uint32_t b, int s) { wgmma_ss_n128(d, a, b, s); } };
template <> struct Wg<192> { static __device__ __forceinline__ void mma(float (&d)[96], uint32_t a, uint32_t b, int s) { wgmma_ss_n192(d, a, b, s); } };
template <> struct Wg<256> { static __device__ __forceinline__ void mma(float (&d)[128], uint32_t a, uint32_t b, int s) { wgmma_ss_n256(d, a, b, s); } };

struct Ring {
  uint32_t full0, rel0;
  int s;
  uint32_t ph;
  bool releaser;
};

template <int N>
__device__ __forceinline__ void fence_regs(float (&a)[N]) {
#pragma unroll
  for (int i = 0; i < N; i++) asm volatile("" : "+f"(a[i])::"memory");
}

template <int BN, int NST, uint32_t STAGE>
__device__ __forceinline__ void kblock(float (&acc)[BN / 2], Ring& g, uint32_t a_addr, bool zero, uint32_t& prev) {
  mbar_wait(g.full0 + 8 * g.s, g.ph);
  const uint32_t da = DESC_A + (a_addr >> 4);
  const uint32_t db = DESC_B + g.s * (STAGE >> 4);
  wg_fence();
#pragma unroll
  for (int k = 0; k < 4; k++) Wg<BN>::mma(acc, da + k * 2, db + k * 128, !(zero && k == 0));
  wg_commit();
  wg_wait<1>();
  if (prev != 0) mbar_arrive_cluster(prev);
  prev = g.releaser ? g.rel0 + 8 * g.s : 0u;
  if (++g.s == NST) { g.s = 0; g.ph ^= 1; }
}
template <int N>
__device__ __forceinline__ void tile_end(float (&acc)[N], uint32_t& prev) {
  wg_wait<0>();
  if (prev != 0) mbar_arrive_cluster(prev);
  prev = 0;
  fence_regs(acc);
}

__device__ __forceinline__ int other_kb(int q, int j) {
  const int ch = q >= 7, jj = q - 7 * ch;
  return 2 * (jj < j ? jj : jj + 1) + ch;
}
__device__ __forceinline__ int own_first(int it, int j) {
  return it >= 16 ? (it & 15) : (it < 2 ? 2 * j + it : other_kb(it - 2, j));
}
__device__ __forceinline__ int qkv_kb(int it, int j) {
  return it < 4 ? 2 * j + (it & 1) : other_kb(it < 18 ? it - 4 : it - 18, j);
}
__device__ __forceinline__ int wo_k(int it, int j) {
  return it < 8 ? it * 128 : (it == 8 ? j : (it - 9 < j ? it - 9 : it - 8)) * 128 + 64;
}
__device__ __forceinline__ int down_k(int it) {
  const int r = (it >> 4) - 1, idx = it & 15;
  return r < 0 ? idx * 64 : (r < 3 ? (idx >> 1) * 448 + r * 128 + (idx & 1) * 64 : idx * 448 + 384);
}
__device__ __forceinline__ void wait_p3_free(uint32_t empty3, int i) {
  mbar_wait(empty3 + 8 * ((i * 2) / 3), 1);
  mbar_wait(empty3 + 8 * ((i * 2 + 1) / 3), 1);
}
__device__ __forceinline__ void wait_p2_free(uint32_t empty2, int i) {
  const int w0 = (i * 3) / 2, w1 = (i * 3 + 2) / 2;
  mbar_wait(empty2 + 8 * w0, w0 < 4 ? 0 : 1);
  mbar_wait(empty2 + 8 * w1, w1 < 4 ? 0 : 1);
}

__device__ __forceinline__ void chan(float& m, float& q, float m2, float q2, float n) {
  const float d = m2 - m;
  m = 0.5f * (m + m2);
  q = q + q2 + d * d * (0.5f * n);
}

__device__ __forceinline__ uint32_t tag16(uint32_t tag) { return tag % 65535u + 1u; }
__device__ __forceinline__ void stat_store(uint2* slot, float m, float q, uint32_t t16) {
  const uint32_t a = ((__float_as_uint(m) + 0x80u) & 0xffffff00u) | (t16 & 0xffu), b = ((__float_as_uint(q) + 0x80u) & 0xffffff00u) | (t16 >> 8);
  asm volatile("st.relaxed.gpu.global.b64 [%0], %1;" ::"l"(slot), "l"((uint64_t)a | ((uint64_t)b << 32)) : "memory");
}
__device__ __forceinline__ void stat_gather(const uint2* rows, uint32_t t16, int lane, float (&rs)[2], float (&nb)[2]) {
  const uint4* sp = (const uint4*)(rows + (lane >> 3) * 128) + (lane & 7);
  const uint32_t want = (t16 & 0xffu) | ((t16 >> 8) << 8);
  uint4 a, b;
  for (;;) {
    a = ll_peek(sp);
    b = ll_peek(sp + 256);
    const uint32_t bad = (__byte_perm(a.x, a.y, 0x40) ^ want) | (__byte_perm(a.z, a.w, 0x40) ^ want) | (__byte_perm(b.x, b.y, 0x40) ^ want) |
                         (__byte_perm(b.z, b.w, 0x40) ^ want);
    if (__all_sync(~0u, (bad & 0xffffu) == 0)) break;
  }
  float m0 = __uint_as_float(a.x & 0xffffff00u), q0 = __uint_as_float(a.y & 0xffffff00u);
  float m1 = __uint_as_float(a.z & 0xffffff00u), q1 = __uint_as_float(a.w & 0xffffff00u);
  chan(m0, q0, __uint_as_float(b.x & 0xffffff00u), __uint_as_float(b.y & 0xffffff00u), 128.f);
  chan(m1, q1, __uint_as_float(b.z & 0xffffff00u), __uint_as_float(b.w & 0xffffff00u), 128.f);
  const bool hi = lane & 8;
  float m = hi ? m1 : m0, q = hi ? q1 : q0;
  chan(m, q, __shfl_xor_sync(~0u, hi ? m0 : m1, 8), __shfl_xor_sync(~0u, hi ? q0 : q1, 8), 256.f);
  chan(m, q, __shfl_xor_sync(~0u, m, 16), __shfl_xor_sync(~0u, q, 16), 512.f);
  const float rstd = rsqrtf(q * (1.0f / DM) + 1e-5f), nmr = -m * rstd;
  const int r = lane >> 2, src = (r >> 1) + (r & 1) * 8;
  rs[0] = __shfl_sync(~0u, rstd, src); nb[0] = __shfl_sync(~0u, nmr, src);
  rs[1] = __shfl_sync(~0u, rstd, src + 4); nb[1] = __shfl_sync(~0u, nmr, src + 4);
}

__device__ __forceinline__ void publish_stats(const uint32_t (&xl)[16], const uint32_t (&xh)[16], uint2* slot, int lane, uint32_t t16) {
  float ds[4] = {0.f, 0.f, 0.f, 0.f}, dl[4] = {0.f, 0.f, 0.f, 0.f}, dh[4] = {0.f, 0.f, 0.f, 0.f};
#pragma unroll
  for (int q = 0; q < 8; q++) {
    mma16816(ds, xl[2 * q], xh[2 * q], xl[2 * q + 1], xh[2 * q + 1], 0x3f803f80u, 0x3f803f80u);
    mma16816(dl, xl[2 * q], xh[2 * q], xl[2 * q + 1], xh[2 * q + 1], xl[2 * q], xl[2 * q + 1]);
    mma16816(dh, xl[2 * q], xh[2 * q], xl[2 * q + 1], xh[2 * q + 1], xh[2 * q], xh[2 * q + 1]);
  }
  const int r = lane >> 2;
  if ((lane & 3) == (r >> 1)) {
    const float ml = ds[0] * (1.0f / 128), mh = ds[2] * (1.0f / 128);
    const float ql = fmaxf(((r & 1) ? dl[1] : dl[0]) - ds[0] * ml, 0.f), qh = fmaxf(((r & 1) ? dh[3] : dh[2]) - ds[2] * mh, 0.f);
    stat_store(slot + r, ml, ql, t16);
    stat_store(slot + r + 8, mh, qh, t16);
  }
  __syncwarp();
}

__device__ __forceinline__ void stage_slab(uint32_t chunk, int warp, int lane, const uint32_t (&lo)[8], const uint32_t (&hi)[8]) {
  const int row = warp * 16 + (lane & 7) + ((lane >> 3) & 1) * 8;
  const uint32_t rbase = chunk + row * 128;
#pragma unroll
  for (int q = 0; q < 4; q++) {
    const int grp = 2 * q + (lane >> 4);
    stmatrix4(rbase + ((grp ^ (row & 7)) << 4), lo[2 * q], hi[2 * q], lo[2 * q + 1], hi[2 * q + 1]);
  }
}
__device__ __forceinline__ float silu_mul(float g, float u) {
  float e, r;
  asm("ex2.approx.ftz.f32 %0, %1;" : "=f"(e) : "f"(g * -1.4426950408889634f));
  asm("rcp.approx.ftz.f32 %0, %1;" : "=f"(r) : "f"(1.0f + e));
  return g * r * u;
}
__device__ __forceinline__ uint32_t swiglu2(uint32_t g2, uint32_t u2) {
  asm volatile("" : "+r"(g2));
  return pack2(silu_mul(bf_lo(g2), bf_lo(u2)), silu_mul(bf_hi(g2), bf_hi(u2)));
}
__device__ __forceinline__ void stage_done(uint32_t bar, int lane) {
  asm volatile("fence.proxy.async.shared::cta;" ::: "memory");
  __syncwarp();
  if (lane == 0) mbar_arrive(bar);
}

__device__ __forceinline__ int fresh_tid() {
  int t;
  asm volatile("mov.u32 %0, %%tid.x;" : "=r"(t));
  return t;
}
#define RING_IDS()                                                                                           \
  const int tid = fresh_tid() - 128;                                                                         \
  const int cw = __shfl_sync(~0u, tid >> 7, 0), warp = __shfl_sync(~0u, (tid >> 5) & 3, 0);                  \
  const bool releaser = (tid & 31) < 2;                                                                      \
  const uint32_t rbars = mapa(bars, tid & 1);                                                                \
  const uint32_t a_base = cw * 8192
#define LANE_IDS()                                                                                           \
  const int lane = fresh_tid() & 31, r = lane >> 2, c = lane & 3;                                            \
  const int srow = warp * 16 + (lane & 7) + ((lane >> 3) & 1) * 8;                                           \
  const uint32_t slab = stg + cw * 8192 + srow * 128, sw0 = (lane >> 4) ^ (srow & 7);                        \
  (void)r; (void)c; (void)slab; (void)sw0

template <int NPRE, bool EAGER, class Step>
__device__ __forceinline__ void attention(float (&acc)[96], const Params& p, int rho, int rb, int cta, int cw, int warp, uint32_t tag,
                                          uint32_t stg, uint32_t bars, uint32_t& prev, Step step) {
  uint32_t ql[8], qh[8], k0[8], k1[8], v0[8], v1[8], hp[16];
  if (EAGER) {
    tile_end(acc, prev);
  } else {
    step();
    fence_regs(acc);
  }
#pragma unroll
  for (int t = 0; t < 8; t++) {
    k0[t] = pack2(acc[4 * (8 + t)], acc[4 * (8 + t) + 1]);
    k1[t] = pack2(acc[4 * (8 + t) + 2], acc[4 * (8 + t) + 3]);
    v0[t] = pack2(acc[4 * (16 + t)], acc[4 * (16 + t) + 1]);
    v1[t] = pack2(acc[4 * (16 + t) + 2], acc[4 * (16 + t) + 3]);
    asm volatile("" : "+r"(k0[t]), "+r"(k1[t]), "+r"(v0[t]), "+r"(v1[t]));
  }
  const int lane = fresh_tid() & 31, r = lane >> 2, c = lane & 3;
#pragma unroll
  for (int t = 0; t < 8; t++) v1[t] = movmatrix(v1[t]);
  mbar_wait(bars + 8 * B_STGE, rho);
  mbar_wait(bars + 8 * (B_STGE + 1), 0);
  const uint32_t xch = stg + 16384 + (cw * 4 + warp) * 2048 + lane * 16;
  if (warp < 3) {
    sts128(xch, k1[0], k1[1], k1[2], k1[3]);
    sts128(xch + 512, k1[4], k1[5], k1[6], k1[7]);
    sts128(xch + 1024, v1[0], v1[1], v1[2], v1[3]);
    sts128(xch + 1536, v1[4], v1[5], v1[6], v1[7]);
  } else if (rb < 15) {
    uint4* dst = p.halo + ((cta * 2 + rho) * 2 + cw) * 256 + lane;
#pragma unroll
    for (int t = 0; t < 4; t++) {
      ll_store(dst + t * 32, k1[2 * t], k1[2 * t + 1], tag);
      ll_store(dst + (4 + t) * 32, v1[2 * t], v1[2 * t + 1], tag);
    }
  }
#pragma unroll
  for (int t = 0; t < 8; t++) {
    v0[t] = movmatrix(v0[t]);
    ql[t] = pack2(acc[4 * t], acc[4 * t + 1]);
    qh[t] = pack2(acc[4 * t + 2], acc[4 * t + 3]);
    asm volatile("" : "+r"(v0[t]), "+r"(ql[t]), "+r"(qh[t]));
  }
#pragma unroll 1
  for (int i = 0; i < NPRE; i++) step();
  const uint4* src = p.halo + (((cta - 8) * 2 + rho) * 2 + cw) * 256 + lane;
  uint4 early[8] = {};
  if (warp == 0 && rb > 0) {
#pragma unroll
    for (int i = 0; i < 8; i++) early[i] = ll_peek(src + i * 32);
  }
  step();
  wg_bar(cw);
  if (warp > 0) {
#pragma unroll
    for (int t = 0; t < 4; t++) {
      const uint4 a = lds128(xch - 2048 + t * 512);
      hp[4 * t] = a.x; hp[4 * t + 1] = a.y; hp[4 * t + 2] = a.z; hp[4 * t + 3] = a.w;
    }
  } else if (rb > 0) {
    uint32_t bad = 0;
#pragma unroll
    for (int i = 0; i < 8; i++) {
      bad |= (early[i].y ^ tag) | (early[i].w ^ tag);
      hp[2 * i] = early[i].x;
      hp[2 * i + 1] = early[i].z;
    }
    if (!__all_sync(~0u, bad == 0)) ll_poll<8>([&](int i) { return src + i * 32; }, tag, hp);
  } else {
#pragma unroll
    for (int t = 0; t < 16; t++) hp[t] = 0;
  }
  wg_wait<0>();
  if (prev != 0) mbar_arrive_cluster(prev);
  prev = 0;
#pragma unroll
  for (int t = 0; t < 8; t++) asm volatile("" : "+r"(ql[t])::"memory");
  const bool up0 = 2 * c > r, up1 = 2 * c + 1 > r;
  const bool first = (rb == 0) && (warp == 0);
  uint32_t a0[2], a2[2], a3[2], a5[2];
  float il[2], ih[2];
#pragma unroll
  for (int h = 0; h < 2; h++) {
    float sp[4] = {0.f, 0.f, 0.f, 0.f}, s0[4] = {0.f, 0.f, 0.f, 0.f}, s1[4] = {0.f, 0.f, 0.f, 0.f};
#pragma unroll
    for (int ks = 0; ks < 2; ks++) {
      const int t = 4 * h + 2 * ks;
      mma16816(sp, ql[t], qh[t], ql[t + 1], qh[t + 1], hp[t], hp[t + 1]);
      mma16816(s0, ql[t], qh[t], ql[t + 1], qh[t + 1], k0[t], k0[t + 1]);
      mma16816(s1, ql[t], qh[t], ql[t + 1], qh[t + 1], k1[t], k1[t + 1]);
    }
    float p0 = (up0 ? sp[0] : s0[0]) * QK_SCALE, p1 = (up1 ? sp[1] : s0[1]) * QK_SCALE;
    float p2 = (up0 ? s0[2] : s1[2]) * QK_SCALE, p3 = (up1 ? s0[3] : s1[3]) * QK_SCALE;
    if (first && up0) p0 = -1000000000.0f;
    if (first && up1) p1 = -1000000000.0f;
    il[h] = softmax8(p0, p1);
    ih[h] = softmax8(p2, p3);
    a0[h] = pack2(up0 ? p0 : 0.f, up1 ? p1 : 0.f);
    a2[h] = pack2(up0 ? 0.f : p0, up1 ? 0.f : p1);
    a3[h] = pack2(up0 ? p2 : 0.f, up1 ? p3 : 0.f);
    a5[h] = pack2(up0 ? 0.f : p2, up1 ? 0.f : p3);
  }
  float o[8][4];
#pragma unroll
  for (int t = 0; t < 8; t++) {
#pragma unroll
    for (int q = 0; q < 4; q++) o[t][q] = 0.f;
    mma1688(o[t], 0u, a5[t >> 2], v1[t]);
    mma16816(o[t], a0[t >> 2], 0u, a2[t >> 2], a3[t >> 2], hp[8 + t], v0[t]);
  }
#pragma unroll
  for (int t = 0; t < 8; t++) fence_regs(o[t]);
  if (!EAGER) step();
  uint32_t ol[8], oh[8];
#pragma unroll
  for (int t = 0; t < 8; t++) {
    ol[t] = pack2(o[t][0] * il[t >> 2], o[t][1] * il[t >> 2]);
    oh[t] = pack2(o[t][2] * ih[t >> 2], o[t][3] * ih[t >> 2]);
  }
  if (!EAGER) step();
  stage_slab(stg + cw * 8192, warp, lane, ol, oh);
  stage_done(bars + 8 * B_STGF, lane);
  if (!EAGER) step();
}

__global__ void __launch_bounds__(384, 1) fused_kernel(const __grid_constant__ Params p) {
  extern __shared__ __align__(1024) uint8_t smem_raw[];
  const uint32_t sm = smem_u32(smem_raw);
  const uint32_t bars = sm + MISC_OFF;
  const uint32_t stg = sm + STG_OFF;
  const int rank = blockIdx.x & 1;
  const int cl = blockIdx.x >> 1;
  if (cl >= NCTA / 2) {
    const int e = blockIdx.x - NCTA, wid = __shfl_sync(~0u, (int)(threadIdx.x >> 5), 0), lane = threadIdx.x & 31;
    if (threadIdx.x == 0) {
      for (int i = 0; i < 6; i++) { mbar_init(bars + 8 * i, 1); mbar_init(bars + 8 * (6 + i), 8); }
      asm volatile("fence.mbarrier_init.release.cluster;" ::: "memory");
    }
    const uint32_t tag = load_epoch(p.epoch) + 1;
    if (threadIdx.x < 256) ll_store(p.modll + 512 + (threadIdx.x >> 6) * 256 + e * 64 + (threadIdx.x & 63), 0u, 0u, 0u);
    for (int i = threadIdx.x; i < 1536; i += 384) {
      uint4 o = make_uint4(0u, 0u, 0u, 0u);
      if (i < 1024 && (i & 63) < 8) {
        const uint4 cv = ldg_nc(p.c + (i >> 6) * 64 + (i & 7) * 8);
        o = make_uint4(pack2(silu_f(bf_lo(cv.x)), silu_f(bf_hi(cv.x))), pack2(silu_f(bf_lo(cv.y)), silu_f(bf_hi(cv.y))),
                       pack2(silu_f(bf_lo(cv.z)), silu_f(bf_hi(cv.z))), pack2(silu_f(bf_lo(cv.w)), silu_f(bf_hi(cv.w))));
      }
      sts128(stg + i * 16, o.x, o.y, o.z, o.w);
    }
    asm volatile("fence.proxy.async.shared::cta;" ::: "memory");
    __syncthreads();
    if (wid == 0) {
      __nanosleep(WMDELAY);
      uint32_t ph = 1;
#pragma unroll 1
      for (int it = 0, s = 0; it < 64; it++) {
        mbar_wait(bars + 8 * (6 + s), ph);
        expect_tx_elect(bars + 8 * s, 32768);
#pragma unroll
        for (int q = 0; q < 4; q++) tma_load_ef(sm + s * 32768 + q * 8192, &p.wm, bars + 8 * s, 2048 + (it >> 4) * 1024 + e * 256 + q * 64, (it & 15) * 64);
        if (++s == 6) { s = 0; ph ^= 1; }
      }
    } else if (wid == 1 && PFW) {
      __nanosleep(PFW);
#pragma unroll 1
      for (int i = 0; i < 64; i++) {
        l2_prefetch_tile(&p.wo, (i & 15) * 64, (e * 4 + (i >> 4)) * 64);
        if (PFP) __nanosleep(PFP);
      }
#pragma unroll 1
      for (int i = 0; i < 128; i++) {
        l2_prefetch_tile((i & 2) ? &p.wu : &p.wg, ((i >> 2) & 7) * 448 + (i & 1) * 64, ((i >> 5) * 4 + e) * 64);
        if (PFP) __nanosleep(PFP);
      }
    } else if (wid >= 4) {
      const int hf = (wid >> 2) - 1;
      uint32_t ph = 0;
      int s = 0;
#pragma unroll 1
      for (int v = 0; v < 4; v++) {
        float acc[64];
#pragma unroll 1
        for (int kb = 0; kb < 16; kb++) {
          mbar_wait_watchdog(bars + 8 * s, ph);
          const uint32_t da = DESC_A + ((STG_OFF + kb * 1024) >> 4), db = DESC_B + ((s * 32768 + hf * 16384) >> 4) - 1024;
          wg_fence();
#pragma unroll
          for (int k = 0; k < 4; k++) wgmma_ss_n128(acc, da + k * 2, db + k * 128, (kb | k) != 0);
          wg_commit();
          wg_wait<0>();
          if (lane == 0) mbar_arrive(bars + 8 * (6 + s));
          if (++s == 6) { s = 0; ph ^= 1; }
        }
        if ((wid & 3) == 0) {
#pragma unroll
          for (int n = 0; n < 16; n++) {
            const uint32_t mine = pack2(acc[4 * n], acc[4 * n + 1]), next = __shfl_down_sync(~0u, mine, 1);
            if (lane < 4 && (lane & 1) == 0) ll_store(p.modll + 512 + v * 256 + e * 64 + hf * 32 + n * 2 + (lane >> 1), mine, next, tag);
          }
        }
      }
    }
    return;
  }
  const int slot = p.slot[cl];
  const int rb = (slot >> 3) * 2 + rank, j = slot & 7;
  const int cta = rb * 8 + j;
  PROF_AT(threadIdx.x == 0, 0);

  if (threadIdx.x < 128) {
    uint32_t tag = load_epoch(p.epoch);
    asm volatile("setmaxnreg.dec.sync.aligned.u32 40;");
    const int warp = __shfl_sync(~0u, (int)(threadIdx.x >> 5), 0), lane = threadIdx.x & 31;
    if (threadIdx.x == 0) {
      if ((sm & 0x3FFFF) != SMEM_BASE) asm volatile("trap;");
      for (int i = 0; i < 4; i++) { mbar_init(bars + 8 * (B_FQ + i), 1); mbar_init(bars + 8 * (B_EQ + i), 16); }
      for (int i = 0; i < 6; i++) { mbar_init(bars + 8 * (B_FW + i), 1); mbar_init(bars + 8 * (B_EW + i), 16); }
      for (int i = 0; i < 4; i++) { mbar_init(bars + 8 * (B_FG + i), 1); mbar_init(bars + 8 * (B_EG + i), 16); }
      for (int i = 0; i < 6; i++) { mbar_init(bars + 8 * (B_FD + i), 1); mbar_init(bars + 8 * (B_ED + i), 16); }
      for (int i = 0; i < 2; i++) { mbar_init(bars + 8 * (B_STGF + i), 8); mbar_init(bars + 8 * (B_STGE + i), 1); }
      mbar_init(bars + 8 * B_MODB, 1);
      mbar_init(bars + 8 * (B_MODB + 1), 1);
      mbar_init(bars + 8 * B_MODA, 1);
      for (int i = 0; i < 8; i++) mbar_init(bars + 8 * (B_RDY + i), 1);
      asm volatile("fence.mbarrier_init.release.cluster;" ::: "memory");
    }
    __syncwarp();
    cluster_arrive_relaxed();
    tag += 1;
    const unsigned target = tag * 8;
    unsigned* cnt = p.cnt + rb * 32;
    cluster_wait();
    if (warp == 0) {
      const CUtensorMap* wgu = rank ? &p.wu : &p.wg;
      uint32_t st = sm + 16384, fb = bars + 8 * B_FQ, ph = 1;
      __nanosleep(BDELAY);
#pragma unroll 1
      for (int it = 0; it < 32; it++) {
        const int kb = qkv_kb(it, j), col = j * 128 + ((it < 4 ? it >= 2 : it >= 18) ? 64 : 0);
        mbar_wait(fb + 8 * (B_EQ - B_FQ), ph);
        expect_tx_elect(fb, it < 4 ? 24576 : 40960);
        tma_load_mc(st + rank * 8192, &p.wqkv, fb, col + rank * 1024, kb * 64);
        tma_load_mc(st + 16384 + rank * 4096, &p.wqkv32, fb, col + 2048, kb * 64 + rank * 32);
        st += 49152; fb += 8;
        if ((it & 3) == 3) { st -= 4 * 49152; fb -= 32; ph ^= 1; }
      }
      fb = bars + 8 * B_FW; ph = 1;
#pragma unroll 1
      for (int it = 0, s = 0; it < 16; it++) {
        if (it < 6) wait_p3_free(bars + 8 * B_EQ, it);
        mbar_wait(fb + 8 * (B_EW - B_FW), ph);
        expect_tx_elect(fb, it == 8 ? 16384 : 32768);
        tma_load_mc(st + rank * 8192, &p.wo, fb, j * 128 + rank * 64, wo_k(it, j));
        st += 32768; fb += 8;
        if (++s == 6) { s = 0; st -= 6 * 32768; fb -= 48; ph ^= 1; }
      }
      st = sm + 16384; fb = bars + 8 * B_FG; ph = 1;
#pragma unroll 1
      for (int it = 0; it < 48; it++) {
        const int kb = own_first(it, j), col = j * 448 + (it >> 4) * 128;
        if (it < 4) wait_p2_free(bars + 8 * B_EW, it);
        mbar_wait(fb + 8 * (B_EG - B_FG), ph);
        expect_tx_elect(fb, it < 2 ? 32768 : 49152);
        tma_load_mc(st + rank * 16384, wgu, fb, col, kb * 64);
        tma_load_mc(st + rank * 16384 + 8192, wgu, fb, col + 64, kb * 64);
        st += 49152; fb += 8;
        if ((it & 3) == 3) { st -= 4 * 49152; fb -= 32; ph ^= 1; }
      }
      fb = bars + 8 * B_FD; ph = 1;
#pragma unroll 1
      for (int it = 0, s = 0; it < 72; it++) {
        if (it < 6) wait_p3_free(bars + 8 * B_EG, it);
        mbar_wait(fb + 8 * (B_ED - B_FD), ph);
        expect_tx_elect(fb, 32768);
        tma_load_mc(st + rank * 8192, it < 16 ? wgu : &p.wd, fb, it < 16 ? j * 448 + 384 : j * 128 + rank * 64, down_k(it));
        st += 32768; fb += 8;
        if (++s == 6) { s = 0; st -= 6 * 32768; fb -= 48; ph ^= 1; }
      }
    } else if (warp == 1) {
      const int arow = rb * 128;
      uint32_t st = sm, fb = bars + 8 * B_FQ, ph = 0;
      cnt_wait(cnt + C_HA, target);
      PROF_AT(lane == 0, 16);
#pragma unroll 1
      for (int it = 4; it < 32; it++) {
        if (it == 11) mbar_wait(bars + 8 * (B_RDY + C_H), 0);
        mbar_wait(fb + 8 * (B_EQ - B_FQ), ph);
        tma_load(st, &p.h, fb, qkv_kb(it, j) * 64, arow);
        st += 49152; fb += 8;
        if ((it & 3) == 3) { st -= 4 * 49152; fb -= 32; ph ^= 1; }
      }
      fb = bars + 8 * B_FW; ph = 1;
#pragma unroll 1
      for (int it = 0, s = 0; it < 16; it++) {
        if (it < 6) wait_p3_free(bars + 8 * B_EQ, it);
        mbar_wait(fb + 8 * (B_EW - B_FW), ph);
        if (it == 0) mbar_wait(bars + 8 * (B_RDY + C_O), 0);
        if (it == 9) cnt_wait(cnt + C_O + 1, target * 8);
        PROF_AT(lane == 0 && (it == 0 || it == 9), 17 + (it >> 3));
        if (it != 8) tma_load(st, &p.o_ld, fb, wo_k(it, j), arow);
        st += 32768; fb += 8;
        if (++s == 6) { s = 0; st -= 6 * 32768; fb -= 48; ph ^= 1; }
      }
      st = sm + 2 * 49152; fb = bars + 8 * (B_FG + 2); ph = 1;
      cnt_wait(cnt + C_H2A, target * 8);
      PROF_AT(lane == 0, 19);
#pragma unroll 1
      for (int it = 2; it < 48; it++) {
        if (it == 9) mbar_wait(bars + 8 * (B_RDY + C_H2), 0);
        mbar_wait(fb + 8 * (B_EG - B_FG), ph);
        tma_load(st, &p.h2, fb, own_first(it, j) * 64, arow);
        st += 49152; fb += 8;
        if ((it & 3) == 3) { st -= 4 * 49152; fb -= 32; ph ^= 1; }
      }
      fb = bars + 8 * B_FD; ph = 1;
#pragma unroll 1
      for (int it = 0, s = 0; it < 72; it++) {
        if (it < 6) wait_p3_free(bars + 8 * B_EG, it);
        mbar_wait(fb + 8 * (B_ED - B_FD), ph);
        if ((it & 15) == 0 && it > 0) { mbar_wait(bars + 8 * (B_RDY + C_ACT - 1 + (it >> 4)), 0); PROF_AT(lane == 0, 19 + (it >> 4)); }
        tma_load(st, it < 16 ? &p.h2 : &p.act, fb, down_k(it), arow);
        st += 32768; fb += 8;
        if (++s == 6) { s = 0; st -= 6 * 32768; fb -= 48; ph ^= 1; }
      }
    } else if (warp == 2) {
      if (lane < 14) prefetch_map(&p.h + lane);
      __syncwarp();
      uint32_t ph1 = 0;
#pragma unroll 1
      for (int n = 0; n < 8; n++) {
        const int nch = (n == 1 || n == 2 || n == 7) ? 1 : 2;
#pragma unroll 1
        for (int ch = 0; ch < nch; ch++) {
          mbar_wait_watchdog(bars + 8 * (B_STGF + ch), ch ? ph1 : (n & 1));
          const uint32_t src = stg + ch * 16384;
          if (n == 2 || n == 3) {
          } else if (n == 1) {
#pragma unroll 1
            for (int q = 0; q < 8; q++) {
              tma_store2(&p.o_st, src + q * 2048, j * 128, rb * 128 + q * 16);
              if (q & 1) store_pause(true);
            }
          } else if (n >= 4 && n < 8) {
#pragma unroll 1
            for (int q = 0; q < 4; q++) {
              tma_store2(&p.act_st, src + q * 4096, j * 448 + (n - 4) * 128 + ch * 64, rb * 128 + q * 32);
              store_pause(true);
            }
          } else {
            tma_store2(&p.h, src, j * 128 + ch * 64, rb * 128);
            asm volatile("cp.async.bulk.commit_group;" ::: "memory");
            if (ch == 1) {
              asm volatile("cp.async.bulk.wait_group 1;" ::: "memory");
              __syncwarp();
              cnt_signal(cnt + C_HA);
            }
          }
          if (n >= 4 && n < 7 && ch == 0) arrive_elect(bars + 8 * B_STGE);
        }
        asm volatile("cp.async.bulk.commit_group;" ::: "memory");
        asm volatile("cp.async.bulk.wait_group 0;" ::: "memory");
        __syncwarp();
        if (n != 2 && n != 3) cnt_signal(cnt + n);
        PROF_AT(lane == 0, n == 0 ? 33 : 23 + n);
        if (n == 0) {
#pragma unroll 1
          for (int t = 0; t < 34; t++) {
            ll_store(t < 32 ? p.halo + cta * 1024 + t * 32 + lane : (uint4*)(p.stats2 + cta * 128) + (t - 32) * 32 + lane, 0u, 0u, 0u);
            __nanosleep(40);
          }
          __syncwarp();
        }
        if (!(n >= 4 && n < 7)) arrive_elect(bars + 8 * B_STGE);
        if (nch == 2) { arrive_elect(bars + 8 * (B_STGE + 1)); ph1 ^= 1; }
      }
      mbar_wait_watchdog(bars + 8 * B_STGF, 0);
      PROF_AT(lane == 0, 31);
    } else {
      if (lane < 4) ll_store(p.modll + cta * 4 + lane, 0u, 0u, 0u);
      bar_sync(1, 288);
      {
        const uint4 t4 = lds128(sm + RED_OFF + lane * 16);
        float a[4] = {__uint_as_float(t4.x), __uint_as_float(t4.y), __uint_as_float(t4.z), __uint_as_float(t4.w)};
#pragma unroll
        for (int o = 4; o < 32; o <<= 1)
#pragma unroll
          for (int q = 0; q < 4; q++) a[q] += __shfl_xor_sync(~0u, a[q], o);
        if (lane < 4) ll_store(p.modll + cta * 4 + lane, pack2(a[0], a[1]), pack2(a[2], a[3]), tag);
        PROF_AT(lane == 0, 1);
        uint32_t m[4];
        const uint4* mp = p.modll + j * 32 + lane;
        ll_poll<2>([&](int i) { return mp + i * 256; }, tag, m);
        const uint32_t c0 = pack2(1.0f + bf_lo(m[2]), 1.0f + bf_hi(m[2])), c1 = pack2(1.0f + bf_lo(m[3]), 1.0f + bf_hi(m[3]));
        sts128(sm + MODB_OFF + lane * 16, c0, m[0], c1, m[1]);
        __syncwarp();
        arrive_elect(bars + 8 * B_MODA);
      }
#pragma unroll 1
      for (int n = C_H; n <= C_O; n++) {
        cnt_wait_lazy(cnt + n, target);
        arrive_elect(bars + 8 * (B_RDY + n));
      }
      {
        uint32_t m[6];
        const uint4* src = p.modll + 512 + j * 32 + lane;
        ll_poll<3, 500>([&](int i) { return src + i * 256; }, tag, m);
#pragma unroll
        for (int vec = 0; vec < 3; vec++) {
          const float add = vec == 2 ? 1.0f : 0.0f;
          sts128(sm + MODB_OFF + (vec * 128 + lane * 4) * 4, __float_as_uint(bf_round(bf_lo(m[2 * vec]) + add)), __float_as_uint(bf_round(bf_hi(m[2 * vec]) + add)),
                 __float_as_uint(bf_round(bf_lo(m[2 * vec + 1]) + add)), __float_as_uint(bf_round(bf_hi(m[2 * vec + 1]) + add)));
        }
        __syncwarp();
        if (lane == 0) mbar_arrive(bars + 8 * B_MODB);
        PROF_AT(lane == 0, 15);
      }
      __syncwarp();
#pragma unroll 1
      for (int n = C_H2; n < 8; n++) {
        cnt_wait_lazy(cnt + n, n == C_H2 ? target * 8 : target);
        arrive_elect(bars + 8 * (B_RDY + n));
      }
      {
        uint32_t m[2];
        const uint4* src = p.modll + 512 + 768 + j * 32 + lane;
        ll_poll<1>([&](int) { return src; }, tag, m);
        sts128(sm + MODB_OFF + (384 + lane * 4) * 4, m[0] << 16, m[0] & 0xffff0000u, m[1] << 16, m[1] & 0xffff0000u);
        __syncwarp();
        if (lane == 0) mbar_arrive(bars + 8 * (B_MODB + 1));
      }
    }
  } else {
    uint32_t tag;

    {
      const int tid = threadIdx.x - 128, cw = tid >> 7, warp = (tid >> 5) & 3, lane = tid & 31;
      const int l16 = lane & 15, half = lane >> 4, w8 = cw * 4 + warp;
      const uint32_t cbuf = sm + 3 * 49152 + w8 * 512;
      if (lane <= 16) cp_async16(cbuf + lane * 16, lane < 16 ? (const void*)(p.c + w8 * 128 + lane * 8) : (const void*)p.epoch);
      asm volatile("cp.async.commit_group;" ::: "memory");
      const uint32_t xbuf = sm + 40960 + (cw * 2 + (l16 >> 3)) * 49152 + (warp * 16 + half) * 128;
      {
        const char* xp = (const char*)p.x + (uint32_t)((rb * 128 + (warp * 16 + half) * 2 + cw) * 2048 + j * 256 + l16 * 16);
#pragma unroll
        for (int i = 0; i < 8; i++) cp_async16(xbuf + i * 256 + (((l16 & 7) ^ ((i * 2 + half) & 7)) << 4), xp + i * 8192);
      }
      asm volatile("cp.async.commit_group;" ::: "memory");
      const uint32_t wbuf = sm + cw * 49152 + warp * 4096;
      {
        const char* wp = (const char*)p.wmod + (uint32_t)(cta * 32 + (lane & 1) * 16 + (w8 * 128 + (lane >> 1)) * 12288);
#pragma unroll
        for (int i = 0; i < 8; i++) cp_async16(wbuf + i * 512 + lane * 16, wp + i * 16 * 12288);
      }
      asm volatile("cp.async.commit_group;" ::: "memory");
      PROF_AT(tid == 0, 32);
      uint2* st1 = p.stats1 + (rb * 8 + j) * 128 + cw * 64 + warp * 16;
      if (lane < 8) ll_store((uint4*)st1 + lane, 0u, 0u, 0u);
      __syncwarp();
      cluster_arrive_relaxed();
      asm volatile("setmaxnreg.inc.sync.aligned.u32 232;");
      uint32_t sa[4][4];
      {
        asm volatile("cp.async.wait_group 2;" ::: "memory");
        __syncwarp();
        tag = lds32(cbuf + 256) + 1;
        const float2 cv = lds64f(cbuf + lane * 8);
        const uint32_t c0 = __float_as_uint(cv.x), c1 = __float_as_uint(cv.y);
        sts64f(cbuf + lane * 8, __uint_as_float(pack2(silu_f(bf_lo(c0)), silu_f(bf_hi(c0)))), __uint_as_float(pack2(silu_f(bf_lo(c1)), silu_f(bf_hi(c1)))));
        __syncwarp();
#pragma unroll
        for (int q = 0; q < 4; q++) ldmatrix4(sa[q][0], sa[q][1], sa[q][2], sa[q][3], cbuf + q * 64 + (lane >> 3) * 16);
      }
      cluster_wait();
      asm volatile("cp.async.wait_group 1;" ::: "memory");
      __syncwarp();
      uint32_t xl[16], xh[16];
      {
        const int srow = warp * 16 + (lane & 15);
#pragma unroll
        for (int q = 0; q < 8; q++)
          ldmatrix4(xl[2 * q], xh[2 * q], xl[2 * q + 1], xh[2 * q + 1],
                    sm + 40960 + (cw * 2 + (q >> 2)) * 49152 + srow * 128 + (((half + (q & 3) * 2) ^ (srow & 7)) << 4));
      }
      publish_stats(xl, xh, st1, lane, tag16(tag));
      PROF_AT(tid == 0, 50);
      asm volatile("cp.async.wait_group 0;" ::: "memory");
      __syncwarp();
      PROF_AT(tid == 0, 51);
      {
        uint32_t b[8][4];
#pragma unroll
        for (int ks = 0; ks < 8; ks++) ldmatrix4t(b[ks], wbuf + (ks * 16 + (lane & 15)) * 32 + (lane >> 4) * 16);
        float d0[4] = {0.f, 0.f, 0.f, 0.f}, d1[4] = {0.f, 0.f, 0.f, 0.f}, d2[4] = {0.f, 0.f, 0.f, 0.f}, d3[4] = {0.f, 0.f, 0.f, 0.f};
#pragma unroll
        for (int q = 0; q < 4; q++) {
          mma16816(d0, sa[q][0], sa[q][0], sa[q][1], sa[q][1], b[2 * q][0], b[2 * q][1]);
          mma16816(d1, sa[q][0], sa[q][0], sa[q][1], sa[q][1], b[2 * q][2], b[2 * q][3]);
          mma16816(d2, sa[q][2], sa[q][2], sa[q][3], sa[q][3], b[2 * q + 1][0], b[2 * q + 1][1]);
          mma16816(d3, sa[q][2], sa[q][2], sa[q][3], sa[q][3], b[2 * q + 1][2], b[2 * q + 1][3]);
        }
        d0[0] += d2[0]; d0[1] += d2[1]; d1[0] += d3[0]; d1[1] += d3[1];
        if (lane < 4) {
          sts64f(sm + RED_OFF + (w8 * 16 + lane * 2) * 4, d0[0], d0[1]);
          sts64f(sm + RED_OFF + (w8 * 16 + 8 + lane * 2) * 4, d1[0], d1[1]);
        }
        asm volatile("bar.arrive 1, 288;" ::: "memory");
      }
      {
        const int c = lane & 3;
        float rs[2], nb[2];
        stat_gather(p.stats1 + rb * 1024 + cw * 64 + warp * 16, tag16(tag), lane, rs, nb);
#pragma unroll
        for (int n = 0; n < 16; n++) {
          xl[n] = pack2(bf_lo(xl[n]) * rs[0] + nb[0], bf_hi(xl[n]) * rs[0] + nb[0]);
          xh[n] = pack2(bf_lo(xh[n]) * rs[1] + nb[1], bf_hi(xh[n]) * rs[1] + nb[1]);
        }
        const int srow = warp * 16 + l16;
        const uint32_t slab = stg + cw * 8192 + srow * 128;
#pragma unroll
        for (int q = 0; q < 8; q++)
          stmatrix4(slab + (q >> 2) * 16384 + (((half + (q & 3) * 2) ^ (srow & 7)) << 4), xl[2 * q], xh[2 * q], xl[2 * q + 1], xh[2 * q + 1]);
        PROF_AT(tid == 0, 52);
        mbar_wait(bars + 8 * B_MODA, 0);
        PROF_AT(tid == 0, 2);
#pragma unroll
        for (int q = 0; q < 8; q++) {
          const float2 m0 = lds64f(sm + MODB_OFF + (8 * q + c) * 8), m1 = lds64f(sm + MODB_OFF + (8 * q + 4 + c) * 8);
          const uint32_t c0 = __float_as_uint(m0.x), s0 = __float_as_uint(m0.y), c1 = __float_as_uint(m1.x), s1 = __float_as_uint(m1.y);
          stmatrix4(slab + (q >> 2) * 16384 + (((half + (q & 3) * 2) ^ (srow & 7)) << 4), fma_bf2(xl[2 * q], c0, s0), fma_bf2(xh[2 * q], c0, s0),
                    fma_bf2(xl[2 * q + 1], c1, s1), fma_bf2(xh[2 * q + 1], c1, s1));
          if ((q & 3) == 3) stage_done(bars + 8 * (B_STGF + (q >> 2)), lane);
        }
        wg_bar(cw);
      }
      PROF_AT(tid == 0, 3);
    }

    uint32_t xl[16], xh[16];
    {
      RING_IDS();
      uint32_t prev = 0;
      float acc1[96];
      {
        Ring g{bars + 8 * B_FQ, rbars + 8 * B_EQ, 0, 0u, releaser TR(0)};
        float acc0[96];
#pragma unroll 1
        for (int kb = 0; kb < 2; kb++) kblock<192, 4, 49152>(acc0, g, a_base + STG_OFF + kb * 16384, kb == 0, prev);
#pragma unroll 1
        for (int kb = 0; kb < 2; kb++) kblock<192, 4, 49152>(acc1, g, a_base + STG_OFF + kb * 16384, kb == 0, prev);
#pragma unroll 1
        for (int kb = 0; kb < 14; kb++) kblock<192, 4, 49152>(acc0, g, a_base + g.s * 49152, false, prev);
        PROF_AT(tid == 0, 4);
        attention<NPRE0, false>(acc0, p, 0, rb, cta, cw, warp, tag, stg, bars, prev, [&]() { kblock<192, 4, 49152>(acc1, g, a_base + g.s * 49152, false, prev); });
        PROF_AT(tid == 0, 5);
        {
          LANE_IDS();
#pragma unroll
          for (int q = 0; q < 8; q++)
            ldmatrix4(xl[2 * q], xh[2 * q], xl[2 * q + 1], xh[2 * q + 1], sm + 40960 + (cw * 2 + (q >> 2)) * 49152 + srow * 128 + ((sw0 ^ ((q & 3) * 2)) << 4));
#pragma unroll
          for (int q = 0; q < 16; q++) asm volatile("" : "+r"(xl[q]), "+r"(xh[q])::"memory");
        }
#pragma unroll 1
        for (int kb = 5 + NPRE0; kb < 14; kb++) kblock<192, 4, 49152>(acc1, g, a_base + g.s * 49152, false, prev);
        PROF_AT(tid == 0, 6);
      }
      float acc[64];
      Ring g{bars + 8 * B_FW, rbars + 8 * B_EW, 0, 0u, releaser TR(32)};
      attention<NPRE1, true>(acc1, p, 1, rb, cta, cw, warp, tag, stg, bars, prev, [&]() { kblock<128, 6, 32768>(acc, g, a_base + g.s * 32768, g.s == 0, prev); });
      PROF_AT(tid == 0, 7);
      LANE_IDS();
      unsigned* cnt = p.cnt + rb * 32;
      tma_store2(&p.o_st, stg + cw * 8192 + warp * 2048, j * 128 + 64, rb * 128 + cw * 64 + warp * 16);
      asm volatile("cp.async.bulk.commit_group;" ::: "memory");
#pragma unroll 1
      for (int kb = 1 + NPRE1; kb < 16; kb++) {
        if (kb == 8) wg_bar(cw);
        kblock<128, 6, 32768>(acc, g, a_base + (kb == 8 ? STG_OFF : g.s * 32768), false, prev);
        if (kb == OSIG + NPRE1) {
          asm volatile("cp.async.bulk.wait_group 0;" ::: "memory");
          __syncwarp();
          cnt_signal(cnt + C_O + 1);
        }
      }
      mbar_wait(bars + 8 * B_MODB, 0);
      float2 ga[16];
#pragma unroll
      for (int n = 0; n < 16; n++) ga[n] = lds64f(sm + MODB_OFF + (8 * n + 2 * c) * 4);
      tile_end(acc, prev);
      PROF_AT(tid == 0, 8);
      uint2* st2 = p.stats2 + (rb * 8 + j) * 128 + cw * 64 + warp * 16 + r + (c & 1) * 8;
      float sl[2] = {0.f, 0.f}, sh[2] = {0.f, 0.f}, ql[2] = {0.f, 0.f}, qh[2] = {0.f, 0.f};
#pragma unroll
      for (int n = 0; n < 16; n++) {
        acc[4 * n] = ga[n].x * acc[4 * n] + bf_lo(xl[n]); acc[4 * n + 1] = ga[n].y * acc[4 * n + 1] + bf_hi(xl[n]);
        acc[4 * n + 2] = ga[n].x * acc[4 * n + 2] + bf_lo(xh[n]); acc[4 * n + 3] = ga[n].y * acc[4 * n + 3] + bf_hi(xh[n]);
        sl[0] += acc[4 * n]; sl[1] += acc[4 * n + 1]; sh[0] += acc[4 * n + 2]; sh[1] += acc[4 * n + 3];
        ql[0] += acc[4 * n] * acc[4 * n]; ql[1] += acc[4 * n + 1] * acc[4 * n + 1];
        qh[0] += acc[4 * n + 2] * acc[4 * n + 2]; qh[1] += acc[4 * n + 3] * acc[4 * n + 3];
      }
      {
        const float ml = (sl[0] + sl[1]) * (1.0f / 32), mh = (sh[0] + sh[1]) * (1.0f / 32);
        const float vl = (ql[0] + ql[1]) - 32.0f * ml * ml, vh = (qh[0] + qh[1]) - 32.0f * mh * mh;
        const bool b0 = c & 1;
        float m = b0 ? mh : ml, q = b0 ? vh : vl;
        chan(m, q, __shfl_xor_sync(~0u, b0 ? ml : mh, 1), __shfl_xor_sync(~0u, b0 ? vl : vh, 1), 32.f);
        chan(m, q, __shfl_xor_sync(~0u, m, 2), __shfl_xor_sync(~0u, q, 2), 64.f);
        if (c < 2) stat_store(st2, m, fmaxf(q, 0.f), tag16(tag));
        __syncwarp();
      }
      PROF_AT(tid == 0, 48);
      float2 sb[16], cb[16];
#pragma unroll
      for (int n = 0; n < 16; n++) {
        sb[n] = lds64f(sm + MODB_OFF + (128 + 8 * n + 2 * c) * 4);
        cb[n] = lds64f(sm + MODB_OFF + (256 + 8 * n + 2 * c) * 4);
        xl[n] = pack2(acc[4 * n], acc[4 * n + 1]);
        xh[n] = pack2(acc[4 * n + 2], acc[4 * n + 3]);
      }
      mbar_wait(bars + 8 * B_STGE, 0);
      PROF_AT(tid == 0, 49);
      float nb[2], rstd[2];
      stat_gather(p.stats2 + rb * 1024 + cw * 64 + warp * 16, tag16(tag), lane, rstd, nb);
      PROF_AT(tid == 0, 9);
#pragma unroll
      for (int ch = 0; ch < 2; ch++) {
        uint32_t lo[8], hi[8];
#pragma unroll
        for (int t = 0; t < 8; t++) {
          const int n = ch * 8 + t;
          lo[t] = pack2((acc[4 * n] * rstd[0] + nb[0]) * cb[n].x + sb[n].x, (acc[4 * n + 1] * rstd[0] + nb[0]) * cb[n].y + sb[n].y);
          hi[t] = pack2((acc[4 * n + 2] * rstd[1] + nb[1]) * cb[n].x + sb[n].x, (acc[4 * n + 3] * rstd[1] + nb[1]) * cb[n].y + sb[n].y);
        }
        stage_slab(stg + ch * 16384 + cw * 8192, warp, lane, lo, hi);
        stage_done(bars + 8 * (B_STGF + ch), lane);
        tma_store2(&p.h2_st, stg + ch * 16384 + cw * 8192 + warp * 2048, j * 128 + ch * 64, rb * 128 + cw * 64 + warp * 16);
        asm volatile("cp.async.bulk.commit_group;" ::: "memory");
      }
      wg_bar(cw);
      PROF_AT(tid == 0, 10);
    }

    uint32_t pg[32], pu[32];
    {
      RING_IDS();
      LANE_IDS();
      Ring g{bars + 8 * B_FG, rbars + 8 * B_EG, 0, 0u, releaser TR(48)};
      float acc[128];
      {
        uint32_t prev = 0;
#pragma unroll 1
        for (int kb = 0; kb < 16; kb++) {
          kblock<256, 4, 49152>(acc, g, a_base + (kb < 2 ? STG_OFF + kb * 16384 : g.s * 49152), kb == 0, prev);
          if (kb == 0) {
            asm volatile("cp.async.bulk.wait_group 1;" ::: "memory");
            __syncwarp();
            cnt_signal(p.cnt + rb * 32 + C_H2A);
          }
          if (kb == 1) {
            asm volatile("cp.async.bulk.wait_group 0;" ::: "memory");
            __syncwarp();
            cnt_signal(p.cnt + rb * 32 + C_H2);
          }
#pragma unroll
          for (int ch = 0; ch < 2; ch++) {
            if (kb == 3 + 3 * ch) {
#pragma unroll
              for (int q = 0; q < 4; q++)
                stmatrix4(slab + ch * 16384 + ((sw0 ^ (q * 2)) << 4), xl[8 * ch + 2 * q], xh[8 * ch + 2 * q], xl[8 * ch + 2 * q + 1], xh[8 * ch + 2 * q + 1]);
              asm volatile("fence.proxy.async.shared::cta;" ::: "memory");
              __syncwarp();
              tma_store3(&p.out, stg + ch * 16384 + cw * 8192 + warp * 2048, j * 128 + ch * 64, rb * 64 + warp * 16, cw);
              asm volatile("cp.async.bulk.commit_group;" ::: "memory");
            }
          }
          if (kb == 12) asm volatile("cp.async.bulk.wait_group 0;" ::: "memory");
        }
        tile_end(acc, prev);
      }
      PROF_AT(tid == 0, 36);
#pragma unroll 1
      for (int t = 1; t < 3; t++) {
#pragma unroll
        for (int q = 0; q < 32; q++) {
          pg[q] = pack2(acc[2 * q], acc[2 * q + 1]);
          pu[q] = pack2(acc[64 + 2 * q], acc[64 + 2 * q + 1]);
        }
        uint32_t prev = 0;
#pragma unroll 1
        for (int blk = 0; blk < 4; blk++) {
          g.s = 0;
#pragma unroll
          for (int i = 0; i < 4; i++) {
            kblock<256, 4, 49152>(acc, g, a_base + i * 49152, blk == 0 && i == 0, prev);
            if ((blk & 1) == 0 && i == 0) mbar_wait(bars + 8 * (B_STGE + (blk >> 1)), t & 1);
            stmatrix2(slab + (blk >> 1) * 16384 + (((srow & 7) ^ ((blk & 1) * 4 + i)) << 4), swiglu2(pg[2 * i], pu[2 * i]), swiglu2(pg[2 * i + 1], pu[2 * i + 1]));
          }
#pragma unroll
          for (int q = 0; q < 24; q++) { pg[q] = pg[q + 8]; pu[q] = pu[q + 8]; }
          if (blk & 1) stage_done(bars + 8 * (B_STGF + (blk >> 1)), lane);
        }
        tile_end(acc, prev);
        PROF_AT(tid == 0, 36 + t);
      }
#pragma unroll
      for (int q = 0; q < 32; q++) {
        pg[q] = pack2(acc[2 * q], acc[2 * q + 1]);
        pu[q] = pack2(acc[64 + 2 * q], acc[64 + 2 * q + 1]);
      }
      PROF_AT(tid == 0, 11);
    }

    {
      RING_IDS();
      LANE_IDS();
      Ring g{bars + 8 * B_FD, rbars + 8 * B_ED, 0, 0u, releaser TR(96)};
      float acc[64];
      uint32_t prev = 0;
#pragma unroll 1
      for (int blk = 0; blk < 6; blk++) {
#pragma unroll
        for (int i = 0; i < 8; i++) {
          kblock<128, 6, 32768>(acc, g, a_base + g.s * 32768, (blk & ~2) == 0 && i == 0, prev);
          if ((blk & 1) == 0 && i == 0) mbar_wait(bars + 8 * (B_STGE + ((blk >> 1) & 1)), blk < 4);
          stmatrix1(slab + ((blk >> 1) & 1) * 16384 + (i & 1) * 1024 + (((srow & 7) ^ ((blk & 1) * 4 + (i >> 1))) << 4), swiglu2(pg[i], pu[i]));
        }
#pragma unroll
        for (int q = 0; q < 24; q++) { pg[q] = pg[q + 8]; pu[q] = pu[q + 8]; }
        if (blk & 1) stage_done(bars + 8 * (B_STGF + ((blk >> 1) & 1)), lane);
        if (blk == 1) {
          tile_end(acc, prev);
          PROF_AT(tid == 0, 39);
#pragma unroll
          for (int q = 0; q < 16; q++) {
            pg[16 + q] = pack2(acc[2 * q], acc[2 * q + 1]);
            pu[16 + q] = pack2(acc[32 + 2 * q], acc[32 + 2 * q + 1]);
          }
          PROF_AT(tid == 0, 12);
        }
      }
#pragma unroll 1
      for (int kb = 48; kb < 72; kb++) {
        if (kb == 66) g.releaser = false;
        kblock<128, 6, 32768>(acc, g, a_base + g.s * 32768, false, prev);
      }
      mbar_wait(bars + 8 * (B_MODB + 1), 0);
      mbar_wait(bars + 8 * B_STGE, 1);
      mbar_wait(bars + 8 * (B_STGE + 1), 0);
      float2 gbv[16];
#pragma unroll
      for (int n = 0; n < 16; n++) gbv[n] = lds64f(sm + MODB_OFF + (384 + 8 * n + 2 * c) * 4);
      tile_end(acc, prev);
      PROF_AT(tid == 0, 13);
#pragma unroll
      for (int ch = 0; ch < 2; ch++) {
        uint32_t lo[8], hi[8];
#pragma unroll
        for (int t = 0; t < 8; t++) {
          const int n = ch * 8 + t;
          const float2 gb = gbv[n];
          lo[t] = pack2(gb.x * acc[4 * n], gb.y * acc[4 * n + 1]);
          hi[t] = pack2(gb.x * acc[4 * n + 2], gb.y * acc[4 * n + 3]);
        }
        stage_slab(stg + ch * 16384 + cw * 8192, warp, lane, lo, hi);
        asm volatile("fence.proxy.async.shared::cta;" ::: "memory");
        __syncwarp();
        tma_add3(&p.out, stg + ch * 16384 + cw * 8192 + warp * 2048, j * 128 + ch * 64, rb * 64 + warp * 16, cw);
      }
      asm volatile("cp.async.bulk.commit_group;" ::: "memory");
      if (lane == 0) mbar_arrive(bars + 8 * B_STGF);
      asm volatile("cp.async.bulk.wait_group.read 0;" ::: "memory");
      PROF_AT(tid == 0, 14);
    }
    if (blockIdx.x == 0 && threadIdx.x == 128) asm volatile("st.relaxed.gpu.global.u32 [%0], %1;" ::"l"(p.epoch), "r"(tag) : "memory");
  }
}

typedef CUresult (*EncodeFn)(CUtensorMap*, CUtensorMapDataType, cuuint32_t, void*, const cuuint64_t*, const cuuint64_t*,
                             const cuuint32_t*, const cuuint32_t*, CUtensorMapInterleave, CUtensorMapSwizzle,
                             CUtensorMapL2promotion, CUtensorMapFloatOOBfill);

void encode2d(EncodeFn fn, CUtensorMap* m, const void* ptr, uint64_t cols, uint64_t rows, uint32_t box_rows) {
  cuuint64_t dims[2] = {cols, rows};
  cuuint64_t strides[1] = {cols * 2};
  cuuint32_t box[2] = {64, box_rows};
  cuuint32_t es[2] = {1, 1};
  fn(m, CU_TENSOR_MAP_DATA_TYPE_BFLOAT16, 2, (void*)ptr, dims, strides, box, es, CU_TENSOR_MAP_INTERLEAVE_NONE,
     CU_TENSOR_MAP_SWIZZLE_128B, CU_TENSOR_MAP_L2_PROMOTION_L2_128B, CU_TENSOR_MAP_FLOAT_OOB_FILL_NONE);
}

}

extern "C" void kernel_launch(void* const* d_in, const int* in_sizes, int n_in, void* d_out, int out_size) {
  (void)in_sizes; (void)n_in; (void)out_size;
  void* fp = nullptr;
  cudaDriverEntryPointQueryResult qr;
  cudaGetDriverEntryPoint("cuTensorMapEncodeTiled", &fp, cudaEnableDefault, &qr);
  EncodeFn fn = (EncodeFn)fp;
  void *ph, *po, *ph2, *pact;
  cudaGetSymbolAddress(&ph, g_h);
  cudaGetSymbolAddress(&po, g_o);
  ph2 = ph;
  cudaGetSymbolAddress(&pact, g_act);
  Params p;
  encode2d(fn, &p.h, ph, DM, SEQ, 128);
  encode2d(fn, &p.o_ld, po, DM, SEQ, 128);
  encode2d(fn, &p.h2, ph2, DM, SEQ, 128);
  encode2d(fn, &p.act, pact, FF, SEQ, 128);
  encode2d(fn, &p.act_st, pact, FF, SEQ, 32);
  encode2d(fn, &p.wm, d_in[8], 6 * DM, DM, 64);
  encode2d(fn, &p.o_st, po, DM, SEQ, 16);
  encode2d(fn, &p.h2_st, ph2, DM, SEQ, 16);
  encode2d(fn, &p.wqkv, d_in[1], 3 * DM, DM, 64);
  encode2d(fn, &p.wqkv32, d_in[1], 3 * DM, DM, 32);
  encode2d(fn, &p.wo, d_in[2], DM, DM, 64);
  encode2d(fn, &p.wg, d_in[4], FF, DM, 64);
  encode2d(fn, &p.wu, d_in[5], FF, DM, 64);
  encode2d(fn, &p.wd, d_in[6], DM, FF, 64);
  {
    cuuint64_t dims[3] = {DM, SEQ / 2, 2};
    cuuint64_t strides[2] = {DM * 4, DM * 2};
    cuuint32_t box[3] = {64, 16, 1};
    cuuint32_t es[3] = {1, 1, 1};
    fn(&p.out, CU_TENSOR_MAP_DATA_TYPE_BFLOAT16, 3, d_out, dims, strides, box, es, CU_TENSOR_MAP_INTERLEAVE_NONE,
       CU_TENSOR_MAP_SWIZZLE_128B, CU_TENSOR_MAP_L2_PROMOTION_L2_128B, CU_TENSOR_MAP_FLOAT_OOB_FILL_NONE);
  }
  p.x = (const bf16*)d_in[0];
  p.c = (const bf16*)d_in[7];
  p.wmod = (const bf16*)d_in[8];
  for (int cl = 0; cl < 64; cl++) {
    const int grp = cl < 4 ? 0 : (cl < 36 ? (cl - 4) & 7 : 1 + (cl - 36) % 7);
    const int j = cl < 4 ? 4 + cl : (cl < 36 ? (cl - 4) >> 3 : 4 + (cl - 36) / 7);
    p.slot[cl] = (uint8_t)(grp * 8 + j);
  }
  void* q;
  cudaGetSymbolAddress(&q, g_modll); p.modll = (uint4*)q;
  cudaGetSymbolAddress(&q, g_halo); p.halo = (uint4*)q;
  cudaGetSymbolAddress(&q, g_stats); p.stats1 = (uint2*)q; p.stats2 = p.stats1 + SEQ * 8;
  cudaGetSymbolAddress(&q, g_cnt); p.cnt = (unsigned*)q;
  cudaGetSymbolAddress(&q, g_epoch); p.epoch = (unsigned*)q;

  cudaFuncSetAttribute(fused_kernel, cudaFuncAttributeMaxDynamicSharedMemorySize, SMEM_BYTES);
  cudaLaunchConfig_t cfg = {};
  cfg.gridDim = dim3(NCTA + 4);
  cfg.blockDim = dim3(384);
  cfg.dynamicSmemBytes = SMEM_BYTES;
  cfg.stream = cudaStreamPerThread;
  cudaLaunchAttribute at[1];
  at[0].id = cudaLaunchAttributeClusterDimension;
  at[0].val.clusterDim.x = 2; at[0].val.clusterDim.y = 1; at[0].val.clusterDim.z = 1;
  cfg.attrs = at;
  cfg.numAttrs = 1;
  cudaLaunchKernelEx(&cfg, fused_kernel, p);
}
```

```cpp
#include <cuda_runtime.h>
#include <cuda_bf16.h>
#include <cuda.h>
#include <stdint.h>

typedef __nv_bfloat16 bf16;

#define PAUSE 200
#define WMDELAY 2000
#define BDELAY 1500
#define NPRE0 3
#define NPRE1 1
#define ALIAS 1

#define PFW 8000
#define PFP 0

#define OSIG 3

#define KH 3

#define HOFF 900

__device__ __forceinline__ void wgmma_ss_n128(float (&d)[64], uint32_t da, uint32_t db, int scale_d) {
  asm volatile("{\n.reg .pred p;\n.reg .b64 da, db;\nsetp.ne.b32 p, %66, 0;\n"
    "mov.b64 da, {%64, 0x40000040};\nmov.b64 db, {%65, 0x40000040};\n"
    "wgmma.mma_async.sync.aligned.m64n128k16.f32.bf16.bf16 "
    "{%0, %1, %2, %3, %4, %5, %6, %7, %8, %9, %10, %11, %12, %13, %14, %15, "
    "%16, %17, %18, %19, %20, %21, %22, %23, %24, %25, %26, %27, %28, %29, %30, %31, "
    "%32, %33, %34, %35, %36, %37, %38, %39, %40, %41, %42, %43, %44, %45, %46, %47, "
    "%48, %49, %50, %51, %52, %53, %54, %55, %56, %57, %58, %59, %60, %61, %62, %63}, "
    "da, db, p, 1, 1, 0, 1;\n}\n"
    : "+f"(d[0]), "+f"(d[1]), "+f"(d[2]), "+f"(d[3]), "+f"(d[4]), "+f"(d[5]), "+f"(d[6]), "+f"(d[7]),
      "+f"(d[8]), "+f"(d[9]), "+f"(d[10]), "+f"(d[11]), "+f"(d[12]), "+f"(d[13]), "+f"(d[14]), "+f"(d[15]),
      "+f"(d[16]), "+f"(d[17]), "+f"(d[18]), "+f"(d[19]), "+f"(d[20]), "+f"(d[21]), "+f"(d[22]), "+f"(d[23]),
      "+f"(d[24]), "+f"(d[25]), "+f"(d[26]), "+f"(d[27]), "+f"(d[28]), "+f"(d[29]), "+f"(d[30]), "+f"(d[31]),
      "+f"(d[32]), "+f"(d[33]), "+f"(d[34]), "+f"(d[35]), "+f"(d[36]), "+f"(d[37]), "+f"(d[38]), "+f"(d[39]),
      "+f"(d[40]), "+f"(d[41]), "+f"(d[42]), "+f"(d[43]), "+f"(d[44]), "+f"(d[45]), "+f"(d[46]), "+f"(d[47]),
      "+f"(d[48]), "+f"(d[49]), "+f"(d[50]), "+f"(d[51]), "+f"(d[52]), "+f"(d[53]), "+f"(d[54]), "+f"(d[55]),
      "+f"(d[56]), "+f"(d[57]), "+f"(d[58]), "+f"(d[59]), "+f"(d[60]), "+f"(d[61]), "+f"(d[62]), "+f"(d[63])
    : "r"(da), "r"(db), "r"(scale_d));
}

__device__ __forceinline__ void wgmma_ss_n192(float (&d)[96], uint32_t da, uint32_t db, int scale_d) {
  asm volatile("{\n.reg .pred p;\n.reg .b64 da, db;\nsetp.ne.b32 p, %98, 0;\n"
    "mov.b64 da, {%96, 0x40000040};\nmov.b64 db, {%97, 0x40000040};\n"
    "wgmma.mma_async.sync.aligned.m64n192k16.f32.bf16.bf16 "
    "{%0, %1, %2, %3, %4, %5, %6, %7, %8, %9, %10, %11, %12, %13, %14, %15, "
    "%16, %17, %18, %19, %20, %21, %22, %23, %24, %25, %26, %27, %28, %29, %30, %31, "
    "%32, %33, %34, %35, %36, %37, %38, %39, %40, %41, %42, %43, %44, %45, %46, %47, "
    "%48, %49, %50, %51, %52, %53, %54, %55, %56, %57, %58, %59, %60, %61, %62, %63, "
    "%64, %65, %66, %67, %68, %69, %70, %71, %72, %73, %74, %75, %76, %77, %78, %79, "
    "%80, %81, %82, %83, %84, %85, %86, %87, %88, %89, %90, %91, %92, %93, %94, %95}, "
    "da, db, p, 1, 1, 0, 1;\n}\n"
    : "+f"(d[0]), "+f"(d[1]), "+f"(d[2]), "+f"(d[3]), "+f"(d[4]), "+f"(d[5]), "+f"(d[6]), "+f"(d[7]),
      "+f"(d[8]), "+f"(d[9]), "+f"(d[10]), "+f"(d[11]), "+f"(d[12]), "+f"(d[13]), "+f"(d[14]), "+f"(d[15]),
      "+f"(d[16]), "+f"(d[17]), "+f"(d[18]), "+f"(d[19]), "+f"(d[20]), "+f"(d[21]), "+f"(d[22]), "+f"(d[23]),
      "+f"(d[24]), "+f"(d[25]), "+f"(d[26]), "+f"(d[27]), "+f"(d[28]), "+f"(d[29]), "+f"(d[30]), "+f"(d[31]),
      "+f"(d[32]), "+f"(d[33]), "+f"(d[34]), "+f"(d[35]), "+f"(d[36]), "+f"(d[37]), "+f"(d[38]), "+f"(d[39]),
      "+f"(d[40]), "+f"(d[41]), "+f"(d[42]), "+f"(d[43]), "+f"(d[44]), "+f"(d[45]), "+f"(d[46]), "+f"(d[47]),
      "+f"(d[48]), "+f"(d[49]), "+f"(d[50]), "+f"(d[51]), "+f"(d[52]), "+f"(d[53]), "+f"(d[54]), "+f"(d[55]),
      "+f"(d[56]), "+f"(d[57]), "+f"(d[58]), "+f"(d[59]), "+f"(d[60]), "+f"(d[61]), "+f"(d[62]), "+f"(d[63]),
      "+f"(d[64]), "+f"(d[65]), "+f"(d[66]), "+f"(d[67]), "+f"(d[68]), "+f"(d[69]), "+f"(d[70]), "+f"(d[71]),
      "+f"(d[72]), "+f"(d[73]), "+f"(d[74]), "+f"(d[75]), "+f"(d[76]), "+f"(d[77]), "+f"(d[78]), "+f"(d[79]),
      "+f"(d[80]), "+f"(d[81]), "+f"(d[82]), "+f"(d[83]), "+f"(d[84]), "+f"(d[85]), "+f"(d[86]), "+f"(d[87]),
      "+f"(d[88]), "+f"(d[89]), "+f"(d[90]), "+f"(d[91]), "+f"(d[92]), "+f"(d[93]), "+f"(d[94]), "+f"(d[95])
    : "r"(da), "r"(db), "r"(scale_d));
}

__device__ __forceinline__ void wgmma_ss_n256(float (&d)[128], uint32_t da, uint32_t db, int scale_d) {
  asm volatile("{\n.reg .pred p;\n.reg .b64 da, db;\nsetp.ne.b32 p, %130, 0;\n"
    "mov.b64 da, {%128, 0x40000040};\nmov.b64 db, {%129, 0x40000040};\n"
    "wgmma.mma_async.sync.aligned.m64n256k16.f32.bf16.bf16 "
    "{%0, %1, %2, %3, %4, %5, %6, %7, %8, %9, %10, %11, %12, %13, %14, %15, "
    "%16, %17, %18, %19, %20, %21, %22, %23, %24, %25, %26, %27, %28, %29, %30, %31, "
    "%32, %33, %34, %35, %36, %37, %38, %39, %40, %41, %42, %43, %44, %45, %46, %47, "
    "%48, %49, %50, %51, %52, %53, %54, %55, %56, %57, %58, %59, %60, %61, %62, %63, "
    "%64, %65, %66, %67, %68, %69, %70, %71, %72, %73, %74, %75, %76, %77, %78, %79, "
    "%80, %81, %82, %83, %84, %85, %86, %87, %88, %89, %90, %91, %92, %93, %94, %95, "
    "%96, %97, %98, %99, %100, %101, %102, %103, %104, %105, %106, %107, %108, %109, %110, %111, "
    "%112, %113, %114, %115, %116, %117, %118, %119, %120, %121, %122, %123, %124, %125, %126, %127}, "
    "da, db, p, 1, 1, 0, 1;\n}\n"
    : "+f"(d[0]), "+f"(d[1]), "+f"(d[2]), "+f"(d[3]), "+f"(d[4]), "+f"(d[5]), "+f"(d[6]), "+f"(d[7]),
      "+f"(d[8]), "+f"(d[9]), "+f"(d[10]), "+f"(d[11]), "+f"(d[12]), "+f"(d[13]), "+f"(d[14]), "+f"(d[15]),
      "+f"(d[16]), "+f"(d[17]), "+f"(d[18]), "+f"(d[19]), "+f"(d[20]), "+f"(d[21]), "+f"(d[22]), "+f"(d[23]),
      "+f"(d[24]), "+f"(d[25]), "+f"(d[26]), "+f"(d[27]), "+f"(d[28]), "+f"(d[29]), "+f"(d[30]), "+f"(d[31]),
      "+f"(d[32]), "+f"(d[33]), "+f"(d[34]), "+f"(d[35]), "+f"(d[36]), "+f"(d[37]), "+f"(d[38]), "+f"(d[39]),
      "+f"(d[40]), "+f"(d[41]), "+f"(d[42]), "+f"(d[43]), "+f"(d[44]), "+f"(d[45]), "+f"(d[46]), "+f"(d[47]),
      "+f"(d[48]), "+f"(d[49]), "+f"(d[50]), "+f"(d[51]), "+f"(d[52]), "+f"(d[53]), "+f"(d[54]), "+f"(d[55]),
      "+f"(d[56]), "+f"(d[57]), "+f"(d[58]), "+f"(d[59]), "+f"(d[60]), "+f"(d[61]), "+f"(d[62]), "+f"(d[63]),
      "+f"(d[64]), "+f"(d[65]), "+f"(d[66]), "+f"(d[67]), "+f"(d[68]), "+f"(d[69]), "+f"(d[70]), "+f"(d[71]),
      "+f"(d[72]), "+f"(d[73]), "+f"(d[74]), "+f"(d[75]), "+f"(d[76]), "+f"(d[77]), "+f"(d[78]), "+f"(d[79]),
      "+f"(d[80]), "+f"(d[81]), "+f"(d[82]), "+f"(d[83]), "+f"(d[84]), "+f"(d[85]), "+f"(d[86]), "+f"(d[87]),
      "+f"(d[88]), "+f"(d[89]), "+f"(d[90]), "+f"(d[91]), "+f"(d[92]), "+f"(d[93]), "+f"(d[94]), "+f"(d[95]),
      "+f"(d[96]), "+f"(d[97]), "+f"(d[98]), "+f"(d[99]), "+f"(d[100]), "+f"(d[101]), "+f"(d[102]), "+f"(d[103]),
      "+f"(d[104]), "+f"(d[105]), "+f"(d[106]), "+f"(d[107]), "+f"(d[108]), "+f"(d[109]), "+f"(d[110]), "+f"(d[111]),
      "+f"(d[112]), "+f"(d[113]), "+f"(d[114]), "+f"(d[115]), "+f"(d[116]), "+f"(d[117]), "+f"(d[118]), "+f"(d[119]),
      "+f"(d[120]), "+f"(d[121]), "+f"(d[122]), "+f"(d[123]), "+f"(d[124]), "+f"(d[125]), "+f"(d[126]), "+f"(d[127])
    : "r"(da), "r"(db), "r"(scale_d));
}

namespace {

constexpr int SEQ = 2048, DM = 1024, FF = 3584;
constexpr int NCTA = 128;

constexpr uint32_t STG_OFF = 196608;
constexpr uint32_t MISC_OFF = STG_OFF + 32768;
constexpr uint32_t SMEM_BYTES = MISC_OFF + 3072;
constexpr uint32_t RED_OFF = 2 * 49152;
constexpr uint32_t MODB_OFF = MISC_OFF + 512;

enum { B_FQ = 0, B_EQ = 4, B_FW = 8, B_EW = 14, B_FG = 20, B_EG = 24, B_FD = 28, B_ED = 34,
       B_STGF = 40, B_MODB = 42, B_MODA = 45, B_RDY = 48, B_STGE = 56, B_COUNT = 58 };
enum { C_H = 0, C_O = 1, C_H2 = 3, C_ACT = 4, C_HA = 8, C_H2A = 9, C_A0 = 10, C_SP = 12 };

struct Params {
  CUtensorMap h, o_ld, o_st, h2, act, out, wqkv, wqkv32, wo, wg, wu, wd, act_st, h2_st, wm;
  const bf16* x;
  const bf16* c;
  const bf16* wmod;
  uint4* modll;
  uint4* halo;
  uint2* stats1;
  uint2* stats2;
  unsigned* cnt;
  unsigned* epoch;
  uint8_t slot[64];
};

__device__ __align__(1024) bf16 g_h[SEQ * DM];
__device__ __align__(1024) bf16 g_o[SEQ * DM];
__device__ __align__(1024) bf16 g_act[SEQ * FF];
__device__ __align__(1024) uint4 g_modll[3072 / 2];
__device__ __align__(1024) uint4 g_halo[16 * 8 * 2 * 2 * 8 * 32];
__device__ __align__(1024) uint2 g_stats[2 * SEQ * 8];
__device__ __align__(1024) unsigned g_cnt[16 * 32];
__device__ uint4 g_epoch;
#define TR(off)

__device__ __forceinline__ uint32_t smem_u32(const void* p) { return (uint32_t)__cvta_generic_to_shared(p); }
__device__ __forceinline__ void mbar_init(uint32_t bar, uint32_t count) {
  asm volatile("mbarrier.init.shared::cta.b64 [%0], %1;" ::"r"(bar), "r"(count));
}
__device__ __forceinline__ void mbar_arrive(uint32_t bar) {
  asm volatile("mbarrier.arrive.shared::cta.b64 _, [%0];" ::"r"(bar) : "memory");
}
__device__ __forceinline__ void mbar_arrive_cluster(uint32_t cluster_addr) {
  asm volatile("mbarrier.arrive.shared::cluster.b64 _, [%0];" ::"r"(cluster_addr) : "memory");
}
__device__ __forceinline__ uint32_t mapa(uint32_t addr, uint32_t cta) {
  uint32_t r;
  asm volatile("mapa.shared::cluster.u32 %0, %1, %2;" : "=r"(r) : "r"(addr), "r"(cta));
  return r;
}
__device__ __forceinline__ void mbar_wait(uint32_t bar, uint32_t parity) {
  asm volatile(
      "{\n.reg .pred p;\n"
      "WAIT_%=:\n"
      "mbarrier.try_wait.parity.shared::cta.b64 p, [%0], %1;\n"
      "@!p bra WAIT_%=;\n}\n" ::"r"(bar), "r"(parity) : "memory");
}
__device__ __forceinline__ void mbar_wait_watchdog(uint32_t bar, uint32_t parity) {
  asm volatile(
      "{\n.reg .pred p;\n.reg .u64 t0, t1;\nmov.u64 t0, %%globaltimer;\n"
      "WAIT_%=:\n"
      "mbarrier.try_wait.parity.shared::cta.b64 p, [%0], %1;\n"
      "@p bra DONE_%=;\n"
      "mov.u64 t1, %%globaltimer;\n"
      "sub.u64 t1, t1, t0;\n"
      "setp.lt.u64 p, t1, 2000000000;\n"
      "@p bra WAIT_%=;\n"
      "trap;\n"
      "DONE_%=:\n}\n" ::"r"(bar), "r"(parity) : "memory");
}
__device__ __forceinline__ void cnt_wait(const unsigned* p, unsigned target) {
  asm volatile(
      "{\n.reg .pred p;\n.reg .u32 v;\n.reg .s32 d;\n"
      "WAIT_%=:\n"
      "ld.relaxed.gpu.global.u32 v, [%0];\n"
      "sub.s32 d, v, %1;\n"
      "setp.lt.s32 p, d, 0;\n"
      "@p bra WAIT_%=;\n"
      "fence.proxy.async.global;\n"
      "}\n" ::"l"(p), "r"(target) : "memory");
}
__device__ __forceinline__ void cnt_wait_lazy(const unsigned* p, unsigned target) {
  asm volatile(
      "{\n.reg .pred p;\n.reg .u32 v;\n.reg .s32 d;\n"
      "WAIT_%=:\n"
      "nanosleep.u32 400;\n"
      "ld.relaxed.gpu.global.u32 v, [%0];\n"
      "sub.s32 d, v, %1;\n"
      "setp.lt.s32 p, d, 0;\n"
      "@p bra WAIT_%=;\n"
      "fence.proxy.async.global;\n"
      "}\n" ::"l"(p), "r"(target) : "memory");
}
__device__ __forceinline__ void cnt_signal(unsigned* p) {
  asm volatile("{\n.reg .pred p;\nelect.sync _|p, 0xffffffff;\n@p red.relaxed.gpu.global.add.u32 [%0], 1;\n}\n" ::"l"(p) : "memory");
}
__device__ __forceinline__ void ll_store(uint4* p, uint32_t a, uint32_t b, uint32_t tag) {
  asm volatile("st.relaxed.gpu.global.v2.b64 [%0], {%1, %2};" ::"l"(p), "l"((uint64_t)a | ((uint64_t)tag << 32)),
               "l"((uint64_t)b | ((uint64_t)tag << 32)) : "memory");
}
__device__ __forceinline__ uint4 ll_peek(const uint4* p) {
  uint4 v;
  asm volatile("ld.relaxed.gpu.global.v4.u32 {%0, %1, %2, %3}, [%4];" : "=r"(v.x), "=r"(v.y), "=r"(v.z), "=r"(v.w) : "l"(p) : "memory");
  return v;
}
template <int N, int SLEEP = 0, class F>
__device__ __forceinline__ void ll_poll(F addr, uint32_t tag, uint32_t (&out)[2 * N]) {
  for (;;) {
    uint4 v[N];
#pragma unroll
    for (int i = 0; i < N; i++) v[i] = ll_peek(addr(i));
    uint32_t bad = 0;
#pragma unroll
    for (int i = 0; i < N; i++) {
      bad |= (v[i].y ^ tag) | (v[i].w ^ tag);
      out[2 * i] = v[i].x;
      out[2 * i + 1] = v[i].z;
    }
    if (__all_sync(~0u, bad == 0)) break;
    if (SLEEP) __nanosleep(SLEEP);
  }
}
constexpr uint64_t POLICY_EVICT_FIRST = 0x12F0000000000000ull;
__device__ __forceinline__ void expect_tx_elect(uint32_t bar, uint32_t bytes) {
  asm volatile("{\n.reg .pred p;\nelect.sync _|p, 0xffffffff;\n@p mbarrier.arrive.expect_tx.shared::cta.b64 _, [%0], %1;\n}\n" ::"r"(bar), "r"(bytes) : "memory");
}
__device__ __forceinline__ void arrive_elect(uint32_t bar) {
  asm volatile("{\n.reg .pred p;\nelect.sync _|p, 0xffffffff;\n@p mbarrier.arrive.shared::cta.b64 _, [%0];\n}\n" ::"r"(bar) : "memory");
}
__device__ __forceinline__ void tma_load(uint32_t dst, const CUtensorMap* m, uint32_t bar, int c0, int c1) {
  asm volatile("{\n.reg .pred p;\nelect.sync _|p, 0xffffffff;\n"
               "@p cp.async.bulk.tensor.2d.shared::cluster.global.mbarrier::complete_tx::bytes [%0], [%1, {%3, %4}], [%2];\n}\n"
               ::"r"(dst), "l"(m), "r"(bar), "r"(c0), "r"(c1) : "memory");
}
__device__ __forceinline__ void tma_load_mc(uint32_t dst, const CUtensorMap* m, uint32_t bar, int c0, int c1) {
  asm volatile("{\n.reg .pred p;\nelect.sync _|p, 0xffffffff;\n"
               "@p cp.async.bulk.tensor.2d.shared::cluster.global.mbarrier::complete_tx::bytes.multicast::cluster.L2::cache_hint [%0], [%1, {%3, %4}], [%2], %5, %6;\n}\n"
               ::"r"(dst), "l"(m), "r"(bar), "r"(c0), "r"(c1), "h"((uint16_t)3), "l"(POLICY_EVICT_FIRST) : "memory");
}
__device__ __forceinline__ void tma_load_ef(uint32_t dst, const CUtensorMap* m, uint32_t bar, int c0, int c1) {
  asm volatile("{\n.reg .pred p;\nelect.sync _|p, 0xffffffff;\n"
               "@p cp.async.bulk.tensor.2d.shared::cluster.global.mbarrier::complete_tx::bytes.L2::cache_hint [%0], [%1, {%3, %4}], [%2], %5;\n}\n"
               ::"r"(dst), "l"(m), "r"(bar), "r"(c0), "r"(c1), "l"(POLICY_EVICT_FIRST) : "memory");
}
__device__ __forceinline__ void tma_store2(const CUtensorMap* m, uint32_t src, int c0, int c1) {
  asm volatile("{\n.reg .pred p;\nelect.sync _|p, 0xffffffff;\n"
               "@p cp.async.bulk.tensor.2d.global.shared::cta.bulk_group [%0, {%2, %3}], [%1];\n}\n"
               ::"l"(m), "r"(src), "r"(c0), "r"(c1) : "memory");
}
__device__ __forceinline__ void tma_store3(const CUtensorMap* m, uint32_t src, int c0, int c1, int c2) {
  asm volatile("{\n.reg .pred p;\nelect.sync _|p, 0xffffffff;\n"
               "@p cp.async.bulk.tensor.3d.global.shared::cta.bulk_group [%0, {%2, %3, %4}], [%1];\n}\n"
               ::"l"(m), "r"(src), "r"(c0), "r"(c1), "r"(c2) : "memory");
}
__device__ __forceinline__ void tma_add3(const CUtensorMap* m, uint32_t src, int c0, int c1, int c2) {
  asm volatile("{\n.reg .pred p;\nelect.sync _|p, 0xffffffff;\n"
               "@p cp.reduce.async.bulk.tensor.3d.global.shared::cta.add.bulk_group [%0, {%2, %3, %4}], [%1];\n}\n"
               ::"l"(m), "r"(src), "r"(c0), "r"(c1), "r"(c2) : "memory");
}
__device__ __forceinline__ void store_pause(bool sleep) {
  asm volatile("cp.async.bulk.commit_group;" ::: "memory");
  asm volatile("cp.async.bulk.wait_group.read 0;" ::: "memory");
  if (sleep) __nanosleep(PAUSE);
}
__device__ __forceinline__ void l2_prefetch_tile(const CUtensorMap* m, int c0, int c1) {
  asm volatile("{\n.reg .pred p;\nelect.sync _|p, 0xffffffff;\n@p cp.async.bulk.prefetch.tensor.2d.L2.global [%0, {%1, %2}];\n}\n"
               ::"l"(m), "r"(c0), "r"(c1) : "memory");
}
__device__ __forceinline__ void prefetch_map(const CUtensorMap* m) {
  asm volatile("prefetch.tensormap [%0];" ::"l"(m) : "memory");
}
__device__ __forceinline__ void wg_fence() { asm volatile("wgmma.fence.sync.aligned;" ::: "memory"); }
__device__ __forceinline__ void wg_commit() { asm volatile("wgmma.commit_group.sync.aligned;" ::: "memory"); }
template <int N>
__device__ __forceinline__ void wg_wait() { asm volatile("wgmma.wait_group.sync.aligned %0;" ::"n"(N) : "memory"); }
__device__ __forceinline__ void bar_sync(int id, int n) { asm volatile("bar.sync %0, %1;" ::"r"(id), "r"(n) : "memory"); }
__device__ __forceinline__ void wg_bar(int cw) {
  asm volatile("{\n.reg .pred p;\nsetp.ne.s32 p, %0, 0;\n@p bar.sync 3, 128;\n@!p bar.sync 2, 128;\n}\n" ::"r"(cw) : "memory");
}
__device__ __forceinline__ void cluster_arrive_relaxed() { asm volatile("barrier.cluster.arrive.relaxed.aligned;" ::: "memory"); }
__device__ __forceinline__ void cluster_wait() { asm volatile("barrier.cluster.wait.acquire.aligned;" ::: "memory"); }
__device__ __forceinline__ uint32_t load_epoch(const unsigned* p) {
  uint32_t e;
  asm volatile("ld.relaxed.gpu.global.u32 %0, [%1];" : "=r"(e) : "l"(p) : "memory");
  return e;
}
__device__ __forceinline__ uint32_t pack2(float lo, float hi) {
  uint32_t r;
  asm("cvt.rn.bf16x2.f32 %0, %1, %2;" : "=r"(r) : "f"(hi), "f"(lo));
  return r;
}
__device__ __forceinline__ float bf_lo(uint32_t v) { return __uint_as_float(v << 16); }
__device__ __forceinline__ float bf_hi(uint32_t v) { return __uint_as_float(v & 0xffff0000u); }
__device__ __forceinline__ uint32_t fma_bf2(uint32_t a, uint32_t b, uint32_t c) {
  uint32_t d;
  asm("fma.rn.bf16x2 %0, %1, %2, %3;" : "=r"(d) : "r"(a), "r"(b), "r"(c));
  return d;
}
__device__ __forceinline__ float bf_round(float v) { return __bfloat162float(__float2bfloat16_rn(v)); }
__device__ __forceinline__ float silu_f(float v) { return __fdividef(v, 1.0f + __expf(-v)); }
__device__ __forceinline__ uint4 ldg_nc(const void* p) {
  uint4 v;
  asm volatile("ld.global.nc.L1::no_allocate.v4.u32 {%0, %1, %2, %3}, [%4];" : "=r"(v.x), "=r"(v.y), "=r"(v.z), "=r"(v.w) : "l"(p));
  return v;
}
__device__ __forceinline__ void stmatrix4(uint32_t addr, uint32_t a, uint32_t b, uint32_t c, uint32_t d) {
  asm volatile("stmatrix.sync.aligned.m8n8.x4.shared.b16 [%0], {%1, %2, %3, %4};" ::"r"(addr), "r"(a), "r"(b), "r"(c), "r"(d) : "memory");
}
__device__ __forceinline__ void stmatrix2(uint32_t addr, uint32_t a, uint32_t b) {
  asm volatile("stmatrix.sync.aligned.m8n8.x2.shared.b16 [%0], {%1, %2};" ::"r"(addr), "r"(a), "r"(b) : "memory");
}
__device__ __forceinline__ void stmatrix1(uint32_t addr, uint32_t a) {
  asm volatile("stmatrix.sync.aligned.m8n8.x1.shared.b16 [%0], {%1};" ::"r"(addr), "r"(a) : "memory");
}
__device__ __forceinline__ uint32_t movmatrix(uint32_t a) {
  uint32_t d;
  asm("movmatrix.sync.aligned.m8n8.trans.b16 %0, %1;" : "=r"(d) : "r"(a));
  return d;
}
__device__ __forceinline__ void mma16816(float (&d)[4], uint32_t a0, uint32_t a1, uint32_t a2, uint32_t a3, uint32_t b0, uint32_t b1) {
  asm("mma.sync.aligned.m16n8k16.row.col.f32.bf16.bf16.f32 {%0, %1, %2, %3}, {%4, %5, %6, %7}, {%8, %9}, {%0, %1, %2, %3};"
               : "+f"(d[0]), "+f"(d[1]), "+f"(d[2]), "+f"(d[3]) : "r"(a0), "r"(a1), "r"(a2), "r"(a3), "r"(b0), "r"(b1));
}
__device__ __forceinline__ void mma1688(float (&d)[4], uint32_t a0, uint32_t a1, uint32_t b0) {
  asm("mma.sync.aligned.m16n8k8.row.col.f32.bf16.bf16.f32 {%0, %1, %2, %3}, {%4, %5}, {%6}, {%0, %1, %2, %3};"
               : "+f"(d[0]), "+f"(d[1]), "+f"(d[2]), "+f"(d[3]) : "r"(a0), "r"(a1), "r"(b0));
}
__device__ __forceinline__ void ldmatrix4t(uint32_t (&b)[4], uint32_t addr) {
  asm volatile("ldmatrix.sync.aligned.m8n8.x4.trans.shared.b16 {%0, %1, %2, %3}, [%4];" : "=r"(b[0]), "=r"(b[1]), "=r"(b[2]), "=r"(b[3]) : "r"(addr) : "memory");
}
__device__ __forceinline__ void ldmatrix4(uint32_t& a, uint32_t& b, uint32_t& c, uint32_t& d, uint32_t addr) {
  asm volatile("ldmatrix.sync.aligned.m8n8.x4.shared.b16 {%0, %1, %2, %3}, [%4];" : "=r"(a), "=r"(b), "=r"(c), "=r"(d) : "r"(addr) : "memory");
}
__device__ __forceinline__ void cp_async16(uint32_t dst, const void* src) {
  asm volatile("cp.async.cg.shared.global.L2::cache_hint [%0], [%1], 16, %2;" ::"r"(dst), "l"(src), "l"(POLICY_EVICT_FIRST) : "memory");
}
__device__ __forceinline__ uint32_t lds32(uint32_t addr) {
  uint32_t v;
  asm volatile("ld.shared.u32 %0, [%1];" : "=r"(v) : "r"(addr) : "memory");
  return v;
}
__device__ __forceinline__ void sts64f(uint32_t addr, float a, float b) {
  asm volatile("st.shared.v2.f32 [%0], {%1, %2};" ::"r"(addr), "f"(a), "f"(b) : "memory");
}
constexpr float QK_SCALE = 0.17677669529663687f;
__device__ __forceinline__ float softmax8(float& p0, float& p1) {
  float m = fmaxf(p0, p1);
  m = fmaxf(m, __shfl_xor_sync(~0u, m, 1));
  m = fmaxf(m, __shfl_xor_sync(~0u, m, 2));
  asm("ex2.approx.ftz.f32 %0, %1;" : "=f"(p0) : "f"((p0 - m) * 1.4426950408889634f));
  asm("ex2.approx.ftz.f32 %0, %1;" : "=f"(p1) : "f"((p1 - m) * 1.4426950408889634f));
  float s = p0 + p1;
  s += __shfl_xor_sync(~0u, s, 1);
  s += __shfl_xor_sync(~0u, s, 2);
  float r;
  asm("rcp.approx.ftz.f32 %0, %1;" : "=f"(r) : "f"(s));
  return r;
}
__device__ __forceinline__ void sts128(uint32_t addr, uint32_t a, uint32_t b, uint32_t c, uint32_t d) {
  asm volatile("st.shared.v4.u32 [%0], {%1, %2, %3, %4};" ::"r"(addr), "r"(a), "r"(b), "r"(c), "r"(d) : "memory");
}
__device__ __forceinline__ uint4 lds128(uint32_t addr) {
  uint4 v;
  asm volatile("ld.shared.v4.u32 {%0, %1, %2, %3}, [%4];" : "=r"(v.x), "=r"(v.y), "=r"(v.z), "=r"(v.w) : "r"(addr) : "memory");
  return v;
}
__device__ __forceinline__ float2 lds64f(uint32_t addr) {
  float2 v;
  asm volatile("ld.shared.v2.f32 {%0, %1}, [%2];" : "=f"(v.x), "=f"(v.y) : "r"(addr) : "memory");
  return v;
}
#define PROF_AT(cond, slot) do {} while (0)

constexpr uint32_t SMEM_BASE = 1024;
constexpr uint32_t DESC_A = (1u << 16) | (SMEM_BASE >> 4);
constexpr uint32_t DESC_B = ((8192u >> 4) << 16) | ((SMEM_BASE + 16384) >> 4);

template <int BN> struct Wg;
template <> struct Wg<128> { static __device__ __forceinline__ void mma(float (&d)[64], uint32_t a, uint32_t b, int s) { wgmma_ss_n128(d, a, b, s); } };
template <> struct Wg<192> { static __device__ __forceinline__ void mma(float (&d)[96], uint32_t a, uint32_t b, int s) { wgmma_ss_n192(d, a, b, s); } };
template <> struct Wg<256> { static __device__ __forceinline__ void mma(float (&d)[128], uint32_t a, uint32_t b, int s) { wgmma_ss_n256(d, a, b, s); } };

struct Ring {
  uint32_t full0, rel0;
  int s;
  uint32_t ph;
  bool releaser;
};

template <int N>
__device__ __forceinline__ void fence_regs(float (&a)[N]) {
#pragma unroll
  for (int i = 0; i < N; i++) asm volatile("" : "+f"(a[i])::"memory");
}

template <int BN, int NST, uint32_t STAGE>
__device__ __forceinline__ void kblock(float (&acc)[BN / 2], Ring& g, uint32_t a_addr, bool zero, uint32_t& prev) {
  mbar_wait(g.full0 + 8 * g.s, g.ph);
  const uint32_t da = DESC_A + (a_addr >> 4);
  const uint32_t db = DESC_B + g.s * (STAGE >> 4);
  wg_fence();
#pragma unroll
  for (int k = 0; k < 4; k++) Wg<BN>::mma(acc, da + k * 2, db + k * 128, !(zero && k == 0));
  wg_commit();
  wg_wait<1>();
  if (prev != 0) mbar_arrive_cluster(prev);
  prev = g.releaser ? g.rel0 + 8 * g.s : 0u;
  if (++g.s == NST) { g.s = 0; g.ph ^= 1; }
}
template <int N>
__device__ __forceinline__ void tile_end(float (&acc)[N], uint32_t& prev) {
  wg_wait<0>();
  if (prev != 0) mbar_arrive_cluster(prev);
  prev = 0;
  fence_regs(acc);
}

__device__ __forceinline__ int other_kb(int q, int j) {
  const int ch = q >= 7, jj = q - 7 * ch;
  return 2 * (jj < j ? jj : jj + 1) + ch;
}
__device__ __forceinline__ int own_first(int it, int j) {
  return it >= 16 ? (it & 15) : (it < 2 ? 2 * j + it : other_kb(it - 2, j));
}
__device__ __forceinline__ int qkv_kb(int it, int j) {
  return it < 4 ? 2 * j + (it & 1) : other_kb(it < 18 ? it - 4 : it - 18, j);
}
__device__ __forceinline__ int wo_k(int it, int j) {
  return it < 8 ? it * 128 : (it == 8 ? j : (it - 9 < j ? it - 9 : it - 8)) * 128 + 64;
}
__device__ __forceinline__ int down_k(int it) {
  if (it < 16) return it * 64;
  if (it < 16 + KH) return (it - 16) * 448 + 64;
  const int r = ((it + KH) >> 4) - 1, idx = (it + KH) & 15;
  return r < 3 ? (idx >> 1) * 448 + r * 128 + (idx & 1) * 64 : idx * 448 + 384;
}
__device__ __forceinline__ void wait_p3_free(uint32_t empty3, int i) {
  mbar_wait(empty3 + 8 * ((i * 2) / 3), 1);
  mbar_wait(empty3 + 8 * ((i * 2 + 1) / 3), 1);
}
__device__ __forceinline__ void wait_p2_free(uint32_t empty2, int i) {
  const int w0 = (i * 3) / 2, w1 = (i * 3 + 2) / 2;
  mbar_wait(empty2 + 8 * w0, w0 < 4 ? 0 : 1);
  mbar_wait(empty2 + 8 * w1, w1 < 4 ? 0 : 1);
}

__device__ __forceinline__ void chan(float& m, float& q, float m2, float q2, float n) {
  const float d = m2 - m;
  m = 0.5f * (m + m2);
  q = q + q2 + d * d * (0.5f * n);
}

__device__ __forceinline__ uint32_t tag16(uint32_t tag) { return tag % 65535u + 1u; }
__device__ __forceinline__ void stat_store(uint2* slot, float m, float q, uint32_t t16) {
  const uint32_t a = ((__float_as_uint(m) + 0x80u) & 0xffffff00u) | (t16 & 0xffu), b = ((__float_as_uint(q) + 0x80u) & 0xffffff00u) | (t16 >> 8);
  asm volatile("st.relaxed.gpu.global.b64 [%0], %1;" ::"l"(slot), "l"((uint64_t)a | ((uint64_t)b << 32)) : "memory");
}
__device__ __forceinline__ void stat_gather(const uint2* rows, uint32_t t16, int lane, float (&rs)[2], float (&nb)[2]) {
  const uint4* sp = (const uint4*)(rows + (lane >> 3) * 128) + (lane & 7);
  const uint32_t want = (t16 & 0xffu) | ((t16 >> 8) << 8);
  uint4 a, b;
  for (;;) {
    a = ll_peek(sp);
    b = ll_peek(sp + 256);
    const uint32_t bad = (__byte_perm(a.x, a.y, 0x40) ^ want) | (__byte_perm(a.z, a.w, 0x40) ^ want) | (__byte_perm(b.x, b.y, 0x40) ^ want) |
                         (__byte_perm(b.z, b.w, 0x40) ^ want);
    if (__all_sync(~0u, (bad & 0xffffu) == 0)) break;
  }
  float m0 = __uint_as_float(a.x & 0xffffff00u), q0 = __uint_as_float(a.y & 0xffffff00u);
  float m1 = __uint_as_float(a.z & 0xffffff00u), q1 = __uint_as_float(a.w & 0xffffff00u);
  chan(m0, q0, __uint_as_float(b.x & 0xffffff00u), __uint_as_float(b.y & 0xffffff00u), 128.f);
  chan(m1, q1, __uint_as_float(b.z & 0xffffff00u), __uint_as_float(b.w & 0xffffff00u), 128.f);
  const bool hi = lane & 8;
  float m = hi ? m1 : m0, q = hi ? q1 : q0;
  chan(m, q, __shfl_xor_sync(~0u, hi ? m0 : m1, 8), __shfl_xor_sync(~0u, hi ? q0 : q1, 8), 256.f);
  chan(m, q, __shfl_xor_sync(~0u, m, 16), __shfl_xor_sync(~0u, q, 16), 512.f);
  const float rstd = rsqrtf(q * (1.0f / DM) + 1e-5f), nmr = -m * rstd;
  const int r = lane >> 2, src = (r >> 1) + (r & 1) * 8;
  rs[0] = __shfl_sync(~0u, rstd, src); nb[0] = __shfl_sync(~0u, nmr, src);
  rs[1] = __shfl_sync(~0u, rstd, src + 4); nb[1] = __shfl_sync(~0u, nmr, src + 4);
}

__device__ __forceinline__ void publish_stats(const uint32_t (&xl)[16], const uint32_t (&xh)[16], uint2* slot, int lane, uint32_t t16) {
  float ds[4] = {0.f, 0.f, 0.f, 0.f}, dl[4] = {0.f, 0.f, 0.f, 0.f}, dh[4] = {0.f, 0.f, 0.f, 0.f};
#pragma unroll
  for (int q = 0; q < 8; q++) {
    mma16816(ds, xl[2 * q], xh[2 * q], xl[2 * q + 1], xh[2 * q + 1], 0x3f803f80u, 0x3f803f80u);
    mma16816(dl, xl[2 * q], xh[2 * q], xl[2 * q + 1], xh[2 * q + 1], xl[2 * q], xl[2 * q + 1]);
    mma16816(dh, xl[2 * q], xh[2 * q], xl[2 * q + 1], xh[2 * q + 1], xh[2 * q], xh[2 * q + 1]);
  }
  const int r = lane >> 2;
  if ((lane & 3) == (r >> 1)) {
    const float ml = ds[0] * (1.0f / 128), mh = ds[2] * (1.0f / 128);
    const float ql = fmaxf(((r & 1) ? dl[1] : dl[0]) - ds[0] * ml, 0.f), qh = fmaxf(((r & 1) ? dh[3] : dh[2]) - ds[2] * mh, 0.f);
    stat_store(slot + r, ml, ql, t16);
    stat_store(slot + r + 8, mh, qh, t16);
  }
  __syncwarp();
}

__device__ __forceinline__ void stage_slab(uint32_t chunk, int warp, int lane, const uint32_t (&lo)[8], const uint32_t (&hi)[8]) {
  const int row = warp * 16 + (lane & 7) + ((lane >> 3) & 1) * 8;
  const uint32_t rbase = chunk + row * 128;
#pragma unroll
  for (int q = 0; q < 4; q++) {
    const int grp = 2 * q + (lane >> 4);
    stmatrix4(rbase + ((grp ^ (row & 7)) << 4), lo[2 * q], hi[2 * q], lo[2 * q + 1], hi[2 * q + 1]);
  }
}
__device__ __forceinline__ float silu_mul(float g, float u) {
  float e, r;
  asm("ex2.approx.ftz.f32 %0, %1;" : "=f"(e) : "f"(g * -1.4426950408889634f));
  asm("rcp.approx.ftz.f32 %0, %1;" : "=f"(r) : "f"(1.0f + e));
  return g * r * u;
}
__device__ __forceinline__ uint32_t swiglu2(uint32_t g2, uint32_t u2) {
  asm volatile("" : "+r"(g2));
  return pack2(silu_mul(bf_lo(g2), bf_lo(u2)), silu_mul(bf_hi(g2), bf_hi(u2)));
}
__device__ __forceinline__ void stage_done(uint32_t bar, int lane) {
  asm volatile("fence.proxy.async.shared::cta;" ::: "memory");
  __syncwarp();
  if (lane == 0) mbar_arrive(bar);
}

__device__ __forceinline__ int fresh_tid() {
  int t;
  asm volatile("mov.u32 %0, %%tid.x;" : "=r"(t));
  return t;
}
#define RING_IDS()                                                                                           \
  const int tid = fresh_tid() - 128;                                                                         \
  const int cw = __shfl_sync(~0u, tid >> 7, 0), warp = __shfl_sync(~0u, (tid >> 5) & 3, 0);                  \
  const bool releaser = (tid & 31) < 2;                                                                      \
  const uint32_t rbars = mapa(bars, tid & 1);                                                                \
  const uint32_t a_base = cw * 8192
#define LANE_IDS()                                                                                           \
  const int lane = fresh_tid() & 31, r = lane >> 2, c = lane & 3;                                            \
  const int srow = warp * 16 + (lane & 7) + ((lane >> 3) & 1) * 8;                                           \
  const uint32_t slab = stg + cw * 8192 + srow * 128, sw0 = (lane >> 4) ^ (srow & 7);                        \
  (void)r; (void)c; (void)slab; (void)sw0

template <int NPRE, bool EAGER, class Step>
__device__ __forceinline__ void attention(float (&acc)[96], const Params& p, int rho, int rb, int cta, int cw, int warp, uint32_t tag,
                                          uint32_t stg, uint32_t bars, uint32_t& prev, Step step) {
  uint32_t ql[8], qh[8], k0[8], k1[8], v0[8], v1[8], hp[16];
  if (EAGER) {
    tile_end(acc, prev);
  } else {
    step();
    fence_regs(acc);
  }
#pragma unroll
  for (int t = 0; t < 8; t++) {
    k0[t] = pack2(acc[4 * (8 + t)], acc[4 * (8 + t) + 1]);
    k1[t] = pack2(acc[4 * (8 + t) + 2], acc[4 * (8 + t) + 3]);
    v0[t] = pack2(acc[4 * (16 + t)], acc[4 * (16 + t) + 1]);
    v1[t] = pack2(acc[4 * (16 + t) + 2], acc[4 * (16 + t) + 3]);
    asm volatile("" : "+r"(k0[t]), "+r"(k1[t]), "+r"(v0[t]), "+r"(v1[t]));
  }
  const int lane = fresh_tid() & 31, r = lane >> 2, c = lane & 3;
#pragma unroll
  for (int t = 0; t < 8; t++) v1[t] = movmatrix(v1[t]);
  mbar_wait(bars + 8 * B_STGE, rho);
  mbar_wait(bars + 8 * (B_STGE + 1), 0);
  const uint32_t xch = stg + 16384 + (cw * 4 + warp) * 2048 + lane * 16;
  if (warp < 3) {
    sts128(xch, k1[0], k1[1], k1[2], k1[3]);
    sts128(xch + 512, k1[4], k1[5], k1[6], k1[7]);
    sts128(xch + 1024, v1[0], v1[1], v1[2], v1[3]);
    sts128(xch + 1536, v1[4], v1[5], v1[6], v1[7]);
  } else if (rb < 15) {
    uint4* dst = p.halo + ((cta * 2 + rho) * 2 + cw) * 256 + lane;
#pragma unroll
    for (int t = 0; t < 4; t++) {
      ll_store(dst + t * 32, k1[2 * t], k1[2 * t + 1], tag);
      ll_store(dst + (4 + t) * 32, v1[2 * t], v1[2 * t + 1], tag);
    }
  }
#pragma unroll
  for (int t = 0; t < 8; t++) {
    v0[t] = movmatrix(v0[t]);
    ql[t] = pack2(acc[4 * t], acc[4 * t + 1]);
    qh[t] = pack2(acc[4 * t + 2], acc[4 * t + 3]);
    asm volatile("" : "+r"(v0[t]), "+r"(ql[t]), "+r"(qh[t]));
  }
#pragma unroll 1
  for (int i = 0; i < NPRE; i++) step();
  const uint4* src = p.halo + (((cta - 8) * 2 + rho) * 2 + cw) * 256 + lane;
  uint4 early[8] = {};
  if (warp == 0 && rb > 0) {
#pragma unroll
    for (int i = 0; i < 8; i++) early[i] = ll_peek(src + i * 32);
  }
  step();
  wg_bar(cw);
  if (warp > 0) {
#pragma unroll
    for (int t = 0; t < 4; t++) {
      const uint4 a = lds128(xch - 2048 + t * 512);
      hp[4 * t] = a.x; hp[4 * t + 1] = a.y; hp[4 * t + 2] = a.z; hp[4 * t + 3] = a.w;
    }
  } else if (rb > 0) {
    uint32_t bad = 0;
#pragma unroll
    for (int i = 0; i < 8; i++) {
      bad |= (early[i].y ^ tag) | (early[i].w ^ tag);
      hp[2 * i] = early[i].x;
      hp[2 * i + 1] = early[i].z;
    }
    if (!__all_sync(~0u, bad == 0)) ll_poll<8>([&](int i) { return src + i * 32; }, tag, hp);
  } else {
#pragma unroll
    for (int t = 0; t < 16; t++) hp[t] = 0;
  }
  wg_wait<0>();
  if (prev != 0) mbar_arrive_cluster(prev);
  prev = 0;
#pragma unroll
  for (int t = 0; t < 8; t++) asm volatile("" : "+r"(ql[t])::"memory");
  const bool up0 = 2 * c > r, up1 = 2 * c + 1 > r;
  const bool first = (rb == 0) && (warp == 0);
  uint32_t a0[2], a2[2], a3[2], a5[2];
  float il[2], ih[2];
#pragma unroll
  for (int h = 0; h < 2; h++) {
    float sp[4] = {0.f, 0.f, 0.f, 0.f}, s0[4] = {0.f, 0.f, 0.f, 0.f}, s1[4] = {0.f, 0.f, 0.f, 0.f};
#pragma unroll
    for (int ks = 0; ks < 2; ks++) {
      const int t = 4 * h + 2 * ks;
      mma16816(sp, ql[t], qh[t], ql[t + 1], qh[t + 1], hp[t], hp[t + 1]);
      mma16816(s0, ql[t], qh[t], ql[t + 1], qh[t + 1], k0[t], k0[t + 1]);
      mma16816(s1, ql[t], qh[t], ql[t + 1], qh[t + 1], k1[t], k1[t + 1]);
    }
    float p0 = (up0 ? sp[0] : s0[0]) * QK_SCALE, p1 = (up1 ? sp[1] : s0[1]) * QK_SCALE;
    float p2 = (up0 ? s0[2] : s1[2]) * QK_SCALE, p3 = (up1 ? s0[3] : s1[3]) * QK_SCALE;
    if (first && up0) p0 = -1000000000.0f;
    if (first && up1) p1 = -1000000000.0f;
    il[h] = softmax8(p0, p1);
    ih[h] = softmax8(p2, p3);
    a0[h] = pack2(up0 ? p0 : 0.f, up1 ? p1 : 0.f);
    a2[h] = pack2(up0 ? 0.f : p0, up1 ? 0.f : p1);
    a3[h] = pack2(up0 ? p2 : 0.f, up1 ? p3 : 0.f);
    a5[h] = pack2(up0 ? 0.f : p2, up1 ? 0.f : p3);
  }
  float o[8][4];
#pragma unroll
  for (int t = 0; t < 8; t++) {
#pragma unroll
    for (int q = 0; q < 4; q++) o[t][q] = 0.f;
    mma1688(o[t], 0u, a5[t >> 2], v1[t]);
    mma16816(o[t], a0[t >> 2], 0u, a2[t >> 2], a3[t >> 2], hp[8 + t], v0[t]);
  }
#pragma unroll
  for (int t = 0; t < 8; t++) fence_regs(o[t]);
  if (!EAGER) step();
  uint32_t ol[8], oh[8];
#pragma unroll
  for (int t = 0; t < 8; t++) {
    ol[t] = pack2(o[t][0] * il[t >> 2], o[t][1] * il[t >> 2]);
    oh[t] = pack2(o[t][2] * ih[t >> 2], o[t][3] * ih[t >> 2]);
  }
  if (!EAGER) step();
  stage_slab(stg + cw * 8192, warp, lane, ol, oh);
  stage_done(bars + 8 * B_STGF, lane);
  if (!EAGER) step();
}

__global__ void __launch_bounds__(384, 1) fused_kernel(const __grid_constant__ Params p) {
  extern __shared__ __align__(1024) uint8_t smem_raw[];
  const uint32_t sm = smem_u32(smem_raw);
  const uint32_t bars = sm + MISC_OFF;
  const uint32_t stg = sm + STG_OFF;
  const int rank = blockIdx.x & 1;
  const int cl = blockIdx.x >> 1;
  if (cl >= NCTA / 2) {
    const int e = blockIdx.x - NCTA, wid = __shfl_sync(~0u, (int)(threadIdx.x >> 5), 0), lane = threadIdx.x & 31;
    if (threadIdx.x == 0) {
      for (int i = 0; i < 6; i++) { mbar_init(bars + 8 * i, 1); mbar_init(bars + 8 * (6 + i), 8); }
      for (int i = 0; i < 8; i++) { mbar_init(bars + 8 * (16 + i), 1); mbar_init(bars + 8 * (24 + i), 4); }
      mbar_init(bars + 8 * 12, 1);
      asm volatile("fence.mbarrier_init.release.cluster;" ::: "memory");
    }
    const uint32_t tag = load_epoch(p.epoch) + 1;
    if (threadIdx.x < 256) ll_store(p.modll + 512 + (threadIdx.x >> 6) * 256 + e * 64 + (threadIdx.x & 63), 0u, 0u, 0u);
    for (int i = threadIdx.x; i < 1536; i += 384) {
      uint4 o = make_uint4(0u, 0u, 0u, 0u);
      if (i < 1024 && (i & 63) < 8) {
        const uint4 cv = ldg_nc(p.c + (i >> 6) * 64 + (i & 7) * 8);
        o = make_uint4(pack2(silu_f(bf_lo(cv.x)), silu_f(bf_hi(cv.x))), pack2(silu_f(bf_lo(cv.y)), silu_f(bf_hi(cv.y))),
                       pack2(silu_f(bf_lo(cv.z)), silu_f(bf_hi(cv.z))), pack2(silu_f(bf_lo(cv.w)), silu_f(bf_hi(cv.w))));
      }
      sts128(stg + i * 16, o.x, o.y, o.z, o.w);
    }
    asm volatile("fence.proxy.async.shared::cta;" ::: "memory");
    __syncthreads();
    if (wid == 0) {
      __nanosleep(WMDELAY);
      uint32_t ph = 1;
#pragma unroll 1
      for (int it = 0, s = 0; it < 64; it++) {
        mbar_wait(bars + 8 * (6 + s), ph);
        expect_tx_elect(bars + 8 * s, 32768);
#pragma unroll
        for (int q = 0; q < 4; q++) tma_load_ef(sm + s * 32768 + q * 8192, &p.wm, bars + 8 * s, 2048 + (it >> 4) * 1024 + e * 256 + q * 64, (it & 15) * 64);
        if (++s == 6) { s = 0; ph ^= 1; }
      }
    } else if (wid == 1 && PFW) {
      __nanosleep(PFW);
#pragma unroll 1
      for (int i = 0; i < 64; i++) {
        l2_prefetch_tile(&p.wo, (i & 15) * 64, (e * 4 + (i >> 4)) * 64);
        if (PFP) __nanosleep(PFP);
      }
#pragma unroll 1
      for (int i = 0; i < 128; i++) {
        l2_prefetch_tile((i & 2) ? &p.wu : &p.wg, ((i >> 2) & 7) * 448 + (i & 1) * 64, ((i >> 5) * 4 + e) * 64);
        if (PFP) __nanosleep(PFP);
      }
    } else if (wid >= 4) {
      const int hf = (wid >> 2) - 1;
      uint32_t ph = 0;
      int s = 0;
#pragma unroll 1
      for (int v = 0; v < 4; v++) {
        float acc[64];
#pragma unroll 1
        for (int kb = 0; kb < 16; kb++) {
          mbar_wait_watchdog(bars + 8 * s, ph);
          const uint32_t da = DESC_A + ((STG_OFF + kb * 1024) >> 4), db = DESC_B + ((s * 32768 + hf * 16384) >> 4) - 1024;
          wg_fence();
#pragma unroll
          for (int k = 0; k < 4; k++) wgmma_ss_n128(acc, da + k * 2, db + k * 128, (kb | k) != 0);
          wg_commit();
          wg_wait<0>();
          if (lane == 0) mbar_arrive(bars + 8 * (6 + s));
          if (++s == 6) { s = 0; ph ^= 1; }
        }
        if ((wid & 3) == 0) {
#pragma unroll
          for (int n = 0; n < 16; n++) {
            const uint32_t mine = pack2(acc[4 * n], acc[4 * n + 1]), next = __shfl_down_sync(~0u, mine, 1);
            if (lane < 4 && (lane & 1) == 0) ll_store(p.modll + 512 + v * 256 + e * 64 + hf * 32 + n * 2 + (lane >> 1), mine, next, tag);
            if (lane < 4) sts64f(sm + MODB_OFF + (hf * 128 + n * 8 + lane * 2) * 4, bf_lo(mine), bf_hi(mine));
          }
        }
      }
    }
    __syncthreads();
    if (wid == 0 || wid == 2) {
      const int w = wid >> 1;
      if (w == 0) {
        expect_tx_elect(bars + 8 * 12, KH * 32768);
#pragma unroll 1
        for (int q = 0; q < 4 * KH; q++) tma_load_ef(sm + q * 8192, &p.wd, bars + 8 * 12, e * 256 + (q & 3) * 64, (q >> 2) * 448);
      }
      cnt_wait_lazy(p.cnt + C_A0, tag * 8);
      if (w == 1) __nanosleep(HOFF);
      uint32_t ph = 1, ready = 0;
#pragma unroll 1
      for (int it = 0, s = 0; it < 16 * KH; it++) {
        const int rb = it / KH, kc = it - rb * KH;
        while (!((ready >> rb) & 1)) {
          ready = __ballot_sync(~0u, (int)(load_epoch(p.cnt + (lane & 15) * 32 + C_A0) - tag * 8) >= 0);
          asm volatile("fence.proxy.async.global;" ::: "memory");
        }
        const uint32_t fb = bars + 8 * (16 + w * 4 + s), dst = sm + 98304 + w * 32768 + s * 8192;
        mbar_wait(fb + 64, ph);
        expect_tx_elect(fb, 8192);
        tma_load(dst, &p.act_st, fb, kc * 448, rb * 128 + w * 64);
        tma_load(dst + 4096, &p.act_st, fb, kc * 448, rb * 128 + w * 64 + 32);
        if (++s == 4) { s = 0; ph ^= 1; }
      }
    } else if (wid >= 4) {
      const int w = (wid >> 2) - 1, warp = wid & 3;
      const uint32_t out_stg = (w ? stg : sm + 163840) + warp * 2048;
      const uint32_t slab = out_stg + (lane & 15) * 128, sw0 = (lane >> 4) ^ (lane & 7);
      mbar_wait_watchdog(bars + 8 * 12, 0);
#pragma unroll 1
      for (int i = threadIdx.x - 128; i < KH * 2048; i += 256) {
        const uint32_t gp = sm + MODB_OFF + (((i >> 9) & 3) * 64 + ((i ^ (i >> 3)) & 7) * 8) * 4;
        const uint4 v = lds128(sm + i * 16), ga = lds128(gp), gc = lds128(gp + 16);
        sts128(sm + i * 16, pack2(bf_lo(v.x) * __uint_as_float(ga.x), bf_hi(v.x) * __uint_as_float(ga.y)),
               pack2(bf_lo(v.y) * __uint_as_float(ga.z), bf_hi(v.y) * __uint_as_float(ga.w)),
               pack2(bf_lo(v.z) * __uint_as_float(gc.x), bf_hi(v.z) * __uint_as_float(gc.y)),
               pack2(bf_lo(v.w) * __uint_as_float(gc.z), bf_hi(v.w) * __uint_as_float(gc.w)));
      }
      asm volatile("fence.proxy.async.shared::cta;" ::: "memory");
      bar_sync(1, 256);
      uint32_t ph = 0;
      int s = 0;
#pragma unroll 1
      for (int rb = 0; rb < 16; rb++) {
        float acc[128];
#pragma unroll 1
        for (int kc = 0; kc < KH; kc++) {
          mbar_wait_watchdog(bars + 8 * (16 + w * 4 + s), ph);
          const uint32_t da = DESC_A + ((98304 + w * 32768 + s * 8192) >> 4), db = DESC_B + ((kc * 32768) >> 4) - 1024;
          wg_fence();
#pragma unroll
          for (int k = 0; k < 4; k++) wgmma_ss_n256(acc, da + k * 2, db + k * 128, (kc | k) != 0);
          wg_commit();
          wg_wait<1>();
          if (kc > 0 && lane == 0) mbar_arrive(bars + 8 * (24 + w * 4 + ((s + 3) & 3)));
          if (++s == 4) { s = 0; ph ^= 1; }
        }
        asm volatile("cp.async.bulk.wait_group 0;" ::: "memory");
        __syncwarp();
        if (rb > 0) cnt_signal(p.cnt + (rb - 1) * 32 + C_SP + e);
        wg_wait<0>();
        fence_regs(acc);
        __syncwarp();
        if (lane == 0) mbar_arrive(bars + 8 * (24 + w * 4 + ((s + 3) & 3)));
#pragma unroll
        for (int q = 0; q < 16; q++)
          stmatrix4(slab + (q >> 2) * 8192 + ((sw0 ^ ((q & 3) * 2)) << 4), pack2(acc[8 * q], acc[8 * q + 1]), pack2(acc[8 * q + 2], acc[8 * q + 3]),
                    pack2(acc[8 * q + 4], acc[8 * q + 5]), pack2(acc[8 * q + 6], acc[8 * q + 7]));
        asm volatile("fence.proxy.async.shared::cta;" ::: "memory");
        __syncwarp();
#pragma unroll
        for (int ch = 0; ch < 4; ch++) tma_add3(&p.out, out_stg + ch * 8192, e * 256 + ch * 64, rb * 64 + warp * 16, w);
        asm volatile("cp.async.bulk.commit_group;" ::: "memory");
      }
      asm volatile("cp.async.bulk.wait_group 0;" ::: "memory");
      __syncwarp();
      cnt_signal(p.cnt + 15 * 32 + C_SP + e);
    }
    return;
  }
  const int slot = p.slot[cl];
  const int rb = (slot >> 3) * 2 + rank, j = slot & 7;
  const int cta = rb * 8 + j;
  PROF_AT(threadIdx.x == 0, 0);

  if (threadIdx.x < 128) {
    uint32_t tag = load_epoch(p.epoch);
    asm volatile("setmaxnreg.dec.sync.aligned.u32 40;");
    const int warp = __shfl_sync(~0u, (int)(threadIdx.x >> 5), 0), lane = threadIdx.x & 31;
    if (threadIdx.x == 0) {
      if ((sm & 0x3FFFF) != SMEM_BASE) asm volatile("trap;");
      for (int i = 0; i < 4; i++) { mbar_init(bars + 8 * (B_FQ + i), 1); mbar_init(bars + 8 * (B_EQ + i), 16); }
      for (int i = 0; i < 6; i++) { mbar_init(bars + 8 * (B_FW + i), 1); mbar_init(bars + 8 * (B_EW + i), 16); }
      for (int i = 0; i < 4; i++) { mbar_init(bars + 8 * (B_FG + i), 1); mbar_init(bars + 8 * (B_EG + i), 16); }
      for (int i = 0; i < 6; i++) { mbar_init(bars + 8 * (B_FD + i), 1); mbar_init(bars + 8 * (B_ED + i), 16); }
      for (int i = 0; i < 2; i++) { mbar_init(bars + 8 * (B_STGF + i), 8); mbar_init(bars + 8 * (B_STGE + i), 1); }
      mbar_init(bars + 8 * B_MODB, 1);
      mbar_init(bars + 8 * (B_MODB + 1), 1);
      mbar_init(bars + 8 * B_MODA, 1);
      for (int i = 0; i < 8; i++) mbar_init(bars + 8 * (B_RDY + i), 1);
      asm volatile("fence.mbarrier_init.release.cluster;" ::: "memory");
    }
    __syncwarp();
    cluster_arrive_relaxed();
    tag += 1;
    const unsigned target = tag * 8;
    unsigned* cnt = p.cnt + rb * 32;
    cluster_wait();
    if (warp == 0) {
      const CUtensorMap* wgu = rank ? &p.wu : &p.wg;
      uint32_t st = sm + 16384, fb = bars + 8 * B_FQ, ph = 1;
      __nanosleep(BDELAY);
#pragma unroll 1
      for (int it = 0; it < 32; it++) {
        const int kb = qkv_kb(it, j), col = j * 128 + ((it < 4 ? it >= 2 : it >= 18) ? 64 : 0);
        mbar_wait(fb + 8 * (B_EQ - B_FQ), ph);
        expect_tx_elect(fb, it < 4 ? 24576 : 40960);
        tma_load_mc(st + rank * 8192, &p.wqkv, fb, col + rank * 1024, kb * 64);
        tma_load_mc(st + 16384 + rank * 4096, &p.wqkv32, fb, col + 2048, kb * 64 + rank * 32);
        st += 49152; fb += 8;
        if ((it & 3) == 3) { st -= 4 * 49152; fb -= 32; ph ^= 1; }
      }
      fb = bars + 8 * B_FW; ph = 1;
#pragma unroll 1
      for (int it = 0, s = 0; it < 16; it++) {
        if (it < 6) wait_p3_free(bars + 8 * B_EQ, it);
        mbar_wait(fb + 8 * (B_EW - B_FW), ph);
        expect_tx_elect(fb, it == 8 ? 16384 : 32768);
        tma_load_mc(st + rank * 8192, &p.wo, fb, j * 128 + rank * 64, wo_k(it, j));
        st += 32768; fb += 8;
        if (++s == 6) { s = 0; st -= 6 * 32768; fb -= 48; ph ^= 1; }
      }
      st = sm + 16384; fb = bars + 8 * B_FG; ph = 1;
#pragma unroll 1
      for (int it = 0; it < 48; it++) {
        const int kb = own_first(it, j), col = j * 448 + (it >> 4) * 128;
        if (it < 4) wait_p2_free(bars + 8 * B_EW, it);
        mbar_wait(fb + 8 * (B_EG - B_FG), ph);
        expect_tx_elect(fb, it < 2 ? 32768 : 49152);
        tma_load_mc(st + rank * 16384, wgu, fb, col, kb * 64);
        tma_load_mc(st + rank * 16384 + 8192, wgu, fb, col + 64, kb * 64);
        st += 49152; fb += 8;
        if ((it & 3) == 3) { st -= 4 * 49152; fb -= 32; ph ^= 1; }
      }
      fb = bars + 8 * B_FD; ph = 1;
#pragma unroll 1
      for (int it = 0, s = 0; it < 72 - KH; it++) {
        if (it < 6) wait_p3_free(bars + 8 * B_EG, it);
        mbar_wait(fb + 8 * (B_ED - B_FD), ph);
        expect_tx_elect(fb, 32768);
        tma_load_mc(st + rank * 8192, it < 16 ? wgu : &p.wd, fb, it < 16 ? j * 448 + 384 : j * 128 + rank * 64, down_k(it));
        st += 32768; fb += 8;
        if (++s == 6) { s = 0; st -= 6 * 32768; fb -= 48; ph ^= 1; }
      }
    } else if (warp == 1) {
      const int arow = rb * 128;
      uint32_t st = sm, fb = bars + 8 * B_FQ, ph = 0;
      cnt_wait(cnt + C_HA, target);
      PROF_AT(lane == 0, 16);
#pragma unroll 1
      for (int it = 4; it < 32; it++) {
        if (it == 11) mbar_wait(bars + 8 * (B_RDY + C_H), 0);
        mbar_wait(fb + 8 * (B_EQ - B_FQ), ph);
        tma_load(st, &p.h, fb, qkv_kb(it, j) * 64, arow);
        st += 49152; fb += 8;
        if ((it & 3) == 3) { st -= 4 * 49152; fb -= 32; ph ^= 1; }
      }
      fb = bars + 8 * B_FW; ph = 1;
#pragma unroll 1
      for (int it = 0, s = 0; it < 16; it++) {
        if (it < 6) wait_p3_free(bars + 8 * B_EQ, it);
        mbar_wait(fb + 8 * (B_EW - B_FW), ph);
        if (it == 0) mbar_wait(bars + 8 * (B_RDY + C_O), 0);
        if (it == 9) cnt_wait(cnt + C_O + 1, target * 8);
        PROF_AT(lane == 0 && (it == 0 || it == 9), 17 + (it >> 3));
        if (it != 8) tma_load(st, &p.o_ld, fb, wo_k(it, j), arow);
        st += 32768; fb += 8;
        if (++s == 6) { s = 0; st -= 6 * 32768; fb -= 48; ph ^= 1; }
      }
      st = sm + 2 * 49152; fb = bars + 8 * (B_FG + 2); ph = 1;
      cnt_wait(cnt + C_H2A, target * 8);
      PROF_AT(lane == 0, 19);
#pragma unroll 1
      for (int it = 2; it < 48; it++) {
        if (it == 9) mbar_wait(bars + 8 * (B_RDY + C_H2), 0);
        mbar_wait(fb + 8 * (B_EG - B_FG), ph);
        tma_load(st, &p.h2, fb, own_first(it, j) * 64, arow);
        st += 49152; fb += 8;
        if ((it & 3) == 3) { st -= 4 * 49152; fb -= 32; ph ^= 1; }
      }
      fb = bars + 8 * B_FD; ph = 1;
#pragma unroll 1
      for (int it = 0, s = 0; it < 72 - KH; it++) {
        if (it < 6) wait_p3_free(bars + 8 * B_EG, it);
        mbar_wait(fb + 8 * (B_ED - B_FD), ph);
        if (it == 16 || (it > 16 && ((it + KH) & 15) == 0)) { mbar_wait(bars + 8 * (B_RDY + C_ACT - 1 + ((it + KH) >> 4)), 0); PROF_AT(lane == 0, 19 + ((it + KH) >> 4)); }
        tma_load(st, it < 16 ? &p.h2 : &p.act, fb, down_k(it), arow);
        st += 32768; fb += 8;
        if (++s == 6) { s = 0; st -= 6 * 32768; fb -= 48; ph ^= 1; }
      }
    } else if (warp == 2) {
      if (lane < 14) prefetch_map(&p.h + lane);
      __syncwarp();
      uint32_t ph1 = 0;
#pragma unroll 1
      for (int n = 0; n < 8; n++) {
        const int nch = (n == 1 || n == 2 || n == 7) ? 1 : 2;
#pragma unroll 1
        for (int ch = 0; ch < nch; ch++) {
          mbar_wait_watchdog(bars + 8 * (B_STGF + ch), ch ? ph1 : (n & 1));
          const uint32_t src = stg + ch * 16384;
          if (n == 2 || n == 3) {
          } else if (n == 1) {
#pragma unroll 1
            for (int q = 0; q < 8; q++) {
              tma_store2(&p.o_st, src + q * 2048, j * 128, rb * 128 + q * 16);
              if (q & 1) store_pause(true);
            }
          } else if (n >= 4 && n < 8) {
#pragma unroll 1
            for (int q = 0; q < 4; q++) {
              tma_store2(&p.act_st, src + q * 4096, j * 448 + (n - 4) * 128 + ch * 64, rb * 128 + q * 32);
              store_pause(true);
            }
          } else {
            tma_store2(&p.h, src, j * 128 + ch * 64, rb * 128);
            asm volatile("cp.async.bulk.commit_group;" ::: "memory");
            if (ch == 1) {
              asm volatile("cp.async.bulk.wait_group 1;" ::: "memory");
              __syncwarp();
              cnt_signal(cnt + C_HA);
            }
          }
          if (n >= 4 && n < 7 && ch == 0) arrive_elect(bars + 8 * B_STGE);
          if (KH && n == 4 && ch == 0) {
            asm volatile("cp.async.bulk.wait_group 0;" ::: "memory");
            __syncwarp();
            cnt_signal(cnt + C_A0);
          }
        }
        asm volatile("cp.async.bulk.commit_group;" ::: "memory");
        asm volatile("cp.async.bulk.wait_group 0;" ::: "memory");
        __syncwarp();
        if (n != 2 && n != 3) cnt_signal(cnt + n);
        PROF_AT(lane == 0, n == 0 ? 33 : 23 + n);
        if (n == 0) {
#pragma unroll 1
          for (int t = 0; t < 34; t++) {
            ll_store(t < 32 ? p.halo + cta * 1024 + t * 32 + lane : (uint4*)(p.stats2 + cta * 128) + (t - 32) * 32 + lane, 0u, 0u, 0u);
            __nanosleep(40);
          }
          __syncwarp();
        }
        if (!(n >= 4 && n < 7)) arrive_elect(bars + 8 * B_STGE);
        if (nch == 2) { arrive_elect(bars + 8 * (B_STGE + 1)); ph1 ^= 1; }
      }
      mbar_wait_watchdog(bars + 8 * B_STGF, 0);
      PROF_AT(lane == 0, 31);
    } else {
      if (lane < 4) ll_store(p.modll + cta * 4 + lane, 0u, 0u, 0u);
      bar_sync(1, 288);
      {
        const uint4 t4 = lds128(sm + RED_OFF + lane * 16);
        float a[4] = {__uint_as_float(t4.x), __uint_as_float(t4.y), __uint_as_float(t4.z), __uint_as_float(t4.w)};
#pragma unroll
        for (int o = 4; o < 32; o <<= 1)
#pragma unroll
          for (int q = 0; q < 4; q++) a[q] += __shfl_xor_sync(~0u, a[q], o);
        if (lane < 4) ll_store(p.modll + cta * 4 + lane, pack2(a[0], a[1]), pack2(a[2], a[3]), tag);
        PROF_AT(lane == 0, 1);
        uint32_t m[4];
        const uint4* mp = p.modll + j * 32 + lane;
        ll_poll<2>([&](int i) { return mp + i * 256; }, tag, m);
        const uint32_t c0 = pack2(1.0f + bf_lo(m[2]), 1.0f + bf_hi(m[2])), c1 = pack2(1.0f + bf_lo(m[3]), 1.0f + bf_hi(m[3]));
        sts128(sm + MODB_OFF + lane * 16, c0, m[0], c1, m[1]);
        __syncwarp();
        arrive_elect(bars + 8 * B_MODA);
      }
#pragma unroll 1
      for (int n = C_H; n <= C_O; n++) {
        cnt_wait_lazy(cnt + n, target);
        arrive_elect(bars + 8 * (B_RDY + n));
      }
      {
        uint32_t m[6];
        const uint4* src = p.modll + 512 + j * 32 + lane;
        ll_poll<3, 500>([&](int i) { return src + i * 256; }, tag, m);
#pragma unroll
        for (int vec = 0; vec < 3; vec++) {
          const float add = vec == 2 ? 1.0f : 0.0f;
          sts128(sm + MODB_OFF + (vec * 128 + lane * 4) * 4, __float_as_uint(bf_round(bf_lo(m[2 * vec]) + add)), __float_as_uint(bf_round(bf_hi(m[2 * vec]) + add)),
                 __float_as_uint(bf_round(bf_lo(m[2 * vec + 1]) + add)), __float_as_uint(bf_round(bf_hi(m[2 * vec + 1]) + add)));
        }
        __syncwarp();
        if (lane == 0) mbar_arrive(bars + 8 * B_MODB);
        PROF_AT(lane == 0, 15);
      }
      __syncwarp();
#pragma unroll 1
      for (int n = C_H2; n < 8; n++) {
        cnt_wait_lazy(cnt + n, n == C_H2 ? target * 8 : target);
        arrive_elect(bars + 8 * (B_RDY + n));
      }
      {
        uint32_t m[2];
        const uint4* src = p.modll + 512 + 768 + j * 32 + lane;
        ll_poll<1>([&](int) { return src; }, tag, m);
        sts128(sm + MODB_OFF + (384 + lane * 4) * 4, m[0] << 16, m[0] & 0xffff0000u, m[1] << 16, m[1] & 0xffff0000u);
        cnt_wait_lazy(cnt + C_SP + (j >> 1), target);
        __syncwarp();
        if (lane == 0) mbar_arrive(bars + 8 * (B_MODB + 1));
      }
    }
  } else {
    uint32_t tag;

    {
      const int tid = threadIdx.x - 128, cw = tid >> 7, warp = (tid >> 5) & 3, lane = tid & 31;
      const int l16 = lane & 15, half = lane >> 4, w8 = cw * 4 + warp;
      const uint32_t cbuf = sm + 3 * 49152 + w8 * 512;
      if (lane <= 16) cp_async16(cbuf + lane * 16, lane < 16 ? (const void*)(p.c + w8 * 128 + lane * 8) : (const void*)p.epoch);
      asm volatile("cp.async.commit_group;" ::: "memory");
      const uint32_t xbuf = sm + 40960 + (cw * 2 + (l16 >> 3)) * 49152 + (warp * 16 + half) * 128;
      {
        const char* xp = (const char*)p.x + (uint32_t)((rb * 128 + (warp * 16 + half) * 2 + cw) * 2048 + j * 256 + l16 * 16);
#pragma unroll
        for (int i = 0; i < 8; i++) cp_async16(xbuf + i * 256 + (((l16 & 7) ^ ((i * 2 + half) & 7)) << 4), xp + i * 8192);
      }
      asm volatile("cp.async.commit_group;" ::: "memory");
      const uint32_t wbuf = sm + cw * 49152 + warp * 4096;
      {
        const char* wp = (const char*)p.wmod + (uint32_t)(cta * 32 + (lane & 1) * 16 + (w8 * 128 + (lane >> 1)) * 12288);
#pragma unroll
        for (int i = 0; i < 8; i++) cp_async16(wbuf + i * 512 + lane * 16, wp + i * 16 * 12288);
      }
      asm volatile("cp.async.commit_group;" ::: "memory");
      PROF_AT(tid == 0, 32);
      uint2* st1 = p.stats1 + (rb * 8 + j) * 128 + cw * 64 + warp * 16;
      if (lane < 8) ll_store((uint4*)st1 + lane, 0u, 0u, 0u);
      __syncwarp();
      cluster_arrive_relaxed();
      asm volatile("setmaxnreg.inc.sync.aligned.u32 232;");
      uint32_t sa[4][4];
      {
        asm volatile("cp.async.wait_group 2;" ::: "memory");
        __syncwarp();
        tag = lds32(cbuf + 256) + 1;
        const float2 cv = lds64f(cbuf + lane * 8);
        const uint32_t c0 = __float_as_uint(cv.x), c1 = __float_as_uint(cv.y);
        sts64f(cbuf + lane * 8, __uint_as_float(pack2(silu_f(bf_lo(c0)), silu_f(bf_hi(c0)))), __uint_as_float(pack2(silu_f(bf_lo(c1)), silu_f(bf_hi(c1)))));
        __syncwarp();
#pragma unroll
        for (int q = 0; q < 4; q++) ldmatrix4(sa[q][0], sa[q][1], sa[q][2], sa[q][3], cbuf + q * 64 + (lane >> 3) * 16);
      }
      cluster_wait();
      asm volatile("cp.async.wait_group 1;" ::: "memory");
      __syncwarp();
      uint32_t xl[16], xh[16];
      {
        const int srow = warp * 16 + (lane & 15);
#pragma unroll
        for (int q = 0; q < 8; q++)
          ldmatrix4(xl[2 * q], xh[2 * q], xl[2 * q + 1], xh[2 * q + 1],
                    sm + 40960 + (cw * 2 + (q >> 2)) * 49152 + srow * 128 + (((half + (q & 3) * 2) ^ (srow & 7)) << 4));
      }
      publish_stats(xl, xh, st1, lane, tag16(tag));
      PROF_AT(tid == 0, 50);
      asm volatile("cp.async.wait_group 0;" ::: "memory");
      __syncwarp();
      PROF_AT(tid == 0, 51);
      {
        uint32_t b[8][4];
#pragma unroll
        for (int ks = 0; ks < 8; ks++) ldmatrix4t(b[ks], wbuf + (ks * 16 + (lane & 15)) * 32 + (lane >> 4) * 16);
        float d0[4] = {0.f, 0.f, 0.f, 0.f}, d1[4] = {0.f, 0.f, 0.f, 0.f}, d2[4] = {0.f, 0.f, 0.f, 0.f}, d3[4] = {0.f, 0.f, 0.f, 0.f};
#pragma unroll
        for (int q = 0; q < 4; q++) {
          mma16816(d0, sa[q][0], sa[q][0], sa[q][1], sa[q][1], b[2 * q][0], b[2 * q][1]);
          mma16816(d1, sa[q][0], sa[q][0], sa[q][1], sa[q][1], b[2 * q][2], b[2 * q][3]);
          mma16816(d2, sa[q][2], sa[q][2], sa[q][3], sa[q][3], b[2 * q + 1][0], b[2 * q + 1][1]);
          mma16816(d3, sa[q][2], sa[q][2], sa[q][3], sa[q][3], b[2 * q + 1][2], b[2 * q + 1][3]);
        }
        d0[0] += d2[0]; d0[1] += d2[1]; d1[0] += d3[0]; d1[1] += d3[1];
        if (lane < 4) {
          sts64f(sm + RED_OFF + (w8 * 16 + lane * 2) * 4, d0[0], d0[1]);
          sts64f(sm + RED_OFF + (w8 * 16 + 8 + lane * 2) * 4, d1[0], d1[1]);
        }
        asm volatile("bar.arrive 1, 288;" ::: "memory");
      }
      {
        const int c = lane & 3;
        float rs[2], nb[2];
        stat_gather(p.stats1 + rb * 1024 + cw * 64 + warp * 16, tag16(tag), lane, rs, nb);
#pragma unroll
        for (int n = 0; n < 16; n++) {
          xl[n] = pack2(bf_lo(xl[n]) * rs[0] + nb[0], bf_hi(xl[n]) * rs[0] + nb[0]);
          xh[n] = pack2(bf_lo(xh[n]) * rs[1] + nb[1], bf_hi(xh[n]) * rs[1] + nb[1]);
        }
        const int srow = warp * 16 + l16;
        const uint32_t slab = stg + cw * 8192 + srow * 128;
#pragma unroll
        for (int q = 0; q < 8; q++)
          stmatrix4(slab + (q >> 2) * 16384 + (((half + (q & 3) * 2) ^ (srow & 7)) << 4), xl[2 * q], xh[2 * q], xl[2 * q + 1], xh[2 * q + 1]);
        PROF_AT(tid == 0, 52);
        mbar_wait(bars + 8 * B_MODA, 0);
        PROF_AT(tid == 0, 2);
#pragma unroll
        for (int q = 0; q < 8; q++) {
          const float2 m0 = lds64f(sm + MODB_OFF + (8 * q + c) * 8), m1 = lds64f(sm + MODB_OFF + (8 * q + 4 + c) * 8);
          const uint32_t c0 = __float_as_uint(m0.x), s0 = __float_as_uint(m0.y), c1 = __float_as_uint(m1.x), s1 = __float_as_uint(m1.y);
          stmatrix4(slab + (q >> 2) * 16384 + (((half + (q & 3) * 2) ^ (srow & 7)) << 4), fma_bf2(xl[2 * q], c0, s0), fma_bf2(xh[2 * q], c0, s0),
                    fma_bf2(xl[2 * q + 1], c1, s1), fma_bf2(xh[2 * q + 1], c1, s1));
          if ((q & 3) == 3) stage_done(bars + 8 * (B_STGF + (q >> 2)), lane);
        }
        wg_bar(cw);
      }
      PROF_AT(tid == 0, 3);
    }

    uint32_t xl[16], xh[16];
    {
      RING_IDS();
      uint32_t prev = 0;
      float acc1[96];
      {
        Ring g{bars + 8 * B_FQ, rbars + 8 * B_EQ, 0, 0u, releaser TR(0)};
        float acc0[96];
#pragma unroll 1
        for (int kb = 0; kb < 2; kb++) kblock<192, 4, 49152>(acc0, g, a_base + STG_OFF + kb * 16384, kb == 0, prev);
#pragma unroll 1
        for (int kb = 0; kb < 2; kb++) kblock<192, 4, 49152>(acc1, g, a_base + STG_OFF + kb * 16384, kb == 0, prev);
#pragma unroll 1
        for (int kb = 0; kb < 14; kb++) kblock<192, 4, 49152>(acc0, g, a_base + g.s * 49152, false, prev);
        PROF_AT(tid == 0, 4);
        attention<NPRE0, false>(acc0, p, 0, rb, cta, cw, warp, tag, stg, bars, prev, [&]() { kblock<192, 4, 49152>(acc1, g, a_base + g.s * 49152, false, prev); });
        PROF_AT(tid == 0, 5);
        {
          LANE_IDS();
#pragma unroll
          for (int q = 0; q < 8; q++)
            ldmatrix4(xl[2 * q], xh[2 * q], xl[2 * q + 1], xh[2 * q + 1], sm + 40960 + (cw * 2 + (q >> 2)) * 49152 + srow * 128 + ((sw0 ^ ((q & 3) * 2)) << 4));
#pragma unroll
          for (int q = 0; q < 16; q++) asm volatile("" : "+r"(xl[q]), "+r"(xh[q])::"memory");
        }
#pragma unroll 1
        for (int kb = 5 + NPRE0; kb < 14; kb++) kblock<192, 4, 49152>(acc1, g, a_base + g.s * 49152, false, prev);
        PROF_AT(tid == 0, 6);
      }
      float acc[64];
      Ring g{bars + 8 * B_FW, rbars + 8 * B_EW, 0, 0u, releaser TR(32)};
      attention<NPRE1, true>(acc1, p, 1, rb, cta, cw, warp, tag, stg, bars, prev, [&]() { kblock<128, 6, 32768>(acc, g, a_base + g.s * 32768, g.s == 0, prev); });
      PROF_AT(tid == 0, 7);
      LANE_IDS();
      unsigned* cnt = p.cnt + rb * 32;
      tma_store2(&p.o_st, stg + cw * 8192 + warp * 2048, j * 128 + 64, rb * 128 + cw * 64 + warp * 16);
      asm volatile("cp.async.bulk.commit_group;" ::: "memory");
#pragma unroll 1
      for (int kb = 1 + NPRE1; kb < 16; kb++) {
        if (kb == 8) wg_bar(cw);
        kblock<128, 6, 32768>(acc, g, a_base + (kb == 8 ? STG_OFF : g.s * 32768), false, prev);
        if (kb == OSIG + NPRE1) {
          asm volatile("cp.async.bulk.wait_group 0;" ::: "memory");
          __syncwarp();
          cnt_signal(cnt + C_O + 1);
        }
      }
      mbar_wait(bars + 8 * B_MODB, 0);
      float2 ga[16];
#pragma unroll
      for (int n = 0; n < 16; n++) ga[n] = lds64f(sm + MODB_OFF + (8 * n + 2 * c) * 4);
      tile_end(acc, prev);
      PROF_AT(tid == 0, 8);
      uint2* st2 = p.stats2 + (rb * 8 + j) * 128 + cw * 64 + warp * 16 + r + (c & 1) * 8;
      float sl[2] = {0.f, 0.f}, sh[2] = {0.f, 0.f}, ql[2] = {0.f, 0.f}, qh[2] = {0.f, 0.f};
#pragma unroll
      for (int n = 0; n < 16; n++) {
        acc[4 * n] = ga[n].x * acc[4 * n] + bf_lo(xl[n]); acc[4 * n + 1] = ga[n].y * acc[4 * n + 1] + bf_hi(xl[n]);
        acc[4 * n + 2] = ga[n].x * acc[4 * n + 2] + bf_lo(xh[n]); acc[4 * n + 3] = ga[n].y * acc[4 * n + 3] + bf_hi(xh[n]);
        sl[0] += acc[4 * n]; sl[1] += acc[4 * n + 1]; sh[0] += acc[4 * n + 2]; sh[1] += acc[4 * n + 3];
        ql[0] += acc[4 * n] * acc[4 * n]; ql[1] += acc[4 * n + 1] * acc[4 * n + 1];
        qh[0] += acc[4 * n + 2] * acc[4 * n + 2]; qh[1] += acc[4 * n + 3] * acc[4 * n + 3];
      }
      {
        const float ml = (sl[0] + sl[1]) * (1.0f / 32), mh = (sh[0] + sh[1]) * (1.0f / 32);
        const float vl = (ql[0] + ql[1]) - 32.0f * ml * ml, vh = (qh[0] + qh[1]) - 32.0f * mh * mh;
        const bool b0 = c & 1;
        float m = b0 ? mh : ml, q = b0 ? vh : vl;
        chan(m, q, __shfl_xor_sync(~0u, b0 ? ml : mh, 1), __shfl_xor_sync(~0u, b0 ? vl : vh, 1), 32.f);
        chan(m, q, __shfl_xor_sync(~0u, m, 2), __shfl_xor_sync(~0u, q, 2), 64.f);
        if (c < 2) stat_store(st2, m, fmaxf(q, 0.f), tag16(tag));
        __syncwarp();
      }
      PROF_AT(tid == 0, 48);
      float2 sb[16], cb[16];
#pragma unroll
      for (int n = 0; n < 16; n++) {
        sb[n] = lds64f(sm + MODB_OFF + (128 + 8 * n + 2 * c) * 4);
        cb[n] = lds64f(sm + MODB_OFF + (256 + 8 * n + 2 * c) * 4);
        xl[n] = pack2(acc[4 * n], acc[4 * n + 1]);
        xh[n] = pack2(acc[4 * n + 2], acc[4 * n + 3]);
      }
      mbar_wait(bars + 8 * B_STGE, 0);
      PROF_AT(tid == 0, 49);
      float nb[2], rstd[2];
      stat_gather(p.stats2 + rb * 1024 + cw * 64 + warp * 16, tag16(tag), lane, rstd, nb);
      PROF_AT(tid == 0, 9);
#pragma unroll
      for (int ch = 0; ch < 2; ch++) {
        uint32_t lo[8], hi[8];
#pragma unroll
        for (int t = 0; t < 8; t++) {
          const int n = ch * 8 + t;
          lo[t] = pack2((acc[4 * n] * rstd[0] + nb[0]) * cb[n].x + sb[n].x, (acc[4 * n + 1] * rstd[0] + nb[0]) * cb[n].y + sb[n].y);
          hi[t] = pack2((acc[4 * n + 2] * rstd[1] + nb[1]) * cb[n].x + sb[n].x, (acc[4 * n + 3] * rstd[1] + nb[1]) * cb[n].y + sb[n].y);
        }
        stage_slab(stg + ch * 16384 + cw * 8192, warp, lane, lo, hi);
        stage_done(bars + 8 * (B_STGF + ch), lane);
        tma_store2(&p.h2_st, stg + ch * 16384 + cw * 8192 + warp * 2048, j * 128 + ch * 64, rb * 128 + cw * 64 + warp * 16);
        asm volatile("cp.async.bulk.commit_group;" ::: "memory");
      }
      wg_bar(cw);
      PROF_AT(tid == 0, 10);
    }

    uint32_t pg[32], pu[32];
    {
      RING_IDS();
      LANE_IDS();
      Ring g{bars + 8 * B_FG, rbars + 8 * B_EG, 0, 0u, releaser TR(48)};
      float acc[128];
      {
        uint32_t prev = 0;
#pragma unroll 1
        for (int kb = 0; kb < 16; kb++) {
          kblock<256, 4, 49152>(acc, g, a_base + (kb < 2 ? STG_OFF + kb * 16384 : g.s * 49152), kb == 0, prev);
          if (kb == 0) {
            asm volatile("cp.async.bulk.wait_group 1;" ::: "memory");
            __syncwarp();
            cnt_signal(p.cnt + rb * 32 + C_H2A);
          }
          if (kb == 1) {
            asm volatile("cp.async.bulk.wait_group 0;" ::: "memory");
            __syncwarp();
            cnt_signal(p.cnt + rb * 32 + C_H2);
          }
#pragma unroll
          for (int ch = 0; ch < 2; ch++) {
            if (kb == 3 + 3 * ch) {
#pragma unroll
              for (int q = 0; q < 4; q++)
                stmatrix4(slab + ch * 16384 + ((sw0 ^ (q * 2)) << 4), xl[8 * ch + 2 * q], xh[8 * ch + 2 * q], xl[8 * ch + 2 * q + 1], xh[8 * ch + 2 * q + 1]);
              asm volatile("fence.proxy.async.shared::cta;" ::: "memory");
              __syncwarp();
              tma_store3(&p.out, stg + ch * 16384 + cw * 8192 + warp * 2048, j * 128 + ch * 64, rb * 64 + warp * 16, cw);
              asm volatile("cp.async.bulk.commit_group;" ::: "memory");
            }
          }
          if (kb == 12) asm volatile("cp.async.bulk.wait_group 0;" ::: "memory");
        }
        tile_end(acc, prev);
      }
      PROF_AT(tid == 0, 36);
#pragma unroll 1
      for (int t = 1; t < 3; t++) {
#pragma unroll
        for (int q = 0; q < 32; q++) {
          pg[q] = pack2(acc[2 * q], acc[2 * q + 1]);
          pu[q] = pack2(acc[64 + 2 * q], acc[64 + 2 * q + 1]);
        }
        uint32_t prev = 0;
#pragma unroll 1
        for (int blk = 0; blk < 4; blk++) {
          g.s = 0;
#pragma unroll
          for (int i = 0; i < 4; i++) {
            kblock<256, 4, 49152>(acc, g, a_base + i * 49152, blk == 0 && i == 0, prev);
            if ((blk & 1) == 0 && i == 0) mbar_wait(bars + 8 * (B_STGE + (blk >> 1)), t & 1);
            stmatrix2(slab + (blk >> 1) * 16384 + (((srow & 7) ^ ((blk & 1) * 4 + i)) << 4), swiglu2(pg[2 * i], pu[2 * i]), swiglu2(pg[2 * i + 1], pu[2 * i + 1]));
          }
#pragma unroll
          for (int q = 0; q < 24; q++) { pg[q] = pg[q + 8]; pu[q] = pu[q + 8]; }
          if (blk & 1) stage_done(bars + 8 * (B_STGF + (blk >> 1)), lane);
        }
        tile_end(acc, prev);
        PROF_AT(tid == 0, 36 + t);
      }
#pragma unroll
      for (int q = 0; q < 32; q++) {
        pg[q] = pack2(acc[2 * q], acc[2 * q + 1]);
        pu[q] = pack2(acc[64 + 2 * q], acc[64 + 2 * q + 1]);
      }
      PROF_AT(tid == 0, 11);
    }

    {
      RING_IDS();
      LANE_IDS();
      Ring g{bars + 8 * B_FD, rbars + 8 * B_ED, 0, 0u, releaser TR(96)};
      float acc[64];
      uint32_t prev = 0;
#pragma unroll 1
      for (int blk = 0; blk < 6; blk++) {
#pragma unroll
        for (int i = 0; i < 8; i++) {
          kblock<128, 6, 32768>(acc, g, a_base + g.s * 32768, (blk & ~2) == 0 && i == 0, prev);
          if ((blk & 1) == 0 && i == 0) mbar_wait(bars + 8 * (B_STGE + ((blk >> 1) & 1)), blk < 4);
          stmatrix1(slab + ((blk >> 1) & 1) * 16384 + (i & 1) * 1024 + (((srow & 7) ^ ((blk & 1) * 4 + (i >> 1))) << 4), swiglu2(pg[i], pu[i]));
        }
#pragma unroll
        for (int q = 0; q < 24; q++) { pg[q] = pg[q + 8]; pu[q] = pu[q + 8]; }
        if (blk & 1) stage_done(bars + 8 * (B_STGF + ((blk >> 1) & 1)), lane);
        if (blk == 1) {
          tile_end(acc, prev);
          PROF_AT(tid == 0, 39);
#pragma unroll
          for (int q = 0; q < 16; q++) {
            pg[16 + q] = pack2(acc[2 * q], acc[2 * q + 1]);
            pu[16 + q] = pack2(acc[32 + 2 * q], acc[32 + 2 * q + 1]);
          }
          PROF_AT(tid == 0, 12);
        }
      }
#pragma unroll 1
      for (int kb = 48; kb < 72 - KH; kb++) {
        if (kb == 66 - KH) g.releaser = false;
        kblock<128, 6, 32768>(acc, g, a_base + g.s * 32768, false, prev);
      }
      mbar_wait(bars + 8 * (B_MODB + 1), 0);
      mbar_wait(bars + 8 * B_STGE, 1);
      mbar_wait(bars + 8 * (B_STGE + 1), 0);
      float2 gbv[16];
#pragma unroll
      for (int n = 0; n < 16; n++) gbv[n] = lds64f(sm + MODB_OFF + (384 + 8 * n + 2 * c) * 4);
      tile_end(acc, prev);
      PROF_AT(tid == 0, 13);
#pragma unroll
      for (int ch = 0; ch < 2; ch++) {
        uint32_t lo[8], hi[8];
#pragma unroll
        for (int t = 0; t < 8; t++) {
          const int n = ch * 8 + t;
          const float2 gb = gbv[n];
          lo[t] = pack2(gb.x * acc[4 * n], gb.y * acc[4 * n + 1]);
          hi[t] = pack2(gb.x * acc[4 * n + 2], gb.y * acc[4 * n + 3]);
        }
        stage_slab(stg + ch * 16384 + cw * 8192, warp, lane, lo, hi);
        asm volatile("fence.proxy.async.shared::cta;" ::: "memory");
        __syncwarp();
        tma_add3(&p.out, stg + ch * 16384 + cw * 8192 + warp * 2048, j * 128 + ch * 64, rb * 64 + warp * 16, cw);
      }
      asm volatile("cp.async.bulk.commit_group;" ::: "memory");
      if (lane == 0) mbar_arrive(bars + 8 * B_STGF);
      asm volatile("cp.async.bulk.wait_group.read 0;" ::: "memory");
      PROF_AT(tid == 0, 14);
    }
    if (blockIdx.x == 0 && threadIdx.x == 128) asm volatile("st.relaxed.gpu.global.u32 [%0], %1;" ::"l"(p.epoch), "r"(tag) : "memory");
  }
}

typedef CUresult (*EncodeFn)(CUtensorMap*, CUtensorMapDataType, cuuint32_t, void*, const cuuint64_t*, const cuuint64_t*,
                             const cuuint32_t*, const cuuint32_t*, CUtensorMapInterleave, CUtensorMapSwizzle,
                             CUtensorMapL2promotion, CUtensorMapFloatOOBfill);

void encode2d(EncodeFn fn, CUtensorMap* m, const void* ptr, uint64_t cols, uint64_t rows, uint32_t box_rows) {
  cuuint64_t dims[2] = {cols, rows};
  cuuint64_t strides[1] = {cols * 2};
  cuuint32_t box[2] = {64, box_rows};
  cuuint32_t es[2] = {1, 1};
  fn(m, CU_TENSOR_MAP_DATA_TYPE_BFLOAT16, 2, (void*)ptr, dims, strides, box, es, CU_TENSOR_MAP_INTERLEAVE_NONE,
     CU_TENSOR_MAP_SWIZZLE_128B, CU_TENSOR_MAP_L2_PROMOTION_L2_128B, CU_TENSOR_MAP_FLOAT_OOB_FILL_NONE);
}

}

extern "C" void kernel_launch(void* const* d_in, const int* in_sizes, int n_in, void* d_out, int out_size) {
  (void)in_sizes; (void)n_in; (void)out_size;
  void* fp = nullptr;
  cudaDriverEntryPointQueryResult qr;
  cudaGetDriverEntryPoint("cuTensorMapEncodeTiled", &fp, cudaEnableDefault, &qr);
  EncodeFn fn = (EncodeFn)fp;
  void *ph, *po, *ph2, *pact;
  cudaGetSymbolAddress(&ph, g_h);
  cudaGetSymbolAddress(&po, g_o);
  ph2 = ph;
  cudaGetSymbolAddress(&pact, g_act);
  Params p;
  encode2d(fn, &p.h, ph, DM, SEQ, 128);
  encode2d(fn, &p.o_ld, po, DM, SEQ, 128);
  encode2d(fn, &p.h2, ph2, DM, SEQ, 128);
  encode2d(fn, &p.act, pact, FF, SEQ, 128);
  encode2d(fn, &p.act_st, pact, FF, SEQ, 32);
  encode2d(fn, &p.wm, d_in[8], 6 * DM, DM, 64);
  encode2d(fn, &p.o_st, po, DM, SEQ, 16);
  encode2d(fn, &p.h2_st, ph2, DM, SEQ, 16);
  encode2d(fn, &p.wqkv, d_in[1], 3 * DM, DM, 64);
  encode2d(fn, &p.wqkv32, d_in[1], 3 * DM, DM, 32);
  encode2d(fn, &p.wo, d_in[2], DM, DM, 64);
  encode2d(fn, &p.wg, d_in[4], FF, DM, 64);
  encode2d(fn, &p.wu, d_in[5], FF, DM, 64);
  encode2d(fn, &p.wd, d_in[6], DM, FF, 64);
  {
    cuuint64_t dims[3] = {DM, SEQ / 2, 2};
    cuuint64_t strides[2] = {DM * 4, DM * 2};
    cuuint32_t box[3] = {64, 16, 1};
    cuuint32_t es[3] = {1, 1, 1};
    fn(&p.out, CU_TENSOR_MAP_DATA_TYPE_BFLOAT16, 3, d_out, dims, strides, box, es, CU_TENSOR_MAP_INTERLEAVE_NONE,
       CU_TENSOR_MAP_SWIZZLE_128B, CU_TENSOR_MAP_L2_PROMOTION_L2_128B, CU_TENSOR_MAP_FLOAT_OOB_FILL_NONE);
  }
  p.x = (const bf16*)d_in[0];
  p.c = (const bf16*)d_in[7];
  p.wmod = (const bf16*)d_in[8];
  for (int cl = 0; cl < 64; cl++) {
    const int grp = cl < 4 ? 0 : (cl < 36 ? (cl - 4) & 7 : 1 + (cl - 36) % 7);
    const int j = cl < 4 ? 4 + cl : (cl < 36 ? (cl - 4) >> 3 : 4 + (cl - 36) / 7);
    p.slot[cl] = (uint8_t)(grp * 8 + j);
  }
  void* q;
  cudaGetSymbolAddress(&q, g_modll); p.modll = (uint4*)q;
  cudaGetSymbolAddress(&q, g_halo); p.halo = (uint4*)q;
  cudaGetSymbolAddress(&q, g_stats); p.stats1 = (uint2*)q; p.stats2 = p.stats1 + SEQ * 8;
  cudaGetSymbolAddress(&q, g_cnt); p.cnt = (unsigned*)q;
  cudaGetSymbolAddress(&q, g_epoch); p.epoch = (unsigned*)q;

  cudaFuncSetAttribute(fused_kernel, cudaFuncAttributeMaxDynamicSharedMemorySize, SMEM_BYTES);
  cudaLaunchConfig_t cfg = {};
  cfg.gridDim = dim3(NCTA + 4);
  cfg.blockDim = dim3(384);
  cfg.dynamicSmemBytes = SMEM_BYTES;
  cfg.stream = cudaStreamPerThread;
  cudaLaunchAttribute at[1];
  at[0].id = cudaLaunchAttributeClusterDimension;
  at[0].val.clusterDim.x = 2; at[0].val.clusterDim.y = 1; at[0].val.clusterDim.z = 1;
  cfg.attrs = at;
  cfg.numAttrs = 1;
  cudaLaunchKernelEx(&cfg, fused_kernel, p);
}
```

```cpp
#include <cuda_runtime.h>
#include <cuda_bf16.h>
#include <cuda.h>
#include <stdint.h>

typedef __nv_bfloat16 bf16;

#define PAUSE 200
#define WMDELAY 500
#define BDELAY 1500
#define NPRE0 3
#define NPRE1 1
#define ALIAS 1

#define PFW 8000
#define PFP 0

#define OSIG 3

#define KH 3

#define HOFF 900

#define X1S 6

#define GW 15

__device__ __forceinline__ void wgmma_ss_n128(float (&d)[64], uint32_t da, uint32_t db, int scale_d) {
  asm volatile("{\n.reg .pred p;\n.reg .b64 da, db;\nsetp.ne.b32 p, %66, 0;\n"
    "mov.b64 da, {%64, 0x40000040};\nmov.b64 db, {%65, 0x40000040};\n"
    "wgmma.mma_async.sync.aligned.m64n128k16.f32.bf16.bf16 "
    "{%0, %1, %2, %3, %4, %5, %6, %7, %8, %9, %10, %11, %12, %13, %14, %15, "
    "%16, %17, %18, %19, %20, %21, %22, %23, %24, %25, %26, %27, %28, %29, %30, %31, "
    "%32, %33, %34, %35, %36, %37, %38, %39, %40, %41, %42, %43, %44, %45, %46, %47, "
    "%48, %49, %50, %51, %52, %53, %54, %55, %56, %57, %58, %59, %60, %61, %62, %63}, "
    "da, db, p, 1, 1, 0, 1;\n}\n"
    : "+f"(d[0]), "+f"(d[1]), "+f"(d[2]), "+f"(d[3]), "+f"(d[4]), "+f"(d[5]), "+f"(d[6]), "+f"(d[7]),
      "+f"(d[8]), "+f"(d[9]), "+f"(d[10]), "+f"(d[11]), "+f"(d[12]), "+f"(d[13]), "+f"(d[14]), "+f"(d[15]),
      "+f"(d[16]), "+f"(d[17]), "+f"(d[18]), "+f"(d[19]), "+f"(d[20]), "+f"(d[21]), "+f"(d[22]), "+f"(d[23]),
      "+f"(d[24]), "+f"(d[25]), "+f"(d[26]), "+f"(d[27]), "+f"(d[28]), "+f"(d[29]), "+f"(d[30]), "+f"(d[31]),
      "+f"(d[32]), "+f"(d[33]), "+f"(d[34]), "+f"(d[35]), "+f"(d[36]), "+f"(d[37]), "+f"(d[38]), "+f"(d[39]),
      "+f"(d[40]), "+f"(d[41]), "+f"(d[42]), "+f"(d[43]), "+f"(d[44]), "+f"(d[45]), "+f"(d[46]), "+f"(d[47]),
      "+f"(d[48]), "+f"(d[49]), "+f"(d[50]), "+f"(d[51]), "+f"(d[52]), "+f"(d[53]), "+f"(d[54]), "+f"(d[55]),
      "+f"(d[56]), "+f"(d[57]), "+f"(d[58]), "+f"(d[59]), "+f"(d[60]), "+f"(d[61]), "+f"(d[62]), "+f"(d[63])
    : "r"(da), "r"(db), "r"(scale_d));
}

__device__ __forceinline__ void wgmma_ss_n192(float (&d)[96], uint32_t da, uint32_t db, int scale_d) {
  asm volatile("{\n.reg .pred p;\n.reg .b64 da, db;\nsetp.ne.b32 p, %98, 0;\n"
    "mov.b64 da, {%96, 0x40000040};\nmov.b64 db, {%97, 0x40000040};\n"
    "wgmma.mma_async.sync.aligned.m64n192k16.f32.bf16.bf16 "
    "{%0, %1, %2, %3, %4, %5, %6, %7, %8, %9, %10, %11, %12, %13, %14, %15, "
    "%16, %17, %18, %19, %20, %21, %22, %23, %24, %25, %26, %27, %28, %29, %30, %31, "
    "%32, %33, %34, %35, %36, %37, %38, %39, %40, %41, %42, %43, %44, %45, %46, %47, "
    "%48, %49, %50, %51, %52, %53, %54, %55, %56, %57, %58, %59, %60, %61, %62, %63, "
    "%64, %65, %66, %67, %68, %69, %70, %71, %72, %73, %74, %75, %76, %77, %78, %79, "
    "%80, %81, %82, %83, %84, %85, %86, %87, %88, %89, %90, %91, %92, %93, %94, %95}, "
    "da, db, p, 1, 1, 0, 1;\n}\n"
    : "+f"(d[0]), "+f"(d[1]), "+f"(d[2]), "+f"(d[3]), "+f"(d[4]), "+f"(d[5]), "+f"(d[6]), "+f"(d[7]),
      "+f"(d[8]), "+f"(d[9]), "+f"(d[10]), "+f"(d[11]), "+f"(d[12]), "+f"(d[13]), "+f"(d[14]), "+f"(d[15]),
      "+f"(d[16]), "+f"(d[17]), "+f"(d[18]), "+f"(d[19]), "+f"(d[20]), "+f"(d[21]), "+f"(d[22]), "+f"(d[23]),
      "+f"(d[24]), "+f"(d[25]), "+f"(d[26]), "+f"(d[27]), "+f"(d[28]), "+f"(d[29]), "+f"(d[30]), "+f"(d[31]),
      "+f"(d[32]), "+f"(d[33]), "+f"(d[34]), "+f"(d[35]), "+f"(d[36]), "+f"(d[37]), "+f"(d[38]), "+f"(d[39]),
      "+f"(d[40]), "+f"(d[41]), "+f"(d[42]), "+f"(d[43]), "+f"(d[44]), "+f"(d[45]), "+f"(d[46]), "+f"(d[47]),
      "+f"(d[48]), "+f"(d[49]), "+f"(d[50]), "+f"(d[51]), "+f"(d[52]), "+f"(d[53]), "+f"(d[54]), "+f"(d[55]),
      "+f"(d[56]), "+f"(d[57]), "+f"(d[58]), "+f"(d[59]), "+f"(d[60]), "+f"(d[61]), "+f"(d[62]), "+f"(d[63]),
      "+f"(d[64]), "+f"(d[65]), "+f"(d[66]), "+f"(d[67]), "+f"(d[68]), "+f"(d[69]), "+f"(d[70]), "+f"(d[71]),
      "+f"(d[72]), "+f"(d[73]), "+f"(d[74]), "+f"(d[75]), "+f"(d[76]), "+f"(d[77]), "+f"(d[78]), "+f"(d[79]),
      "+f"(d[80]), "+f"(d[81]), "+f"(d[82]), "+f"(d[83]), "+f"(d[84]), "+f"(d[85]), "+f"(d[86]), "+f"(d[87]),
      "+f"(d[88]), "+f"(d[89]), "+f"(d[90]), "+f"(d[91]), "+f"(d[92]), "+f"(d[93]), "+f"(d[94]), "+f"(d[95])
    : "r"(da), "r"(db), "r"(scale_d));
}

__device__ __forceinline__ void wgmma_ss_n256(float (&d)[128], uint32_t da, uint32_t db, int scale_d) {
  asm volatile("{\n.reg .pred p;\n.reg .b64 da, db;\nsetp.ne.b32 p, %130, 0;\n"
    "mov.b64 da, {%128, 0x40000040};\nmov.b64 db, {%129, 0x40000040};\n"
    "wgmma.mma_async.sync.aligned.m64n256k16.f32.bf16.bf16 "
    "{%0, %1, %2, %3, %4, %5, %6, %7, %8, %9, %10, %11, %12, %13, %14, %15, "
    "%16, %17, %18, %19, %20, %21, %22, %23, %24, %25, %26, %27, %28, %29, %30, %31, "
    "%32, %33, %34, %35, %36, %37, %38, %39, %40, %41, %42, %43, %44, %45, %46, %47, "
    "%48, %49, %50, %51, %52, %53, %54, %55, %56, %57, %58, %59, %60, %61, %62, %63, "
    "%64, %65, %66, %67, %68, %69, %70, %71, %72, %73, %74, %75, %76, %77, %78, %79, "
    "%80, %81, %82, %83, %84, %85, %86, %87, %88, %89, %90, %91, %92, %93, %94, %95, "
    "%96, %97, %98, %99, %100, %101, %102, %103, %104, %105, %106, %107, %108, %109, %110, %111, "
    "%112, %113, %114, %115, %116, %117, %118, %119, %120, %121, %122, %123, %124, %125, %126, %127}, "
    "da, db, p, 1, 1, 0, 1;\n}\n"
    : "+f"(d[0]), "+f"(d[1]), "+f"(d[2]), "+f"(d[3]), "+f"(d[4]), "+f"(d[5]), "+f"(d[6]), "+f"(d[7]),
      "+f"(d[8]), "+f"(d[9]), "+f"(d[10]), "+f"(d[11]), "+f"(d[12]), "+f"(d[13]), "+f"(d[14]), "+f"(d[15]),
      "+f"(d[16]), "+f"(d[17]), "+f"(d[18]), "+f"(d[19]), "+f"(d[20]), "+f"(d[21]), "+f"(d[22]), "+f"(d[23]),
      "+f"(d[24]), "+f"(d[25]), "+f"(d[26]), "+f"(d[27]), "+f"(d[28]), "+f"(d[29]), "+f"(d[30]), "+f"(d[31]),
      "+f"(d[32]), "+f"(d[33]), "+f"(d[34]), "+f"(d[35]), "+f"(d[36]), "+f"(d[37]), "+f"(d[38]), "+f"(d[39]),
      "+f"(d[40]), "+f"(d[41]), "+f"(d[42]), "+f"(d[43]), "+f"(d[44]), "+f"(d[45]), "+f"(d[46]), "+f"(d[47]),
      "+f"(d[48]), "+f"(d[49]), "+f"(d[50]), "+f"(d[51]), "+f"(d[52]), "+f"(d[53]), "+f"(d[54]), "+f"(d[55]),
      "+f"(d[56]), "+f"(d[57]), "+f"(d[58]), "+f"(d[59]), "+f"(d[60]), "+f"(d[61]), "+f"(d[62]), "+f"(d[63]),
      "+f"(d[64]), "+f"(d[65]), "+f"(d[66]), "+f"(d[67]), "+f"(d[68]), "+f"(d[69]), "+f"(d[70]), "+f"(d[71]),
      "+f"(d[72]), "+f"(d[73]), "+f"(d[74]), "+f"(d[75]), "+f"(d[76]), "+f"(d[77]), "+f"(d[78]), "+f"(d[79]),
      "+f"(d[80]), "+f"(d[81]), "+f"(d[82]), "+f"(d[83]), "+f"(d[84]), "+f"(d[85]), "+f"(d[86]), "+f"(d[87]),
      "+f"(d[88]), "+f"(d[89]), "+f"(d[90]), "+f"(d[91]), "+f"(d[92]), "+f"(d[93]), "+f"(d[94]), "+f"(d[95]),
      "+f"(d[96]), "+f"(d[97]), "+f"(d[98]), "+f"(d[99]), "+f"(d[100]), "+f"(d[101]), "+f"(d[102]), "+f"(d[103]),
      "+f"(d[104]), "+f"(d[105]), "+f"(d[106]), "+f"(d[107]), "+f"(d[108]), "+f"(d[109]), "+f"(d[110]), "+f"(d[111]),
      "+f"(d[112]), "+f"(d[113]), "+f"(d[114]), "+f"(d[115]), "+f"(d[116]), "+f"(d[117]), "+f"(d[118]), "+f"(d[119]),
      "+f"(d[120]), "+f"(d[121]), "+f"(d[122]), "+f"(d[123]), "+f"(d[124]), "+f"(d[125]), "+f"(d[126]), "+f"(d[127])
    : "r"(da), "r"(db), "r"(scale_d));
}

namespace {

constexpr int SEQ = 2048, DM = 1024, FF = 3584;
constexpr int NCTA = 128;

constexpr uint32_t STG_OFF = 196608;
constexpr uint32_t MISC_OFF = STG_OFF + 32768;
constexpr uint32_t SMEM_BYTES = MISC_OFF + 3072;
constexpr uint32_t RED_OFF = 2 * 49152;
constexpr uint32_t MODB_OFF = MISC_OFF + 512;

enum { B_FQ = 0, B_EQ = 4, B_FW = 8, B_EW = 14, B_FG = 20, B_EG = 24, B_FD = 28, B_ED = 34,
       B_STGF = 40, B_MODB = 42, B_MODA = 45, B_RDY = 46, B_STGE = 58, B_COUNT = 60 };
enum { C_H = 0, C_O = 1, C_H2 = 3, C_ACT = 4, C_HA = 8, C_H2A = 9, C_A0 = 10, C_SP = 12 };

struct Params {
  CUtensorMap h, o_ld, o_st, h2, act, out, wqkv, wqkv32, wo, wg, wu, wd, act_st, h2_st, wm;
  const bf16* x;
  const bf16* c;
  const bf16* wmod;
  uint4* modll;
  uint4* halo;
  uint2* stats1;
  uint2* stats2;
  unsigned* cnt;
  unsigned* epoch;
  uint8_t slot[64];
};

__device__ __align__(1024) bf16 g_h[SEQ * DM];
__device__ __align__(1024) bf16 g_o[SEQ * DM];
__device__ __align__(1024) bf16 g_act[SEQ * FF];
__device__ __align__(1024) uint4 g_modll[3072 / 2];
__device__ __align__(1024) uint4 g_halo[16 * 8 * 2 * 2 * 8 * 32];
__device__ __align__(1024) uint2 g_stats[2 * SEQ * 8];
__device__ __align__(1024) unsigned g_cnt[16 * 32];
__device__ uint4 g_epoch;
#define TR(off)

__device__ __forceinline__ uint32_t smem_u32(const void* p) { return (uint32_t)__cvta_generic_to_shared(p); }
__device__ __forceinline__ void mbar_init(uint32_t bar, uint32_t count) {
  asm volatile("mbarrier.init.shared::cta.b64 [%0], %1;" ::"r"(bar), "r"(count));
}
__device__ __forceinline__ void mbar_arrive(uint32_t bar) {
  asm volatile("mbarrier.arrive.shared::cta.b64 _, [%0];" ::"r"(bar) : "memory");
}
__device__ __forceinline__ void mbar_arrive_cluster(uint32_t cluster_addr) {
  asm volatile("mbarrier.arrive.shared::cluster.b64 _, [%0];" ::"r"(cluster_addr) : "memory");
}
__device__ __forceinline__ uint32_t mapa(uint32_t addr, uint32_t cta) {
  uint32_t r;
  asm volatile("mapa.shared::cluster.u32 %0, %1, %2;" : "=r"(r) : "r"(addr), "r"(cta));
  return r;
}
__device__ __forceinline__ void mbar_wait(uint32_t bar, uint32_t parity) {
  asm volatile(
      "{\n.reg .pred p;\n"
      "WAIT_%=:\n"
      "mbarrier.try_wait.parity.shared::cta.b64 p, [%0], %1;\n"
      "@!p bra WAIT_%=;\n}\n" ::"r"(bar), "r"(parity) : "memory");
}
__device__ __forceinline__ void mbar_wait_watchdog(uint32_t bar, uint32_t parity) {
  asm volatile(
      "{\n.reg .pred p;\n.reg .u64 t0, t1;\nmov.u64 t0, %%globaltimer;\n"
      "WAIT_%=:\n"
      "mbarrier.try_wait.parity.shared::cta.b64 p, [%0], %1;\n"
      "@p bra DONE_%=;\n"
      "mov.u64 t1, %%globaltimer;\n"
      "sub.u64 t1, t1, t0;\n"
      "setp.lt.u64 p, t1, 2000000000;\n"
      "@p bra WAIT_%=;\n"
      "trap;\n"
      "DONE_%=:\n}\n" ::"r"(bar), "r"(parity) : "memory");
}
__device__ __forceinline__ void cnt_wait(const unsigned* p, unsigned target) {
  asm volatile(
      "{\n.reg .pred p;\n.reg .u32 v;\n.reg .s32 d;\n"
      "WAIT_%=:\n"
      "ld.relaxed.gpu.global.u32 v, [%0];\n"
      "sub.s32 d, v, %1;\n"
      "setp.lt.s32 p, d, 0;\n"
      "@p bra WAIT_%=;\n"
      "fence.proxy.async.global;\n"
      "}\n" ::"l"(p), "r"(target) : "memory");
}
__device__ __forceinline__ void cnt_wait_lazy(const unsigned* p, unsigned target) {
  asm volatile(
      "{\n.reg .pred p;\n.reg .u32 v;\n.reg .s32 d;\n"
      "WAIT_%=:\n"
      "nanosleep.u32 400;\n"
      "ld.relaxed.gpu.global.u32 v, [%0];\n"
      "sub.s32 d, v, %1;\n"
      "setp.lt.s32 p, d, 0;\n"
      "@p bra WAIT_%=;\n"
      "fence.proxy.async.global;\n"
      "}\n" ::"l"(p), "r"(target) : "memory");
}
__device__ __forceinline__ void cnt_signal(unsigned* p) {
  asm volatile("{\n.reg .pred p;\nelect.sync _|p, 0xffffffff;\n@p red.relaxed.gpu.global.add.u32 [%0], 1;\n}\n" ::"l"(p) : "memory");
}
__device__ __forceinline__ void ll_store(uint4* p, uint32_t a, uint32_t b, uint32_t tag) {
  asm volatile("st.relaxed.gpu.global.v2.b64 [%0], {%1, %2};" ::"l"(p), "l"((uint64_t)a | ((uint64_t)tag << 32)),
               "l"((uint64_t)b | ((uint64_t)tag << 32)) : "memory");
}
__device__ __forceinline__ uint4 ll_peek(const uint4* p) {
  uint4 v;
  asm volatile("ld.relaxed.gpu.global.v4.u32 {%0, %1, %2, %3}, [%4];" : "=r"(v.x), "=r"(v.y), "=r"(v.z), "=r"(v.w) : "l"(p) : "memory");
  return v;
}
template <int N, int SLEEP = 0, class F>
__device__ __forceinline__ void ll_poll(F addr, uint32_t tag, uint32_t (&out)[2 * N]) {
  for (;;) {
    uint4 v[N];
#pragma unroll
    for (int i = 0; i < N; i++) v[i] = ll_peek(addr(i));
    uint32_t bad = 0;
#pragma unroll
    for (int i = 0; i < N; i++) {
      bad |= (v[i].y ^ tag) | (v[i].w ^ tag);
      out[2 * i] = v[i].x;
      out[2 * i + 1] = v[i].z;
    }
    if (__all_sync(~0u, bad == 0)) break;
    if (SLEEP) __nanosleep(SLEEP);
  }
}
constexpr uint64_t POLICY_EVICT_FIRST = 0x12F0000000000000ull;
__device__ __forceinline__ void expect_tx_elect(uint32_t bar, uint32_t bytes) {
  asm volatile("{\n.reg .pred p;\nelect.sync _|p, 0xffffffff;\n@p mbarrier.arrive.expect_tx.shared::cta.b64 _, [%0], %1;\n}\n" ::"r"(bar), "r"(bytes) : "memory");
}
__device__ __forceinline__ void arrive_elect(uint32_t bar) {
  asm volatile("{\n.reg .pred p;\nelect.sync _|p, 0xffffffff;\n@p mbarrier.arrive.shared::cta.b64 _, [%0];\n}\n" ::"r"(bar) : "memory");
}
__device__ __forceinline__ void tma_load(uint32_t dst, const CUtensorMap* m, uint32_t bar, int c0, int c1) {
  asm volatile("{\n.reg .pred p;\nelect.sync _|p, 0xffffffff;\n"
               "@p cp.async.bulk.tensor.2d.shared::cluster.global.mbarrier::complete_tx::bytes [%0], [%1, {%3, %4}], [%2];\n}\n"
               ::"r"(dst), "l"(m), "r"(bar), "r"(c0), "r"(c1) : "memory");
}
__device__ __forceinline__ void tma_load_mc(uint32_t dst, const CUtensorMap* m, uint32_t bar, int c0, int c1) {
  asm volatile("{\n.reg .pred p;\nelect.sync _|p, 0xffffffff;\n"
               "@p cp.async.bulk.tensor.2d.shared::cluster.global.mbarrier::complete_tx::bytes.multicast::cluster.L2::cache_hint [%0], [%1, {%3, %4}], [%2], %5, %6;\n}\n"
               ::"r"(dst), "l"(m), "r"(bar), "r"(c0), "r"(c1), "h"((uint16_t)3), "l"(POLICY_EVICT_FIRST) : "memory");
}
__device__ __forceinline__ void tma_load_ef(uint32_t dst, const CUtensorMap* m, uint32_t bar, int c0, int c1) {
  asm volatile("{\n.reg .pred p;\nelect.sync _|p, 0xffffffff;\n"
               "@p cp.async.bulk.tensor.2d.shared::cluster.global.mbarrier::complete_tx::bytes.L2::cache_hint [%0], [%1, {%3, %4}], [%2], %5;\n}\n"
               ::"r"(dst), "l"(m), "r"(bar), "r"(c0), "r"(c1), "l"(POLICY_EVICT_FIRST) : "memory");
}
__device__ __forceinline__ void tma_store2(const CUtensorMap* m, uint32_t src, int c0, int c1) {
  asm volatile("{\n.reg .pred p;\nelect.sync _|p, 0xffffffff;\n"
               "@p cp.async.bulk.tensor.2d.global.shared::cta.bulk_group [%0, {%2, %3}], [%1];\n}\n"
               ::"l"(m), "r"(src), "r"(c0), "r"(c1) : "memory");
}
__device__ __forceinline__ void tma_store3(const CUtensorMap* m, uint32_t src, int c0, int c1, int c2) {
  asm volatile("{\n.reg .pred p;\nelect.sync _|p, 0xffffffff;\n"
               "@p cp.async.bulk.tensor.3d.global.shared::cta.bulk_group [%0, {%2, %3, %4}], [%1];\n}\n"
               ::"l"(m), "r"(src), "r"(c0), "r"(c1), "r"(c2) : "memory");
}
__device__ __forceinline__ void tma_add3(const CUtensorMap* m, uint32_t src, int c0, int c1, int c2) {
  asm volatile("{\n.reg .pred p;\nelect.sync _|p, 0xffffffff;\n"
               "@p cp.reduce.async.bulk.tensor.3d.global.shared::cta.add.bulk_group [%0, {%2, %3, %4}], [%1];\n}\n"
               ::"l"(m), "r"(src), "r"(c0), "r"(c1), "r"(c2) : "memory");
}
__device__ __forceinline__ void store_pause(bool sleep) {
  asm volatile("cp.async.bulk.commit_group;" ::: "memory");
  asm volatile("cp.async.bulk.wait_group.read 0;" ::: "memory");
  if (sleep) __nanosleep(PAUSE);
}
__device__ __forceinline__ void l2_prefetch_tile(const CUtensorMap* m, int c0, int c1) {
  asm volatile("{\n.reg .pred p;\nelect.sync _|p, 0xffffffff;\n@p cp.async.bulk.prefetch.tensor.2d.L2.global [%0, {%1, %2}];\n}\n"
               ::"l"(m), "r"(c0), "r"(c1) : "memory");
}
__device__ __forceinline__ void prefetch_map(const CUtensorMap* m) {
  asm volatile("prefetch.tensormap [%0];" ::"l"(m) : "memory");
}
__device__ __forceinline__ void wg_fence() { asm volatile("wgmma.fence.sync.aligned;" ::: "memory"); }
__device__ __forceinline__ void wg_commit() { asm volatile("wgmma.commit_group.sync.aligned;" ::: "memory"); }
template <int N>
__device__ __forceinline__ void wg_wait() { asm volatile("wgmma.wait_group.sync.aligned %0;" ::"n"(N) : "memory"); }
__device__ __forceinline__ void bar_sync(int id, int n) { asm volatile("bar.sync %0, %1;" ::"r"(id), "r"(n) : "memory"); }
__device__ __forceinline__ void wg_bar(int cw) {
  asm volatile("{\n.reg .pred p;\nsetp.ne.s32 p, %0, 0;\n@p bar.sync 3, 128;\n@!p bar.sync 2, 128;\n}\n" ::"r"(cw) : "memory");
}
__device__ __forceinline__ void cluster_arrive_relaxed() { asm volatile("barrier.cluster.arrive.relaxed.aligned;" ::: "memory"); }
__device__ __forceinline__ void cluster_wait() { asm volatile("barrier.cluster.wait.acquire.aligned;" ::: "memory"); }
__device__ __forceinline__ uint32_t load_epoch(const unsigned* p) {
  uint32_t e;
  asm volatile("ld.relaxed.gpu.global.u32 %0, [%1];" : "=r"(e) : "l"(p) : "memory");
  return e;
}
__device__ __forceinline__ uint32_t pack2(float lo, float hi) {
  uint32_t r;
  asm("cvt.rn.bf16x2.f32 %0, %1, %2;" : "=r"(r) : "f"(hi), "f"(lo));
  return r;
}
__device__ __forceinline__ float bf_lo(uint32_t v) { return __uint_as_float(v << 16); }
__device__ __forceinline__ float bf_hi(uint32_t v) { return __uint_as_float(v & 0xffff0000u); }
__device__ __forceinline__ uint32_t fma_bf2(uint32_t a, uint32_t b, uint32_t c) {
  uint32_t d;
  asm("fma.rn.bf16x2 %0, %1, %2, %3;" : "=r"(d) : "r"(a), "r"(b), "r"(c));
  return d;
}
__device__ __forceinline__ float bf_round(float v) { return __bfloat162float(__float2bfloat16_rn(v)); }
__device__ __forceinline__ float silu_f(float v) { return __fdividef(v, 1.0f + __expf(-v)); }
__device__ __forceinline__ uint4 ldg_nc(const void* p) {
  uint4 v;
  asm volatile("ld.global.nc.L1::no_allocate.v4.u32 {%0, %1, %2, %3}, [%4];" : "=r"(v.x), "=r"(v.y), "=r"(v.z), "=r"(v.w) : "l"(p));
  return v;
}
__device__ __forceinline__ void stmatrix4(uint32_t addr, uint32_t a, uint32_t b, uint32_t c, uint32_t d) {
  asm volatile("stmatrix.sync.aligned.m8n8.x4.shared.b16 [%0], {%1, %2, %3, %4};" ::"r"(addr), "r"(a), "r"(b), "r"(c), "r"(d) : "memory");
}
__device__ __forceinline__ void stmatrix2(uint32_t addr, uint32_t a, uint32_t b) {
  asm volatile("stmatrix.sync.aligned.m8n8.x2.shared.b16 [%0], {%1, %2};" ::"r"(addr), "r"(a), "r"(b) : "memory");
}
__device__ __forceinline__ void stmatrix1(uint32_t addr, uint32_t a) {
  asm volatile("stmatrix.sync.aligned.m8n8.x1.shared.b16 [%0], {%1};" ::"r"(addr), "r"(a) : "memory");
}
__device__ __forceinline__ uint32_t movmatrix(uint32_t a) {
  uint32_t d;
  asm("movmatrix.sync.aligned.m8n8.trans.b16 %0, %1;" : "=r"(d) : "r"(a));
  return d;
}
__device__ __forceinline__ void mma16816(float (&d)[4], uint32_t a0, uint32_t a1, uint32_t a2, uint32_t a3, uint32_t b0, uint32_t b1) {
  asm("mma.sync.aligned.m16n8k16.row.col.f32.bf16.bf16.f32 {%0, %1, %2, %3}, {%4, %5, %6, %7}, {%8, %9}, {%0, %1, %2, %3};"
               : "+f"(d[0]), "+f"(d[1]), "+f"(d[2]), "+f"(d[3]) : "r"(a0), "r"(a1), "r"(a2), "r"(a3), "r"(b0), "r"(b1));
}
__device__ __forceinline__ void mma1688(float (&d)[4], uint32_t a0, uint32_t a1, uint32_t b0) {
  asm("mma.sync.aligned.m16n8k8.row.col.f32.bf16.bf16.f32 {%0, %1, %2, %3}, {%4, %5}, {%6}, {%0, %1, %2, %3};"
               : "+f"(d[0]), "+f"(d[1]), "+f"(d[2]), "+f"(d[3]) : "r"(a0), "r"(a1), "r"(b0));
}
__device__ __forceinline__ void ldmatrix4t(uint32_t (&b)[4], uint32_t addr) {
  asm volatile("ldmatrix.sync.aligned.m8n8.x4.trans.shared.b16 {%0, %1, %2, %3}, [%4];" : "=r"(b[0]), "=r"(b[1]), "=r"(b[2]), "=r"(b[3]) : "r"(addr) : "memory");
}
__device__ __forceinline__ void ldmatrix4(uint32_t& a, uint32_t& b, uint32_t& c, uint32_t& d, uint32_t addr) {
  asm volatile("ldmatrix.sync.aligned.m8n8.x4.shared.b16 {%0, %1, %2, %3}, [%4];" : "=r"(a), "=r"(b), "=r"(c), "=r"(d) : "r"(addr) : "memory");
}
__device__ __forceinline__ void cp_async16(uint32_t dst, const void* src) {
  asm volatile("cp.async.cg.shared.global.L2::cache_hint [%0], [%1], 16, %2;" ::"r"(dst), "l"(src), "l"(POLICY_EVICT_FIRST) : "memory");
}
__device__ __forceinline__ uint32_t lds32(uint32_t addr) {
  uint32_t v;
  asm volatile("ld.shared.u32 %0, [%1];" : "=r"(v) : "r"(addr) : "memory");
  return v;
}
__device__ __forceinline__ void sts64f(uint32_t addr, float a, float b) {
  asm volatile("st.shared.v2.f32 [%0], {%1, %2};" ::"r"(addr), "f"(a), "f"(b) : "memory");
}
constexpr float QK_SCALE = 0.17677669529663687f;
__device__ __forceinline__ float softmax8(float& p0, float& p1) {
  float m = fmaxf(p0, p1);
  m = fmaxf(m, __shfl_xor_sync(~0u, m, 1));
  m = fmaxf(m, __shfl_xor_sync(~0u, m, 2));
  asm("ex2.approx.ftz.f32 %0, %1;" : "=f"(p0) : "f"((p0 - m) * 1.4426950408889634f));
  asm("ex2.approx.ftz.f32 %0, %1;" : "=f"(p1) : "f"((p1 - m) * 1.4426950408889634f));
  float s = p0 + p1;
  s += __shfl_xor_sync(~0u, s, 1);
  s += __shfl_xor_sync(~0u, s, 2);
  float r;
  asm("rcp.approx.ftz.f32 %0, %1;" : "=f"(r) : "f"(s));
  return r;
}
__device__ __forceinline__ void sts128(uint32_t addr, uint32_t a, uint32_t b, uint32_t c, uint32_t d) {
  asm volatile("st.shared.v4.u32 [%0], {%1, %2, %3, %4};" ::"r"(addr), "r"(a), "r"(b), "r"(c), "r"(d) : "memory");
}
__device__ __forceinline__ uint4 lds128(uint32_t addr) {
  uint4 v;
  asm volatile("ld.shared.v4.u32 {%0, %1, %2, %3}, [%4];" : "=r"(v.x), "=r"(v.y), "=r"(v.z), "=r"(v.w) : "r"(addr) : "memory");
  return v;
}
__device__ __forceinline__ float2 lds64f(uint32_t addr) {
  float2 v;
  asm volatile("ld.shared.v2.f32 {%0, %1}, [%2];" : "=f"(v.x), "=f"(v.y) : "r"(addr) : "memory");
  return v;
}
#define PROF_AT(cond, slot) do {} while (0)

constexpr uint32_t SMEM_BASE = 1024;
constexpr uint32_t DESC_A = (1u << 16) | (SMEM_BASE >> 4);
constexpr uint32_t DESC_B = ((8192u >> 4) << 16) | (SMEM_BASE >> 4);

template <int BN> struct Wg;
template <> struct Wg<128> { static __device__ __forceinline__ void mma(float (&d)[64], uint32_t a, uint32_t b, int s) { wgmma_ss_n128(d, a, b, s); } };
template <> struct Wg<192> { static __device__ __forceinline__ void mma(float (&d)[96], uint32_t a, uint32_t b, int s) { wgmma_ss_n192(d, a, b, s); } };
template <> struct Wg<256> { static __device__ __forceinline__ void mma(float (&d)[128], uint32_t a, uint32_t b, int s) { wgmma_ss_n256(d, a, b, s); } };

struct Ring {
  uint32_t full0, rel0;
  int s;
  uint32_t ph;
  uint32_t off;
  bool releaser;
};

template <int N>
__device__ __forceinline__ void fence_regs(float (&a)[N]) {
#pragma unroll
  for (int i = 0; i < N; i++) asm volatile("" : "+f"(a[i])::"memory");
}

template <int BN, int NST, uint32_t STAGE>
__device__ __forceinline__ void kblock(float (&acc)[BN / 2], Ring& g, uint32_t a_addr, bool zero, uint32_t& prev, uint32_t b_rel = 16384) {
  mbar_wait(g.full0 + 8 * g.s, g.ph);
  const uint32_t da = DESC_A + (a_addr >> 4);
  const uint32_t db = DESC_B + ((g.off + b_rel) >> 4);
  wg_fence();
#pragma unroll
  for (int k = 0; k < 4; k++) Wg<BN>::mma(acc, da + k * 2, db + k * 128, !(zero && k == 0));
  wg_commit();
  wg_wait<1>();
  if (prev != 0) mbar_arrive_cluster(prev);
  prev = g.releaser ? g.rel0 + 8 * g.s : 0u;
  if (++g.s == NST) { g.s = 0; g.ph ^= 1; }
  g.off += STAGE;
  if (g.off == NST * STAGE) g.off = 0;
}
template <int N>
__device__ __forceinline__ void tile_end(float (&acc)[N], uint32_t& prev) {
  wg_wait<0>();
  if (prev != 0) mbar_arrive_cluster(prev);
  prev = 0;
  fence_regs(acc);
}

__device__ __forceinline__ int other_kb(int q, int j) {
  const int ch = q >= 7, jj = q - 7 * ch;
  return 2 * (jj < j ? jj : jj + 1) + ch;
}
__device__ __forceinline__ int qkv_kb(int it, int j) {
  return it < 4 ? 2 * j + (it & 1) : other_kb(it < 18 ? it - 4 : it - 18, j);
}
__device__ __forceinline__ int wo_k(int it, int j) {
  return it < 8 ? it * 128 : (it == 8 ? j : (it - 9 < j ? it - 9 : it - 8)) * 128 + 64;
}
__device__ __forceinline__ int down_k(int d) {
  const int u = d + KH;
  if (u < 8) return u * 448 + 384;
  if (u < 40) return (((u - 8) & 15) >> 1) * 448 + ((u - 8) >> 4) * 128 + (u & 1) * 64;
  return (u & 7) * 448 + 256 + (u >= 48 ? 64 : 0);
}
__device__ __forceinline__ void wait_q_free(uint32_t empty, int i) {
  mbar_wait(empty + 8 * ((i * 2) / 3), 1);
  mbar_wait(empty + 8 * ((i * 2 + 1) / 3), 1);
}
__device__ __forceinline__ void wait_w_free(uint32_t empty, int i) {
  const int t = (i + 3) & 3, w0 = (t * 3) / 2, w1 = (t * 3 + 2) / 2;
  mbar_wait(empty + 8 * w0, w0 < 4);
  mbar_wait(empty + 8 * w1, w1 < 4);
}
__device__ __forceinline__ void wait_g_free(uint32_t empty, int i) {
  const int s = i < 4 ? i + 2 : i - 4, b0 = ((s * 2) / 3 + 1) & 3, b1 = ((s * 2 + 1) / 3 + 1) & 3;
  mbar_wait(empty + 8 * b0, b0 < 2);
  mbar_wait(empty + 8 * b1, b1 < 2);
}

__device__ __forceinline__ void chan(float& m, float& q, float m2, float q2, float n) {
  const float d = m2 - m;
  m = 0.5f * (m + m2);
  q = q + q2 + d * d * (0.5f * n);
}

__device__ __forceinline__ uint32_t tag16(uint32_t tag) { return tag % 65535u + 1u; }
__device__ __forceinline__ void stat_store(uint2* slot, float m, float q, uint32_t t16) {
  const uint32_t a = ((__float_as_uint(m) + 0x80u) & 0xffffff00u) | (t16 & 0xffu), b = ((__float_as_uint(q) + 0x80u) & 0xffffff00u) | (t16 >> 8);
  asm volatile("st.relaxed.gpu.global.b64 [%0], %1;" ::"l"(slot), "l"((uint64_t)a | ((uint64_t)b << 32)) : "memory");
}
__device__ __forceinline__ void stat_gather(const uint2* rows, uint32_t t16, int lane, float (&rs)[2], float (&nb)[2]) {
  const uint4* sp = (const uint4*)(rows + (lane >> 3) * 128) + (lane & 7);
  const uint32_t want = (t16 & 0xffu) | ((t16 >> 8) << 8);
  uint4 a, b;
  for (;;) {
    a = ll_peek(sp);
    b = ll_peek(sp + 256);
    const uint32_t bad = (__byte_perm(a.x, a.y, 0x40) ^ want) | (__byte_perm(a.z, a.w, 0x40) ^ want) | (__byte_perm(b.x, b.y, 0x40) ^ want) |
                         (__byte_perm(b.z, b.w, 0x40) ^ want);
    if (__all_sync(~0u, (bad & 0xffffu) == 0)) break;
  }
  float m0 = __uint_as_float(a.x & 0xffffff00u), q0 = __uint_as_float(a.y & 0xffffff00u);
  float m1 = __uint_as_float(a.z & 0xffffff00u), q1 = __uint_as_float(a.w & 0xffffff00u);
  chan(m0, q0, __uint_as_float(b.x & 0xffffff00u), __uint_as_float(b.y & 0xffffff00u), 128.f);
  chan(m1, q1, __uint_as_float(b.z & 0xffffff00u), __uint_as_float(b.w & 0xffffff00u), 128.f);
  const bool hi = lane & 8;
  float m = hi ? m1 : m0, q = hi ? q1 : q0;
  chan(m, q, __shfl_xor_sync(~0u, hi ? m0 : m1, 8), __shfl_xor_sync(~0u, hi ? q0 : q1, 8), 256.f);
  chan(m, q, __shfl_xor_sync(~0u, m, 16), __shfl_xor_sync(~0u, q, 16), 512.f);
  const float rstd = rsqrtf(q * (1.0f / DM) + 1e-5f), nmr = -m * rstd;
  const int r = lane >> 2, src = (r >> 1) + (r & 1) * 8;
  rs[0] = __shfl_sync(~0u, rstd, src); nb[0] = __shfl_sync(~0u, nmr, src);
  rs[1] = __shfl_sync(~0u, rstd, src + 4); nb[1] = __shfl_sync(~0u, nmr, src + 4);
}

__device__ __forceinline__ void publish_stats(const uint32_t (&xl)[16], const uint32_t (&xh)[16], uint2* slot, int lane, uint32_t t16) {
  float ds[4] = {0.f, 0.f, 0.f, 0.f}, dl[4] = {0.f, 0.f, 0.f, 0.f}, dh[4] = {0.f, 0.f, 0.f, 0.f};
#pragma unroll
  for (int q = 0; q < 8; q++) {
    mma16816(ds, xl[2 * q], xh[2 * q], xl[2 * q + 1], xh[2 * q + 1], 0x3f803f80u, 0x3f803f80u);
    mma16816(dl, xl[2 * q], xh[2 * q], xl[2 * q + 1], xh[2 * q + 1], xl[2 * q], xl[2 * q + 1]);
    mma16816(dh, xl[2 * q], xh[2 * q], xl[2 * q + 1], xh[2 * q + 1], xh[2 * q], xh[2 * q + 1]);
  }
  const int r = lane >> 2;
  if ((lane & 3) == (r >> 1)) {
    const float ml = ds[0] * (1.0f / 128), mh = ds[2] * (1.0f / 128);
    const float ql = fmaxf(((r & 1) ? dl[1] : dl[0]) - ds[0] * ml, 0.f), qh = fmaxf(((r & 1) ? dh[3] : dh[2]) - ds[2] * mh, 0.f);
    stat_store(slot + r, ml, ql, t16);
    stat_store(slot + r + 8, mh, qh, t16);
  }
  __syncwarp();
}

__device__ __forceinline__ void stage_slab(uint32_t chunk, int warp, int lane, const uint32_t (&lo)[8], const uint32_t (&hi)[8]) {
  const int row = warp * 16 + (lane & 7) + ((lane >> 3) & 1) * 8;
  const uint32_t rbase = chunk + row * 128;
#pragma unroll
  for (int q = 0; q < 4; q++) {
    const int grp = 2 * q + (lane >> 4);
    stmatrix4(rbase + ((grp ^ (row & 7)) << 4), lo[2 * q], hi[2 * q], lo[2 * q + 1], hi[2 * q + 1]);
  }
}
__device__ __forceinline__ float silu_mul(float g, float u) {
  float e, r;
  asm("ex2.approx.ftz.f32 %0, %1;" : "=f"(e) : "f"(g * -1.4426950408889634f));
  asm("rcp.approx.ftz.f32 %0, %1;" : "=f"(r) : "f"(1.0f + e));
  return g * r * u;
}
__device__ __forceinline__ uint32_t swiglu2(uint32_t g2, uint32_t u2) {
  asm volatile("" : "+r"(g2));
  return pack2(silu_mul(bf_lo(g2), bf_lo(u2)), silu_mul(bf_hi(g2), bf_hi(u2)));
}
__device__ __forceinline__ void stage_done(uint32_t bar, int lane) {
  asm volatile("fence.proxy.async.shared::cta;" ::: "memory");
  __syncwarp();
  if (lane == 0) mbar_arrive(bar);
}

__device__ __forceinline__ int fresh_tid() {
  int t;
  asm volatile("mov.u32 %0, %%tid.x;" : "=r"(t));
  return t;
}
#define RING_IDS()                                                                                           \
  const int tid = fresh_tid() - 128;                                                                         \
  const int cw = __shfl_sync(~0u, tid >> 7, 0), warp = __shfl_sync(~0u, (tid >> 5) & 3, 0);                  \
  const bool releaser = (tid & 31) < 2;                                                                      \
  const uint32_t rbars = mapa(bars, tid & 1);                                                                \
  const uint32_t a_base = cw * 8192
#define LANE_IDS()                                                                                           \
  const int lane = fresh_tid() & 31, r = lane >> 2, c = lane & 3;                                            \
  const int srow = warp * 16 + (lane & 7) + ((lane >> 3) & 1) * 8;                                           \
  const uint32_t slab = stg + cw * 8192 + srow * 128, sw0 = (lane >> 4) ^ (srow & 7);                        \
  (void)r; (void)c; (void)slab; (void)sw0

template <int NPRE, bool EAGER, class Step>
__device__ __forceinline__ void attention(float (&acc)[96], const Params& p, int rho, int rb, int cta, int cw, int warp, uint32_t tag,
                                          uint32_t stg, uint32_t bars, uint32_t& prev, Step step) {
  uint32_t ql[8], qh[8], k0[8], k1[8], v0[8], v1[8], hp[16];
  if (EAGER) {
    tile_end(acc, prev);
  } else {
    step();
    fence_regs(acc);
  }
#pragma unroll
  for (int t = 0; t < 8; t++) {
    k0[t] = pack2(acc[4 * (8 + t)], acc[4 * (8 + t) + 1]);
    k1[t] = pack2(acc[4 * (8 + t) + 2], acc[4 * (8 + t) + 3]);
    v0[t] = pack2(acc[4 * (16 + t)], acc[4 * (16 + t) + 1]);
    v1[t] = pack2(acc[4 * (16 + t) + 2], acc[4 * (16 + t) + 3]);
    asm volatile("" : "+r"(k0[t]), "+r"(k1[t]), "+r"(v0[t]), "+r"(v1[t]));
  }
  const int lane = fresh_tid() & 31, r = lane >> 2, c = lane & 3;
#pragma unroll
  for (int t = 0; t < 8; t++) v1[t] = movmatrix(v1[t]);
  mbar_wait(bars + 8 * B_STGE, rho);
  mbar_wait(bars + 8 * (B_STGE + 1), 0);
  const uint32_t xch = stg + 16384 + (cw * 4 + warp) * 2048 + lane * 16;
  if (warp < 3) {
    sts128(xch, k1[0], k1[1], k1[2], k1[3]);
    sts128(xch + 512, k1[4], k1[5], k1[6], k1[7]);
    sts128(xch + 1024, v1[0], v1[1], v1[2], v1[3]);
    sts128(xch + 1536, v1[4], v1[5], v1[6], v1[7]);
  } else if (rb < 15) {
    uint4* dst = p.halo + ((cta * 2 + rho) * 2 + cw) * 256 + lane;
#pragma unroll
    for (int t = 0; t < 4; t++) {
      ll_store(dst + t * 32, k1[2 * t], k1[2 * t + 1], tag);
      ll_store(dst + (4 + t) * 32, v1[2 * t], v1[2 * t + 1], tag);
    }
  }
#pragma unroll
  for (int t = 0; t < 8; t++) {
    v0[t] = movmatrix(v0[t]);
    ql[t] = pack2(acc[4 * t], acc[4 * t + 1]);
    qh[t] = pack2(acc[4 * t + 2], acc[4 * t + 3]);
    asm volatile("" : "+r"(v0[t]), "+r"(ql[t]), "+r"(qh[t]));
  }
#pragma unroll 1
  for (int i = 0; i < NPRE; i++) step();
  const uint4* src = p.halo + (((cta - 8) * 2 + rho) * 2 + cw) * 256 + lane;
  uint4 early[8] = {};
  if (warp == 0 && rb > 0) {
#pragma unroll
    for (int i = 0; i < 8; i++) early[i] = ll_peek(src + i * 32);
  }
  step();
  wg_bar(cw);
  if (warp > 0) {
#pragma unroll
    for (int t = 0; t < 4; t++) {
      const uint4 a = lds128(xch - 2048 + t * 512);
      hp[4 * t] = a.x; hp[4 * t + 1] = a.y; hp[4 * t + 2] = a.z; hp[4 * t + 3] = a.w;
    }
  } else if (rb > 0) {
    uint32_t bad = 0;
#pragma unroll
    for (int i = 0; i < 8; i++) {
      bad |= (early[i].y ^ tag) | (early[i].w ^ tag);
      hp[2 * i] = early[i].x;
      hp[2 * i + 1] = early[i].z;
    }
    if (!__all_sync(~0u, bad == 0)) ll_poll<8>([&](int i) { return src + i * 32; }, tag, hp);
  } else {
#pragma unroll
    for (int t = 0; t < 16; t++) hp[t] = 0;
  }
  wg_wait<0>();
  if (prev != 0) mbar_arrive_cluster(prev);
  prev = 0;
#pragma unroll
  for (int t = 0; t < 8; t++) asm volatile("" : "+r"(ql[t])::"memory");
  const bool up0 = 2 * c > r, up1 = 2 * c + 1 > r;
  const bool first = (rb == 0) && (warp == 0);
  uint32_t a0[2], a2[2], a3[2], a5[2];
  float il[2], ih[2];
#pragma unroll
  for (int h = 0; h < 2; h++) {
    float sp[4] = {0.f, 0.f, 0.f, 0.f}, s0[4] = {0.f, 0.f, 0.f, 0.f}, s1[4] = {0.f, 0.f, 0.f, 0.f};
#pragma unroll
    for (int ks = 0; ks < 2; ks++) {
      const int t = 4 * h + 2 * ks;
      mma16816(sp, ql[t], qh[t], ql[t + 1], qh[t + 1], hp[t], hp[t + 1]);
      mma16816(s0, ql[t], qh[t], ql[t + 1], qh[t + 1], k0[t], k0[t + 1]);
      mma16816(s1, ql[t], qh[t], ql[t + 1], qh[t + 1], k1[t], k1[t + 1]);
    }
    float p0 = (up0 ? sp[0] : s0[0]) * QK_SCALE, p1 = (up1 ? sp[1] : s0[1]) * QK_SCALE;
    float p2 = (up0 ? s0[2] : s1[2]) * QK_SCALE, p3 = (up1 ? s0[3] : s1[3]) * QK_SCALE;
    if (first && up0) p0 = -1000000000.0f;
    if (first && up1) p1 = -1000000000.0f;
    il[h] = softmax8(p0, p1);
    ih[h] = softmax8(p2, p3);
    a0[h] = pack2(up0 ? p0 : 0.f, up1 ? p1 : 0.f);
    a2[h] = pack2(up0 ? 0.f : p0, up1 ? 0.f : p1);
    a3[h] = pack2(up0 ? p2 : 0.f, up1 ? p3 : 0.f);
    a5[h] = pack2(up0 ? 0.f : p2, up1 ? 0.f : p3);
  }
  float o[8][4];
#pragma unroll
  for (int t = 0; t < 8; t++) {
#pragma unroll
    for (int q = 0; q < 4; q++) o[t][q] = 0.f;
    mma1688(o[t], 0u, a5[t >> 2], v1[t]);
    mma16816(o[t], a0[t >> 2], 0u, a2[t >> 2], a3[t >> 2], hp[8 + t], v0[t]);
  }
#pragma unroll
  for (int t = 0; t < 8; t++) fence_regs(o[t]);
  if (!EAGER) step();
  uint32_t ol[8], oh[8];
#pragma unroll
  for (int t = 0; t < 8; t++) {
    ol[t] = pack2(o[t][0] * il[t >> 2], o[t][1] * il[t >> 2]);
    oh[t] = pack2(o[t][2] * ih[t >> 2], o[t][3] * ih[t >> 2]);
  }
  if (!EAGER) step();
  stage_slab(stg + cw * 8192, warp, lane, ol, oh);
  stage_done(bars + 8 * B_STGF, lane);
  if (!EAGER) step();
}

__global__ void __launch_bounds__(384, 1) fused_kernel(const __grid_constant__ Params p) {
  extern __shared__ __align__(1024) uint8_t smem_raw[];
  const uint32_t sm = smem_u32(smem_raw);
  const uint32_t bars = sm + MISC_OFF;
  const uint32_t stg = sm + STG_OFF;
  const int rank = blockIdx.x & 1;
  const int cl = blockIdx.x >> 1;
  if (cl >= NCTA / 2) {
    const int e = blockIdx.x - NCTA, wid = __shfl_sync(~0u, (int)(threadIdx.x >> 5), 0), lane = threadIdx.x & 31;
    if (threadIdx.x == 0) {
      for (int i = 0; i < 6; i++) { mbar_init(bars + 8 * i, 1); mbar_init(bars + 8 * (6 + i), 8); }
      for (int i = 0; i < 8; i++) { mbar_init(bars + 8 * (16 + i), 1); mbar_init(bars + 8 * (24 + i), 4); }
      mbar_init(bars + 8 * 12, 1);
      asm volatile("fence.mbarrier_init.release.cluster;" ::: "memory");
    }
    const uint32_t tag = load_epoch(p.epoch) + 1;
    if (threadIdx.x < 256) ll_store(p.modll + 512 + (threadIdx.x >> 6) * 256 + e * 64 + (threadIdx.x & 63), 0u, 0u, 0u);
    for (int i = threadIdx.x; i < 1536; i += 384) {
      uint4 o = make_uint4(0u, 0u, 0u, 0u);
      if (i < 1024 && (i & 63) < 8) {
        const uint4 cv = ldg_nc(p.c + (i >> 6) * 64 + (i & 7) * 8);
        o = make_uint4(pack2(silu_f(bf_lo(cv.x)), silu_f(bf_hi(cv.x))), pack2(silu_f(bf_lo(cv.y)), silu_f(bf_hi(cv.y))),
                       pack2(silu_f(bf_lo(cv.z)), silu_f(bf_hi(cv.z))), pack2(silu_f(bf_lo(cv.w)), silu_f(bf_hi(cv.w))));
      }
      sts128(stg + i * 16, o.x, o.y, o.z, o.w);
    }
    asm volatile("fence.proxy.async.shared::cta;" ::: "memory");
    __syncthreads();
    if (wid == 0) {
      __nanosleep(WMDELAY);
      uint32_t ph = 1;
#pragma unroll 1
      for (int it = 0, s = 0; it < 64; it++) {
        mbar_wait(bars + 8 * (6 + s), ph);
        expect_tx_elect(bars + 8 * s, 32768);
#pragma unroll
        for (int q = 0; q < 4; q++) tma_load_ef(sm + s * 32768 + q * 8192, &p.wm, bars + 8 * s, 2048 + (it >> 4) * 1024 + e * 256 + q * 64, (it & 15) * 64);
        if (++s == 6) { s = 0; ph ^= 1; }
      }
    } else if (wid == 1 && PFW) {
      __nanosleep(PFW);
#pragma unroll 1
      for (int i = 0; i < 64; i++) {
        l2_prefetch_tile(&p.wo, (i & 15) * 64, (e * 4 + (i >> 4)) * 64);
        if (PFP) __nanosleep(PFP);
      }
#pragma unroll 1
      for (int i = 0; i < 80; i++) {
        if (i < 64) l2_prefetch_tile((i & 1) ? &p.wu : &p.wg, ((i >> 1) & 7) * 448 + 384, ((i >> 4) * 4 + e) * 64);
        else l2_prefetch_tile((i & 2) ? &p.wu : &p.wg, (e * 2 + ((i >> 3) & 1)) * 448 + (i & 1) * 64, (e * 4 + ((i >> 2) & 3)) * 64);
        if (PFP) __nanosleep(PFP);
      }
    } else if (wid >= 4) {
      const int hf = (wid >> 2) - 1;
      uint32_t ph = 0;
      int s = 0;
#pragma unroll 1
      for (int v = 0; v < 4; v++) {
        float acc[64];
#pragma unroll 1
        for (int kb = 0; kb < 16; kb++) {
          mbar_wait_watchdog(bars + 8 * s, ph);
          const uint32_t da = DESC_A + ((STG_OFF + kb * 1024) >> 4), db = DESC_B + ((s * 32768 + hf * 16384) >> 4);
          wg_fence();
#pragma unroll
          for (int k = 0; k < 4; k++) wgmma_ss_n128(acc, da + k * 2, db + k * 128, (kb | k) != 0);
          wg_commit();
          wg_wait<0>();
          if (lane == 0) mbar_arrive(bars + 8 * (6 + s));
          if (++s == 6) { s = 0; ph ^= 1; }
        }
        fence_regs(acc);
        if ((wid & 3) == 0) {
#pragma unroll
          for (int n = 0; n < 16; n++) {
            const uint32_t mine = pack2(acc[4 * n], acc[4 * n + 1]), next = __shfl_down_sync(~0u, mine, 1);
            if (lane < 4 && (lane & 1) == 0) ll_store(p.modll + 512 + v * 256 + e * 64 + hf * 32 + n * 2 + (lane >> 1), mine, next, tag);
            if (lane < 4) sts64f(sm + MODB_OFF + (hf * 128 + n * 8 + lane * 2) * 4, bf_lo(mine), bf_hi(mine));
          }
        }
      }
    }
    __syncthreads();
    if (wid == 0 || wid == 2) {
      const int w = wid >> 1;
      if (w == 0) {
        expect_tx_elect(bars + 8 * 12, KH * 32768);
#pragma unroll 1
        for (int q = 0; q < 4 * KH; q++) tma_load_ef(sm + q * 8192, &p.wd, bars + 8 * 12, e * 256 + (q & 3) * 64, (q >> 2) * 448 + 384);
      }
      cnt_wait_lazy(p.cnt + C_ACT, tag * 8);
      if (w == 1) __nanosleep(HOFF);
      uint32_t ph = 1, ready = 0;
#pragma unroll 1
      for (int it = 0, s = 0; it < 16 * KH; it++) {
        const int rb = it / KH, kc = it - rb * KH;
        while (!((ready >> rb) & 1)) {
          ready = __ballot_sync(~0u, (int)(load_epoch(p.cnt + (lane & 15) * 32 + C_ACT) - tag * 8) >= 0);
          asm volatile("fence.proxy.async.global;" ::: "memory");
        }
        const uint32_t fb = bars + 8 * (16 + w * 4 + s), dst = sm + 98304 + w * 32768 + s * 8192;
        mbar_wait(fb + 64, ph);
        expect_tx_elect(fb, 8192);
        tma_load(dst, &p.act_st, fb, kc * 448 + 384, rb * 128 + w * 64);
        tma_load(dst + 4096, &p.act_st, fb, kc * 448 + 384, rb * 128 + w * 64 + 32);
        if (++s == 4) { s = 0; ph ^= 1; }
      }
    } else if (wid >= 4) {
      const int w = (wid >> 2) - 1, warp = wid & 3;
      const uint32_t out_stg = (w ? stg : sm + 163840) + warp * 2048;
      const uint32_t slab = out_stg + (lane & 15) * 128, sw0 = (lane >> 4) ^ (lane & 7);
      mbar_wait_watchdog(bars + 8 * 12, 0);
#pragma unroll 1
      for (int i = threadIdx.x - 128; i < KH * 2048; i += 256) {
        const uint32_t gp = sm + MODB_OFF + (((i >> 9) & 3) * 64 + ((i ^ (i >> 3)) & 7) * 8) * 4;
        const uint4 v = lds128(sm + i * 16), ga = lds128(gp), gc = lds128(gp + 16);
        sts128(sm + i * 16, pack2(bf_lo(v.x) * __uint_as_float(ga.x), bf_hi(v.x) * __uint_as_float(ga.y)),
               pack2(bf_lo(v.y) * __uint_as_float(ga.z), bf_hi(v.y) * __uint_as_float(ga.w)),
               pack2(bf_lo(v.z) * __uint_as_float(gc.x), bf_hi(v.z) * __uint_as_float(gc.y)),
               pack2(bf_lo(v.w) * __uint_as_float(gc.z), bf_hi(v.w) * __uint_as_float(gc.w)));
      }
      asm volatile("fence.proxy.async.shared::cta;" ::: "memory");
      bar_sync(1, 256);
      uint32_t ph = 0;
      int s = 0;
#pragma unroll 1
      for (int rb = 0; rb < 16; rb++) {
        float acc[128];
#pragma unroll 1
        for (int kc = 0; kc < KH; kc++) {
          mbar_wait_watchdog(bars + 8 * (16 + w * 4 + s), ph);
          const uint32_t da = DESC_A + ((98304 + w * 32768 + s * 8192) >> 4), db = DESC_B + ((kc * 32768) >> 4);
          wg_fence();
#pragma unroll
          for (int k = 0; k < 4; k++) wgmma_ss_n256(acc, da + k * 2, db + k * 128, (kc | k) != 0);
          wg_commit();
          wg_wait<1>();
          if (kc > 0 && lane == 0) mbar_arrive(bars + 8 * (24 + w * 4 + ((s + 3) & 3)));
          if (++s == 4) { s = 0; ph ^= 1; }
        }
        asm volatile("cp.async.bulk.wait_group 0;" ::: "memory");
        __syncwarp();
        if (rb > 0) cnt_signal(p.cnt + (rb - 1) * 32 + C_SP + e);
        wg_wait<0>();
        fence_regs(acc);
        __syncwarp();
        if (lane == 0) mbar_arrive(bars + 8 * (24 + w * 4 + ((s + 3) & 3)));
#pragma unroll
        for (int q = 0; q < 16; q++)
          stmatrix4(slab + (q >> 2) * 8192 + ((sw0 ^ ((q & 3) * 2)) << 4), pack2(acc[8 * q], acc[8 * q + 1]), pack2(acc[8 * q + 2], acc[8 * q + 3]),
                    pack2(acc[8 * q + 4], acc[8 * q + 5]), pack2(acc[8 * q + 6], acc[8 * q + 7]));
        asm volatile("fence.proxy.async.shared::cta;" ::: "memory");
        __syncwarp();
#pragma unroll
        for (int ch = 0; ch < 4; ch++) tma_add3(&p.out, out_stg + ch * 8192, e * 256 + ch * 64, rb * 64 + warp * 16, w);
        asm volatile("cp.async.bulk.commit_group;" ::: "memory");
      }
      asm volatile("cp.async.bulk.wait_group 0;" ::: "memory");
      __syncwarp();
      cnt_signal(p.cnt + 15 * 32 + C_SP + e);
    }
    return;
  }
  const int slot = p.slot[cl];
  const int rb = (slot >> 3) * 2 + rank, j = slot & 7;
  const int cta = rb * 8 + j;
  PROF_AT(threadIdx.x == 0, 0);

  if (threadIdx.x < 128) {
    uint32_t tag = load_epoch(p.epoch);
    asm volatile("setmaxnreg.dec.sync.aligned.u32 40;");
    const int warp = __shfl_sync(~0u, (int)(threadIdx.x >> 5), 0), lane = threadIdx.x & 31;
    if (threadIdx.x == 0) {
      if ((sm & 0x3FFFF) != SMEM_BASE) asm volatile("trap;");
      for (int i = 0; i < 4; i++) { mbar_init(bars + 8 * (B_FQ + i), 1); mbar_init(bars + 8 * (B_EQ + i), 16); }
      for (int i = 0; i < 6; i++) { mbar_init(bars + 8 * (B_FW + i), 1); mbar_init(bars + 8 * (B_EW + i), 16); }
      for (int i = 0; i < 4; i++) { mbar_init(bars + 8 * (B_FG + i), 1); mbar_init(bars + 8 * (B_EG + i), 16); }
      for (int i = 0; i < 6; i++) { mbar_init(bars + 8 * (B_FD + i), 1); mbar_init(bars + 8 * (B_ED + i), 16); }
      for (int i = 0; i < 2; i++) { mbar_init(bars + 8 * (B_STGF + i), 8); mbar_init(bars + 8 * (B_STGE + i), 1); }
      mbar_init(bars + 8 * B_MODB, 1);
      mbar_init(bars + 8 * (B_MODB + 1), 1);
      mbar_init(bars + 8 * B_MODA, 1);
      for (int i = 0; i < 11; i++) mbar_init(bars + 8 * (B_RDY + i), 1);
      asm volatile("fence.mbarrier_init.release.cluster;" ::: "memory");
    }
    __syncwarp();
    cluster_arrive_relaxed();
    tag += 1;
    const unsigned target = tag * 8;
    unsigned* cnt = p.cnt + rb * 32;
    cluster_wait();
    if (warp == 0) {
      const CUtensorMap* wgu = rank ? &p.wu : &p.wg;
      uint32_t st = sm + 16384, fb = bars + 8 * B_FQ, ph = 1;
      __nanosleep(BDELAY);
#pragma unroll 1
      for (int it = 0; it < 32; it++) {
        const int kb = qkv_kb(it, j), col = j * 128 + ((it < 4 ? it >= 2 : it >= 18) ? 64 : 0);
        mbar_wait(fb + 8 * (B_EQ - B_FQ), ph);
        expect_tx_elect(fb, it < 4 ? 24576 : 40960);
        tma_load_mc(st + rank * 8192, &p.wqkv, fb, col + rank * 1024, kb * 64);
        tma_load_mc(st + 16384 + rank * 4096, &p.wqkv32, fb, col + 2048, kb * 64 + rank * 32);
        st += 49152; fb += 8;
        if ((it & 3) == 3) { st -= 4 * 49152; fb -= 32; ph ^= 1; }
      }
      fb = bars + 8 * B_FW; ph = 1;
#pragma unroll 1
      for (int it = 0, s = 0; it < 34; it++) {
        if (it < 6) wait_q_free(bars + 8 * B_EQ, it);
        if (it == 16) mbar_wait(bars + 8 * (B_FW + GW % 6), (GW / 6) & 1);
        mbar_wait(fb + 8 * (B_EW - B_FW), ph);
        expect_tx_elect(fb, (it == 8 || it == 18 || it == 19) ? 16384 : 32768);
        const int k0 = it < 16 ? wo_k(it, j) : (it < 20 ? 2 * j + (it & 1) : other_kb(it - 20, j)) * 64;
        if (it == 16 || it == 17) {
          tma_load_mc(st - 16384 + rank * 16384, wgu, fb, j * 448, k0);
          tma_load_mc(st - 8192 + rank * 16384, wgu, fb, j * 448 + 64, k0);
        } else {
          tma_load_mc(st + rank * 8192, it < 16 ? &p.wo : wgu, fb, it < 16 ? j * 128 + rank * 64 : j * 448 + 384, k0);
        }
        st += 32768; fb += 8;
        if (++s == 6) { s = 0; st -= 6 * 32768; fb -= 48; ph ^= 1; }
      }
      st = sm + 16384 + 3 * 49152; fb = bars + 8 * B_FG; ph = 1;
#pragma unroll 1
      for (int it = 0; it < 46; it++) {
        const int kb = it < 14 ? other_kb(it, j) : (it + 2) & 15, col = j * 448 + ((it + 2) >> 4) * 128;
        if (it < 4) wait_w_free(bars + 8 * B_EW, it);
        mbar_wait(fb + 8 * (B_EG - B_FG), ph);
        expect_tx_elect(fb, 49152);
        tma_load_mc(st + rank * 16384, wgu, fb, col, kb * 64);
        tma_load_mc(st + rank * 16384 + 8192, wgu, fb, col + 64, kb * 64);
        st += (it & 3) == 0 ? -3 * 49152 : 49152; fb += 8;
        if ((it & 3) == 3) { fb -= 32; ph ^= 1; }
      }
      st = sm + 16384 + 2 * 32768; fb = bars + 8 * B_FD; ph = 1;
#pragma unroll 1
      for (int it = 0, s = 0; it < 56 - KH; it++) {
        if (it < 6) wait_g_free(bars + 8 * B_EG, it);
        mbar_wait(fb + 8 * (B_ED - B_FD), ph);
        expect_tx_elect(fb, 32768);
        tma_load_mc(st + rank * 8192, &p.wd, fb, j * 128 + rank * 64, down_k(it));
        st += s == 3 ? -5 * 32768 : 32768; fb += 8;
        if (++s == 6) { s = 0; fb -= 48; ph ^= 1; }
      }
    } else if (warp == 1) {
      const int arow = rb * 128;
      uint32_t st = sm, fb = bars + 8 * B_FQ, ph = 0;
      cnt_wait(cnt + C_HA, target);
      PROF_AT(lane == 0, 16);
#pragma unroll 1
      for (int it = 4; it < 32; it++) {
        if (it == 11) mbar_wait(bars + 8 * (B_RDY + C_H), 0);
        mbar_wait(fb + 8 * (B_EQ - B_FQ), ph);
        tma_load(st, &p.h, fb, qkv_kb(it, j) * 64, arow);
        st += 49152; fb += 8;
        if ((it & 3) == 3) { st -= 4 * 49152; fb -= 32; ph ^= 1; }
      }
      fb = bars + 8 * B_FW; ph = 1;
#pragma unroll 1
      for (int it = 0, s = 0; it < 34; it++) {
        if (it < 16 || it >= 20) {
          if (it < 6) wait_q_free(bars + 8 * B_EQ, it);
          mbar_wait(fb + 8 * (B_EW - B_FW), ph);
          if (it == 0) mbar_wait(bars + 8 * (B_RDY + C_O), 0);
          if (it == 9 || it == 20) cnt_wait(cnt + (it == 9 ? C_O + 1 : C_H2A), target * 8);
          if (it == 27) mbar_wait(bars + 8 * (B_RDY + C_H2), 0);
          PROF_AT(lane == 0 && (it == 0 || it == 9 || it == 20), 17 + (it >> 3));
          if (it != 8) tma_load(st, it < 16 ? &p.o_ld : &p.h2, fb, it < 16 ? wo_k(it, j) : other_kb(it - 20, j) * 64, arow);
        }
        st += 32768; fb += 8;
        if (++s == 6) { s = 0; st -= 6 * 32768; fb -= 48; ph ^= 1; }
      }
      st = sm + 3 * 49152; fb = bars + 8 * B_FG; ph = 1;
#pragma unroll 1
      for (int it = 0; it < 46; it++) {
        if (it < 4) wait_w_free(bars + 8 * B_EW, it);
        mbar_wait(fb + 8 * (B_EG - B_FG), ph);
        tma_load(st, &p.h2, fb, (it < 14 ? other_kb(it, j) : (it + 2) & 15) * 64, arow);
        st += (it & 3) == 0 ? -3 * 49152 : 49152; fb += 8;
        if ((it & 3) == 3) { fb -= 32; ph ^= 1; }
      }
      st = sm + 2 * 32768; fb = bars + 8 * B_FD; ph = 1;
#pragma unroll 1
      for (int it = 0, s = 0; it < 56 - KH; it++) {
        if (it < 6) wait_g_free(bars + 8 * B_EG, it);
        mbar_wait(fb + 8 * (B_ED - B_FD), ph);
        const int u = it + KH, dep = it == 0 ? C_ACT : (u == 8 ? C_ACT + 1 : (u == 24 ? C_ACT + 2 : (u == 40 ? C_A0 : (u == 48 ? C_ACT + 3 : -1))));
        if (dep >= 0) mbar_wait(bars + 8 * (B_RDY + dep), 0);
        tma_load(st, &p.act, fb, down_k(it), arow);
        st += s == 3 ? -5 * 32768 : 32768; fb += 8;
        if (++s == 6) { s = 0; fb -= 48; ph ^= 1; }
      }
    } else if (warp == 2) {
      if (lane < 14) prefetch_map(&p.h + lane);
      __syncwarp();
      uint32_t ph1 = 0;
#pragma unroll 1
      for (int n = 0; n < 8; n++) {
        const int nch = (n == 1 || n == 2 || n == 4) ? 1 : 2;
#pragma unroll 1
        for (int ch = 0; ch < nch; ch++) {
          mbar_wait_watchdog(bars + 8 * (B_STGF + ch), ch ? ph1 : (n & 1));
          const uint32_t src = stg + ch * 16384;
          if (n == 2 || n == 3) {
          } else if (n == 1) {
#pragma unroll 1
            for (int q = 0; q < 8; q++) {
              tma_store2(&p.o_st, src + q * 2048, j * 128, rb * 128 + q * 16);
              if (q & 1) store_pause(true);
            }
          } else if (n >= 4 && n < 8) {
#pragma unroll 1
            for (int q = 0; q < 4; q++) {
              tma_store2(&p.act_st, src + q * 4096, j * 448 + (n == 4 ? 384 : (n - 5) * 128 + ch * 64), rb * 128 + q * 32);
              store_pause(true);
            }
          } else {
            tma_store2(&p.h, src, j * 128 + ch * 64, rb * 128);
            asm volatile("cp.async.bulk.commit_group;" ::: "memory");
            if (ch == 1) {
              asm volatile("cp.async.bulk.wait_group 1;" ::: "memory");
              __syncwarp();
              cnt_signal(cnt + C_HA);
            }
          }
          if (n >= 5 && ch == 0) arrive_elect(bars + 8 * B_STGE);
          if (n == 7 && ch == 0) {
            asm volatile("cp.async.bulk.wait_group 0;" ::: "memory");
            __syncwarp();
            cnt_signal(cnt + C_A0);
          }
        }
        asm volatile("cp.async.bulk.commit_group;" ::: "memory");
        asm volatile("cp.async.bulk.wait_group 0;" ::: "memory");
        __syncwarp();
        if (n != 2 && n != 3) cnt_signal(cnt + n);
        PROF_AT(lane == 0, n == 0 ? 33 : 23 + n);
        if (n == 0) {
#pragma unroll 1
          for (int t = 0; t < 34; t++) {
            ll_store(t < 32 ? p.halo + cta * 1024 + t * 32 + lane : (uint4*)(p.stats2 + cta * 128) + (t - 32) * 32 + lane, 0u, 0u, 0u);
            __nanosleep(40);
          }
          __syncwarp();
        }
        if (n < 5) arrive_elect(bars + 8 * B_STGE);
        if (nch == 2) { arrive_elect(bars + 8 * (B_STGE + 1)); ph1 ^= 1; }
      }
      mbar_wait_watchdog(bars + 8 * B_STGF, 0);
      PROF_AT(lane == 0, 31);
    } else {
      if (lane < 4) ll_store(p.modll + cta * 4 + lane, 0u, 0u, 0u);
      bar_sync(1, 288);
      {
        const uint4 t4 = lds128(sm + RED_OFF + lane * 16);
        float a[4] = {__uint_as_float(t4.x), __uint_as_float(t4.y), __uint_as_float(t4.z), __uint_as_float(t4.w)};
#pragma unroll
        for (int o = 4; o < 32; o <<= 1)
#pragma unroll
          for (int q = 0; q < 4; q++) a[q] += __shfl_xor_sync(~0u, a[q], o);
        if (lane < 4) ll_store(p.modll + cta * 4 + lane, pack2(a[0], a[1]), pack2(a[2], a[3]), tag);
        PROF_AT(lane == 0, 1);
        uint32_t m[4];
        const uint4* mp = p.modll + j * 32 + lane;
        ll_poll<2>([&](int i) { return mp + i * 256; }, tag, m);
        const uint32_t c0 = pack2(1.0f + bf_lo(m[2]), 1.0f + bf_hi(m[2])), c1 = pack2(1.0f + bf_lo(m[3]), 1.0f + bf_hi(m[3]));
        sts128(sm + MODB_OFF + lane * 16, c0, m[0], c1, m[1]);
        __syncwarp();
        arrive_elect(bars + 8 * B_MODA);
      }
#pragma unroll 1
      for (int n = C_H; n <= C_O; n++) {
        cnt_wait_lazy(cnt + n, target);
        arrive_elect(bars + 8 * (B_RDY + n));
      }
      {
        uint32_t m[6];
        const uint4* src = p.modll + 512 + j * 32 + lane;
        ll_poll<3, 500>([&](int i) { return src + i * 256; }, tag, m);
#pragma unroll
        for (int vec = 0; vec < 3; vec++) {
          const float add = vec == 2 ? 1.0f : 0.0f;
          sts128(sm + MODB_OFF + (vec * 128 + lane * 4) * 4, __float_as_uint(bf_round(bf_lo(m[2 * vec]) + add)), __float_as_uint(bf_round(bf_hi(m[2 * vec]) + add)),
                 __float_as_uint(bf_round(bf_lo(m[2 * vec + 1]) + add)), __float_as_uint(bf_round(bf_hi(m[2 * vec + 1]) + add)));
        }
        __syncwarp();
        if (lane == 0) mbar_arrive(bars + 8 * B_MODB);
        PROF_AT(lane == 0, 15);
      }
      __syncwarp();
#pragma unroll 1
      for (int q = C_H2; q < 9; q++) {
        const int n = q < 7 ? q : (q == 7 ? C_A0 : C_ACT + 3);
        cnt_wait_lazy(cnt + n, n == C_H2 ? target * 8 : target);
        arrive_elect(bars + 8 * (B_RDY + n));
      }
      {
        uint32_t m[2];
        const uint4* src = p.modll + 512 + 768 + j * 32 + lane;
        ll_poll<1>([&](int) { return src; }, tag, m);
        sts128(sm + MODB_OFF + (384 + lane * 4) * 4, m[0] << 16, m[0] & 0xffff0000u, m[1] << 16, m[1] & 0xffff0000u);
        cnt_wait_lazy(cnt + C_SP + (j >> 1), target);
        __syncwarp();
        if (lane == 0) mbar_arrive(bars + 8 * (B_MODB + 1));
      }
    }
  } else {
    uint32_t tag;

    {
      const int tid = threadIdx.x - 128, cw = tid >> 7, warp = (tid >> 5) & 3, lane = tid & 31;
      const int l16 = lane & 15, half = lane >> 4, w8 = cw * 4 + warp;
      const uint32_t cbuf = sm + 3 * 49152 + w8 * 512;
      if (lane <= 16) cp_async16(cbuf + lane * 16, lane < 16 ? (const void*)(p.c + w8 * 128 + lane * 8) : (const void*)p.epoch);
      asm volatile("cp.async.commit_group;" ::: "memory");
      const uint32_t xbuf = sm + 40960 + (cw * 2 + (l16 >> 3)) * 49152 + (warp * 16 + half) * 128;
      {
        const char* xp = (const char*)p.x + (uint32_t)((rb * 128 + (warp * 16 + half) * 2 + cw) * 2048 + j * 256 + l16 * 16);
#pragma unroll
        for (int i = 0; i < 8; i++) cp_async16(xbuf + i * 256 + (((l16 & 7) ^ ((i * 2 + half) & 7)) << 4), xp + i * 8192);
      }
      asm volatile("cp.async.commit_group;" ::: "memory");
      const uint32_t wbuf = sm + cw * 49152 + warp * 4096;
      {
        const char* wp = (const char*)p.wmod + (uint32_t)(cta * 32 + (lane & 1) * 16 + (w8 * 128 + (lane >> 1)) * 12288);
#pragma unroll
        for (int i = 0; i < 8; i++) cp_async16(wbuf + i * 512 + lane * 16, wp + i * 16 * 12288);
      }
      asm volatile("cp.async.commit_group;" ::: "memory");
      PROF_AT(tid == 0, 32);
      uint2* st1 = p.stats1 + (rb * 8 + j) * 128 + cw * 64 + warp * 16;
      if (lane < 8) ll_store((uint4*)st1 + lane, 0u, 0u, 0u);
      __syncwarp();
      cluster_arrive_relaxed();
      asm volatile("setmaxnreg.inc.sync.aligned.u32 232;");
      uint32_t sa[4][4];
      {
        asm volatile("cp.async.wait_group 2;" ::: "memory");
        __syncwarp();
        tag = lds32(cbuf + 256) + 1;
        const float2 cv = lds64f(cbuf + lane * 8);
        const uint32_t c0 = __float_as_uint(cv.x), c1 = __float_as_uint(cv.y);
        sts64f(cbuf + lane * 8, __uint_as_float(pack2(silu_f(bf_lo(c0)), silu_f(bf_hi(c0)))), __uint_as_float(pack2(silu_f(bf_lo(c1)), silu_f(bf_hi(c1)))));
        __syncwarp();
#pragma unroll
        for (int q = 0; q < 4; q++) ldmatrix4(sa[q][0], sa[q][1], sa[q][2], sa[q][3], cbuf + q * 64 + (lane >> 3) * 16);
      }
      cluster_wait();
      asm volatile("cp.async.wait_group 1;" ::: "memory");
      __syncwarp();
      uint32_t xl[16], xh[16];
      {
        const int srow = warp * 16 + (lane & 15);
#pragma unroll
        for (int q = 0; q < 8; q++)
          ldmatrix4(xl[2 * q], xh[2 * q], xl[2 * q + 1], xh[2 * q + 1],
                    sm + 40960 + (cw * 2 + (q >> 2)) * 49152 + srow * 128 + (((half + (q & 3) * 2) ^ (srow & 7)) << 4));
      }
      publish_stats(xl, xh, st1, lane, tag16(tag));
      PROF_AT(tid == 0, 50);
      asm volatile("cp.async.wait_group 0;" ::: "memory");
      __syncwarp();
      PROF_AT(tid == 0, 51);
      {
        uint32_t b[8][4];
#pragma unroll
        for (int ks = 0; ks < 8; ks++) ldmatrix4t(b[ks], wbuf + (ks * 16 + (lane & 15)) * 32 + (lane >> 4) * 16);
        float d0[4] = {0.f, 0.f, 0.f, 0.f}, d1[4] = {0.f, 0.f, 0.f, 0.f}, d2[4] = {0.f, 0.f, 0.f, 0.f}, d3[4] = {0.f, 0.f, 0.f, 0.f};
#pragma unroll
        for (int q = 0; q < 4; q++) {
          mma16816(d0, sa[q][0], sa[q][0], sa[q][1], sa[q][1], b[2 * q][0], b[2 * q][1]);
          mma16816(d1, sa[q][0], sa[q][0], sa[q][1], sa[q][1], b[2 * q][2], b[2 * q][3]);
          mma16816(d2, sa[q][2], sa[q][2], sa[q][3], sa[q][3], b[2 * q + 1][0], b[2 * q + 1][1]);
          mma16816(d3, sa[q][2], sa[q][2], sa[q][3], sa[q][3], b[2 * q + 1][2], b[2 * q + 1][3]);
        }
        d0[0] += d2[0]; d0[1] += d2[1]; d1[0] += d3[0]; d1[1] += d3[1];
        if (lane < 4) {
          sts64f(sm + RED_OFF + (w8 * 16 + lane * 2) * 4, d0[0], d0[1]);
          sts64f(sm + RED_OFF + (w8 * 16 + 8 + lane * 2) * 4, d1[0], d1[1]);
        }
        asm volatile("bar.arrive 1, 288;" ::: "memory");
      }
      {
        const int c = lane & 3;
        float rs[2], nb[2];
        stat_gather(p.stats1 + rb * 1024 + cw * 64 + warp * 16, tag16(tag), lane, rs, nb);
#pragma unroll
        for (int n = 0; n < 16; n++) {
          xl[n] = pack2(bf_lo(xl[n]) * rs[0] + nb[0], bf_hi(xl[n]) * rs[0] + nb[0]);
          xh[n] = pack2(bf_lo(xh[n]) * rs[1] + nb[1], bf_hi(xh[n]) * rs[1] + nb[1]);
        }
        const int srow = warp * 16 + l16;
        const uint32_t slab = stg + cw * 8192 + srow * 128;
#pragma unroll
        for (int q = 0; q < 8; q++)
          stmatrix4(slab + (q >> 2) * 16384 + (((half + (q & 3) * 2) ^ (srow & 7)) << 4), xl[2 * q], xh[2 * q], xl[2 * q + 1], xh[2 * q + 1]);
        PROF_AT(tid == 0, 52);
        mbar_wait(bars + 8 * B_MODA, 0);
        PROF_AT(tid == 0, 2);
#pragma unroll
        for (int q = 0; q < 8; q++) {
          const float2 m0 = lds64f(sm + MODB_OFF + (8 * q + c) * 8), m1 = lds64f(sm + MODB_OFF + (8 * q + 4 + c) * 8);
          const uint32_t c0 = __float_as_uint(m0.x), s0 = __float_as_uint(m0.y), c1 = __float_as_uint(m1.x), s1 = __float_as_uint(m1.y);
          stmatrix4(slab + (q >> 2) * 16384 + (((half + (q & 3) * 2) ^ (srow & 7)) << 4), fma_bf2(xl[2 * q], c0, s0), fma_bf2(xh[2 * q], c0, s0),
                    fma_bf2(xl[2 * q + 1], c1, s1), fma_bf2(xh[2 * q + 1], c1, s1));
          if ((q & 3) == 3) stage_done(bars + 8 * (B_STGF + (q >> 2)), lane);
        }
        wg_bar(cw);
      }
      PROF_AT(tid == 0, 3);
    }

    uint32_t xl[16], xh[16];
    {
      RING_IDS();
      uint32_t prev = 0;
      float acc1[96];
      {
        Ring g{bars + 8 * B_FQ, rbars + 8 * B_EQ, 0, 0u, 0u, releaser TR(0)};
        float acc0[96];
#pragma unroll 1
        for (int kb = 0; kb < 2; kb++) kblock<192, 4, 49152>(acc0, g, a_base + STG_OFF + kb * 16384, kb == 0, prev);
#pragma unroll 1
        for (int kb = 0; kb < 2; kb++) kblock<192, 4, 49152>(acc1, g, a_base + STG_OFF + kb * 16384, kb == 0, prev);
#pragma unroll 1
        for (int kb = 0; kb < 14; kb++) kblock<192, 4, 49152>(acc0, g, a_base + g.off, false, prev);
        PROF_AT(tid == 0, 4);
        attention<NPRE0, false>(acc0, p, 0, rb, cta, cw, warp, tag, stg, bars, prev, [&]() { kblock<192, 4, 49152>(acc1, g, a_base + g.off, false, prev); });
        PROF_AT(tid == 0, 5);
        {
          LANE_IDS();
#pragma unroll
          for (int q = 0; q < 8; q++)
            ldmatrix4(xl[2 * q], xh[2 * q], xl[2 * q + 1], xh[2 * q + 1], sm + 40960 + (cw * 2 + (q >> 2)) * 49152 + srow * 128 + ((sw0 ^ ((q & 3) * 2)) << 4));
#pragma unroll
          for (int q = 0; q < 16; q++) asm volatile("" : "+r"(xl[q]), "+r"(xh[q])::"memory");
        }
#pragma unroll 1
        for (int kb = 5 + NPRE0; kb < 14; kb++) kblock<192, 4, 49152>(acc1, g, a_base + g.off, false, prev);
        PROF_AT(tid == 0, 6);
      }
      float acc[64];
      Ring g{bars + 8 * B_FW, rbars + 8 * B_EW, 0, 0u, 0u, releaser TR(32)};
      attention<NPRE1, true>(acc1, p, 1, rb, cta, cw, warp, tag, stg, bars, prev, [&]() { kblock<128, 6, 32768>(acc, g, a_base + g.off, g.s == 0, prev); });
      PROF_AT(tid == 0, 7);
      LANE_IDS();
      unsigned* cnt = p.cnt + rb * 32;
      tma_store2(&p.o_st, stg + cw * 8192 + warp * 2048, j * 128 + 64, rb * 128 + cw * 64 + warp * 16);
      asm volatile("cp.async.bulk.commit_group;" ::: "memory");
#pragma unroll 1
      for (int kb = 1 + NPRE1; kb < 16; kb++) {
        if (kb == 8) wg_bar(cw);
        kblock<128, 6, 32768>(acc, g, a_base + (kb == 8 ? STG_OFF : g.off), false, prev);
        if (kb == OSIG + NPRE1) {
          asm volatile("cp.async.bulk.wait_group 0;" ::: "memory");
          __syncwarp();
          cnt_signal(cnt + C_O + 1);
        }
      }
      mbar_wait(bars + 8 * B_MODB, 0);
      float2 ga[16];
#pragma unroll
      for (int n = 0; n < 16; n++) ga[n] = lds64f(sm + MODB_OFF + (8 * n + 2 * c) * 4);
      tile_end(acc, prev);
      PROF_AT(tid == 0, 8);
      uint2* st2 = p.stats2 + (rb * 8 + j) * 128 + cw * 64 + warp * 16 + r + (c & 1) * 8;
      float sl[2] = {0.f, 0.f}, sh[2] = {0.f, 0.f}, ql[2] = {0.f, 0.f}, qh[2] = {0.f, 0.f};
#pragma unroll
      for (int n = 0; n < 16; n++) {
        acc[4 * n] = ga[n].x * acc[4 * n] + bf_lo(xl[n]); acc[4 * n + 1] = ga[n].y * acc[4 * n + 1] + bf_hi(xl[n]);
        acc[4 * n + 2] = ga[n].x * acc[4 * n + 2] + bf_lo(xh[n]); acc[4 * n + 3] = ga[n].y * acc[4 * n + 3] + bf_hi(xh[n]);
        sl[0] += acc[4 * n]; sl[1] += acc[4 * n + 1]; sh[0] += acc[4 * n + 2]; sh[1] += acc[4 * n + 3];
        ql[0] += acc[4 * n] * acc[4 * n]; ql[1] += acc[4 * n + 1] * acc[4 * n + 1];
        qh[0] += acc[4 * n + 2] * acc[4 * n + 2]; qh[1] += acc[4 * n + 3] * acc[4 * n + 3];
      }
      {
        const float ml = (sl[0] + sl[1]) * (1.0f / 32), mh = (sh[0] + sh[1]) * (1.0f / 32);
        const float vl = (ql[0] + ql[1]) - 32.0f * ml * ml, vh = (qh[0] + qh[1]) - 32.0f * mh * mh;
        const bool b0 = c & 1;
        float m = b0 ? mh : ml, q = b0 ? vh : vl;
        chan(m, q, __shfl_xor_sync(~0u, b0 ? ml : mh, 1), __shfl_xor_sync(~0u, b0 ? vl : vh, 1), 32.f);
        chan(m, q, __shfl_xor_sync(~0u, m, 2), __shfl_xor_sync(~0u, q, 2), 64.f);
        if (c < 2) stat_store(st2, m, fmaxf(q, 0.f), tag16(tag));
        __syncwarp();
      }
      PROF_AT(tid == 0, 48);
      float2 sb[16], cb[16];
#pragma unroll
      for (int n = 0; n < 16; n++) {
        sb[n] = lds64f(sm + MODB_OFF + (128 + 8 * n + 2 * c) * 4);
        cb[n] = lds64f(sm + MODB_OFF + (256 + 8 * n + 2 * c) * 4);
        xl[n] = pack2(acc[4 * n], acc[4 * n + 1]);
        xh[n] = pack2(acc[4 * n + 2], acc[4 * n + 3]);
      }
      mbar_wait(bars + 8 * B_STGE, 0);
      PROF_AT(tid == 0, 49);
      float nb[2], rstd[2];
      stat_gather(p.stats2 + rb * 1024 + cw * 64 + warp * 16, tag16(tag), lane, rstd, nb);
      PROF_AT(tid == 0, 9);
#pragma unroll
      for (int ch = 0; ch < 2; ch++) {
        uint32_t lo[8], hi[8];
#pragma unroll
        for (int t = 0; t < 8; t++) {
          const int n = ch * 8 + t;
          lo[t] = pack2((acc[4 * n] * rstd[0] + nb[0]) * cb[n].x + sb[n].x, (acc[4 * n + 1] * rstd[0] + nb[0]) * cb[n].y + sb[n].y);
          hi[t] = pack2((acc[4 * n + 2] * rstd[1] + nb[1]) * cb[n].x + sb[n].x, (acc[4 * n + 3] * rstd[1] + nb[1]) * cb[n].y + sb[n].y);
        }
        stage_slab(stg + ch * 16384 + cw * 8192, warp, lane, lo, hi);
        stage_done(bars + 8 * (B_STGF + ch), lane);
        tma_store2(&p.h2_st, stg + ch * 16384 + cw * 8192 + warp * 2048, j * 128 + ch * 64, rb * 128 + cw * 64 + warp * 16);
        asm volatile("cp.async.bulk.commit_group;" ::: "memory");
      }
      wg_bar(cw);
      PROF_AT(tid == 0, 10);
    }

    uint32_t pg[32], pu[32];
    {
      RING_IDS();
      float acc[128];
      uint32_t prev = 0;
      Ring g{bars + 8 * B_FG, rbars + 8 * B_EG, 0, 0u, 3 * 49152u, releaser TR(66)};
      {
        Ring w{bars + 8 * B_FW, rbars + 8 * B_EW, 4, 0u, 4 * 32768u, releaser TR(48)};
        float acn[64];
#pragma unroll 1
        for (int kb = 0; kb < 2; kb++) {
          kblock<256, 6, 32768>(acc, w, a_base + STG_OFF + kb * 16384, kb == 0, prev, 0u);
          if (kb == 0) asm volatile("cp.async.bulk.wait_group 1;" ::: "memory");
          else asm volatile("cp.async.bulk.wait_group 0;" ::: "memory");
          __syncwarp();
          cnt_signal(p.cnt + rb * 32 + (kb == 0 ? C_H2A : C_H2));
        }
        {
          LANE_IDS();
#pragma unroll
          for (int q = 0; q < 8; q++)
            stmatrix4(slab - STG_OFF + (q >> 2) * 32768 + ((sw0 ^ ((q & 3) * 2)) << 4), xl[2 * q], xh[2 * q], xl[2 * q + 1], xh[2 * q + 1]);
          __syncwarp();
        }
#pragma unroll 1
        for (int kb = 0; kb < 16; kb++) {
          kblock<128, 6, 32768>(acn, w, a_base + (kb < 2 ? STG_OFF + kb * 16384 : w.off), kb == 0, prev);
          if (kb < 2) prev = 0;
          if (kb == 1 || kb == 2) {
            const uint32_t o = cw * 8192 + warp * 2048 + (fresh_tid() & 31) * 16;
            uint4 v[4];
#pragma unroll
            for (int q = 0; q < 4; q++) v[q] = lds128(sm + (kb - 1) * 32768 + o + q * 512);
#pragma unroll
            for (int q = 0; q < 4; q++) sts128(stg + (kb - 1) * 16384 + o + q * 512, v[q].x, v[q].y, v[q].z, v[q].w);
            __syncwarp();
            if (releaser) mbar_arrive_cluster(rbars + 8 * (B_EW + kb - 1));
          }
          if (kb == 4) {
            asm volatile("fence.proxy.async.shared::cta;" ::: "memory");
            __syncwarp();
          }
          if (kb == X1S + warp || kb == X1S + 4 + warp) {
            const int ch = kb != X1S + warp;
            tma_store3(&p.out, stg + ch * 16384 + cw * 8192 + warp * 2048, j * 128 + ch * 64, rb * 64 + warp * 16, cw);
            asm volatile("cp.async.bulk.commit_group;" ::: "memory");
          }
        }
        PROF_AT(tid == 0, 39);
        kblock<256, 4, 49152>(acc, g, a_base + g.off, false, prev);
        fence_regs(acn);
#pragma unroll
        for (int q = 0; q < 16; q++) {
          pg[q] = pack2(acn[2 * q], acn[2 * q + 1]);
          pu[q] = pack2(acn[32 + 2 * q], acn[32 + 2 * q + 1]);
          pg[16 + q] = 0; pu[16 + q] = 0;
        }
        asm volatile("cp.async.bulk.wait_group 0;" ::: "memory");
        kblock<256, 4, 49152>(acc, g, a_base + g.off, false, prev);
      }
      LANE_IDS();
#pragma unroll 1
      for (int t = 0; t < 3; t++) {
#pragma unroll 1
        for (int blk = 0; blk < (t == 0 ? 2 : 4); blk++) {
          g.s = 2;
#pragma unroll
          for (int i = 0; i < 4; i++) {
            g.off = ((i + 1) & 3) * 49152;
            kblock<256, 4, 49152>(acc, g, a_base + g.off, t > 0 && blk == 0 && i == 0, prev);
            if ((blk & 1) == 0 && i == 0) mbar_wait(bars + 8 * (B_STGE + (blk >> 1)), (t + 1 + (blk >> 1)) & 1);
            stmatrix2(slab + (blk >> 1) * 16384 + (((srow & 7) ^ ((blk & 1) * 4 + i)) << 4), swiglu2(pg[2 * i], pu[2 * i]), swiglu2(pg[2 * i + 1], pu[2 * i + 1]));
          }
#pragma unroll
          for (int q = 0; q < 24; q++) { pg[q] = pg[q + 8]; pu[q] = pu[q + 8]; }
          if (blk & 1) stage_done(bars + 8 * (B_STGF + (blk >> 1)), lane);
        }
#pragma unroll 1
        for (int kb = t == 0 ? 0 : 4; kb < 4; kb++) kblock<256, 4, 49152>(acc, g, a_base + g.off, false, prev);
        tile_end(acc, prev);
        PROF_AT(tid == 0, 36 + t);
#pragma unroll
        for (int q = 0; q < 32; q++) {
          pg[q] = pack2(acc[2 * q], acc[2 * q + 1]);
          pu[q] = pack2(acc[64 + 2 * q], acc[64 + 2 * q + 1]);
        }
      }
      PROF_AT(tid == 0, 11);
    }

    {
      RING_IDS();
      LANE_IDS();
      Ring g{bars + 8 * B_FD, rbars + 8 * B_ED, 0, 0u, 2 * 32768u, releaser TR(112)};
      float acc[64];
      uint32_t prev = 0;
#pragma unroll 1
      for (int blk = 0; blk < 4; blk++) {
#pragma unroll
        for (int i = 0; i < 8; i++) {
          kblock<128, 6, 32768>(acc, g, a_base + g.off, blk == 0 && i == 0, prev);
          if ((blk & 1) == 0 && i == 0) mbar_wait(bars + 8 * (B_STGE + (blk >> 1)), blk >> 1);
          stmatrix1(slab + (blk >> 1) * 16384 + (i & 1) * 1024 + (((srow & 7) ^ ((blk & 1) * 4 + (i >> 1))) << 4), swiglu2(pg[i], pu[i]));
        }
#pragma unroll
        for (int q = 0; q < 24; q++) { pg[q] = pg[q + 8]; pu[q] = pu[q + 8]; }
        if (blk & 1) stage_done(bars + 8 * (B_STGF + (blk >> 1)), lane);
      }
#pragma unroll 1
      for (int kb = 32; kb < 56 - KH; kb++) {
        if (kb == 50 - KH) g.releaser = false;
        kblock<128, 6, 32768>(acc, g, a_base + g.off, false, prev);
      }
      mbar_wait(bars + 8 * (B_MODB + 1), 0);
      mbar_wait(bars + 8 * B_STGE, 1);
      mbar_wait(bars + 8 * (B_STGE + 1), 0);
      float2 gbv[16];
#pragma unroll
      for (int n = 0; n < 16; n++) gbv[n] = lds64f(sm + MODB_OFF + (384 + 8 * n + 2 * c) * 4);
      tile_end(acc, prev);
      PROF_AT(tid == 0, 13);
#pragma unroll
      for (int ch = 0; ch < 2; ch++) {
        uint32_t lo[8], hi[8];
#pragma unroll
        for (int t = 0; t < 8; t++) {
          const int n = ch * 8 + t;
          const float2 gb = gbv[n];
          lo[t] = pack2(gb.x * acc[4 * n], gb.y * acc[4 * n + 1]);
          hi[t] = pack2(gb.x * acc[4 * n + 2], gb.y * acc[4 * n + 3]);
        }
        stage_slab(stg + ch * 16384 + cw * 8192, warp, lane, lo, hi);
        asm volatile("fence.proxy.async.shared::cta;" ::: "memory");
        __syncwarp();
        tma_add3(&p.out, stg + ch * 16384 + cw * 8192 + warp * 2048, j * 128 + ch * 64, rb * 64 + warp * 16, cw);
      }
      asm volatile("cp.async.bulk.commit_group;" ::: "memory");
      if (lane == 0) mbar_arrive(bars + 8 * B_STGF);
      asm volatile("cp.async.bulk.wait_group.read 0;" ::: "memory");
      PROF_AT(tid == 0, 14);
    }
    if (blockIdx.x == 0 && threadIdx.x == 128) asm volatile("st.relaxed.gpu.global.u32 [%0], %1;" ::"l"(p.epoch), "r"(tag) : "memory");
  }
}

typedef CUresult (*EncodeFn)(CUtensorMap*, CUtensorMapDataType, cuuint32_t, void*, const cuuint64_t*, const cuuint64_t*,
                             const cuuint32_t*, const cuuint32_t*, CUtensorMapInterleave, CUtensorMapSwizzle,
                             CUtensorMapL2promotion, CUtensorMapFloatOOBfill);

void encode2d(EncodeFn fn, CUtensorMap* m, const void* ptr, uint64_t cols, uint64_t rows, uint32_t box_rows) {
  cuuint64_t dims[2] = {cols, rows};
  cuuint64_t strides[1] = {cols * 2};
  cuuint32_t box[2] = {64, box_rows};
  cuuint32_t es[2] = {1, 1};
  fn(m, CU_TENSOR_MAP_DATA_TYPE_BFLOAT16, 2, (void*)ptr, dims, strides, box, es, CU_TENSOR_MAP_INTERLEAVE_NONE,
     CU_TENSOR_MAP_SWIZZLE_128B, CU_TENSOR_MAP_L2_PROMOTION_L2_128B, CU_TENSOR_MAP_FLOAT_OOB_FILL_NONE);
}

}

extern "C" void kernel_launch(void* const* d_in, const int* in_sizes, int n_in, void* d_out, int out_size) {
  (void)in_sizes; (void)n_in; (void)out_size;
  void* fp = nullptr;
  cudaDriverEntryPointQueryResult qr;
  cudaGetDriverEntryPoint("cuTensorMapEncodeTiled", &fp, cudaEnableDefault, &qr);
  EncodeFn fn = (EncodeFn)fp;
  void *ph, *po, *ph2, *pact;
  cudaGetSymbolAddress(&ph, g_h);
  cudaGetSymbolAddress(&po, g_o);
  ph2 = ph;
  cudaGetSymbolAddress(&pact, g_act);
  Params p;
  encode2d(fn, &p.h, ph, DM, SEQ, 128);
  encode2d(fn, &p.o_ld, po, DM, SEQ, 128);
  encode2d(fn, &p.h2, ph2, DM, SEQ, 128);
  encode2d(fn, &p.act, pact, FF, SEQ, 128);
  encode2d(fn, &p.act_st, pact, FF, SEQ, 32);
  encode2d(fn, &p.wm, d_in[8], 6 * DM, DM, 64);
  encode2d(fn, &p.o_st, po, DM, SEQ, 16);
  encode2d(fn, &p.h2_st, ph2, DM, SEQ, 16);
  encode2d(fn, &p.wqkv, d_in[1], 3 * DM, DM, 64);
  encode2d(fn, &p.wqkv32, d_in[1], 3 * DM, DM, 32);
  encode2d(fn, &p.wo, d_in[2], DM, DM, 64);
  encode2d(fn, &p.wg, d_in[4], FF, DM, 64);
  encode2d(fn, &p.wu, d_in[5], FF, DM, 64);
  encode2d(fn, &p.wd, d_in[6], DM, FF, 64);
  {
    cuuint64_t dims[3] = {DM, SEQ / 2, 2};
    cuuint64_t strides[2] = {DM * 4, DM * 2};
    cuuint32_t box[3] = {64, 16, 1};
    cuuint32_t es[3] = {1, 1, 1};
    fn(&p.out, CU_TENSOR_MAP_DATA_TYPE_BFLOAT16, 3, d_out, dims, strides, box, es, CU_TENSOR_MAP_INTERLEAVE_NONE,
       CU_TENSOR_MAP_SWIZZLE_128B, CU_TENSOR_MAP_L2_PROMOTION_L2_128B, CU_TENSOR_MAP_FLOAT_OOB_FILL_NONE);
  }
  p.x = (const bf16*)d_in[0];
  p.c = (const bf16*)d_in[7];
  p.wmod = (const bf16*)d_in[8];
  for (int cl = 0; cl < 64; cl++) {
    const int grp = cl < 4 ? 0 : (cl < 36 ? (cl - 4) & 7 : 1 + (cl - 36) % 7);
    const int j = cl < 4 ? 4 + cl : (cl < 36 ? (cl - 4) >> 3 : 4 + (cl - 36) / 7);
    p.slot[cl] = (uint8_t)(grp * 8 + j);
  }
  void* q;
  cudaGetSymbolAddress(&q, g_modll); p.modll = (uint4*)q;
  cudaGetSymbolAddress(&q, g_halo); p.halo = (uint4*)q;
  cudaGetSymbolAddress(&q, g_stats); p.stats1 = (uint2*)q; p.stats2 = p.stats1 + SEQ * 8;
  cudaGetSymbolAddress(&q, g_cnt); p.cnt = (unsigned*)q;
  cudaGetSymbolAddress(&q, g_epoch); p.epoch = (unsigned*)q;

  cudaFuncSetAttribute(fused_kernel, cudaFuncAttributeMaxDynamicSharedMemorySize, SMEM_BYTES);
  cudaLaunchConfig_t cfg = {};
  cfg.gridDim = dim3(NCTA + 4);
  cfg.blockDim = dim3(384);
  cfg.dynamicSmemBytes = SMEM_BYTES;
  cfg.stream = cudaStreamPerThread;
  cudaLaunchAttribute at[1];
  at[0].id = cudaLaunchAttributeClusterDimension;
  at[0].val.clusterDim.x = 2; at[0].val.clusterDim.y = 1; at[0].val.clusterDim.z = 1;
  cfg.attrs = at;
  cfg.numAttrs = 1;
  cudaLaunchKernelEx(&cfg, fused_kernel, p);
}
```

```cpp
#include <cuda_runtime.h>
#include <cuda_bf16.h>
#include <cuda.h>
#include <stdint.h>

typedef __nv_bfloat16 bf16;

#define PAUSE 200
#define WMDELAY 500
#define BDELAY 1500
#define NPRE0 3
#define NPRE1 1
#define ALIAS 1

#define PFW 8000
#define PFP 0

#define OSIG 3

#define KH 3

#define HOFF 900

#define X1S 6

#define GW 15

__device__ __forceinline__ void wgmma_ss_n128(float (&d)[64], uint32_t da, uint32_t db, int scale_d) {
  asm volatile("{\n.reg .pred p;\n.reg .b64 da, db;\nsetp.ne.b32 p, %66, 0;\n"
    "mov.b64 da, {%64, 0x40000040};\nmov.b64 db, {%65, 0x40000040};\n"
    "wgmma.mma_async.sync.aligned.m64n128k16.f32.bf16.bf16 "
    "{%0, %1, %2, %3, %4, %5, %6, %7, %8, %9, %10, %11, %12, %13, %14, %15, "
    "%16, %17, %18, %19, %20, %21, %22, %23, %24, %25, %26, %27, %28, %29, %30, %31, "
    "%32, %33, %34, %35, %36, %37, %38, %39, %40, %41, %42, %43, %44, %45, %46, %47, "
    "%48, %49, %50, %51, %52, %53, %54, %55, %56, %57, %58, %59, %60, %61, %62, %63}, "
    "da, db, p, 1, 1, 0, 1;\n}\n"
    : "+f"(d[0]), "+f"(d[1]), "+f"(d[2]), "+f"(d[3]), "+f"(d[4]), "+f"(d[5]), "+f"(d[6]), "+f"(d[7]),
      "+f"(d[8]), "+f"(d[9]), "+f"(d[10]), "+f"(d[11]), "+f"(d[12]), "+f"(d[13]), "+f"(d[14]), "+f"(d[15]),
      "+f"(d[16]), "+f"(d[17]), "+f"(d[18]), "+f"(d[19]), "+f"(d[20]), "+f"(d[21]), "+f"(d[22]), "+f"(d[23]),
      "+f"(d[24]), "+f"(d[25]), "+f"(d[26]), "+f"(d[27]), "+f"(d[28]), "+f"(d[29]), "+f"(d[30]), "+f"(d[31]),
      "+f"(d[32]), "+f"(d[33]), "+f"(d[34]), "+f"(d[35]), "+f"(d[36]), "+f"(d[37]), "+f"(d[38]), "+f"(d[39]),
      "+f"(d[40]), "+f"(d[41]), "+f"(d[42]), "+f"(d[43]), "+f"(d[44]), "+f"(d[45]), "+f"(d[46]), "+f"(d[47]),
      "+f"(d[48]), "+f"(d[49]), "+f"(d[50]), "+f"(d[51]), "+f"(d[52]), "+f"(d[53]), "+f"(d[54]), "+f"(d[55]),
      "+f"(d[56]), "+f"(d[57]), "+f"(d[58]), "+f"(d[59]), "+f"(d[60]), "+f"(d[61]), "+f"(d[62]), "+f"(d[63])
    : "r"(da), "r"(db), "r"(scale_d));
}

__device__ __forceinline__ void wgmma_ss_n192(float (&d)[96], uint32_t da, uint32_t db, int scale_d) {
  asm volatile("{\n.reg .pred p;\n.reg .b64 da, db;\nsetp.ne.b32 p, %98, 0;\n"
    "mov.b64 da, {%96, 0x40000040};\nmov.b64 db, {%97, 0x40000040};\n"
    "wgmma.mma_async.sync.aligned.m64n192k16.f32.bf16.bf16 "
    "{%0, %1, %2, %3, %4, %5, %6, %7, %8, %9, %10, %11, %12, %13, %14, %15, "
    "%16, %17, %18, %19, %20, %21, %22, %23, %24, %25, %26, %27, %28, %29, %30, %31, "
    "%32, %33, %34, %35, %36, %37, %38, %39, %40, %41, %42, %43, %44, %45, %46, %47, "
    "%48, %49, %50, %51, %52, %53, %54, %55, %56, %57, %58, %59, %60, %61, %62, %63, "
    "%64, %65, %66, %67, %68, %69, %70, %71, %72, %73, %74, %75, %76, %77, %78, %79, "
    "%80, %81, %82, %83, %84, %85, %86, %87, %88, %89, %90, %91, %92, %93, %94, %95}, "
    "da, db, p, 1, 1, 0, 1;\n}\n"
    : "+f"(d[0]), "+f"(d[1]), "+f"(d[2]), "+f"(d[3]), "+f"(d[4]), "+f"(d[5]), "+f"(d[6]), "+f"(d[7]),
      "+f"(d[8]), "+f"(d[9]), "+f"(d[10]), "+f"(d[11]), "+f"(d[12]), "+f"(d[13]), "+f"(d[14]), "+f"(d[15]),
      "+f"(d[16]), "+f"(d[17]), "+f"(d[18]), "+f"(d[19]), "+f"(d[20]), "+f"(d[21]), "+f"(d[22]), "+f"(d[23]),
      "+f"(d[24]), "+f"(d[25]), "+f"(d[26]), "+f"(d[27]), "+f"(d[28]), "+f"(d[29]), "+f"(d[30]), "+f"(d[31]),
      "+f"(d[32]), "+f"(d[33]), "+f"(d[34]), "+f"(d[35]), "+f"(d[36]), "+f"(d[37]), "+f"(d[38]), "+f"(d[39]),
      "+f"(d[40]), "+f"(d[41]), "+f"(d[42]), "+f"(d[43]), "+f"(d[44]), "+f"(d[45]), "+f"(d[46]), "+f"(d[47]),
      "+f"(d[48]), "+f"(d[49]), "+f"(d[50]), "+f"(d[51]), "+f"(d[52]), "+f"(d[53]), "+f"(d[54]), "+f"(d[55]),
      "+f"(d[56]), "+f"(d[57]), "+f"(d[58]), "+f"(d[59]), "+f"(d[60]), "+f"(d[61]), "+f"(d[62]), "+f"(d[63]),
      "+f"(d[64]), "+f"(d[65]), "+f"(d[66]), "+f"(d[67]), "+f"(d[68]), "+f"(d[69]), "+f"(d[70]), "+f"(d[71]),
      "+f"(d[72]), "+f"(d[73]), "+f"(d[74]), "+f"(d[75]), "+f"(d[76]), "+f"(d[77]), "+f"(d[78]), "+f"(d[79]),
      "+f"(d[80]), "+f"(d[81]), "+f"(d[82]), "+f"(d[83]), "+f"(d[84]), "+f"(d[85]), "+f"(d[86]), "+f"(d[87]),
      "+f"(d[88]), "+f"(d[89]), "+f"(d[90]), "+f"(d[91]), "+f"(d[92]), "+f"(d[93]), "+f"(d[94]), "+f"(d[95])
    : "r"(da), "r"(db), "r"(scale_d));
}

__device__ __forceinline__ void wgmma_ss_n256(float (&d)[128], uint32_t da, uint32_t db, int scale_d) {
  asm volatile("{\n.reg .pred p;\n.reg .b64 da, db;\nsetp.ne.b32 p, %130, 0;\n"
    "mov.b64 da, {%128, 0x40000040};\nmov.b64 db, {%129, 0x40000040};\n"
    "wgmma.mma_async.sync.aligned.m64n256k16.f32.bf16.bf16 "
    "{%0, %1, %2, %3, %4, %5, %6, %7, %8, %9, %10, %11, %12, %13, %14, %15, "
    "%16, %17, %18, %19, %20, %21, %22, %23, %24, %25, %26, %27, %28, %29, %30, %31, "
    "%32, %33, %34, %35, %36, %37, %38, %39, %40, %41, %42, %43, %44, %45, %46, %47, "
    "%48, %49, %50, %51, %52, %53, %54, %55, %56, %57, %58, %59, %60, %61, %62, %63, "
    "%64, %65, %66, %67, %68, %69, %70, %71, %72, %73, %74, %75, %76, %77, %78, %79, "
    "%80, %81, %82, %83, %84, %85, %86, %87, %88, %89, %90, %91, %92, %93, %94, %95, "
    "%96, %97, %98, %99, %100, %101, %102, %103, %104, %105, %106, %107, %108, %109, %110, %111, "
    "%112, %113, %114, %115, %116, %117, %118, %119, %120, %121, %122, %123, %124, %125, %126, %127}, "
    "da, db, p, 1, 1, 0, 1;\n}\n"
    : "+f"(d[0]), "+f"(d[1]), "+f"(d[2]), "+f"(d[3]), "+f"(d[4]), "+f"(d[5]), "+f"(d[6]), "+f"(d[7]),
      "+f"(d[8]), "+f"(d[9]), "+f"(d[10]), "+f"(d[11]), "+f"(d[12]), "+f"(d[13]), "+f"(d[14]), "+f"(d[15]),
      "+f"(d[16]), "+f"(d[17]), "+f"(d[18]), "+f"(d[19]), "+f"(d[20]), "+f"(d[21]), "+f"(d[22]), "+f"(d[23]),
      "+f"(d[24]), "+f"(d[25]), "+f"(d[26]), "+f"(d[27]), "+f"(d[28]), "+f"(d[29]), "+f"(d[30]), "+f"(d[31]),
      "+f"(d[32]), "+f"(d[33]), "+f"(d[34]), "+f"(d[35]), "+f"(d[36]), "+f"(d[37]), "+f"(d[38]), "+f"(d[39]),
      "+f"(d[40]), "+f"(d[41]), "+f"(d[42]), "+f"(d[43]), "+f"(d[44]), "+f"(d[45]), "+f"(d[46]), "+f"(d[47]),
      "+f"(d[48]), "+f"(d[49]), "+f"(d[50]), "+f"(d[51]), "+f"(d[52]), "+f"(d[53]), "+f"(d[54]), "+f"(d[55]),
      "+f"(d[56]), "+f"(d[57]), "+f"(d[58]), "+f"(d[59]), "+f"(d[60]), "+f"(d[61]), "+f"(d[62]), "+f"(d[63]),
      "+f"(d[64]), "+f"(d[65]), "+f"(d[66]), "+f"(d[67]), "+f"(d[68]), "+f"(d[69]), "+f"(d[70]), "+f"(d[71]),
      "+f"(d[72]), "+f"(d[73]), "+f"(d[74]), "+f"(d[75]), "+f"(d[76]), "+f"(d[77]), "+f"(d[78]), "+f"(d[79]),
      "+f"(d[80]), "+f"(d[81]), "+f"(d[82]), "+f"(d[83]), "+f"(d[84]), "+f"(d[85]), "+f"(d[86]), "+f"(d[87]),
      "+f"(d[88]), "+f"(d[89]), "+f"(d[90]), "+f"(d[91]), "+f"(d[92]), "+f"(d[93]), "+f"(d[94]), "+f"(d[95]),
      "+f"(d[96]), "+f"(d[97]), "+f"(d[98]), "+f"(d[99]), "+f"(d[100]), "+f"(d[101]), "+f"(d[102]), "+f"(d[103]),
      "+f"(d[104]), "+f"(d[105]), "+f"(d[106]), "+f"(d[107]), "+f"(d[108]), "+f"(d[109]), "+f"(d[110]), "+f"(d[111]),
      "+f"(d[112]), "+f"(d[113]), "+f"(d[114]), "+f"(d[115]), "+f"(d[116]), "+f"(d[117]), "+f"(d[118]), "+f"(d[119]),
      "+f"(d[120]), "+f"(d[121]), "+f"(d[122]), "+f"(d[123]), "+f"(d[124]), "+f"(d[125]), "+f"(d[126]), "+f"(d[127])
    : "r"(da), "r"(db), "r"(scale_d));
}

namespace {

constexpr int SEQ = 2048, DM = 1024, FF = 3584;
constexpr int NCTA = 128;

constexpr uint32_t STG_OFF = 196608;
constexpr uint32_t MISC_OFF = STG_OFF + 32768;
constexpr uint32_t SMEM_BYTES = MISC_OFF + 3072;
constexpr uint32_t RED_OFF = 2 * 49152;
constexpr uint32_t MODB_OFF = MISC_OFF + 512;

enum { B_FQ = 0, B_EQ = 4, B_FW = 8, B_EW = 14, B_FG = 20, B_EG = 24, B_FD = 28, B_ED = 34,
       B_STGF = 40, B_MODB = 42, B_MODA = 45, B_RDY = 46, B_STGE = 58, B_COUNT = 60 };
enum { C_H = 0, C_O = 1, C_H2 = 3, C_ACT = 4, C_HA = 8, C_H2A = 9, C_A0 = 10, C_SP = 12 };

struct Params {
  CUtensorMap h, o_ld, o_st, h2, act, out, wqkv, wqkv32, wo, wg, wu, wd, act_st, h2_st, wm;
  const bf16* x;
  const bf16* c;
  const bf16* wmod;
  uint4* modll;
  uint4* halo;
  uint2* stats1;
  uint2* stats2;
  unsigned* cnt;
  unsigned* epoch;
  uint8_t slot[64];
};

__device__ __align__(1024) bf16 g_h[SEQ * DM];
__device__ __align__(1024) bf16 g_o[SEQ * DM];
__device__ __align__(1024) bf16 g_act[SEQ * FF];
__device__ __align__(1024) uint4 g_modll[3072 / 2];
__device__ __align__(1024) uint4 g_halo[16 * 8 * 2 * 2 * 8 * 32];
__device__ __align__(1024) uint2 g_stats[2 * SEQ * 8];
__device__ __align__(1024) unsigned g_cnt[16 * 32];
__device__ uint4 g_epoch;
#define TR(off)

__device__ __forceinline__ uint32_t smem_u32(const void* p) { return (uint32_t)__cvta_generic_to_shared(p); }
__device__ __forceinline__ void mbar_init(uint32_t bar, uint32_t count) {
  asm volatile("mbarrier.init.shared::cta.b64 [%0], %1;" ::"r"(bar), "r"(count));
}
__device__ __forceinline__ void mbar_arrive(uint32_t bar) {
  asm volatile("mbarrier.arrive.shared::cta.b64 _, [%0];" ::"r"(bar) : "memory");
}
__device__ __forceinline__ void mbar_arrive_cluster(uint32_t cluster_addr) {
  asm volatile("mbarrier.arrive.shared::cluster.b64 _, [%0];" ::"r"(cluster_addr) : "memory");
}
__device__ __forceinline__ uint32_t mapa(uint32_t addr, uint32_t cta) {
  uint32_t r;
  asm volatile("mapa.shared::cluster.u32 %0, %1, %2;" : "=r"(r) : "r"(addr), "r"(cta));
  return r;
}
__device__ __forceinline__ void mbar_wait(uint32_t bar, uint32_t parity) {
  asm volatile(
      "{\n.reg .pred p;\n"
      "WAIT_%=:\n"
      "mbarrier.try_wait.parity.shared::cta.b64 p, [%0], %1;\n"
      "@!p bra WAIT_%=;\n}\n" ::"r"(bar), "r"(parity) : "memory");
}
__device__ __forceinline__ void mbar_wait_watchdog(uint32_t bar, uint32_t parity) {
  asm volatile(
      "{\n.reg .pred p;\n.reg .u64 t0, t1;\nmov.u64 t0, %%globaltimer;\n"
      "WAIT_%=:\n"
      "mbarrier.try_wait.parity.shared::cta.b64 p, [%0], %1;\n"
      "@p bra DONE_%=;\n"
      "mov.u64 t1, %%globaltimer;\n"
      "sub.u64 t1, t1, t0;\n"
      "setp.lt.u64 p, t1, 2000000000;\n"
      "@p bra WAIT_%=;\n"
      "trap;\n"
      "DONE_%=:\n}\n" ::"r"(bar), "r"(parity) : "memory");
}
__device__ __forceinline__ void cnt_wait(const unsigned* p, unsigned target) {
  asm volatile(
      "{\n.reg .pred p;\n.reg .u32 v;\n.reg .s32 d;\n"
      "WAIT_%=:\n"
      "ld.relaxed.gpu.global.u32 v, [%0];\n"
      "sub.s32 d, v, %1;\n"
      "setp.lt.s32 p, d, 0;\n"
      "@p bra WAIT_%=;\n"
      "fence.proxy.async.global;\n"
      "}\n" ::"l"(p), "r"(target) : "memory");
}
__device__ __forceinline__ void cnt_wait_lazy(const unsigned* p, unsigned target) {
  asm volatile(
      "{\n.reg .pred p;\n.reg .u32 v;\n.reg .s32 d;\n"
      "WAIT_%=:\n"
      "nanosleep.u32 400;\n"
      "ld.relaxed.gpu.global.u32 v, [%0];\n"
      "sub.s32 d, v, %1;\n"
      "setp.lt.s32 p, d, 0;\n"
      "@p bra WAIT_%=;\n"
      "fence.proxy.async.global;\n"
      "}\n" ::"l"(p), "r"(target) : "memory");
}
__device__ __forceinline__ void cnt_signal(unsigned* p) {
  asm volatile("{\n.reg .pred p;\nelect.sync _|p, 0xffffffff;\n@p red.relaxed.gpu.global.add.u32 [%0], 1;\n}\n" ::"l"(p) : "memory");
}
__device__ __forceinline__ void ll_store(uint4* p, uint32_t a, uint32_t b, uint32_t tag) {
  asm volatile("st.relaxed.gpu.global.v2.b64 [%0], {%1, %2};" ::"l"(p), "l"((uint64_t)a | ((uint64_t)tag << 32)),
               "l"((uint64_t)b | ((uint64_t)tag << 32)) : "memory");
}
__device__ __forceinline__ uint4 ll_peek(const uint4* p) {
  uint4 v;
  asm volatile("ld.relaxed.gpu.global.v4.u32 {%0, %1, %2, %3}, [%4];" : "=r"(v.x), "=r"(v.y), "=r"(v.z), "=r"(v.w) : "l"(p) : "memory");
  return v;
}
template <int N, int SLEEP = 0, class F>
__device__ __forceinline__ void ll_poll(F addr, uint32_t tag, uint32_t (&out)[2 * N]) {
  for (;;) {
    uint4 v[N];
#pragma unroll
    for (int i = 0; i < N; i++) v[i] = ll_peek(addr(i));
    uint32_t bad = 0;
#pragma unroll
    for (int i = 0; i < N; i++) {
      bad |= (v[i].y ^ tag) | (v[i].w ^ tag);
      out[2 * i] = v[i].x;
      out[2 * i + 1] = v[i].z;
    }
    if (__all_sync(~0u, bad == 0)) break;
    if (SLEEP) __nanosleep(SLEEP);
  }
}
constexpr uint64_t POLICY_EVICT_FIRST = 0x12F0000000000000ull;
__device__ __forceinline__ void expect_tx_elect(uint32_t bar, uint32_t bytes) {
  asm volatile("{\n.reg .pred p;\nelect.sync _|p, 0xffffffff;\n@p mbarrier.arrive.expect_tx.shared::cta.b64 _, [%0], %1;\n}\n" ::"r"(bar), "r"(bytes) : "memory");
}
__device__ __forceinline__ void arrive_elect(uint32_t bar) {
  asm volatile("{\n.reg .pred p;\nelect.sync _|p, 0xffffffff;\n@p mbarrier.arrive.shared::cta.b64 _, [%0];\n}\n" ::"r"(bar) : "memory");
}
__device__ __forceinline__ void tma_load(uint32_t dst, const CUtensorMap* m, uint32_t bar, int c0, int c1) {
  asm volatile("{\n.reg .pred p;\nelect.sync _|p, 0xffffffff;\n"
               "@p cp.async.bulk.tensor.2d.shared::cluster.global.mbarrier::complete_tx::bytes [%0], [%1, {%3, %4}], [%2];\n}\n"
               ::"r"(dst), "l"(m), "r"(bar), "r"(c0), "r"(c1) : "memory");
}
__device__ __forceinline__ void tma_load_mc(uint32_t dst, const CUtensorMap* m, uint32_t bar, int c0, int c1) {
  asm volatile("{\n.reg .pred p;\nelect.sync _|p, 0xffffffff;\n"
               "@p cp.async.bulk.tensor.2d.shared::cluster.global.mbarrier::complete_tx::bytes.multicast::cluster.L2::cache_hint [%0], [%1, {%3, %4}], [%2], %5, %6;\n}\n"
               ::"r"(dst), "l"(m), "r"(bar), "r"(c0), "r"(c1), "h"((uint16_t)3), "l"(POLICY_EVICT_FIRST) : "memory");
}
__device__ __forceinline__ void tma_load_ef(uint32_t dst, const CUtensorMap* m, uint32_t bar, int c0, int c1) {
  asm volatile("{\n.reg .pred p;\nelect.sync _|p, 0xffffffff;\n"
               "@p cp.async.bulk.tensor.2d.shared::cluster.global.mbarrier::complete_tx::bytes.L2::cache_hint [%0], [%1, {%3, %4}], [%2], %5;\n}\n"
               ::"r"(dst), "l"(m), "r"(bar), "r"(c0), "r"(c1), "l"(POLICY_EVICT_FIRST) : "memory");
}
__device__ __forceinline__ void tma_store2(const CUtensorMap* m, uint32_t src, int c0, int c1) {
  asm volatile("{\n.reg .pred p;\nelect.sync _|p, 0xffffffff;\n"
               "@p cp.async.bulk.tensor.2d.global.shared::cta.bulk_group [%0, {%2, %3}], [%1];\n}\n"
               ::"l"(m), "r"(src), "r"(c0), "r"(c1) : "memory");
}
__device__ __forceinline__ void tma_store3(const CUtensorMap* m, uint32_t src, int c0, int c1, int c2) {
  asm volatile("{\n.reg .pred p;\nelect.sync _|p, 0xffffffff;\n"
               "@p cp.async.bulk.tensor.3d.global.shared::cta.bulk_group [%0, {%2, %3, %4}], [%1];\n}\n"
               ::"l"(m), "r"(src), "r"(c0), "r"(c1), "r"(c2) : "memory");
}
__device__ __forceinline__ void tma_add3(const CUtensorMap* m, uint32_t src, int c0, int c1, int c2) {
  asm volatile("{\n.reg .pred p;\nelect.sync _|p, 0xffffffff;\n"
               "@p cp.reduce.async.bulk.tensor.3d.global.shared::cta.add.bulk_group [%0, {%2, %3, %4}], [%1];\n}\n"
               ::"l"(m), "r"(src), "r"(c0), "r"(c1), "r"(c2) : "memory");
}
__device__ __forceinline__ void store_pause(bool sleep) {
  asm volatile("cp.async.bulk.commit_group;" ::: "memory");
  asm volatile("cp.async.bulk.wait_group.read 0;" ::: "memory");
  if (sleep) __nanosleep(PAUSE);
}
__device__ __forceinline__ void l2_prefetch_tile(const CUtensorMap* m, int c0, int c1) {
  asm volatile("{\n.reg .pred p;\nelect.sync _|p, 0xffffffff;\n@p cp.async.bulk.prefetch.tensor.2d.L2.global [%0, {%1, %2}];\n}\n"
               ::"l"(m), "r"(c0), "r"(c1) : "memory");
}
__device__ __forceinline__ void prefetch_map(const CUtensorMap* m) {
  asm volatile("prefetch.tensormap [%0];" ::"l"(m) : "memory");
}
__device__ __forceinline__ void wg_fence() { asm volatile("wgmma.fence.sync.aligned;" ::: "memory"); }
__device__ __forceinline__ void wg_commit() { asm volatile("wgmma.commit_group.sync.aligned;" ::: "memory"); }
template <int N>
__device__ __forceinline__ void wg_wait() { asm volatile("wgmma.wait_group.sync.aligned %0;" ::"n"(N) : "memory"); }
__device__ __forceinline__ void bar_sync(int id, int n) { asm volatile("bar.sync %0, %1;" ::"r"(id), "r"(n) : "memory"); }
__device__ __forceinline__ void wg_bar(int cw) {
  asm volatile("{\n.reg .pred p;\nsetp.ne.s32 p, %0, 0;\n@p bar.sync 3, 128;\n@!p bar.sync 2, 128;\n}\n" ::"r"(cw) : "memory");
}
__device__ __forceinline__ void cluster_arrive_relaxed() { asm volatile("barrier.cluster.arrive.relaxed.aligned;" ::: "memory"); }
__device__ __forceinline__ void cluster_wait() { asm volatile("barrier.cluster.wait.acquire.aligned;" ::: "memory"); }
__device__ __forceinline__ uint32_t load_epoch(const unsigned* p) {
  uint32_t e;
  asm volatile("ld.relaxed.gpu.global.u32 %0, [%1];" : "=r"(e) : "l"(p) : "memory");
  return e;
}
__device__ __forceinline__ uint32_t pack2(float lo, float hi) {
  uint32_t r;
  asm("cvt.rn.bf16x2.f32 %0, %1, %2;" : "=r"(r) : "f"(hi), "f"(lo));
  return r;
}
__device__ __forceinline__ float bf_lo(uint32_t v) { return __uint_as_float(v << 16); }
__device__ __forceinline__ float bf_hi(uint32_t v) { return __uint_as_float(v & 0xffff0000u); }
__device__ __forceinline__ uint32_t fma_bf2(uint32_t a, uint32_t b, uint32_t c) {
  uint32_t d;
  asm("fma.rn.bf16x2 %0, %1, %2, %3;" : "=r"(d) : "r"(a), "r"(b), "r"(c));
  return d;
}
__device__ __forceinline__ float bf_round(float v) { return __bfloat162float(__float2bfloat16_rn(v)); }
__device__ __forceinline__ float silu_f(float v) { return __fdividef(v, 1.0f + __expf(-v)); }
__device__ __forceinline__ uint4 ldg_nc(const void* p) {
  uint4 v;
  asm volatile("ld.global.nc.L1::no_allocate.v4.u32 {%0, %1, %2, %3}, [%4];" : "=r"(v.x), "=r"(v.y), "=r"(v.z), "=r"(v.w) : "l"(p));
  return v;
}
__device__ __forceinline__ void stmatrix4(uint32_t addr, uint32_t a, uint32_t b, uint32_t c, uint32_t d) {
  asm volatile("stmatrix.sync.aligned.m8n8.x4.shared.b16 [%0], {%1, %2, %3, %4};" ::"r"(addr), "r"(a), "r"(b), "r"(c), "r"(d) : "memory");
}
__device__ __forceinline__ void stmatrix2(uint32_t addr, uint32_t a, uint32_t b) {
  asm volatile("stmatrix.sync.aligned.m8n8.x2.shared.b16 [%0], {%1, %2};" ::"r"(addr), "r"(a), "r"(b) : "memory");
}
__device__ __forceinline__ void stmatrix1(uint32_t addr, uint32_t a) {
  asm volatile("stmatrix.sync.aligned.m8n8.x1.shared.b16 [%0], {%1};" ::"r"(addr), "r"(a) : "memory");
}
__device__ __forceinline__ uint32_t movmatrix(uint32_t a) {
  uint32_t d;
  asm("movmatrix.sync.aligned.m8n8.trans.b16 %0, %1;" : "=r"(d) : "r"(a));
  return d;
}
__device__ __forceinline__ void mma16816(float (&d)[4], uint32_t a0, uint32_t a1, uint32_t a2, uint32_t a3, uint32_t b0, uint32_t b1) {
  asm("mma.sync.aligned.m16n8k16.row.col.f32.bf16.bf16.f32 {%0, %1, %2, %3}, {%4, %5, %6, %7}, {%8, %9}, {%0, %1, %2, %3};"
               : "+f"(d[0]), "+f"(d[1]), "+f"(d[2]), "+f"(d[3]) : "r"(a0), "r"(a1), "r"(a2), "r"(a3), "r"(b0), "r"(b1));
}
__device__ __forceinline__ void mma1688(float (&d)[4], uint32_t a0, uint32_t a1, uint32_t b0) {
  asm("mma.sync.aligned.m16n8k8.row.col.f32.bf16.bf16.f32 {%0, %1, %2, %3}, {%4, %5}, {%6}, {%0, %1, %2, %3};"
               : "+f"(d[0]), "+f"(d[1]), "+f"(d[2]), "+f"(d[3]) : "r"(a0), "r"(a1), "r"(b0));
}
__device__ __forceinline__ void ldmatrix4t(uint32_t (&b)[4], uint32_t addr) {
  asm volatile("ldmatrix.sync.aligned.m8n8.x4.trans.shared.b16 {%0, %1, %2, %3}, [%4];" : "=r"(b[0]), "=r"(b[1]), "=r"(b[2]), "=r"(b[3]) : "r"(addr) : "memory");
}
__device__ __forceinline__ void ldmatrix4(uint32_t& a, uint32_t& b, uint32_t& c, uint32_t& d, uint32_t addr) {
  asm volatile("ldmatrix.sync.aligned.m8n8.x4.shared.b16 {%0, %1, %2, %3}, [%4];" : "=r"(a), "=r"(b), "=r"(c), "=r"(d) : "r"(addr) : "memory");
}
__device__ __forceinline__ void cp_async16(uint32_t dst, const void* src) {
  asm volatile("cp.async.cg.shared.global.L2::cache_hint [%0], [%1], 16, %2;" ::"r"(dst), "l"(src), "l"(POLICY_EVICT_FIRST) : "memory");
}
__device__ __forceinline__ uint32_t lds32(uint32_t addr) {
  uint32_t v;
  asm volatile("ld.shared.u32 %0, [%1];" : "=r"(v) : "r"(addr) : "memory");
  return v;
}
__device__ __forceinline__ void sts64f(uint32_t addr, float a, float b) {
  asm volatile("st.shared.v2.f32 [%0], {%1, %2};" ::"r"(addr), "f"(a), "f"(b) : "memory");
}
constexpr float QK_SCALE = 0.17677669529663687f;
__device__ __forceinline__ float softmax8(float& p0, float& p1) {
  float m = fmaxf(p0, p1);
  m = fmaxf(m, __shfl_xor_sync(~0u, m, 1));
  m = fmaxf(m, __shfl_xor_sync(~0u, m, 2));
  asm("ex2.approx.ftz.f32 %0, %1;" : "=f"(p0) : "f"((p0 - m) * 1.4426950408889634f));
  asm("ex2.approx.ftz.f32 %0, %1;" : "=f"(p1) : "f"((p1 - m) * 1.4426950408889634f));
  float s = p0 + p1;
  s += __shfl_xor_sync(~0u, s, 1);
  s += __shfl_xor_sync(~0u, s, 2);
  float r;
  asm("rcp.approx.ftz.f32 %0, %1;" : "=f"(r) : "f"(s));
  return r;
}
__device__ __forceinline__ void sts128(uint32_t addr, uint32_t a, uint32_t b, uint32_t c, uint32_t d) {
  asm volatile("st.shared.v4.u32 [%0], {%1, %2, %3, %4};" ::"r"(addr), "r"(a), "r"(b), "r"(c), "r"(d) : "memory");
}
__device__ __forceinline__ uint4 lds128(uint32_t addr) {
  uint4 v;
  asm volatile("ld.shared.v4.u32 {%0, %1, %2, %3}, [%4];" : "=r"(v.x), "=r"(v.y), "=r"(v.z), "=r"(v.w) : "r"(addr) : "memory");
  return v;
}
__device__ __forceinline__ float2 lds64f(uint32_t addr) {
  float2 v;
  asm volatile("ld.shared.v2.f32 {%0, %1}, [%2];" : "=f"(v.x), "=f"(v.y) : "r"(addr) : "memory");
  return v;
}
#define PROF_AT(cond, slot) do {} while (0)

constexpr uint32_t SMEM_BASE = 1024;
constexpr uint32_t DESC_A = (1u << 16) | (SMEM_BASE >> 4);
constexpr uint32_t DESC_B = ((8192u >> 4) << 16) | (SMEM_BASE >> 4);

template <int BN> struct Wg;
template <> struct Wg<128> { static __device__ __forceinline__ void mma(float (&d)[64], uint32_t a, uint32_t b, int s) { wgmma_ss_n128(d, a, b, s); } };
template <> struct Wg<192> { static __device__ __forceinline__ void mma(float (&d)[96], uint32_t a, uint32_t b, int s) { wgmma_ss_n192(d, a, b, s); } };
template <> struct Wg<256> { static __device__ __forceinline__ void mma(float (&d)[128], uint32_t a, uint32_t b, int s) { wgmma_ss_n256(d, a, b, s); } };

struct Ring {
  uint32_t full0, rel0;
  int s;
  uint32_t ph;
  uint32_t off;
  bool releaser;
};

template <int N>
__device__ __forceinline__ void fence_regs(float (&a)[N]) {
#pragma unroll
  for (int i = 0; i < N; i++) asm volatile("" : "+f"(a[i])::"memory");
}

template <int BN, int NST, uint32_t STAGE>
__device__ __forceinline__ void kblock(float (&acc)[BN / 2], Ring& g, uint32_t a_addr, bool zero, uint32_t& prev, uint32_t b_rel = 16384) {
  mbar_wait(g.full0 + 8 * g.s, g.ph);
  const uint32_t da = DESC_A + (a_addr >> 4);
  const uint32_t db = DESC_B + ((g.off + b_rel) >> 4);
  wg_fence();
#pragma unroll
  for (int k = 0; k < 4; k++) Wg<BN>::mma(acc, da + k * 2, db + k * 128, !(zero && k == 0));
  wg_commit();
  wg_wait<1>();
  if (prev != 0) mbar_arrive_cluster(prev);
  prev = g.releaser ? g.rel0 + 8 * g.s : 0u;
  if (++g.s == NST) { g.s = 0; g.ph ^= 1; }
  g.off += STAGE;
  if (g.off == NST * STAGE) g.off = 0;
}
template <int N>
__device__ __forceinline__ void tile_end(float (&acc)[N], uint32_t& prev) {
  wg_wait<0>();
  if (prev != 0) mbar_arrive_cluster(prev);
  prev = 0;
  fence_regs(acc);
}

__device__ __forceinline__ int other_kb(int q, int j) {
  const int ch = q >= 7, jj = q - 7 * ch;
  return 2 * (jj < j ? jj : jj + 1) + ch;
}
__device__ __forceinline__ int qkv_kb(int it, int j) {
  return it < 4 ? 2 * j + (it & 1) : other_kb(it < 18 ? it - 4 : it - 18, j);
}
__device__ __forceinline__ int wo_k(int it, int j) {
  return it < 8 ? it * 128 : (it == 8 ? j : (it - 9 < j ? it - 9 : it - 8)) * 128 + 64;
}
__device__ __forceinline__ int down_k(int d) {
  const int u = d + KH;
  if (u < 8) return u * 448 + 384;
  if (u < 40) return (((u - 8) & 15) >> 1) * 448 + ((u - 8) >> 4) * 128 + (u & 1) * 64;
  return (u & 7) * 448 + 256 + (u >= 48 ? 64 : 0);
}
__device__ __forceinline__ void wait_q_free(uint32_t empty, int i) {
  mbar_wait(empty + 8 * ((i * 2) / 3), 1);
  mbar_wait(empty + 8 * ((i * 2 + 1) / 3), 1);
}
__device__ __forceinline__ void wait_w_free(uint32_t empty, int i) {
  const int t = (i + 3) & 3, w0 = (t * 3) / 2, w1 = (t * 3 + 2) / 2;
  mbar_wait(empty + 8 * w0, w0 < 4);
  mbar_wait(empty + 8 * w1, w1 < 4);
}
__device__ __forceinline__ void wait_g_free(uint32_t empty, int i) {
  const int s = i < 4 ? i + 2 : i - 4, b0 = ((s * 2) / 3 + 1) & 3, b1 = ((s * 2 + 1) / 3 + 1) & 3;
  mbar_wait(empty + 8 * b0, b0 < 2);
  mbar_wait(empty + 8 * b1, b1 < 2);
}

__device__ __forceinline__ void chan(float& m, float& q, float m2, float q2, float n) {
  const float d = m2 - m;
  m = 0.5f * (m + m2);
  q = q + q2 + d * d * (0.5f * n);
}

__device__ __forceinline__ uint32_t tag16(uint32_t tag) { return tag % 65535u + 1u; }
__device__ __forceinline__ void stat_store(uint2* slot, float m, float q, uint32_t t16) {
  const uint32_t a = ((__float_as_uint(m) + 0x80u) & 0xffffff00u) | (t16 & 0xffu), b = ((__float_as_uint(q) + 0x80u) & 0xffffff00u) | (t16 >> 8);
  asm volatile("st.relaxed.gpu.global.b64 [%0], %1;" ::"l"(slot), "l"((uint64_t)a | ((uint64_t)b << 32)) : "memory");
}
__device__ __forceinline__ void stat_gather(const uint2* rows, uint32_t t16, int lane, float (&rs)[2], float (&nb)[2]) {
  const uint4* sp = (const uint4*)(rows + (lane >> 3) * 128) + (lane & 7);
  const uint32_t want = (t16 & 0xffu) | ((t16 >> 8) << 8);
  uint4 a, b;
  for (;;) {
    a = ll_peek(sp);
    b = ll_peek(sp + 256);
    const uint32_t bad = (__byte_perm(a.x, a.y, 0x40) ^ want) | (__byte_perm(a.z, a.w, 0x40) ^ want) | (__byte_perm(b.x, b.y, 0x40) ^ want) |
                         (__byte_perm(b.z, b.w, 0x40) ^ want);
    if (__all_sync(~0u, (bad & 0xffffu) == 0)) break;
  }
  float m0 = __uint_as_float(a.x & 0xffffff00u), q0 = __uint_as_float(a.y & 0xffffff00u);
  float m1 = __uint_as_float(a.z & 0xffffff00u), q1 = __uint_as_float(a.w & 0xffffff00u);
  chan(m0, q0, __uint_as_float(b.x & 0xffffff00u), __uint_as_float(b.y & 0xffffff00u), 128.f);
  chan(m1, q1, __uint_as_float(b.z & 0xffffff00u), __uint_as_float(b.w & 0xffffff00u), 128.f);
  const bool hi = lane & 8;
  float m = hi ? m1 : m0, q = hi ? q1 : q0;
  chan(m, q, __shfl_xor_sync(~0u, hi ? m0 : m1, 8), __shfl_xor_sync(~0u, hi ? q0 : q1, 8), 256.f);
  chan(m, q, __shfl_xor_sync(~0u, m, 16), __shfl_xor_sync(~0u, q, 16), 512.f);
  const float rstd = rsqrtf(q * (1.0f / DM) + 1e-5f), nmr = -m * rstd;
  const int r = lane >> 2, src = (r >> 1) + (r & 1) * 8;
  rs[0] = __shfl_sync(~0u, rstd, src); nb[0] = __shfl_sync(~0u, nmr, src);
  rs[1] = __shfl_sync(~0u, rstd, src + 4); nb[1] = __shfl_sync(~0u, nmr, src + 4);
}

__device__ __forceinline__ void publish_stats(const uint32_t (&xl)[16], const uint32_t (&xh)[16], uint2* slot, int lane, uint32_t t16) {
  float ds[4] = {0.f, 0.f, 0.f, 0.f}, dl[4] = {0.f, 0.f, 0.f, 0.f}, dh[4] = {0.f, 0.f, 0.f, 0.f};
#pragma unroll
  for (int q = 0; q < 8; q++) {
    mma16816(ds, xl[2 * q], xh[2 * q], xl[2 * q + 1], xh[2 * q + 1], 0x3f803f80u, 0x3f803f80u);
    mma16816(dl, xl[2 * q], xh[2 * q], xl[2 * q + 1], xh[2 * q + 1], xl[2 * q], xl[2 * q + 1]);
    mma16816(dh, xl[2 * q], xh[2 * q], xl[2 * q + 1], xh[2 * q + 1], xh[2 * q], xh[2 * q + 1]);
  }
  const int r = lane >> 2;
  if ((lane & 3) == (r >> 1)) {
    const float ml = ds[0] * (1.0f / 128), mh = ds[2] * (1.0f / 128);
    const float ql = fmaxf(((r & 1) ? dl[1] : dl[0]) - ds[0] * ml, 0.f), qh = fmaxf(((r & 1) ? dh[3] : dh[2]) - ds[2] * mh, 0.f);
    stat_store(slot + r, ml, ql, t16);
    stat_store(slot + r + 8, mh, qh, t16);
  }
  __syncwarp();
}

__device__ __forceinline__ void stage_slab(uint32_t chunk, int warp, int lane, const uint32_t (&lo)[8], const uint32_t (&hi)[8]) {
  const int row = warp * 16 + (lane & 7) + ((lane >> 3) & 1) * 8;
  const uint32_t rbase = chunk + row * 128;
#pragma unroll
  for (int q = 0; q < 4; q++) {
    const int grp = 2 * q + (lane >> 4);
    stmatrix4(rbase + ((grp ^ (row & 7)) << 4), lo[2 * q], hi[2 * q], lo[2 * q + 1], hi[2 * q + 1]);
  }
}
__device__ __forceinline__ float silu_mul(float g, float u) {
  float e, r;
  asm("ex2.approx.ftz.f32 %0, %1;" : "=f"(e) : "f"(g * -1.4426950408889634f));
  asm("rcp.approx.ftz.f32 %0, %1;" : "=f"(r) : "f"(1.0f + e));
  return g * r * u;
}
__device__ __forceinline__ uint32_t swiglu2(uint32_t g2, uint32_t u2) {
  asm volatile("" : "+r"(g2));
  return pack2(silu_mul(bf_lo(g2), bf_lo(u2)), silu_mul(bf_hi(g2), bf_hi(u2)));
}
__device__ __forceinline__ void stage_done(uint32_t bar, int lane) {
  asm volatile("fence.proxy.async.shared::cta;" ::: "memory");
  __syncwarp();
  if (lane == 0) mbar_arrive(bar);
}

__device__ __forceinline__ int fresh_tid() {
  int t;
  asm volatile("mov.u32 %0, %%tid.x;" : "=r"(t));
  return t;
}
#define RING_IDS()                                                                                           \
  const int tid = fresh_tid() - 128;                                                                         \
  const int cw = __shfl_sync(~0u, tid >> 7, 0), warp = __shfl_sync(~0u, (tid >> 5) & 3, 0);                  \
  const bool releaser = (tid & 31) < 2;                                                                      \
  const uint32_t rbars = mapa(bars, tid & 1);                                                                \
  const uint32_t a_base = cw * 8192
#define LANE_IDS()                                                                                           \
  const int lane = fresh_tid() & 31, r = lane >> 2, c = lane & 3;                                            \
  const int srow = warp * 16 + (lane & 7) + ((lane >> 3) & 1) * 8;                                           \
  const uint32_t slab = stg + cw * 8192 + srow * 128, sw0 = (lane >> 4) ^ (srow & 7);                        \
  (void)r; (void)c; (void)slab; (void)sw0

template <int NPRE, bool EAGER, class Step>
__device__ __forceinline__ void attention(float (&acc)[96], const Params& p, int rho, int rb, int cta, int cw, int warp, uint32_t tag,
                                          uint32_t stg, uint32_t bars, uint32_t& prev, Step step) {
  uint32_t ql[8], qh[8], k0[8], k1[8], v0[8], v1[8], hp[16];
  if (EAGER) {
    tile_end(acc, prev);
  } else {
    step();
    fence_regs(acc);
  }
#pragma unroll
  for (int t = 0; t < 8; t++) {
    k0[t] = pack2(acc[4 * (8 + t)], acc[4 * (8 + t) + 1]);
    k1[t] = pack2(acc[4 * (8 + t) + 2], acc[4 * (8 + t) + 3]);
    v0[t] = pack2(acc[4 * (16 + t)], acc[4 * (16 + t) + 1]);
    v1[t] = pack2(acc[4 * (16 + t) + 2], acc[4 * (16 + t) + 3]);
    asm volatile("" : "+r"(k0[t]), "+r"(k1[t]), "+r"(v0[t]), "+r"(v1[t]));
  }
  const int lane = fresh_tid() & 31, r = lane >> 2, c = lane & 3;
#pragma unroll
  for (int t = 0; t < 8; t++) v1[t] = movmatrix(v1[t]);
  mbar_wait(bars + 8 * B_STGE, rho);
  mbar_wait(bars + 8 * (B_STGE + 1), 0);
  const uint32_t xch = stg + 16384 + (cw * 4 + warp) * 2048 + lane * 16;
  if (warp < 3) {
    sts128(xch, k1[0], k1[1], k1[2], k1[3]);
    sts128(xch + 512, k1[4], k1[5], k1[6], k1[7]);
    sts128(xch + 1024, v1[0], v1[1], v1[2], v1[3]);
    sts128(xch + 1536, v1[4], v1[5], v1[6], v1[7]);
  } else if (rb < 15) {
    uint4* dst = p.halo + ((cta * 2 + rho) * 2 + cw) * 256 + lane;
#pragma unroll
    for (int t = 0; t < 4; t++) {
      ll_store(dst + t * 32, k1[2 * t], k1[2 * t + 1], tag);
      ll_store(dst + (4 + t) * 32, v1[2 * t], v1[2 * t + 1], tag);
    }
  }
#pragma unroll
  for (int t = 0; t < 8; t++) {
    v0[t] = movmatrix(v0[t]);
    ql[t] = pack2(acc[4 * t], acc[4 * t + 1]);
    qh[t] = pack2(acc[4 * t + 2], acc[4 * t + 3]);
    asm volatile("" : "+r"(v0[t]), "+r"(ql[t]), "+r"(qh[t]));
  }
#pragma unroll 1
  for (int i = 0; i < NPRE; i++) step();
  const uint4* src = p.halo + (((cta - 8) * 2 + rho) * 2 + cw) * 256 + lane;
  uint4 early[8] = {};
  if (warp == 0 && rb > 0) {
#pragma unroll
    for (int i = 0; i < 8; i++) early[i] = ll_peek(src + i * 32);
  }
  step();
  wg_bar(cw);
  if (warp > 0) {
#pragma unroll
    for (int t = 0; t < 4; t++) {
      const uint4 a = lds128(xch - 2048 + t * 512);
      hp[4 * t] = a.x; hp[4 * t + 1] = a.y; hp[4 * t + 2] = a.z; hp[4 * t + 3] = a.w;
    }
  } else if (rb > 0) {
    uint32_t bad = 0;
#pragma unroll
    for (int i = 0; i < 8; i++) {
      bad |= (early[i].y ^ tag) | (early[i].w ^ tag);
      hp[2 * i] = early[i].x;
      hp[2 * i + 1] = early[i].z;
    }
    if (!__all_sync(~0u, bad == 0)) ll_poll<8>([&](int i) { return src + i * 32; }, tag, hp);
  } else {
#pragma unroll
    for (int t = 0; t < 16; t++) hp[t] = 0;
  }
  wg_wait<0>();
  if (prev != 0) mbar_arrive_cluster(prev);
  prev = 0;
#pragma unroll
  for (int t = 0; t < 8; t++) asm volatile("" : "+r"(ql[t])::"memory");
  const bool up0 = 2 * c > r, up1 = 2 * c + 1 > r;
  const bool first = (rb == 0) && (warp == 0);
  uint32_t a0[2], a2[2], a3[2], a5[2];
  float il[2], ih[2];
#pragma unroll
  for (int h = 0; h < 2; h++) {
    float sp[4] = {0.f, 0.f, 0.f, 0.f}, s0[4] = {0.f, 0.f, 0.f, 0.f}, s1[4] = {0.f, 0.f, 0.f, 0.f};
#pragma unroll
    for (int ks = 0; ks < 2; ks++) {
      const int t = 4 * h + 2 * ks;
      mma16816(sp, ql[t], qh[t], ql[t + 1], qh[t + 1], hp[t], hp[t + 1]);
      mma16816(s0, ql[t], qh[t], ql[t + 1], qh[t + 1], k0[t], k0[t + 1]);
      mma16816(s1, ql[t], qh[t], ql[t + 1], qh[t + 1], k1[t], k1[t + 1]);
    }
    float p0 = (up0 ? sp[0] : s0[0]) * QK_SCALE, p1 = (up1 ? sp[1] : s0[1]) * QK_SCALE;
    float p2 = (up0 ? s0[2] : s1[2]) * QK_SCALE, p3 = (up1 ? s0[3] : s1[3]) * QK_SCALE;
    if (first && up0) p0 = -1000000000.0f;
    if (first && up1) p1 = -1000000000.0f;
    il[h] = softmax8(p0, p1);
    ih[h] = softmax8(p2, p3);
    a0[h] = pack2(up0 ? p0 : 0.f, up1 ? p1 : 0.f);
    a2[h] = pack2(up0 ? 0.f : p0, up1 ? 0.f : p1);
    a3[h] = pack2(up0 ? p2 : 0.f, up1 ? p3 : 0.f);
    a5[h] = pack2(up0 ? 0.f : p2, up1 ? 0.f : p3);
  }
  float o[8][4];
#pragma unroll
  for (int t = 0; t < 8; t++) {
#pragma unroll
    for (int q = 0; q < 4; q++) o[t][q] = 0.f;
    mma1688(o[t], 0u, a5[t >> 2], v1[t]);
    mma16816(o[t], a0[t >> 2], 0u, a2[t >> 2], a3[t >> 2], hp[8 + t], v0[t]);
  }
#pragma unroll
  for (int t = 0; t < 8; t++) fence_regs(o[t]);
  if (!EAGER) step();
  uint32_t ol[8], oh[8];
#pragma unroll
  for (int t = 0; t < 8; t++) {
    ol[t] = pack2(o[t][0] * il[t >> 2], o[t][1] * il[t >> 2]);
    oh[t] = pack2(o[t][2] * ih[t >> 2], o[t][3] * ih[t >> 2]);
  }
  if (!EAGER) step();
  stage_slab(stg + cw * 8192, warp, lane, ol, oh);
  stage_done(bars + 8 * B_STGF, lane);
  if (!EAGER) step();
}

__global__ void __launch_bounds__(384, 1) fused_kernel(const __grid_constant__ Params p) {
  extern __shared__ __align__(1024) uint8_t smem_raw[];
  const uint32_t sm = smem_u32(smem_raw);
  const uint32_t bars = sm + MISC_OFF;
  const uint32_t stg = sm + STG_OFF;
  const int rank = blockIdx.x & 1;
  const int cl = blockIdx.x >> 1;
  if (cl >= NCTA / 2) {
    const int e = blockIdx.x - NCTA, wid = __shfl_sync(~0u, (int)(threadIdx.x >> 5), 0), lane = threadIdx.x & 31;
    if (threadIdx.x == 0) {
      for (int i = 0; i < 6; i++) { mbar_init(bars + 8 * i, 1); mbar_init(bars + 8 * (6 + i), 8); }
      for (int i = 0; i < 8; i++) { mbar_init(bars + 8 * (16 + i), 1); mbar_init(bars + 8 * (24 + i), 4); }
      mbar_init(bars + 8 * 12, 1);
      asm volatile("fence.mbarrier_init.release.cluster;" ::: "memory");
    }
    const uint32_t tag = load_epoch(p.epoch) + 1;
    if (threadIdx.x < 256) ll_store(p.modll + 512 + (threadIdx.x >> 6) * 256 + e * 64 + (threadIdx.x & 63), 0u, 0u, 0u);
    for (int i = threadIdx.x; i < 1536; i += 384) {
      uint4 o = make_uint4(0u, 0u, 0u, 0u);
      if (i < 1024 && (i & 63) < 8) {
        const uint4 cv = ldg_nc(p.c + (i >> 6) * 64 + (i & 7) * 8);
        o = make_uint4(pack2(silu_f(bf_lo(cv.x)), silu_f(bf_hi(cv.x))), pack2(silu_f(bf_lo(cv.y)), silu_f(bf_hi(cv.y))),
                       pack2(silu_f(bf_lo(cv.z)), silu_f(bf_hi(cv.z))), pack2(silu_f(bf_lo(cv.w)), silu_f(bf_hi(cv.w))));
      }
      sts128(stg + i * 16, o.x, o.y, o.z, o.w);
    }
    asm volatile("fence.proxy.async.shared::cta;" ::: "memory");
    __syncthreads();
    if (wid == 0) {
      __nanosleep(WMDELAY);
      uint32_t ph = 1;
#pragma unroll 1
      for (int it = 0, s = 0; it < 64; it++) {
        mbar_wait(bars + 8 * (6 + s), ph);
        expect_tx_elect(bars + 8 * s, 32768);
#pragma unroll
        for (int q = 0; q < 4; q++) tma_load_ef(sm + s * 32768 + q * 8192, &p.wm, bars + 8 * s, 2048 + (it >> 4) * 1024 + e * 256 + q * 64, (it & 15) * 64);
        if (++s == 6) { s = 0; ph ^= 1; }
      }
    } else if (wid == 1 && PFW) {
      __nanosleep(PFW);
#pragma unroll 1
      for (int i = 0; i < 64; i++) {
        l2_prefetch_tile(&p.wo, (i & 15) * 64, (e * 4 + (i >> 4)) * 64);
        if (PFP) __nanosleep(PFP);
      }
#pragma unroll 1
      for (int i = 0; i < 80; i++) {
        if (i < 64) l2_prefetch_tile((i & 1) ? &p.wu : &p.wg, ((i >> 1) & 7) * 448 + 384, ((i >> 4) * 4 + e) * 64);
        else l2_prefetch_tile((i & 2) ? &p.wu : &p.wg, (e * 2 + ((i >> 3) & 1)) * 448 + (i & 1) * 64, (e * 4 + ((i >> 2) & 3)) * 64);
        if (PFP) __nanosleep(PFP);
      }
    } else if (wid >= 4) {
      const int hf = (wid >> 2) - 1;
      uint32_t ph = 0;
      int s = 0;
#pragma unroll 1
      for (int v = 0; v < 4; v++) {
        float acc[64];
#pragma unroll 1
        for (int kb = 0; kb < 16; kb++) {
          mbar_wait_watchdog(bars + 8 * s, ph);
          const uint32_t da = DESC_A + ((STG_OFF + kb * 1024) >> 4), db = DESC_B + ((s * 32768 + hf * 16384) >> 4);
          wg_fence();
#pragma unroll
          for (int k = 0; k < 4; k++) wgmma_ss_n128(acc, da + k * 2, db + k * 128, (kb | k) != 0);
          wg_commit();
          wg_wait<0>();
          if (lane == 0) mbar_arrive(bars + 8 * (6 + s));
          if (++s == 6) { s = 0; ph ^= 1; }
        }
        fence_regs(acc);
        if ((wid & 3) == 0) {
#pragma unroll
          for (int n = 0; n < 16; n++) {
            const uint32_t mine = pack2(acc[4 * n], acc[4 * n + 1]), next = __shfl_down_sync(~0u, mine, 1);
            if (lane < 4 && (lane & 1) == 0) ll_store(p.modll + 512 + v * 256 + e * 64 + hf * 32 + n * 2 + (lane >> 1), mine, next, tag);
            if (lane < 4) sts64f(sm + MODB_OFF + (hf * 128 + n * 8 + lane * 2) * 4, bf_lo(mine), bf_hi(mine));
          }
        }
      }
    }
    __syncthreads();
    if (wid == 0 || wid == 2) {
      const int w = wid >> 1;
      if (w == 0) {
        expect_tx_elect(bars + 8 * 12, KH * 32768);
#pragma unroll 1
        for (int q = 0; q < 4 * KH; q++) tma_load_ef(sm + q * 8192, &p.wd, bars + 8 * 12, e * 256 + (q & 3) * 64, (q >> 2) * 448 + 384);
      }
      cnt_wait_lazy(p.cnt + C_ACT, tag * 8);
      if (w == 1) __nanosleep(HOFF);
      uint32_t ph = 1, ready = 0;
#pragma unroll 1
      for (int it = 0, s = 0; it < 16 * KH; it++) {
        const int rb = it / KH, kc = it - rb * KH;
        while (!((ready >> rb) & 1)) {
          ready = __ballot_sync(~0u, (int)(load_epoch(p.cnt + (lane & 15) * 32 + C_ACT) - tag * 8) >= 0);
          asm volatile("fence.proxy.async.global;" ::: "memory");
        }
        const uint32_t fb = bars + 8 * (16 + w * 4 + s), dst = sm + 98304 + w * 32768 + s * 8192;
        mbar_wait(fb + 64, ph);
        expect_tx_elect(fb, 8192);
        tma_load(dst, &p.act_st, fb, kc * 448 + 384, rb * 128 + w * 64);
        tma_load(dst + 4096, &p.act_st, fb, kc * 448 + 384, rb * 128 + w * 64 + 32);
        if (++s == 4) { s = 0; ph ^= 1; }
      }
    } else if (wid >= 4) {
      const int w = (wid >> 2) - 1, warp = wid & 3;
      const uint32_t out_stg = (w ? stg : sm + 163840) + warp * 2048;
      const uint32_t slab = out_stg + (lane & 15) * 128, sw0 = (lane >> 4) ^ (lane & 7);
      mbar_wait_watchdog(bars + 8 * 12, 0);
#pragma unroll 1
      for (int i = threadIdx.x - 128; i < KH * 2048; i += 256) {
        const uint32_t gp = sm + MODB_OFF + (((i >> 9) & 3) * 64 + ((i ^ (i >> 3)) & 7) * 8) * 4;
        const uint4 v = lds128(sm + i * 16), ga = lds128(gp), gc = lds128(gp + 16);
        sts128(sm + i * 16, pack2(bf_lo(v.x) * __uint_as_float(ga.x), bf_hi(v.x) * __uint_as_float(ga.y)),
               pack2(bf_lo(v.y) * __uint_as_float(ga.z), bf_hi(v.y) * __uint_as_float(ga.w)),
               pack2(bf_lo(v.z) * __uint_as_float(gc.x), bf_hi(v.z) * __uint_as_float(gc.y)),
               pack2(bf_lo(v.w) * __uint_as_float(gc.z), bf_hi(v.w) * __uint_as_float(gc.w)));
      }
      asm volatile("fence.proxy.async.shared::cta;" ::: "memory");
      bar_sync(1, 256);
      uint32_t ph = 0;
      int s = 0;
#pragma unroll 1
      for (int rb = 0; rb < 16; rb++) {
        float acc[128];
#pragma unroll 1
        for (int kc = 0; kc < KH; kc++) {
          mbar_wait_watchdog(bars + 8 * (16 + w * 4 + s), ph);
          const uint32_t da = DESC_A + ((98304 + w * 32768 + s * 8192) >> 4), db = DESC_B + ((kc * 32768) >> 4);
          wg_fence();
#pragma unroll
          for (int k = 0; k < 4; k++) wgmma_ss_n256(acc, da + k * 2, db + k * 128, (kc | k) != 0);
          wg_commit();
          wg_wait<1>();
          if (kc > 0 && lane == 0) mbar_arrive(bars + 8 * (24 + w * 4 + ((s + 3) & 3)));
          if (++s == 4) { s = 0; ph ^= 1; }
        }
        asm volatile("cp.async.bulk.wait_group 0;" ::: "memory");
        __syncwarp();
        if (rb > 0) cnt_signal(p.cnt + (rb - 1) * 32 + C_SP + e);
        wg_wait<0>();
        fence_regs(acc);
        __syncwarp();
        if (lane == 0) mbar_arrive(bars + 8 * (24 + w * 4 + ((s + 3) & 3)));
#pragma unroll
        for (int q = 0; q < 16; q++)
          stmatrix4(slab + (q >> 2) * 8192 + ((sw0 ^ ((q & 3) * 2)) << 4), pack2(acc[8 * q], acc[8 * q + 1]), pack2(acc[8 * q + 2], acc[8 * q + 3]),
                    pack2(acc[8 * q + 4], acc[8 * q + 5]), pack2(acc[8 * q + 6], acc[8 * q + 7]));
        asm volatile("fence.proxy.async.shared::cta;" ::: "memory");
        __syncwarp();
#pragma unroll
        for (int ch = 0; ch < 4; ch++) tma_add3(&p.out, out_stg + ch * 8192, e * 256 + ch * 64, rb * 64 + warp * 16, w);
        asm volatile("cp.async.bulk.commit_group;" ::: "memory");
      }
      asm volatile("cp.async.bulk.wait_group 0;" ::: "memory");
      __syncwarp();
      cnt_signal(p.cnt + 15 * 32 + C_SP + e);
    }
    return;
  }
  const int slot = p.slot[cl];
  const int rb = (slot >> 3) * 2 + rank, j = slot & 7;
  const int cta = rb * 8 + j;
  PROF_AT(threadIdx.x == 0, 0);

  if (threadIdx.x < 128) {
    uint32_t tag = load_epoch(p.epoch);
    asm volatile("setmaxnreg.dec.sync.aligned.u32 40;");
    const int warp = __shfl_sync(~0u, (int)(threadIdx.x >> 5), 0), lane = threadIdx.x & 31;
    if (threadIdx.x == 0) {
      if ((sm & 0x3FFFF) != SMEM_BASE) asm volatile("trap;");
      for (int i = 0; i < 4; i++) { mbar_init(bars + 8 * (B_FQ + i), 1); mbar_init(bars + 8 * (B_EQ + i), 16); }
      for (int i = 0; i < 6; i++) { mbar_init(bars + 8 * (B_FW + i), 1); mbar_init(bars + 8 * (B_EW + i), 16); }
      for (int i = 0; i < 4; i++) { mbar_init(bars + 8 * (B_FG + i), 1); mbar_init(bars + 8 * (B_EG + i), 16); }
      for (int i = 0; i < 6; i++) { mbar_init(bars + 8 * (B_FD + i), 1); mbar_init(bars + 8 * (B_ED + i), 16); }
      for (int i = 0; i < 2; i++) { mbar_init(bars + 8 * (B_STGF + i), 8); mbar_init(bars + 8 * (B_STGE + i), 1); }
      mbar_init(bars + 8 * B_MODB, 1);
      mbar_init(bars + 8 * (B_MODB + 1), 1);
      mbar_init(bars + 8 * B_MODA, 1);
      for (int i = 0; i < 11; i++) mbar_init(bars + 8 * (B_RDY + i), 1);
      asm volatile("fence.mbarrier_init.release.cluster;" ::: "memory");
    }
    __syncwarp();
    cluster_arrive_relaxed();
    tag += 1;
    const unsigned target = tag * 8;
    unsigned* cnt = p.cnt + rb * 32;
    cluster_wait();
    if (warp == 0) {
      const CUtensorMap* wgu = rank ? &p.wu : &p.wg;
      uint32_t st = sm + 16384, fb = bars + 8 * B_FQ, ph = 1;
      __nanosleep(BDELAY);
#pragma unroll 1
      for (int it = 0; it < 32; it++) {
        const int kb = qkv_kb(it, j), col = j * 128 + ((it < 4 ? it >= 2 : it >= 18) ? 64 : 0);
        mbar_wait(fb + 8 * (B_EQ - B_FQ), ph);
        expect_tx_elect(fb, it < 4 ? 24576 : 40960);
        tma_load_mc(st + rank * 8192, &p.wqkv, fb, col + rank * 1024, kb * 64);
        tma_load_mc(st + 16384 + rank * 4096, &p.wqkv32, fb, col + 2048, kb * 64 + rank * 32);
        st += 49152; fb += 8;
        if ((it & 3) == 3) { st -= 4 * 49152; fb -= 32; ph ^= 1; }
      }
      fb = bars + 8 * B_FW; ph = 1;
#pragma unroll 1
      for (int it = 0, s = 0; it < 34; it++) {
        if (it < 6) wait_q_free(bars + 8 * B_EQ, it);
        if (it == 16) mbar_wait(bars + 8 * (B_FW + GW % 6), (GW / 6) & 1);
        mbar_wait(fb + 8 * (B_EW - B_FW), ph);
        expect_tx_elect(fb, (it == 8 || it == 18 || it == 19) ? 16384 : 32768);
        const int k0 = it < 16 ? wo_k(it, j) : (it < 20 ? 2 * j + (it & 1) : other_kb(it - 20, j)) * 64;
        if (it == 16 || it == 17) {
          tma_load_mc(st - 16384 + rank * 16384, wgu, fb, j * 448, k0);
          tma_load_mc(st - 8192 + rank * 16384, wgu, fb, j * 448 + 64, k0);
        } else {
          tma_load_mc(st + rank * 8192, it < 16 ? &p.wo : wgu, fb, it < 16 ? j * 128 + rank * 64 : j * 448 + 384, k0);
        }
        st += 32768; fb += 8;
        if (++s == 6) { s = 0; st -= 6 * 32768; fb -= 48; ph ^= 1; }
      }
      st = sm + 16384 + 3 * 49152; fb = bars + 8 * B_FG; ph = 1;
#pragma unroll 1
      for (int it = 0; it < 46; it++) {
        const int kb = it < 14 ? other_kb(it, j) : (it + 2) & 15, col = j * 448 + ((it + 2) >> 4) * 128;
        if (it < 4) wait_w_free(bars + 8 * B_EW, it);
        mbar_wait(fb + 8 * (B_EG - B_FG), ph);
        expect_tx_elect(fb, 49152);
        tma_load_mc(st + rank * 16384, wgu, fb, col, kb * 64);
        tma_load_mc(st + rank * 16384 + 8192, wgu, fb, col + 64, kb * 64);
        st += (it & 3) == 0 ? -3 * 49152 : 49152; fb += 8;
        if ((it & 3) == 3) { fb -= 32; ph ^= 1; }
      }
      st = sm + 16384 + 2 * 32768; fb = bars + 8 * B_FD; ph = 1;
#pragma unroll 1
      for (int it = 0, s = 0; it < 56 - KH; it++) {
        if (it < 6) wait_g_free(bars + 8 * B_EG, it);
        mbar_wait(fb + 8 * (B_ED - B_FD), ph);
        expect_tx_elect(fb, 32768);
        tma_load_mc(st + rank * 8192, &p.wd, fb, j * 128 + rank * 64, down_k(it));
        st += s == 3 ? -5 * 32768 : 32768; fb += 8;
        if (++s == 6) { s = 0; fb -= 48; ph ^= 1; }
      }
    } else if (warp == 1) {
      const int arow = rb * 128;
      uint32_t st = sm, fb = bars + 8 * B_FQ, ph = 0;
      cnt_wait(cnt + C_HA, target);
      PROF_AT(lane == 0, 16);
#pragma unroll 1
      for (int it = 4; it < 32; it++) {
        if (it == 11) mbar_wait(bars + 8 * (B_RDY + C_H), 0);
        mbar_wait(fb + 8 * (B_EQ - B_FQ), ph);
        tma_load(st, &p.h, fb, qkv_kb(it, j) * 64, arow);
        st += 49152; fb += 8;
        if ((it & 3) == 3) { st -= 4 * 49152; fb -= 32; ph ^= 1; }
      }
      fb = bars + 8 * B_FW; ph = 1;
#pragma unroll 1
      for (int it = 0, s = 0; it < 34; it++) {
        if (it < 16 || it >= 20) {
          if (it < 6) wait_q_free(bars + 8 * B_EQ, it);
          mbar_wait(fb + 8 * (B_EW - B_FW), ph);
          if (it == 0) mbar_wait(bars + 8 * (B_RDY + C_O), 0);
          if (it == 9 || it == 20) cnt_wait(cnt + (it == 9 ? C_O + 1 : C_H2A), target * 8);
          if (it == 27) mbar_wait(bars + 8 * (B_RDY + C_H2), 0);
          PROF_AT(lane == 0 && (it == 0 || it == 9 || it == 20), 17 + (it >> 3));
          if (it != 8) tma_load(st, it < 16 ? &p.o_ld : &p.h2, fb, it < 16 ? wo_k(it, j) : other_kb(it - 20, j) * 64, arow);
        }
        st += 32768; fb += 8;
        if (++s == 6) { s = 0; st -= 6 * 32768; fb -= 48; ph ^= 1; }
      }
      st = sm + 3 * 49152; fb = bars + 8 * B_FG; ph = 1;
#pragma unroll 1
      for (int it = 0; it < 46; it++) {
        if (it < 4) wait_w_free(bars + 8 * B_EW, it);
        mbar_wait(fb + 8 * (B_EG - B_FG), ph);
        tma_load(st, &p.h2, fb, (it < 14 ? other_kb(it, j) : (it + 2) & 15) * 64, arow);
        st += (it & 3) == 0 ? -3 * 49152 : 49152; fb += 8;
        if ((it & 3) == 3) { fb -= 32; ph ^= 1; }
      }
      st = sm + 2 * 32768; fb = bars + 8 * B_FD; ph = 1;
#pragma unroll 1
      for (int it = 0, s = 0; it < 56 - KH; it++) {
        if (it < 6) wait_g_free(bars + 8 * B_EG, it);
        mbar_wait(fb + 8 * (B_ED - B_FD), ph);
        const int u = it + KH, dep = it == 0 ? C_ACT : (u == 8 ? C_ACT + 1 : (u == 24 ? C_ACT + 2 : (u == 40 ? C_A0 : (u == 48 ? C_ACT + 3 : -1))));
        if (dep >= 0) mbar_wait(bars + 8 * (B_RDY + dep), 0);
        tma_load(st, &p.act, fb, down_k(it), arow);
        st += s == 3 ? -5 * 32768 : 32768; fb += 8;
        if (++s == 6) { s = 0; fb -= 48; ph ^= 1; }
      }
    } else if (warp == 2) {
      if (lane < 14) prefetch_map(&p.h + lane);
      __syncwarp();
      uint32_t ph1 = 0;
#pragma unroll 1
      for (int n = 0; n < 8; n++) {
        const int nch = (n == 1 || n == 2 || n == 4) ? 1 : 2;
#pragma unroll 1
        for (int ch = 0; ch < nch; ch++) {
          mbar_wait_watchdog(bars + 8 * (B_STGF + ch), ch ? ph1 : (n & 1));
          const uint32_t src = stg + ch * 16384;
          if (n == 2 || n == 3) {
          } else if (n == 1) {
#pragma unroll 1
            for (int q = 0; q < 8; q++) {
              tma_store2(&p.o_st, src + q * 2048, j * 128, rb * 128 + q * 16);
              if (q & 1) store_pause(true);
            }
          } else if (n >= 4 && n < 8) {
#pragma unroll 1
            for (int q = 0; q < 4; q++) {
              tma_store2(&p.act_st, src + q * 4096, j * 448 + (n == 4 ? 384 : (n - 5) * 128 + ch * 64), rb * 128 + q * 32);
              store_pause(true);
            }
          } else {
            tma_store2(&p.h, src, j * 128 + ch * 64, rb * 128);
            asm volatile("cp.async.bulk.commit_group;" ::: "memory");
            if (ch == 1) {
              asm volatile("cp.async.bulk.wait_group 1;" ::: "memory");
              __syncwarp();
              cnt_signal(cnt + C_HA);
            }
          }
          if (n >= 5 && ch == 0) arrive_elect(bars + 8 * B_STGE);
          if (n == 7 && ch == 0) {
            asm volatile("cp.async.bulk.wait_group 0;" ::: "memory");
            __syncwarp();
            cnt_signal(cnt + C_A0);
          }
        }
        asm volatile("cp.async.bulk.commit_group;" ::: "memory");
        asm volatile("cp.async.bulk.wait_group 0;" ::: "memory");
        __syncwarp();
        if (n != 2 && n != 3) cnt_signal(cnt + n);
        PROF_AT(lane == 0, n == 0 ? 33 : 23 + n);
        if (n == 0) {
#pragma unroll 1
          for (int t = 0; t < 34; t++) {
            ll_store(t < 32 ? p.halo + cta * 1024 + t * 32 + lane : (uint4*)(p.stats2 + cta * 128) + (t - 32) * 32 + lane, 0u, 0u, 0u);
            __nanosleep(40);
          }
          __syncwarp();
        }
        if (n < 5) arrive_elect(bars + 8 * B_STGE);
        if (nch == 2) { arrive_elect(bars + 8 * (B_STGE + 1)); ph1 ^= 1; }
      }
      mbar_wait_watchdog(bars + 8 * B_STGF, 0);
      PROF_AT(lane == 0, 31);
    } else {
      if (lane < 4) ll_store(p.modll + cta * 4 + lane, 0u, 0u, 0u);
      bar_sync(1, 288);
      {
        const uint4 t4 = lds128(sm + RED_OFF + lane * 16);
        float a[4] = {__uint_as_float(t4.x), __uint_as_float(t4.y), __uint_as_float(t4.z), __uint_as_float(t4.w)};
#pragma unroll
        for (int o = 4; o < 32; o <<= 1)
#pragma unroll
          for (int q = 0; q < 4; q++) a[q] += __shfl_xor_sync(~0u, a[q], o);
        if (lane < 4) ll_store(p.modll + cta * 4 + lane, pack2(a[0], a[1]), pack2(a[2], a[3]), tag);
        PROF_AT(lane == 0, 1);
        uint32_t m[4];
        const uint4* mp = p.modll + j * 32 + lane;
        ll_poll<2>([&](int i) { return mp + i * 256; }, tag, m);
        const uint32_t c0 = pack2(1.0f + bf_lo(m[2]), 1.0f + bf_hi(m[2])), c1 = pack2(1.0f + bf_lo(m[3]), 1.0f + bf_hi(m[3]));
        sts128(sm + MODB_OFF + lane * 16, c0, m[0], c1, m[1]);
        __syncwarp();
        arrive_elect(bars + 8 * B_MODA);
      }
#pragma unroll 1
      for (int n = C_H; n <= C_O; n++) {
        cnt_wait_lazy(cnt + n, target);
        arrive_elect(bars + 8 * (B_RDY + n));
      }
      {
        uint32_t m[6];
        const uint4* src = p.modll + 512 + j * 32 + lane;
        ll_poll<3, 500>([&](int i) { return src + i * 256; }, tag, m);
#pragma unroll
        for (int vec = 0; vec < 3; vec++) {
          const float add = vec == 2 ? 1.0f : 0.0f;
          sts128(sm + MODB_OFF + (vec * 128 + lane * 4) * 4, __float_as_uint(bf_round(bf_lo(m[2 * vec]) + add)), __float_as_uint(bf_round(bf_hi(m[2 * vec]) + add)),
                 __float_as_uint(bf_round(bf_lo(m[2 * vec + 1]) + add)), __float_as_uint(bf_round(bf_hi(m[2 * vec + 1]) + add)));
        }
        __syncwarp();
        if (lane == 0) mbar_arrive(bars + 8 * B_MODB);
        PROF_AT(lane == 0, 15);
      }
      __syncwarp();
#pragma unroll 1
      for (int q = C_H2; q < 9; q++) {
        const int n = q < 7 ? q : (q == 7 ? C_A0 : C_ACT + 3);
        cnt_wait_lazy(cnt + n, n == C_H2 ? target * 8 : target);
        arrive_elect(bars + 8 * (B_RDY + n));
      }
      {
        uint32_t m[2];
        const uint4* src = p.modll + 512 + 768 + j * 32 + lane;
        ll_poll<1>([&](int) { return src; }, tag, m);
        sts128(sm + MODB_OFF + (384 + lane * 4) * 4, m[0] << 16, m[0] & 0xffff0000u, m[1] << 16, m[1] & 0xffff0000u);
        cnt_wait_lazy(cnt + C_SP + (j >> 1), target);
        __syncwarp();
        if (lane == 0) mbar_arrive(bars + 8 * (B_MODB + 1));
      }
    }
  } else {
    uint32_t tag;

    {
      const int tid = threadIdx.x - 128, cw = tid >> 7, warp = (tid >> 5) & 3, lane = tid & 31;
      const int l16 = lane & 15, half = lane >> 4, w8 = cw * 4 + warp;
      const uint32_t cbuf = sm + 3 * 49152 + w8 * 512;
      if (lane <= 16) cp_async16(cbuf + lane * 16, lane < 16 ? (const void*)(p.c + w8 * 128 + lane * 8) : (const void*)p.epoch);
      asm volatile("cp.async.commit_group;" ::: "memory");
      const uint32_t xbuf = sm + 40960 + (cw * 2 + (l16 >> 3)) * 49152 + (warp * 16 + half) * 128;
      {
        const char* xp = (const char*)p.x + (uint32_t)((rb * 128 + (warp * 16 + half) * 2 + cw) * 2048 + j * 256 + l16 * 16);
#pragma unroll
        for (int i = 0; i < 8; i++) cp_async16(xbuf + i * 256 + (((l16 & 7) ^ ((i * 2 + half) & 7)) << 4), xp + i * 8192);
      }
      asm volatile("cp.async.commit_group;" ::: "memory");
      const uint32_t wbuf = sm + cw * 49152 + warp * 4096;
      {
        const char* wp = (const char*)p.wmod + (uint32_t)(cta * 32 + (lane & 1) * 16 + (w8 * 128 + (lane >> 1)) * 12288);
#pragma unroll
        for (int i = 0; i < 8; i++) cp_async16(wbuf + i * 512 + lane * 16, wp + i * 16 * 12288);
      }
      asm volatile("cp.async.commit_group;" ::: "memory");
      PROF_AT(tid == 0, 32);
      uint2* st1 = p.stats1 + (rb * 8 + j) * 128 + cw * 64 + warp * 16;
      if (lane < 8) ll_store((uint4*)st1 + lane, 0u, 0u, 0u);
      __syncwarp();
      cluster_arrive_relaxed();
      asm volatile("setmaxnreg.inc.sync.aligned.u32 232;");
      uint32_t sa[4][4];
      {
        asm volatile("cp.async.wait_group 2;" ::: "memory");
        __syncwarp();
        tag = lds32(cbuf + 256) + 1;
        const float2 cv = lds64f(cbuf + lane * 8);
        const uint32_t c0 = __float_as_uint(cv.x), c1 = __float_as_uint(cv.y);
        sts64f(cbuf + lane * 8, __uint_as_float(pack2(silu_f(bf_lo(c0)), silu_f(bf_hi(c0)))), __uint_as_float(pack2(silu_f(bf_lo(c1)), silu_f(bf_hi(c1)))));
        __syncwarp();
#pragma unroll
        for (int q = 0; q < 4; q++) ldmatrix4(sa[q][0], sa[q][1], sa[q][2], sa[q][3], cbuf + q * 64 + (lane >> 3) * 16);
      }
      cluster_wait();
      asm volatile("cp.async.wait_group 1;" ::: "memory");
      __syncwarp();
      uint32_t xl[16], xh[16];
      {
        const int srow = warp * 16 + (lane & 15);
#pragma unroll
        for (int q = 0; q < 8; q++)
          ldmatrix4(xl[2 * q], xh[2 * q], xl[2 * q + 1], xh[2 * q + 1],
                    sm + 40960 + (cw * 2 + (q >> 2)) * 49152 + srow * 128 + (((half + (q & 3) * 2) ^ (srow & 7)) << 4));
      }
      publish_stats(xl, xh, st1, lane, tag16(tag));
      PROF_AT(tid == 0, 50);
      asm volatile("cp.async.wait_group 0;" ::: "memory");
      __syncwarp();
      PROF_AT(tid == 0, 51);
      {
        uint32_t b[8][4];
#pragma unroll
        for (int ks = 0; ks < 8; ks++) ldmatrix4t(b[ks], wbuf + (ks * 16 + (lane & 15)) * 32 + (lane >> 4) * 16);
        float d0[4] = {0.f, 0.f, 0.f, 0.f}, d1[4] = {0.f, 0.f, 0.f, 0.f}, d2[4] = {0.f, 0.f, 0.f, 0.f}, d3[4] = {0.f, 0.f, 0.f, 0.f};
#pragma unroll
        for (int q = 0; q < 4; q++) {
          mma16816(d0, sa[q][0], sa[q][0], sa[q][1], sa[q][1], b[2 * q][0], b[2 * q][1]);
          mma16816(d1, sa[q][0], sa[q][0], sa[q][1], sa[q][1], b[2 * q][2], b[2 * q][3]);
          mma16816(d2, sa[q][2], sa[q][2], sa[q][3], sa[q][3], b[2 * q + 1][0], b[2 * q + 1][1]);
          mma16816(d3, sa[q][2], sa[q][2], sa[q][3], sa[q][3], b[2 * q + 1][2], b[2 * q + 1][3]);
        }
        d0[0] += d2[0]; d0[1] += d2[1]; d1[0] += d3[0]; d1[1] += d3[1];
        if (lane < 4) {
          sts64f(sm + RED_OFF + (w8 * 16 + lane * 2) * 4, d0[0], d0[1]);
          sts64f(sm + RED_OFF + (w8 * 16 + 8 + lane * 2) * 4, d1[0], d1[1]);
        }
        asm volatile("bar.arrive 1, 288;" ::: "memory");
      }
      {
        const int c = lane & 3;
        float rs[2], nb[2];
        stat_gather(p.stats1 + rb * 1024 + cw * 64 + warp * 16, tag16(tag), lane, rs, nb);
#pragma unroll
        for (int n = 0; n < 16; n++) {
          xl[n] = pack2(bf_lo(xl[n]) * rs[0] + nb[0], bf_hi(xl[n]) * rs[0] + nb[0]);
          xh[n] = pack2(bf_lo(xh[n]) * rs[1] + nb[1], bf_hi(xh[n]) * rs[1] + nb[1]);
        }
        const int srow = warp * 16 + l16;
        const uint32_t slab = stg + cw * 8192 + srow * 128;
#pragma unroll
        for (int q = 0; q < 8; q++)
          stmatrix4(slab + (q >> 2) * 16384 + (((half + (q & 3) * 2) ^ (srow & 7)) << 4), xl[2 * q], xh[2 * q], xl[2 * q + 1], xh[2 * q + 1]);
        PROF_AT(tid == 0, 52);
        mbar_wait(bars + 8 * B_MODA, 0);
        PROF_AT(tid == 0, 2);
#pragma unroll
        for (int q = 0; q < 8; q++) {
          const float2 m0 = lds64f(sm + MODB_OFF + (8 * q + c) * 8), m1 = lds64f(sm + MODB_OFF + (8 * q + 4 + c) * 8);
          const uint32_t c0 = __float_as_uint(m0.x), s0 = __float_as_uint(m0.y), c1 = __float_as_uint(m1.x), s1 = __float_as_uint(m1.y);
          stmatrix4(slab + (q >> 2) * 16384 + (((half + (q & 3) * 2) ^ (srow & 7)) << 4), fma_bf2(xl[2 * q], c0, s0), fma_bf2(xh[2 * q], c0, s0),
                    fma_bf2(xl[2 * q + 1], c1, s1), fma_bf2(xh[2 * q + 1], c1, s1));
          if ((q & 3) == 3) stage_done(bars + 8 * (B_STGF + (q >> 2)), lane);
        }
        wg_bar(cw);
      }
      PROF_AT(tid == 0, 3);
    }

    uint32_t xl[16], xh[16];
    {
      RING_IDS();
      uint32_t prev = 0;
      float acc1[96];
      {
        Ring g{bars + 8 * B_FQ, rbars + 8 * B_EQ, 0, 0u, 0u, releaser TR(0)};
        float acc0[96];
#pragma unroll 1
        for (int kb = 0; kb < 2; kb++) kblock<192, 4, 49152>(acc0, g, a_base + STG_OFF + kb * 16384, kb == 0, prev);
#pragma unroll 1
        for (int kb = 0; kb < 2; kb++) kblock<192, 4, 49152>(acc1, g, a_base + STG_OFF + kb * 16384, kb == 0, prev);
#pragma unroll 1
        for (int kb = 0; kb < 14; kb++) kblock<192, 4, 49152>(acc0, g, a_base + g.off, false, prev);
        PROF_AT(tid == 0, 4);
        attention<NPRE0, false>(acc0, p, 0, rb, cta, cw, warp, tag, stg, bars, prev, [&]() { kblock<192, 4, 49152>(acc1, g, a_base + g.off, false, prev); });
        PROF_AT(tid == 0, 5);
        {
          LANE_IDS();
#pragma unroll
          for (int q = 0; q < 8; q++)
            ldmatrix4(xl[2 * q], xh[2 * q], xl[2 * q + 1], xh[2 * q + 1], sm + 40960 + (cw * 2 + (q >> 2)) * 49152 + srow * 128 + ((sw0 ^ ((q & 3) * 2)) << 4));
#pragma unroll
          for (int q = 0; q < 16; q++) asm volatile("" : "+r"(xl[q]), "+r"(xh[q])::"memory");
        }
#pragma unroll 1
        for (int kb = 5 + NPRE0; kb < 14; kb++) kblock<192, 4, 49152>(acc1, g, a_base + g.off, false, prev);
        PROF_AT(tid == 0, 6);
      }
      float acc[64];
      Ring g{bars + 8 * B_FW, rbars + 8 * B_EW, 0, 0u, 0u, releaser TR(32)};
      attention<NPRE1, true>(acc1, p, 1, rb, cta, cw, warp, tag, stg, bars, prev, [&]() { kblock<128, 6, 32768>(acc, g, a_base + g.off, g.s == 0, prev); });
      PROF_AT(tid == 0, 7);
      LANE_IDS();
      unsigned* cnt = p.cnt + rb * 32;
      tma_store2(&p.o_st, stg + cw * 8192 + warp * 2048, j * 128 + 64, rb * 128 + cw * 64 + warp * 16);
      asm volatile("cp.async.bulk.commit_group;" ::: "memory");
#pragma unroll 1
      for (int kb = 1 + NPRE1; kb < 16; kb++) {
        if (kb == 8) wg_bar(cw);
        kblock<128, 6, 32768>(acc, g, a_base + (kb == 8 ? STG_OFF : g.off), false, prev);
        if (kb == OSIG + NPRE1) {
          asm volatile("cp.async.bulk.wait_group 0;" ::: "memory");
          __syncwarp();
          cnt_signal(cnt + C_O + 1);
        }
      }
      mbar_wait(bars + 8 * B_MODB, 0);
      float2 ga[16];
#pragma unroll
      for (int n = 0; n < 16; n++) ga[n] = lds64f(sm + MODB_OFF + (8 * n + 2 * c) * 4);
      tile_end(acc, prev);
      PROF_AT(tid == 0, 8);
      uint2* st2 = p.stats2 + (rb * 8 + j) * 128 + cw * 64 + warp * 16 + r + (c & 1) * 8;
      float sl[2] = {0.f, 0.f}, sh[2] = {0.f, 0.f}, ql[2] = {0.f, 0.f}, qh[2] = {0.f, 0.f};
#pragma unroll
      for (int n = 0; n < 16; n++) {
        acc[4 * n] = ga[n].x * acc[4 * n] + bf_lo(xl[n]); acc[4 * n + 1] = ga[n].y * acc[4 * n + 1] + bf_hi(xl[n]);
        acc[4 * n + 2] = ga[n].x * acc[4 * n + 2] + bf_lo(xh[n]); acc[4 * n + 3] = ga[n].y * acc[4 * n + 3] + bf_hi(xh[n]);
        sl[0] += acc[4 * n]; sl[1] += acc[4 * n + 1]; sh[0] += acc[4 * n + 2]; sh[1] += acc[4 * n + 3];
        ql[0] += acc[4 * n] * acc[4 * n]; ql[1] += acc[4 * n + 1] * acc[4 * n + 1];
        qh[0] += acc[4 * n + 2] * acc[4 * n + 2]; qh[1] += acc[4 * n + 3] * acc[4 * n + 3];
      }
      {
        const float ml = (sl[0] + sl[1]) * (1.0f / 32), mh = (sh[0] + sh[1]) * (1.0f / 32);
        const float vl = (ql[0] + ql[1]) - 32.0f * ml * ml, vh = (qh[0] + qh[1]) - 32.0f * mh * mh;
        const bool b0 = c & 1;
        float m = b0 ? mh : ml, q = b0 ? vh : vl;
        chan(m, q, __shfl_xor_sync(~0u, b0 ? ml : mh, 1), __shfl_xor_sync(~0u, b0 ? vl : vh, 1), 32.f);
        chan(m, q, __shfl_xor_sync(~0u, m, 2), __shfl_xor_sync(~0u, q, 2), 64.f);
        if (c < 2) stat_store(st2, m, fmaxf(q, 0.f), tag16(tag));
        __syncwarp();
      }
      PROF_AT(tid == 0, 48);
      float2 sb[16], cb[16];
#pragma unroll
      for (int n = 0; n < 16; n++) {
        sb[n] = lds64f(sm + MODB_OFF + (128 + 8 * n + 2 * c) * 4);
        cb[n] = lds64f(sm + MODB_OFF + (256 + 8 * n + 2 * c) * 4);
        xl[n] = pack2(acc[4 * n], acc[4 * n + 1]);
        xh[n] = pack2(acc[4 * n + 2], acc[4 * n + 3]);
      }
      mbar_wait(bars + 8 * B_STGE, 0);
      PROF_AT(tid == 0, 49);
      float nb[2], rstd[2];
      stat_gather(p.stats2 + rb * 1024 + cw * 64 + warp * 16, tag16(tag), lane, rstd, nb);
      PROF_AT(tid == 0, 9);
#pragma unroll
      for (int ch = 0; ch < 2; ch++) {
        uint32_t lo[8], hi[8];
#pragma unroll
        for (int t = 0; t < 8; t++) {
          const int n = ch * 8 + t;
          lo[t] = pack2((acc[4 * n] * rstd[0] + nb[0]) * cb[n].x + sb[n].x, (acc[4 * n + 1] * rstd[0] + nb[0]) * cb[n].y + sb[n].y);
          hi[t] = pack2((acc[4 * n + 2] * rstd[1] + nb[1]) * cb[n].x + sb[n].x, (acc[4 * n + 3] * rstd[1] + nb[1]) * cb[n].y + sb[n].y);
        }
        stage_slab(sm + ch * 32768 + cw * 8192, warp, lane, lo, hi);
        stage_done(bars + 8 * (B_STGF + ch), lane);
        tma_store2(&p.h2_st, sm + ch * 32768 + cw * 8192 + warp * 2048, j * 128 + ch * 64, rb * 128 + cw * 64 + warp * 16);
        asm volatile("cp.async.bulk.commit_group;" ::: "memory");
      }
      wg_bar(cw);
      PROF_AT(tid == 0, 10);
    }

    uint32_t pg[32], pu[32];
    {
      RING_IDS();
      float acc[128];
      uint32_t prev = 0;
      Ring g{bars + 8 * B_FG, rbars + 8 * B_EG, 0, 0u, 3 * 49152u, releaser TR(66)};
      {
        Ring w{bars + 8 * B_FW, rbars + 8 * B_EW, 4, 0u, 4 * 32768u, releaser TR(48)};
        float acn[64];
#pragma unroll 1
        for (int kb = 0; kb < 2; kb++) {
          kblock<256, 6, 32768>(acc, w, a_base + kb * 32768, kb == 0, prev, 0u);
          if (kb == 0) asm volatile("cp.async.bulk.wait_group 1;" ::: "memory");
          else asm volatile("cp.async.bulk.wait_group 0;" ::: "memory");
          __syncwarp();
          cnt_signal(p.cnt + rb * 32 + (kb == 0 ? C_H2A : C_H2));
        }
        {
          LANE_IDS();
#pragma unroll
          for (int q = 0; q < 8; q++)
            stmatrix4(slab + (q >> 2) * 16384 + ((sw0 ^ ((q & 3) * 2)) << 4), xl[2 * q], xh[2 * q], xl[2 * q + 1], xh[2 * q + 1]);
          __syncwarp();
        }
#pragma unroll 1
        for (int kb = 0; kb < 16; kb++) {
          kblock<128, 6, 32768>(acn, w, a_base + w.off, kb == 0, prev);
          if (kb == 4) {
            asm volatile("fence.proxy.async.shared::cta;" ::: "memory");
            __syncwarp();
          }
          if (kb == X1S + warp || kb == X1S + 4 + warp) {
            const int ch = kb != X1S + warp;
            tma_store3(&p.out, stg + ch * 16384 + cw * 8192 + warp * 2048, j * 128 + ch * 64, rb * 64 + warp * 16, cw);
            asm volatile("cp.async.bulk.commit_group;" ::: "memory");
          }
        }
        PROF_AT(tid == 0, 39);
        kblock<256, 4, 49152>(acc, g, a_base + g.off, false, prev);
        fence_regs(acn);
#pragma unroll
        for (int q = 0; q < 16; q++) {
          pg[q] = pack2(acn[2 * q], acn[2 * q + 1]);
          pu[q] = pack2(acn[32 + 2 * q], acn[32 + 2 * q + 1]);
          pg[16 + q] = 0; pu[16 + q] = 0;
        }
        asm volatile("cp.async.bulk.wait_group 0;" ::: "memory");
        kblock<256, 4, 49152>(acc, g, a_base + g.off, false, prev);
      }
      LANE_IDS();
#pragma unroll 1
      for (int t = 0; t < 3; t++) {
#pragma unroll 1
        for (int blk = 0; blk < (t == 0 ? 2 : 4); blk++) {
          g.s = 2;
#pragma unroll
          for (int i = 0; i < 4; i++) {
            g.off = ((i + 1) & 3) * 49152;
            kblock<256, 4, 49152>(acc, g, a_base + g.off, t > 0 && blk == 0 && i == 0, prev);
            if ((blk & 1) == 0 && i == 0) mbar_wait(bars + 8 * (B_STGE + (blk >> 1)), (t + 1 + (blk >> 1)) & 1);
            stmatrix2(slab + (blk >> 1) * 16384 + (((srow & 7) ^ ((blk & 1) * 4 + i)) << 4), swiglu2(pg[2 * i], pu[2 * i]), swiglu2(pg[2 * i + 1], pu[2 * i + 1]));
          }
#pragma unroll
          for (int q = 0; q < 24; q++) { pg[q] = pg[q + 8]; pu[q] = pu[q + 8]; }
          if (blk & 1) stage_done(bars + 8 * (B_STGF + (blk >> 1)), lane);
        }
#pragma unroll 1
        for (int kb = t == 0 ? 0 : 4; kb < 4; kb++) kblock<256, 4, 49152>(acc, g, a_base + g.off, false, prev);
        tile_end(acc, prev);
        PROF_AT(tid == 0, 36 + t);
#pragma unroll
        for (int q = 0; q < 32; q++) {
          pg[q] = pack2(acc[2 * q], acc[2 * q + 1]);
          pu[q] = pack2(acc[64 + 2 * q], acc[64 + 2 * q + 1]);
        }
      }
      PROF_AT(tid == 0, 11);
    }

    {
      RING_IDS();
      LANE_IDS();
      Ring g{bars + 8 * B_FD, rbars + 8 * B_ED, 0, 0u, 2 * 32768u, releaser TR(112)};
      float acc[64];
      uint32_t prev = 0;
#pragma unroll 1
      for (int blk = 0; blk < 4; blk++) {
#pragma unroll
        for (int i = 0; i < 8; i++) {
          kblock<128, 6, 32768>(acc, g, a_base + g.off, blk == 0 && i == 0, prev);
          if ((blk & 1) == 0 && i == 0) mbar_wait(bars + 8 * (B_STGE + (blk >> 1)), blk >> 1);
          stmatrix1(slab + (blk >> 1) * 16384 + (i & 1) * 1024 + (((srow & 7) ^ ((blk & 1) * 4 + (i >> 1))) << 4), swiglu2(pg[i], pu[i]));
        }
#pragma unroll
        for (int q = 0; q < 24; q++) { pg[q] = pg[q + 8]; pu[q] = pu[q + 8]; }
        if (blk & 1) stage_done(bars + 8 * (B_STGF + (blk >> 1)), lane);
      }
#pragma unroll 1
      for (int kb = 32; kb < 56 - KH; kb++) {
        if (kb == 50 - KH) g.releaser = false;
        kblock<128, 6, 32768>(acc, g, a_base + g.off, false, prev);
      }
      mbar_wait(bars + 8 * (B_MODB + 1), 0);
      mbar_wait(bars + 8 * B_STGE, 1);
      mbar_wait(bars + 8 * (B_STGE + 1), 0);
      float2 gbv[16];
#pragma unroll
      for (int n = 0; n < 16; n++) gbv[n] = lds64f(sm + MODB_OFF + (384 + 8 * n + 2 * c) * 4);
      tile_end(acc, prev);
      PROF_AT(tid == 0, 13);
#pragma unroll
      for (int ch = 0; ch < 2; ch++) {
        uint32_t lo[8], hi[8];
#pragma unroll
        for (int t = 0; t < 8; t++) {
          const int n = ch * 8 + t;
          const float2 gb = gbv[n];
          lo[t] = pack2(gb.x * acc[4 * n], gb.y * acc[4 * n + 1]);
          hi[t] = pack2(gb.x * acc[4 * n + 2], gb.y * acc[4 * n + 3]);
        }
        stage_slab(stg + ch * 16384 + cw * 8192, warp, lane, lo, hi);
        asm volatile("fence.proxy.async.shared::cta;" ::: "memory");
        __syncwarp();
        tma_add3(&p.out, stg + ch * 16384 + cw * 8192 + warp * 2048, j * 128 + ch * 64, rb * 64 + warp * 16, cw);
      }
      asm volatile("cp.async.bulk.commit_group;" ::: "memory");
      if (lane == 0) mbar_arrive(bars + 8 * B_STGF);
      asm volatile("cp.async.bulk.wait_group.read 0;" ::: "memory");
      PROF_AT(tid == 0, 14);
    }
    if (blockIdx.x == 0 && threadIdx.x == 128) asm volatile("st.relaxed.gpu.global.u32 [%0], %1;" ::"l"(p.epoch), "r"(tag) : "memory");
  }
}

typedef CUresult (*EncodeFn)(CUtensorMap*, CUtensorMapDataType, cuuint32_t, void*, const cuuint64_t*, const cuuint64_t*,
                             const cuuint32_t*, const cuuint32_t*, CUtensorMapInterleave, CUtensorMapSwizzle,
                             CUtensorMapL2promotion, CUtensorMapFloatOOBfill);

void encode2d(EncodeFn fn, CUtensorMap* m, const void* ptr, uint64_t cols, uint64_t rows, uint32_t box_rows) {
  cuuint64_t dims[2] = {cols, rows};
  cuuint64_t strides[1] = {cols * 2};
  cuuint32_t box[2] = {64, box_rows};
  cuuint32_t es[2] = {1, 1};
  fn(m, CU_TENSOR_MAP_DATA_TYPE_BFLOAT16, 2, (void*)ptr, dims, strides, box, es, CU_TENSOR_MAP_INTERLEAVE_NONE,
     CU_TENSOR_MAP_SWIZZLE_128B, CU_TENSOR_MAP_L2_PROMOTION_L2_128B, CU_TENSOR_MAP_FLOAT_OOB_FILL_NONE);
}

}

extern "C" void kernel_launch(void* const* d_in, const int* in_sizes, int n_in, void* d_out, int out_size) {
  (void)in_sizes; (void)n_in; (void)out_size;
  void* fp = nullptr;
  cudaDriverEntryPointQueryResult qr;
  cudaGetDriverEntryPoint("cuTensorMapEncodeTiled", &fp, cudaEnableDefault, &qr);
  EncodeFn fn = (EncodeFn)fp;
  void *ph, *po, *ph2, *pact;
  cudaGetSymbolAddress(&ph, g_h);
  cudaGetSymbolAddress(&po, g_o);
  ph2 = ph;
  cudaGetSymbolAddress(&pact, g_act);
  Params p;
  encode2d(fn, &p.h, ph, DM, SEQ, 128);
  encode2d(fn, &p.o_ld, po, DM, SEQ, 128);
  encode2d(fn, &p.h2, ph2, DM, SEQ, 128);
  encode2d(fn, &p.act, pact, FF, SEQ, 128);
  encode2d(fn, &p.act_st, pact, FF, SEQ, 32);
  encode2d(fn, &p.wm, d_in[8], 6 * DM, DM, 64);
  encode2d(fn, &p.o_st, po, DM, SEQ, 16);
  encode2d(fn, &p.h2_st, ph2, DM, SEQ, 16);
  encode2d(fn, &p.wqkv, d_in[1], 3 * DM, DM, 64);
  encode2d(fn, &p.wqkv32, d_in[1], 3 * DM, DM, 32);
  encode2d(fn, &p.wo, d_in[2], DM, DM, 64);
  encode2d(fn, &p.wg, d_in[4], FF, DM, 64);
  encode2d(fn, &p.wu, d_in[5], FF, DM, 64);
  encode2d(fn, &p.wd, d_in[6], DM, FF, 64);
  {
    cuuint64_t dims[3] = {DM, SEQ / 2, 2};
    cuuint64_t strides[2] = {DM * 4, DM * 2};
    cuuint32_t box[3] = {64, 16, 1};
    cuuint32_t es[3] = {1, 1, 1};
    fn(&p.out, CU_TENSOR_MAP_DATA_TYPE_BFLOAT16, 3, d_out, dims, strides, box, es, CU_TENSOR_MAP_INTERLEAVE_NONE,
       CU_TENSOR_MAP_SWIZZLE_128B, CU_TENSOR_MAP_L2_PROMOTION_L2_128B, CU_TENSOR_MAP_FLOAT_OOB_FILL_NONE);
  }
  p.x = (const bf16*)d_in[0];
  p.c = (const bf16*)d_in[7];
  p.wmod = (const bf16*)d_in[8];
  for (int cl = 0; cl < 64; cl++) {
    const int grp = cl < 4 ? 0 : (cl < 36 ? (cl - 4) & 7 : 1 + (cl - 36) % 7);
    const int j = cl < 4 ? 4 + cl : (cl < 36 ? (cl - 4) >> 3 : 4 + (cl - 36) / 7);
    p.slot[cl] = (uint8_t)(grp * 8 + j);
  }
  void* q;
  cudaGetSymbolAddress(&q, g_modll); p.modll = (uint4*)q;
  cudaGetSymbolAddress(&q, g_halo); p.halo = (uint4*)q;
  cudaGetSymbolAddress(&q, g_stats); p.stats1 = (uint2*)q; p.stats2 = p.stats1 + SEQ * 8;
  cudaGetSymbolAddress(&q, g_cnt); p.cnt = (unsigned*)q;
  cudaGetSymbolAddress(&q, g_epoch); p.epoch = (unsigned*)q;

  cudaFuncSetAttribute(fused_kernel, cudaFuncAttributeMaxDynamicSharedMemorySize, SMEM_BYTES);
  cudaLaunchConfig_t cfg = {};
  cfg.gridDim = dim3(NCTA + 4);
  cfg.blockDim = dim3(384);
  cfg.dynamicSmemBytes = SMEM_BYTES;
  cfg.stream = cudaStreamPerThread;
  cudaLaunchAttribute at[1];
  at[0].id = cudaLaunchAttributeClusterDimension;
  at[0].val.clusterDim.x = 2; at[0].val.clusterDim.y = 1; at[0].val.clusterDim.z = 1;
  cfg.attrs = at;
  cfg.numAttrs = 1;
  cudaLaunchKernelEx(&cfg, fused_kernel, p);
}
```

```cpp
#include <cuda_runtime.h>
#include <cuda_bf16.h>
#include <cuda.h>
#include <stdint.h>

typedef __nv_bfloat16 bf16;

#define PAUSE 200
#define WMDELAY 500
#define BDELAY 1500
#define NPRE0 3
#define NPRE1 1
#define ALIAS 1

#define PFW 8000
#define PFP 0

#define OSIG 3

#define KH 3

#define HOFF 900

#define X1S 6

#define GW 15

#define BG 2

#define TL 4

__device__ __forceinline__ void wgmma_ss_n128(float (&d)[64], uint32_t da, uint32_t db, int scale_d) {
  asm volatile("{\n.reg .pred p;\n.reg .b64 da, db;\nsetp.ne.b32 p, %66, 0;\n"
    "mov.b64 da, {%64, 0x40000040};\nmov.b64 db, {%65, 0x40000040};\n"
    "wgmma.mma_async.sync.aligned.m64n128k16.f32.bf16.bf16 "
    "{%0, %1, %2, %3, %4, %5, %6, %7, %8, %9, %10, %11, %12, %13, %14, %15, "
    "%16, %17, %18, %19, %20, %21, %22, %23, %24, %25, %26, %27, %28, %29, %30, %31, "
    "%32, %33, %34, %35, %36, %37, %38, %39, %40, %41, %42, %43, %44, %45, %46, %47, "
    "%48, %49, %50, %51, %52, %53, %54, %55, %56, %57, %58, %59, %60, %61, %62, %63}, "
    "da, db, p, 1, 1, 0, 1;\n}\n"
    : "+f"(d[0]), "+f"(d[1]), "+f"(d[2]), "+f"(d[3]), "+f"(d[4]), "+f"(d[5]), "+f"(d[6]), "+f"(d[7]),
      "+f"(d[8]), "+f"(d[9]), "+f"(d[10]), "+f"(d[11]), "+f"(d[12]), "+f"(d[13]), "+f"(d[14]), "+f"(d[15]),
      "+f"(d[16]), "+f"(d[17]), "+f"(d[18]), "+f"(d[19]), "+f"(d[20]), "+f"(d[21]), "+f"(d[22]), "+f"(d[23]),
      "+f"(d[24]), "+f"(d[25]), "+f"(d[26]), "+f"(d[27]), "+f"(d[28]), "+f"(d[29]), "+f"(d[30]), "+f"(d[31]),
      "+f"(d[32]), "+f"(d[33]), "+f"(d[34]), "+f"(d[35]), "+f"(d[36]), "+f"(d[37]), "+f"(d[38]), "+f"(d[39]),
      "+f"(d[40]), "+f"(d[41]), "+f"(d[42]), "+f"(d[43]), "+f"(d[44]), "+f"(d[45]), "+f"(d[46]), "+f"(d[47]),
      "+f"(d[48]), "+f"(d[49]), "+f"(d[50]), "+f"(d[51]), "+f"(d[52]), "+f"(d[53]), "+f"(d[54]), "+f"(d[55]),
      "+f"(d[56]), "+f"(d[57]), "+f"(d[58]), "+f"(d[59]), "+f"(d[60]), "+f"(d[61]), "+f"(d[62]), "+f"(d[63])
    : "r"(da), "r"(db), "r"(scale_d));
}

__device__ __forceinline__ void wgmma_ss_n192(float (&d)[96], uint32_t da, uint32_t db, int scale_d) {
  asm volatile("{\n.reg .pred p;\n.reg .b64 da, db;\nsetp.ne.b32 p, %98, 0;\n"
    "mov.b64 da, {%96, 0x40000040};\nmov.b64 db, {%97, 0x40000040};\n"
    "wgmma.mma_async.sync.aligned.m64n192k16.f32.bf16.bf16 "
    "{%0, %1, %2, %3, %4, %5, %6, %7, %8, %9, %10, %11, %12, %13, %14, %15, "
    "%16, %17, %18, %19, %20, %21, %22, %23, %24, %25, %26, %27, %28, %29, %30, %31, "
    "%32, %33, %34, %35, %36, %37, %38, %39, %40, %41, %42, %43, %44, %45, %46, %47, "
    "%48, %49, %50, %51, %52, %53, %54, %55, %56, %57, %58, %59, %60, %61, %62, %63, "
    "%64, %65, %66, %67, %68, %69, %70, %71, %72, %73, %74, %75, %76, %77, %78, %79, "
    "%80, %81, %82, %83, %84, %85, %86, %87, %88, %89, %90, %91, %92, %93, %94, %95}, "
    "da, db, p, 1, 1, 0, 1;\n}\n"
    : "+f"(d[0]), "+f"(d[1]), "+f"(d[2]), "+f"(d[3]), "+f"(d[4]), "+f"(d[5]), "+f"(d[6]), "+f"(d[7]),
      "+f"(d[8]), "+f"(d[9]), "+f"(d[10]), "+f"(d[11]), "+f"(d[12]), "+f"(d[13]), "+f"(d[14]), "+f"(d[15]),
      "+f"(d[16]), "+f"(d[17]), "+f"(d[18]), "+f"(d[19]), "+f"(d[20]), "+f"(d[21]), "+f"(d[22]), "+f"(d[23]),
      "+f"(d[24]), "+f"(d[25]), "+f"(d[26]), "+f"(d[27]), "+f"(d[28]), "+f"(d[29]), "+f"(d[30]), "+f"(d[31]),
      "+f"(d[32]), "+f"(d[33]), "+f"(d[34]), "+f"(d[35]), "+f"(d[36]), "+f"(d[37]), "+f"(d[38]), "+f"(d[39]),
      "+f"(d[40]), "+f"(d[41]), "+f"(d[42]), "+f"(d[43]), "+f"(d[44]), "+f"(d[45]), "+f"(d[46]), "+f"(d[47]),
      "+f"(d[48]), "+f"(d[49]), "+f"(d[50]), "+f"(d[51]), "+f"(d[52]), "+f"(d[53]), "+f"(d[54]), "+f"(d[55]),
      "+f"(d[56]), "+f"(d[57]), "+f"(d[58]), "+f"(d[59]), "+f"(d[60]), "+f"(d[61]), "+f"(d[62]), "+f"(d[63]),
      "+f"(d[64]), "+f"(d[65]), "+f"(d[66]), "+f"(d[67]), "+f"(d[68]), "+f"(d[69]), "+f"(d[70]), "+f"(d[71]),
      "+f"(d[72]), "+f"(d[73]), "+f"(d[74]), "+f"(d[75]), "+f"(d[76]), "+f"(d[77]), "+f"(d[78]), "+f"(d[79]),
      "+f"(d[80]), "+f"(d[81]), "+f"(d[82]), "+f"(d[83]), "+f"(d[84]), "+f"(d[85]), "+f"(d[86]), "+f"(d[87]),
      "+f"(d[88]), "+f"(d[89]), "+f"(d[90]), "+f"(d[91]), "+f"(d[92]), "+f"(d[93]), "+f"(d[94]), "+f"(d[95])
    : "r"(da), "r"(db), "r"(scale_d));
}

__device__ __forceinline__ void wgmma_ss_n256(float (&d)[128], uint32_t da, uint32_t db, int scale_d) {
  asm volatile("{\n.reg .pred p;\n.reg .b64 da, db;\nsetp.ne.b32 p, %130, 0;\n"
    "mov.b64 da, {%128, 0x40000040};\nmov.b64 db, {%129, 0x40000040};\n"
    "wgmma.mma_async.sync.aligned.m64n256k16.f32.bf16.bf16 "
    "{%0, %1, %2, %3, %4, %5, %6, %7, %8, %9, %10, %11, %12, %13, %14, %15, "
    "%16, %17, %18, %19, %20, %21, %22, %23, %24, %25, %26, %27, %28, %29, %30, %31, "
    "%32, %33, %34, %35, %36, %37, %38, %39, %40, %41, %42, %43, %44, %45, %46, %47, "
    "%48, %49, %50, %51, %52, %53, %54, %55, %56, %57, %58, %59, %60, %61, %62, %63, "
    "%64, %65, %66, %67, %68, %69, %70, %71, %72, %73, %74, %75, %76, %77, %78, %79, "
    "%80, %81, %82, %83, %84, %85, %86, %87, %88, %89, %90, %91, %92, %93, %94, %95, "
    "%96, %97, %98, %99, %100, %101, %102, %103, %104, %105, %106, %107, %108, %109, %110, %111, "
    "%112, %113, %114, %115, %116, %117, %118, %119, %120, %121, %122, %123, %124, %125, %126, %127}, "
    "da, db, p, 1, 1, 0, 1;\n}\n"
    : "+f"(d[0]), "+f"(d[1]), "+f"(d[2]), "+f"(d[3]), "+f"(d[4]), "+f"(d[5]), "+f"(d[6]), "+f"(d[7]),
      "+f"(d[8]), "+f"(d[9]), "+f"(d[10]), "+f"(d[11]), "+f"(d[12]), "+f"(d[13]), "+f"(d[14]), "+f"(d[15]),
      "+f"(d[16]), "+f"(d[17]), "+f"(d[18]), "+f"(d[19]), "+f"(d[20]), "+f"(d[21]), "+f"(d[22]), "+f"(d[23]),
      "+f"(d[24]), "+f"(d[25]), "+f"(d[26]), "+f"(d[27]), "+f"(d[28]), "+f"(d[29]), "+f"(d[30]), "+f"(d[31]),
      "+f"(d[32]), "+f"(d[33]), "+f"(d[34]), "+f"(d[35]), "+f"(d[36]), "+f"(d[37]), "+f"(d[38]), "+f"(d[39]),
      "+f"(d[40]), "+f"(d[41]), "+f"(d[42]), "+f"(d[43]), "+f"(d[44]), "+f"(d[45]), "+f"(d[46]), "+f"(d[47]),
      "+f"(d[48]), "+f"(d[49]), "+f"(d[50]), "+f"(d[51]), "+f"(d[52]), "+f"(d[53]), "+f"(d[54]), "+f"(d[55]),
      "+f"(d[56]), "+f"(d[57]), "+f"(d[58]), "+f"(d[59]), "+f"(d[60]), "+f"(d[61]), "+f"(d[62]), "+f"(d[63]),
      "+f"(d[64]), "+f"(d[65]), "+f"(d[66]), "+f"(d[67]), "+f"(d[68]), "+f"(d[69]), "+f"(d[70]), "+f"(d[71]),
      "+f"(d[72]), "+f"(d[73]), "+f"(d[74]), "+f"(d[75]), "+f"(d[76]), "+f"(d[77]), "+f"(d[78]), "+f"(d[79]),
      "+f"(d[80]), "+f"(d[81]), "+f"(d[82]), "+f"(d[83]), "+f"(d[84]), "+f"(d[85]), "+f"(d[86]), "+f"(d[87]),
      "+f"(d[88]), "+f"(d[89]), "+f"(d[90]), "+f"(d[91]), "+f"(d[92]), "+f"(d[93]), "+f"(d[94]), "+f"(d[95]),
      "+f"(d[96]), "+f"(d[97]), "+f"(d[98]), "+f"(d[99]), "+f"(d[100]), "+f"(d[101]), "+f"(d[102]), "+f"(d[103]),
      "+f"(d[104]), "+f"(d[105]), "+f"(d[106]), "+f"(d[107]), "+f"(d[108]), "+f"(d[109]), "+f"(d[110]), "+f"(d[111]),
      "+f"(d[112]), "+f"(d[113]), "+f"(d[114]), "+f"(d[115]), "+f"(d[116]), "+f"(d[117]), "+f"(d[118]), "+f"(d[119]),
      "+f"(d[120]), "+f"(d[121]), "+f"(d[122]), "+f"(d[123]), "+f"(d[124]), "+f"(d[125]), "+f"(d[126]), "+f"(d[127])
    : "r"(da), "r"(db), "r"(scale_d));
}

namespace {

constexpr int SEQ = 2048, DM = 1024, FF = 3584;
constexpr int NCTA = 128;

constexpr uint32_t STG_OFF = 196608;
constexpr uint32_t MISC_OFF = STG_OFF + 32768;
constexpr uint32_t SMEM_BYTES = MISC_OFF + 3072;
constexpr uint32_t RED_OFF = 2 * 49152;
constexpr uint32_t MODB_OFF = MISC_OFF + 512;

enum { B_FQ = 0, B_EQ = 4, B_FW = 8, B_EW = 14, B_FG = 20, B_EG = 24, B_FD = 28, B_ED = 34,
       B_STGF = 40, B_MODB = 42, B_MODA = 45, B_RDY = 46, B_STGE = 58, B_COUNT = 60 };
enum { C_H = 0, C_O = 1, C_H2 = 3, C_ACT = 4, C_HA = 8, C_H2A = 9, C_A0 = 10, C_SP = 12 };

struct Params {
  CUtensorMap h, o_ld, o_st, h2, act, out, wqkv, wqkv32, wo, wg, wu, wd, act_st, h2_st, wm;
  const bf16* x;
  const bf16* c;
  const bf16* wmod;
  uint4* modll;
  uint4* halo;
  uint2* stats1;
  uint2* stats2;
  unsigned* cnt;
  unsigned* epoch;
  uint8_t slot[64];
};

__device__ __align__(1024) bf16 g_h[SEQ * DM];
__device__ __align__(1024) bf16 g_o[SEQ * DM];
__device__ __align__(1024) bf16 g_act[SEQ * FF];
__device__ __align__(1024) uint4 g_modll[3072 / 2];
__device__ __align__(1024) uint4 g_halo[16 * 8 * 2 * 2 * 8 * 32];
__device__ __align__(1024) uint2 g_stats[2 * SEQ * 8];
__device__ __align__(1024) unsigned g_cnt[16 * 32];
__device__ uint4 g_epoch;
#define TR(off)

__device__ __forceinline__ uint32_t smem_u32(const void* p) { return (uint32_t)__cvta_generic_to_shared(p); }
__device__ __forceinline__ void mbar_init(uint32_t bar, uint32_t count) {
  asm volatile("mbarrier.init.shared::cta.b64 [%0], %1;" ::"r"(bar), "r"(count));
}
__device__ __forceinline__ void mbar_arrive(uint32_t bar) {
  asm volatile("mbarrier.arrive.shared::cta.b64 _, [%0];" ::"r"(bar) : "memory");
}
__device__ __forceinline__ void mbar_arrive_cluster(uint32_t cluster_addr) {
  asm volatile("mbarrier.arrive.shared::cluster.b64 _, [%0];" ::"r"(cluster_addr) : "memory");
}
__device__ __forceinline__ uint32_t mapa(uint32_t addr, uint32_t cta) {
  uint32_t r;
  asm volatile("mapa.shared::cluster.u32 %0, %1, %2;" : "=r"(r) : "r"(addr), "r"(cta));
  return r;
}
__device__ __forceinline__ void mbar_wait(uint32_t bar, uint32_t parity) {
  asm volatile(
      "{\n.reg .pred p;\n"
      "WAIT_%=:\n"
      "mbarrier.try_wait.parity.shared::cta.b64 p, [%0], %1;\n"
      "@!p bra WAIT_%=;\n}\n" ::"r"(bar), "r"(parity) : "memory");
}
__device__ __forceinline__ void mbar_wait_watchdog(uint32_t bar, uint32_t parity) {
  asm volatile(
      "{\n.reg .pred p;\n.reg .u64 t0, t1;\nmov.u64 t0, %%globaltimer;\n"
      "WAIT_%=:\n"
      "mbarrier.try_wait.parity.shared::cta.b64 p, [%0], %1;\n"
      "@p bra DONE_%=;\n"
      "mov.u64 t1, %%globaltimer;\n"
      "sub.u64 t1, t1, t0;\n"
      "setp.lt.u64 p, t1, 2000000000;\n"
      "@p bra WAIT_%=;\n"
      "trap;\n"
      "DONE_%=:\n}\n" ::"r"(bar), "r"(parity) : "memory");
}
__device__ __forceinline__ void cnt_wait(const unsigned* p, unsigned target) {
  asm volatile(
      "{\n.reg .pred p;\n.reg .u32 v;\n.reg .s32 d;\n"
      "WAIT_%=:\n"
      "ld.relaxed.gpu.global.u32 v, [%0];\n"
      "sub.s32 d, v, %1;\n"
      "setp.lt.s32 p, d, 0;\n"
      "@p bra WAIT_%=;\n"
      "fence.proxy.async.global;\n"
      "}\n" ::"l"(p), "r"(target) : "memory");
}
__device__ __forceinline__ void cnt_wait_lazy(const unsigned* p, unsigned target) {
  asm volatile(
      "{\n.reg .pred p;\n.reg .u32 v;\n.reg .s32 d;\n"
      "WAIT_%=:\n"
      "nanosleep.u32 400;\n"
      "ld.relaxed.gpu.global.u32 v, [%0];\n"
      "sub.s32 d, v, %1;\n"
      "setp.lt.s32 p, d, 0;\n"
      "@p bra WAIT_%=;\n"
      "fence.proxy.async.global;\n"
      "}\n" ::"l"(p), "r"(target) : "memory");
}
__device__ __forceinline__ void cnt_signal(unsigned* p) {
  asm volatile("{\n.reg .pred p;\nelect.sync _|p, 0xffffffff;\n@p red.relaxed.gpu.global.add.u32 [%0], 1;\n}\n" ::"l"(p) : "memory");
}
__device__ __forceinline__ void ll_store(uint4* p, uint32_t a, uint32_t b, uint32_t tag) {
  asm volatile("st.relaxed.gpu.global.v2.b64 [%0], {%1, %2};" ::"l"(p), "l"((uint64_t)a | ((uint64_t)tag << 32)),
               "l"((uint64_t)b | ((uint64_t)tag << 32)) : "memory");
}
__device__ __forceinline__ uint4 ll_peek(const uint4* p) {
  uint4 v;
  asm volatile("ld.relaxed.gpu.global.v4.u32 {%0, %1, %2, %3}, [%4];" : "=r"(v.x), "=r"(v.y), "=r"(v.z), "=r"(v.w) : "l"(p) : "memory");
  return v;
}
template <int N, int SLEEP = 0, class F>
__device__ __forceinline__ void ll_poll(F addr, uint32_t tag, uint32_t (&out)[2 * N]) {
  for (;;) {
    uint4 v[N];
#pragma unroll
    for (int i = 0; i < N; i++) v[i] = ll_peek(addr(i));
    uint32_t bad = 0;
#pragma unroll
    for (int i = 0; i < N; i++) {
      bad |= (v[i].y ^ tag) | (v[i].w ^ tag);
      out[2 * i] = v[i].x;
      out[2 * i + 1] = v[i].z;
    }
    if (__all_sync(~0u, bad == 0)) break;
    if (SLEEP) __nanosleep(SLEEP);
  }
}
constexpr uint64_t POLICY_EVICT_FIRST = 0x12F0000000000000ull;
__device__ __forceinline__ void expect_tx_elect(uint32_t bar, uint32_t bytes) {
  asm volatile("{\n.reg .pred p;\nelect.sync _|p, 0xffffffff;\n@p mbarrier.arrive.expect_tx.shared::cta.b64 _, [%0], %1;\n}\n" ::"r"(bar), "r"(bytes) : "memory");
}
__device__ __forceinline__ void arrive_elect(uint32_t bar) {
  asm volatile("{\n.reg .pred p;\nelect.sync _|p, 0xffffffff;\n@p mbarrier.arrive.shared::cta.b64 _, [%0];\n}\n" ::"r"(bar) : "memory");
}
__device__ __forceinline__ void tma_load(uint32_t dst, const CUtensorMap* m, uint32_t bar, int c0, int c1) {
  asm volatile("{\n.reg .pred p;\nelect.sync _|p, 0xffffffff;\n"
               "@p cp.async.bulk.tensor.2d.shared::cluster.global.mbarrier::complete_tx::bytes [%0], [%1, {%3, %4}], [%2];\n}\n"
               ::"r"(dst), "l"(m), "r"(bar), "r"(c0), "r"(c1) : "memory");
}
__device__ __forceinline__ void tma_load_mc(uint32_t dst, const CUtensorMap* m, uint32_t bar, int c0, int c1) {
  asm volatile("{\n.reg .pred p;\nelect.sync _|p, 0xffffffff;\n"
               "@p cp.async.bulk.tensor.2d.shared::cluster.global.mbarrier::complete_tx::bytes.multicast::cluster.L2::cache_hint [%0], [%1, {%3, %4}], [%2], %5, %6;\n}\n"
               ::"r"(dst), "l"(m), "r"(bar), "r"(c0), "r"(c1), "h"((uint16_t)3), "l"(POLICY_EVICT_FIRST) : "memory");
}
__device__ __forceinline__ void tma_load_ef(uint32_t dst, const CUtensorMap* m, uint32_t bar, int c0, int c1) {
  asm volatile("{\n.reg .pred p;\nelect.sync _|p, 0xffffffff;\n"
               "@p cp.async.bulk.tensor.2d.shared::cluster.global.mbarrier::complete_tx::bytes.L2::cache_hint [%0], [%1, {%3, %4}], [%2], %5;\n}\n"
               ::"r"(dst), "l"(m), "r"(bar), "r"(c0), "r"(c1), "l"(POLICY_EVICT_FIRST) : "memory");
}
__device__ __forceinline__ void tma_store2(const CUtensorMap* m, uint32_t src, int c0, int c1) {
  asm volatile("{\n.reg .pred p;\nelect.sync _|p, 0xffffffff;\n"
               "@p cp.async.bulk.tensor.2d.global.shared::cta.bulk_group [%0, {%2, %3}], [%1];\n}\n"
               ::"l"(m), "r"(src), "r"(c0), "r"(c1) : "memory");
}
__device__ __forceinline__ void tma_store3(const CUtensorMap* m, uint32_t src, int c0, int c1, int c2) {
  asm volatile("{\n.reg .pred p;\nelect.sync _|p, 0xffffffff;\n"
               "@p cp.async.bulk.tensor.3d.global.shared::cta.bulk_group [%0, {%2, %3, %4}], [%1];\n}\n"
               ::"l"(m), "r"(src), "r"(c0), "r"(c1), "r"(c2) : "memory");
}
__device__ __forceinline__ void tma_add3(const CUtensorMap* m, uint32_t src, int c0, int c1, int c2) {
  asm volatile("{\n.reg .pred p;\nelect.sync _|p, 0xffffffff;\n"
               "@p cp.reduce.async.bulk.tensor.3d.global.shared::cta.add.bulk_group [%0, {%2, %3, %4}], [%1];\n}\n"
               ::"l"(m), "r"(src), "r"(c0), "r"(c1), "r"(c2) : "memory");
}
__device__ __forceinline__ void store_pause(bool sleep) {
  asm volatile("cp.async.bulk.commit_group;" ::: "memory");
  asm volatile("cp.async.bulk.wait_group.read 0;" ::: "memory");
  if (sleep) __nanosleep(PAUSE);
}
__device__ __forceinline__ void l2_prefetch_tile(const CUtensorMap* m, int c0, int c1) {
  asm volatile("{\n.reg .pred p;\nelect.sync _|p, 0xffffffff;\n@p cp.async.bulk.prefetch.tensor.2d.L2.global [%0, {%1, %2}];\n}\n"
               ::"l"(m), "r"(c0), "r"(c1) : "memory");
}
__device__ __forceinline__ void prefetch_map(const CUtensorMap* m) {
  asm volatile("prefetch.tensormap [%0];" ::"l"(m) : "memory");
}
__device__ __forceinline__ void wg_fence() { asm volatile("wgmma.fence.sync.aligned;" ::: "memory"); }
__device__ __forceinline__ void wg_commit() { asm volatile("wgmma.commit_group.sync.aligned;" ::: "memory"); }
template <int N>
__device__ __forceinline__ void wg_wait() { asm volatile("wgmma.wait_group.sync.aligned %0;" ::"n"(N) : "memory"); }
__device__ __forceinline__ void bar_sync(int id, int n) { asm volatile("bar.sync %0, %1;" ::"r"(id), "r"(n) : "memory"); }
__device__ __forceinline__ void wg_bar(int cw) {
  asm volatile("{\n.reg .pred p;\nsetp.ne.s32 p, %0, 0;\n@p bar.sync 3, 128;\n@!p bar.sync 2, 128;\n}\n" ::"r"(cw) : "memory");
}
__device__ __forceinline__ void cluster_arrive_relaxed() { asm volatile("barrier.cluster.arrive.relaxed.aligned;" ::: "memory"); }
__device__ __forceinline__ void cluster_wait() { asm volatile("barrier.cluster.wait.acquire.aligned;" ::: "memory"); }
__device__ __forceinline__ uint32_t load_epoch(const unsigned* p) {
  uint32_t e;
  asm volatile("ld.relaxed.gpu.global.u32 %0, [%1];" : "=r"(e) : "l"(p) : "memory");
  return e;
}
__device__ __forceinline__ uint32_t pack2(float lo, float hi) {
  uint32_t r;
  asm("cvt.rn.bf16x2.f32 %0, %1, %2;" : "=r"(r) : "f"(hi), "f"(lo));
  return r;
}
__device__ __forceinline__ float bf_lo(uint32_t v) { return __uint_as_float(v << 16); }
__device__ __forceinline__ float bf_hi(uint32_t v) { return __uint_as_float(v & 0xffff0000u); }
__device__ __forceinline__ uint32_t fma_bf2(uint32_t a, uint32_t b, uint32_t c) {
  uint32_t d;
  asm("fma.rn.bf16x2 %0, %1, %2, %3;" : "=r"(d) : "r"(a), "r"(b), "r"(c));
  return d;
}
__device__ __forceinline__ float bf_round(float v) { return __bfloat162float(__float2bfloat16_rn(v)); }
__device__ __forceinline__ float silu_f(float v) { return __fdividef(v, 1.0f + __expf(-v)); }
__device__ __forceinline__ uint4 ldg_nc(const void* p) {
  uint4 v;
  asm volatile("ld.global.nc.L1::no_allocate.v4.u32 {%0, %1, %2, %3}, [%4];" : "=r"(v.x), "=r"(v.y), "=r"(v.z), "=r"(v.w) : "l"(p));
  return v;
}
__device__ __forceinline__ void stmatrix4(uint32_t addr, uint32_t a, uint32_t b, uint32_t c, uint32_t d) {
  asm volatile("stmatrix.sync.aligned.m8n8.x4.shared.b16 [%0], {%1, %2, %3, %4};" ::"r"(addr), "r"(a), "r"(b), "r"(c), "r"(d) : "memory");
}
__device__ __forceinline__ void stmatrix2(uint32_t addr, uint32_t a, uint32_t b) {
  asm volatile("stmatrix.sync.aligned.m8n8.x2.shared.b16 [%0], {%1, %2};" ::"r"(addr), "r"(a), "r"(b) : "memory");
}
__device__ __forceinline__ void stmatrix1(uint32_t addr, uint32_t a) {
  asm volatile("stmatrix.sync.aligned.m8n8.x1.shared.b16 [%0], {%1};" ::"r"(addr), "r"(a) : "memory");
}
__device__ __forceinline__ uint32_t movmatrix(uint32_t a) {
  uint32_t d;
  asm("movmatrix.sync.aligned.m8n8.trans.b16 %0, %1;" : "=r"(d) : "r"(a));
  return d;
}
__device__ __forceinline__ void mma16816(float (&d)[4], uint32_t a0, uint32_t a1, uint32_t a2, uint32_t a3, uint32_t b0, uint32_t b1) {
  asm("mma.sync.aligned.m16n8k16.row.col.f32.bf16.bf16.f32 {%0, %1, %2, %3}, {%4, %5, %6, %7}, {%8, %9}, {%0, %1, %2, %3};"
               : "+f"(d[0]), "+f"(d[1]), "+f"(d[2]), "+f"(d[3]) : "r"(a0), "r"(a1), "r"(a2), "r"(a3), "r"(b0), "r"(b1));
}
__device__ __forceinline__ void mma1688(float (&d)[4], uint32_t a0, uint32_t a1, uint32_t b0) {
  asm("mma.sync.aligned.m16n8k8.row.col.f32.bf16.bf16.f32 {%0, %1, %2, %3}, {%4, %5}, {%6}, {%0, %1, %2, %3};"
               : "+f"(d[0]), "+f"(d[1]), "+f"(d[2]), "+f"(d[3]) : "r"(a0), "r"(a1), "r"(b0));
}
__device__ __forceinline__ void ldmatrix4t(uint32_t (&b)[4], uint32_t addr) {
  asm volatile("ldmatrix.sync.aligned.m8n8.x4.trans.shared.b16 {%0, %1, %2, %3}, [%4];" : "=r"(b[0]), "=r"(b[1]), "=r"(b[2]), "=r"(b[3]) : "r"(addr) : "memory");
}
__device__ __forceinline__ void ldmatrix4(uint32_t& a, uint32_t& b, uint32_t& c, uint32_t& d, uint32_t addr) {
  asm volatile("ldmatrix.sync.aligned.m8n8.x4.shared.b16 {%0, %1, %2, %3}, [%4];" : "=r"(a), "=r"(b), "=r"(c), "=r"(d) : "r"(addr) : "memory");
}
__device__ __forceinline__ void cp_async16(uint32_t dst, const void* src) {
  asm volatile("cp.async.cg.shared.global.L2::cache_hint [%0], [%1], 16, %2;" ::"r"(dst), "l"(src), "l"(POLICY_EVICT_FIRST) : "memory");
}
__device__ __forceinline__ uint32_t lds32(uint32_t addr) {
  uint32_t v;
  asm volatile("ld.shared.u32 %0, [%1];" : "=r"(v) : "r"(addr) : "memory");
  return v;
}
__device__ __forceinline__ void sts64f(uint32_t addr, float a, float b) {
  asm volatile("st.shared.v2.f32 [%0], {%1, %2};" ::"r"(addr), "f"(a), "f"(b) : "memory");
}
constexpr float QK_SCALE = 0.17677669529663687f;
__device__ __forceinline__ float softmax8(float& p0, float& p1) {
  float m = fmaxf(p0, p1);
  m = fmaxf(m, __shfl_xor_sync(~0u, m, 1));
  m = fmaxf(m, __shfl_xor_sync(~0u, m, 2));
  asm("ex2.approx.ftz.f32 %0, %1;" : "=f"(p0) : "f"((p0 - m) * 1.4426950408889634f));
  asm("ex2.approx.ftz.f32 %0, %1;" : "=f"(p1) : "f"((p1 - m) * 1.4426950408889634f));
  float s = p0 + p1;
  s += __shfl_xor_sync(~0u, s, 1);
  s += __shfl_xor_sync(~0u, s, 2);
  float r;
  asm("rcp.approx.ftz.f32 %0, %1;" : "=f"(r) : "f"(s));
  return r;
}
__device__ __forceinline__ void sts128(uint32_t addr, uint32_t a, uint32_t b, uint32_t c, uint32_t d) {
  asm volatile("st.shared.v4.u32 [%0], {%1, %2, %3, %4};" ::"r"(addr), "r"(a), "r"(b), "r"(c), "r"(d) : "memory");
}
__device__ __forceinline__ uint4 lds128(uint32_t addr) {
  uint4 v;
  asm volatile("ld.shared.v4.u32 {%0, %1, %2, %3}, [%4];" : "=r"(v.x), "=r"(v.y), "=r"(v.z), "=r"(v.w) : "r"(addr) : "memory");
  return v;
}
__device__ __forceinline__ float2 lds64f(uint32_t addr) {
  float2 v;
  asm volatile("ld.shared.v2.f32 {%0, %1}, [%2];" : "=f"(v.x), "=f"(v.y) : "r"(addr) : "memory");
  return v;
}
#define PROF_AT(cond, slot) do {} while (0)

constexpr uint32_t SMEM_BASE = 1024;
constexpr uint32_t DESC_A = (1u << 16) | (SMEM_BASE >> 4);
constexpr uint32_t DESC_B = ((8192u >> 4) << 16) | (SMEM_BASE >> 4);

template <int BN> struct Wg;
template <> struct Wg<128> { static __device__ __forceinline__ void mma(float (&d)[64], uint32_t a, uint32_t b, int s) { wgmma_ss_n128(d, a, b, s); } };
template <> struct Wg<192> { static __device__ __forceinline__ void mma(float (&d)[96], uint32_t a, uint32_t b, int s) { wgmma_ss_n192(d, a, b, s); } };
template <> struct Wg<256> { static __device__ __forceinline__ void mma(float (&d)[128], uint32_t a, uint32_t b, int s) { wgmma_ss_n256(d, a, b, s); } };

struct Ring {
  uint32_t full0, rel0;
  int s;
  uint32_t ph;
  uint32_t off;
  bool releaser;
};

template <int N>
__device__ __forceinline__ void fence_regs(float (&a)[N]) {
#pragma unroll
  for (int i = 0; i < N; i++) asm volatile("" : "+f"(a[i])::"memory");
}

template <int BN, int NST, uint32_t STAGE>
__device__ __forceinline__ void kblock(float (&acc)[BN / 2], Ring& g, uint32_t a_addr, bool zero, uint32_t& prev, uint32_t b_rel = 16384) {
  mbar_wait(g.full0 + 8 * g.s, g.ph);
  const uint32_t da = DESC_A + (a_addr >> 4);
  const uint32_t db = DESC_B + ((g.off + b_rel) >> 4);
  wg_fence();
#pragma unroll
  for (int k = 0; k < 4; k++) Wg<BN>::mma(acc, da + k * 2, db + k * 128, !(zero && k == 0));
  wg_commit();
  wg_wait<1>();
  if (prev != 0) mbar_arrive_cluster(prev);
  prev = g.releaser ? g.rel0 + 8 * g.s : 0u;
  if (++g.s == NST) { g.s = 0; g.ph ^= 1; }
  g.off += STAGE;
  if (g.off == NST * STAGE) g.off = 0;
}
template <int N>
__device__ __forceinline__ void tile_end(float (&acc)[N], uint32_t& prev) {
  wg_wait<0>();
  if (prev != 0) mbar_arrive_cluster(prev);
  prev = 0;
  fence_regs(acc);
}

__device__ __forceinline__ int other_kb(int q, int j) {
  const int ch = q >= 7, jj = q - 7 * ch;
  return 2 * (jj < j ? jj : jj + 1) + ch;
}
__device__ __forceinline__ int qkv_kb(int it, int j) {
  return it < 4 ? 2 * j + (it & 1) : other_kb(it < 18 ? it - 4 : it - 18, j);
}
__device__ __forceinline__ int wo_k(int it, int j) {
  return it < 8 ? it * 128 : (it == 8 ? j : (it - 9 < j ? it - 9 : it - 8)) * 128 + 64;
}
__device__ __forceinline__ int down_k(int d) {
  const int u = d + KH;
  if (u < 8) return u * 448 + 384;
  if (u < 40) return (((u - 8) & 15) >> 1) * 448 + ((u - 8) >> 4) * 128 + (u & 1) * 64;
  return (u & 7) * 448 + 256 + (u >= 48 ? 64 : 0);
}
__device__ __forceinline__ void wait_q_free(uint32_t empty, int i) {
  mbar_wait(empty + 8 * ((i * 2) / 3), 1);
  mbar_wait(empty + 8 * ((i * 2 + 1) / 3), 1);
}
__device__ __forceinline__ void wait_w_free(uint32_t empty, int i) {
  const int t = (i + 3) & 3, w0 = (t * 3) / 2, w1 = (t * 3 + 2) / 2;
  mbar_wait(empty + 8 * w0, w0 < 4);
  mbar_wait(empty + 8 * w1, w1 < 4);
}
__device__ __forceinline__ void wait_g_free(uint32_t empty, int i) {
  const int s = i < 4 ? i + 2 : i - 4, b0 = ((s * 2) / 3 + 1) & 3, b1 = ((s * 2 + 1) / 3 + 1) & 3;
  mbar_wait(empty + 8 * b0, b0 < 2);
  mbar_wait(empty + 8 * b1, b1 < 2);
}

__device__ __forceinline__ void chan(float& m, float& q, float m2, float q2, float n) {
  const float d = m2 - m;
  m = 0.5f * (m + m2);
  q = q + q2 + d * d * (0.5f * n);
}

__device__ __forceinline__ uint32_t tag16(uint32_t tag) { return tag % 65535u + 1u; }
__device__ __forceinline__ void stat_store(uint2* slot, float m, float q, uint32_t t16) {
  const uint32_t a = ((__float_as_uint(m) + 0x80u) & 0xffffff00u) | (t16 & 0xffu), b = ((__float_as_uint(q) + 0x80u) & 0xffffff00u) | (t16 >> 8);
  asm volatile("st.relaxed.gpu.global.b64 [%0], %1;" ::"l"(slot), "l"((uint64_t)a | ((uint64_t)b << 32)) : "memory");
}
__device__ __forceinline__ void stat_gather(const uint2* rows, uint32_t t16, int lane, float (&rs)[2], float (&nb)[2]) {
  const uint4* sp = (const uint4*)(rows + (lane >> 3) * 128) + (lane & 7);
  const uint32_t want = (t16 & 0xffu) | ((t16 >> 8) << 8);
  uint4 a, b;
  for (;;) {
    a = ll_peek(sp);
    b = ll_peek(sp + 256);
    const uint32_t bad = (__byte_perm(a.x, a.y, 0x40) ^ want) | (__byte_perm(a.z, a.w, 0x40) ^ want) | (__byte_perm(b.x, b.y, 0x40) ^ want) |
                         (__byte_perm(b.z, b.w, 0x40) ^ want);
    if (__all_sync(~0u, (bad & 0xffffu) == 0)) break;
  }
  float m0 = __uint_as_float(a.x & 0xffffff00u), q0 = __uint_as_float(a.y & 0xffffff00u);
  float m1 = __uint_as_float(a.z & 0xffffff00u), q1 = __uint_as_float(a.w & 0xffffff00u);
  chan(m0, q0, __uint_as_float(b.x & 0xffffff00u), __uint_as_float(b.y & 0xffffff00u), 128.f);
  chan(m1, q1, __uint_as_float(b.z & 0xffffff00u), __uint_as_float(b.w & 0xffffff00u), 128.f);
  const bool hi = lane & 8;
  float m = hi ? m1 : m0, q = hi ? q1 : q0;
  chan(m, q, __shfl_xor_sync(~0u, hi ? m0 : m1, 8), __shfl_xor_sync(~0u, hi ? q0 : q1, 8), 256.f);
  chan(m, q, __shfl_xor_sync(~0u, m, 16), __shfl_xor_sync(~0u, q, 16), 512.f);
  const float rstd = rsqrtf(q * (1.0f / DM) + 1e-5f), nmr = -m * rstd;
  const int r = lane >> 2, src = (r >> 1) + (r & 1) * 8;
  rs[0] = __shfl_sync(~0u, rstd, src); nb[0] = __shfl_sync(~0u, nmr, src);
  rs[1] = __shfl_sync(~0u, rstd, src + 4); nb[1] = __shfl_sync(~0u, nmr, src + 4);
}

__device__ __forceinline__ void publish_stats(const uint32_t (&xl)[16], const uint32_t (&xh)[16], uint2* slot, int lane, uint32_t t16) {
  float ds[4] = {0.f, 0.f, 0.f, 0.f}, dl[4] = {0.f, 0.f, 0.f, 0.f}, dh[4] = {0.f, 0.f, 0.f, 0.f};
#pragma unroll
  for (int q = 0; q < 8; q++) {
    mma16816(ds, xl[2 * q], xh[2 * q], xl[2 * q + 1], xh[2 * q + 1], 0x3f803f80u, 0x3f803f80u);
    mma16816(dl, xl[2 * q], xh[2 * q], xl[2 * q + 1], xh[2 * q + 1], xl[2 * q], xl[2 * q + 1]);
    mma16816(dh, xl[2 * q], xh[2 * q], xl[2 * q + 1], xh[2 * q + 1], xh[2 * q], xh[2 * q + 1]);
  }
  const int r = lane >> 2;
  if ((lane & 3) == (r >> 1)) {
    const float ml = ds[0] * (1.0f / 128), mh = ds[2] * (1.0f / 128);
    const float ql = fmaxf(((r & 1) ? dl[1] : dl[0]) - ds[0] * ml, 0.f), qh = fmaxf(((r & 1) ? dh[3] : dh[2]) - ds[2] * mh, 0.f);
    stat_store(slot + r, ml, ql, t16);
    stat_store(slot + r + 8, mh, qh, t16);
  }
  __syncwarp();
}

__device__ __forceinline__ void stage_slab(uint32_t chunk, int warp, int lane, const uint32_t (&lo)[8], const uint32_t (&hi)[8]) {
  const int row = warp * 16 + (lane & 7) + ((lane >> 3) & 1) * 8;
  const uint32_t rbase = chunk + row * 128;
#pragma unroll
  for (int q = 0; q < 4; q++) {
    const int grp = 2 * q + (lane >> 4);
    stmatrix4(rbase + ((grp ^ (row & 7)) << 4), lo[2 * q], hi[2 * q], lo[2 * q + 1], hi[2 * q + 1]);
  }
}
__device__ __forceinline__ float silu_mul(float g, float u) {
  float e, r;
  asm("ex2.approx.ftz.f32 %0, %1;" : "=f"(e) : "f"(g * -1.4426950408889634f));
  asm("rcp.approx.ftz.f32 %0, %1;" : "=f"(r) : "f"(1.0f + e));
  return g * r * u;
}
__device__ __forceinline__ uint32_t swiglu2(uint32_t g2, uint32_t u2) {
  asm volatile("" : "+r"(g2));
  return pack2(silu_mul(bf_lo(g2), bf_lo(u2)), silu_mul(bf_hi(g2), bf_hi(u2)));
}
__device__ __forceinline__ void stage_done(uint32_t bar, int lane) {
  asm volatile("fence.proxy.async.shared::cta;" ::: "memory");
  __syncwarp();
  if (lane == 0) mbar_arrive(bar);
}

__device__ __forceinline__ int fresh_tid() {
  int t;
  asm volatile("mov.u32 %0, %%tid.x;" : "=r"(t));
  return t;
}
#define RING_IDS()                                                                                           \
  const int tid = fresh_tid() - 128;                                                                         \
  const int cw = __shfl_sync(~0u, tid >> 7, 0), warp = __shfl_sync(~0u, (tid >> 5) & 3, 0);                  \
  const bool releaser = (tid & 31) < 2;                                                                      \
  const uint32_t rbars = mapa(bars, tid & 1);                                                                \
  const uint32_t a_base = cw * 8192
#define LANE_IDS()                                                                                           \
  const int lane = fresh_tid() & 31, r = lane >> 2, c = lane & 3;                                            \
  const int srow = warp * 16 + (lane & 7) + ((lane >> 3) & 1) * 8;                                           \
  const uint32_t slab = stg + cw * 8192 + srow * 128, sw0 = (lane >> 4) ^ (srow & 7);                        \
  (void)r; (void)c; (void)slab; (void)sw0

template <int NPRE, bool EAGER, class Step>
__device__ __forceinline__ void attention(float (&acc)[96], const Params& p, int rho, int rb, int cta, int cw, int warp, uint32_t tag,
                                          uint32_t stg, uint32_t bars, uint32_t& prev, Step step) {
  uint32_t ql[8], qh[8], k0[8], k1[8], v0[8], v1[8], hp[16];
  if (EAGER) {
    tile_end(acc, prev);
  } else {
    step();
    fence_regs(acc);
  }
#pragma unroll
  for (int t = 0; t < 8; t++) {
    k0[t] = pack2(acc[4 * (8 + t)], acc[4 * (8 + t) + 1]);
    k1[t] = pack2(acc[4 * (8 + t) + 2], acc[4 * (8 + t) + 3]);
    v0[t] = pack2(acc[4 * (16 + t)], acc[4 * (16 + t) + 1]);
    v1[t] = pack2(acc[4 * (16 + t) + 2], acc[4 * (16 + t) + 3]);
    asm volatile("" : "+r"(k0[t]), "+r"(k1[t]), "+r"(v0[t]), "+r"(v1[t]));
  }
  const int lane = fresh_tid() & 31, r = lane >> 2, c = lane & 3;
#pragma unroll
  for (int t = 0; t < 8; t++) v1[t] = movmatrix(v1[t]);
  mbar_wait(bars + 8 * B_STGE, rho);
  mbar_wait(bars + 8 * (B_STGE + 1), 0);
  const uint32_t xch = stg + 16384 + (cw * 4 + warp) * 2048 + lane * 16;
  if (warp < 3) {
    sts128(xch, k1[0], k1[1], k1[2], k1[3]);
    sts128(xch + 512, k1[4], k1[5], k1[6], k1[7]);
    sts128(xch + 1024, v1[0], v1[1], v1[2], v1[3]);
    sts128(xch + 1536, v1[4], v1[5], v1[6], v1[7]);
  } else if (rb < 15) {
    uint4* dst = p.halo + ((cta * 2 + rho) * 2 + cw) * 256 + lane;
#pragma unroll
    for (int t = 0; t < 4; t++) {
      ll_store(dst + t * 32, k1[2 * t], k1[2 * t + 1], tag);
      ll_store(dst + (4 + t) * 32, v1[2 * t], v1[2 * t + 1], tag);
    }
  }
#pragma unroll
  for (int t = 0; t < 8; t++) {
    v0[t] = movmatrix(v0[t]);
    ql[t] = pack2(acc[4 * t], acc[4 * t + 1]);
    qh[t] = pack2(acc[4 * t + 2], acc[4 * t + 3]);
    asm volatile("" : "+r"(v0[t]), "+r"(ql[t]), "+r"(qh[t]));
  }
#pragma unroll 1
  for (int i = 0; i < NPRE; i++) step();
  const uint4* src = p.halo + (((cta - 8) * 2 + rho) * 2 + cw) * 256 + lane;
  uint4 early[8] = {};
  if (warp == 0 && rb > 0) {
#pragma unroll
    for (int i = 0; i < 8; i++) early[i] = ll_peek(src + i * 32);
  }
  step();
  wg_bar(cw);
  if (warp > 0) {
#pragma unroll
    for (int t = 0; t < 4; t++) {
      const uint4 a = lds128(xch - 2048 + t * 512);
      hp[4 * t] = a.x; hp[4 * t + 1] = a.y; hp[4 * t + 2] = a.z; hp[4 * t + 3] = a.w;
    }
  } else if (rb > 0) {
    uint32_t bad = 0;
#pragma unroll
    for (int i = 0; i < 8; i++) {
      bad |= (early[i].y ^ tag) | (early[i].w ^ tag);
      hp[2 * i] = early[i].x;
      hp[2 * i + 1] = early[i].z;
    }
    if (!__all_sync(~0u, bad == 0)) ll_poll<8>([&](int i) { return src + i * 32; }, tag, hp);
  } else {
#pragma unroll
    for (int t = 0; t < 16; t++) hp[t] = 0;
  }
  wg_wait<0>();
  if (prev != 0) mbar_arrive_cluster(prev);
  prev = 0;
#pragma unroll
  for (int t = 0; t < 8; t++) asm volatile("" : "+r"(ql[t])::"memory");
  const bool up0 = 2 * c > r, up1 = 2 * c + 1 > r;
  const bool first = (rb == 0) && (warp == 0);
  uint32_t a0[2], a2[2], a3[2], a5[2];
  float il[2], ih[2];
#pragma unroll
  for (int h = 0; h < 2; h++) {
    float sp[4] = {0.f, 0.f, 0.f, 0.f}, s0[4] = {0.f, 0.f, 0.f, 0.f}, s1[4] = {0.f, 0.f, 0.f, 0.f};
#pragma unroll
    for (int ks = 0; ks < 2; ks++) {
      const int t = 4 * h + 2 * ks;
      mma16816(sp, ql[t], qh[t], ql[t + 1], qh[t + 1], hp[t], hp[t + 1]);
      mma16816(s0, ql[t], qh[t], ql[t + 1], qh[t + 1], k0[t], k0[t + 1]);
      mma16816(s1, ql[t], qh[t], ql[t + 1], qh[t + 1], k1[t], k1[t + 1]);
    }
    float p0 = (up0 ? sp[0] : s0[0]) * QK_SCALE, p1 = (up1 ? sp[1] : s0[1]) * QK_SCALE;
    float p2 = (up0 ? s0[2] : s1[2]) * QK_SCALE, p3 = (up1 ? s0[3] : s1[3]) * QK_SCALE;
    if (first && up0) p0 = -1000000000.0f;
    if (first && up1) p1 = -1000000000.0f;
    il[h] = softmax8(p0, p1);
    ih[h] = softmax8(p2, p3);
    a0[h] = pack2(up0 ? p0 : 0.f, up1 ? p1 : 0.f);
    a2[h] = pack2(up0 ? 0.f : p0, up1 ? 0.f : p1);
    a3[h] = pack2(up0 ? p2 : 0.f, up1 ? p3 : 0.f);
    a5[h] = pack2(up0 ? 0.f : p2, up1 ? 0.f : p3);
  }
  float o[8][4];
#pragma unroll
  for (int t = 0; t < 8; t++) {
#pragma unroll
    for (int q = 0; q < 4; q++) o[t][q] = 0.f;
    mma1688(o[t], 0u, a5[t >> 2], v1[t]);
    mma16816(o[t], a0[t >> 2], 0u, a2[t >> 2], a3[t >> 2], hp[8 + t], v0[t]);
  }
#pragma unroll
  for (int t = 0; t < 8; t++) fence_regs(o[t]);
  if (!EAGER) step();
  uint32_t ol[8], oh[8];
#pragma unroll
  for (int t = 0; t < 8; t++) {
    ol[t] = pack2(o[t][0] * il[t >> 2], o[t][1] * il[t >> 2]);
    oh[t] = pack2(o[t][2] * ih[t >> 2], o[t][3] * ih[t >> 2]);
  }
  if (!EAGER) step();
  stage_slab(stg + cw * 8192, warp, lane, ol, oh);
  stage_done(bars + 8 * B_STGF, lane);
  if (!EAGER) step();
}

__global__ void __launch_bounds__(384, 1) fused_kernel(const __grid_constant__ Params p) {
  extern __shared__ __align__(1024) uint8_t smem_raw[];
  const uint32_t sm = smem_u32(smem_raw);
  const uint32_t bars = sm + MISC_OFF;
  const uint32_t stg = sm + STG_OFF;
  const int rank = blockIdx.x & 1;
  const int cl = blockIdx.x >> 1;
  if (cl >= NCTA / 2) {
    const int e = blockIdx.x - NCTA, wid = __shfl_sync(~0u, (int)(threadIdx.x >> 5), 0), lane = threadIdx.x & 31;
    if (threadIdx.x == 0) {
      for (int i = 0; i < 6; i++) { mbar_init(bars + 8 * i, 1); mbar_init(bars + 8 * (6 + i), 8); }
      for (int i = 0; i < 8; i++) { mbar_init(bars + 8 * (16 + i), 1); mbar_init(bars + 8 * (24 + i), 4); }
      mbar_init(bars + 8 * 12, 1);
      asm volatile("fence.mbarrier_init.release.cluster;" ::: "memory");
    }
    const uint32_t tag = load_epoch(p.epoch) + 1;
    if (threadIdx.x < 256) ll_store(p.modll + 512 + (threadIdx.x >> 6) * 256 + e * 64 + (threadIdx.x & 63), 0u, 0u, 0u);
    for (int i = threadIdx.x; i < 1536; i += 384) {
      uint4 o = make_uint4(0u, 0u, 0u, 0u);
      if (i < 1024 && (i & 63) < 8) {
        const uint4 cv = ldg_nc(p.c + (i >> 6) * 64 + (i & 7) * 8);
        o = make_uint4(pack2(silu_f(bf_lo(cv.x)), silu_f(bf_hi(cv.x))), pack2(silu_f(bf_lo(cv.y)), silu_f(bf_hi(cv.y))),
                       pack2(silu_f(bf_lo(cv.z)), silu_f(bf_hi(cv.z))), pack2(silu_f(bf_lo(cv.w)), silu_f(bf_hi(cv.w))));
      }
      sts128(stg + i * 16, o.x, o.y, o.z, o.w);
    }
    asm volatile("fence.proxy.async.shared::cta;" ::: "memory");
    __syncthreads();
    if (wid == 0) {
      __nanosleep(WMDELAY);
      uint32_t ph = 1;
#pragma unroll 1
      for (int it = 0, s = 0; it < 64; it++) {
        mbar_wait(bars + 8 * (6 + s), ph);
        expect_tx_elect(bars + 8 * s, 32768);
#pragma unroll
        for (int q = 0; q < 4; q++) tma_load_ef(sm + s * 32768 + q * 8192, &p.wm, bars + 8 * s, 2048 + (it >> 4) * 1024 + e * 256 + q * 64, (it & 15) * 64);
        if (++s == 6) { s = 0; ph ^= 1; }
      }
    } else if (wid == 1 && PFW) {
      __nanosleep(PFW);
#pragma unroll 1
      for (int i = 0; i < 64; i++) {
        l2_prefetch_tile(&p.wo, (i & 15) * 64, (e * 4 + (i >> 4)) * 64);
        if (PFP) __nanosleep(PFP);
      }
#pragma unroll 1
      for (int i = 0; i < 80; i++) {
        if (i < 64) l2_prefetch_tile((i & 1) ? &p.wu : &p.wg, ((i >> 1) & 7) * 448 + 384, ((i >> 4) * 4 + e) * 64);
        else l2_prefetch_tile((i & 2) ? &p.wu : &p.wg, (e * 2 + ((i >> 3) & 1)) * 448 + (i & 1) * 64, (e * 4 + ((i >> 2) & 3)) * 64);
        if (PFP) __nanosleep(PFP);
      }
    } else if (wid >= 4) {
      const int hf = (wid >> 2) - 1;
      uint32_t ph = 0;
      int s = 0;
#pragma unroll 1
      for (int v = 0; v < 4; v++) {
        float acc[64];
#pragma unroll 1
        for (int kb = 0; kb < 16; kb++) {
          mbar_wait_watchdog(bars + 8 * s, ph);
          const uint32_t da = DESC_A + ((STG_OFF + kb * 1024) >> 4), db = DESC_B + ((s * 32768 + hf * 16384) >> 4);
          wg_fence();
#pragma unroll
          for (int k = 0; k < 4; k++) wgmma_ss_n128(acc, da + k * 2, db + k * 128, (kb | k) != 0);
          wg_commit();
          wg_wait<0>();
          if (lane == 0) mbar_arrive(bars + 8 * (6 + s));
          if (++s == 6) { s = 0; ph ^= 1; }
        }
        fence_regs(acc);
        if ((wid & 3) == 0) {
#pragma unroll
          for (int n = 0; n < 16; n++) {
            const uint32_t mine = pack2(acc[4 * n], acc[4 * n + 1]), next = __shfl_down_sync(~0u, mine, 1);
            if (lane < 4 && (lane & 1) == 0) ll_store(p.modll + 512 + v * 256 + e * 64 + hf * 32 + n * 2 + (lane >> 1), mine, next, tag);
            if (lane < 4) sts64f(sm + MODB_OFF + (hf * 128 + n * 8 + lane * 2) * 4, bf_lo(mine), bf_hi(mine));
          }
        }
      }
    }
    __syncthreads();
    if (wid == 0 || wid == 2) {
      const int w = wid >> 1;
      if (w == 0) {
        expect_tx_elect(bars + 8 * 12, KH * 32768);
#pragma unroll 1
        for (int q = 0; q < 4 * KH; q++) tma_load_ef(sm + q * 8192, &p.wd, bars + 8 * 12, e * 256 + (q & 3) * 64, (q >> 2) * 448 + 384);
      }
      cnt_wait_lazy(p.cnt + C_ACT, tag * 8);
      if (w == 1) __nanosleep(HOFF);
      uint32_t ph = 1, ready = 0;
#pragma unroll 1
      for (int it = 0, s = 0; it < 16 * KH; it++) {
        const int rb = it / KH, kc = it - rb * KH;
        while (!((ready >> rb) & 1)) {
          ready = __ballot_sync(~0u, (int)(load_epoch(p.cnt + (lane & 15) * 32 + C_ACT) - tag * 8) >= 0);
          asm volatile("fence.proxy.async.global;" ::: "memory");
        }
        const uint32_t fb = bars + 8 * (16 + w * 4 + s), dst = sm + 98304 + w * 32768 + s * 8192;
        mbar_wait(fb + 64, ph);
        expect_tx_elect(fb, 8192);
        tma_load(dst, &p.act_st, fb, kc * 448 + 384, rb * 128 + w * 64);
        tma_load(dst + 4096, &p.act_st, fb, kc * 448 + 384, rb * 128 + w * 64 + 32);
        if (++s == 4) { s = 0; ph ^= 1; }
      }
    } else if (wid >= 4) {
      const int w = (wid >> 2) - 1, warp = wid & 3;
      const uint32_t out_stg = (w ? stg : sm + 163840) + warp * 2048;
      const uint32_t slab = out_stg + (lane & 15) * 128, sw0 = (lane >> 4) ^ (lane & 7);
      mbar_wait_watchdog(bars + 8 * 12, 0);
#pragma unroll 1
      for (int i = threadIdx.x - 128; i < KH * 2048; i += 256) {
        const uint32_t gp = sm + MODB_OFF + (((i >> 9) & 3) * 64 + ((i ^ (i >> 3)) & 7) * 8) * 4;
        const uint4 v = lds128(sm + i * 16), ga = lds128(gp), gc = lds128(gp + 16);
        sts128(sm + i * 16, pack2(bf_lo(v.x) * __uint_as_float(ga.x), bf_hi(v.x) * __uint_as_float(ga.y)),
               pack2(bf_lo(v.y) * __uint_as_float(ga.z), bf_hi(v.y) * __uint_as_float(ga.w)),
               pack2(bf_lo(v.z) * __uint_as_float(gc.x), bf_hi(v.z) * __uint_as_float(gc.y)),
               pack2(bf_lo(v.w) * __uint_as_float(gc.z), bf_hi(v.w) * __uint_as_float(gc.w)));
      }
      asm volatile("fence.proxy.async.shared::cta;" ::: "memory");
      bar_sync(1, 256);
      uint32_t ph = 0;
      int s = 0;
#pragma unroll 1
      for (int rb = 0; rb < 16; rb++) {
        float acc[128];
#pragma unroll 1
        for (int kc = 0; kc < KH; kc++) {
          mbar_wait_watchdog(bars + 8 * (16 + w * 4 + s), ph);
          const uint32_t da = DESC_A + ((98304 + w * 32768 + s * 8192) >> 4), db = DESC_B + ((kc * 32768) >> 4);
          wg_fence();
#pragma unroll
          for (int k = 0; k < 4; k++) wgmma_ss_n256(acc, da + k * 2, db + k * 128, (kc | k) != 0);
          wg_commit();
          wg_wait<1>();
          if (kc > 0 && lane == 0) mbar_arrive(bars + 8 * (24 + w * 4 + ((s + 3) & 3)));
          if (++s == 4) { s = 0; ph ^= 1; }
        }
        asm volatile("cp.async.bulk.wait_group 0;" ::: "memory");
        __syncwarp();
        if (rb > 0) cnt_signal(p.cnt + (rb - 1) * 32 + C_SP + e);
        wg_wait<0>();
        fence_regs(acc);
        __syncwarp();
        if (lane == 0) mbar_arrive(bars + 8 * (24 + w * 4 + ((s + 3) & 3)));
#pragma unroll
        for (int q = 0; q < 16; q++)
          stmatrix4(slab + (q >> 2) * 8192 + ((sw0 ^ ((q & 3) * 2)) << 4), pack2(acc[8 * q], acc[8 * q + 1]), pack2(acc[8 * q + 2], acc[8 * q + 3]),
                    pack2(acc[8 * q + 4], acc[8 * q + 5]), pack2(acc[8 * q + 6], acc[8 * q + 7]));
        asm volatile("fence.proxy.async.shared::cta;" ::: "memory");
        __syncwarp();
#pragma unroll
        for (int ch = 0; ch < 4; ch++) tma_add3(&p.out, out_stg + ch * 8192, e * 256 + ch * 64, rb * 64 + warp * 16, w);
        asm volatile("cp.async.bulk.commit_group;" ::: "memory");
      }
      asm volatile("cp.async.bulk.wait_group 0;" ::: "memory");
      __syncwarp();
      cnt_signal(p.cnt + 15 * 32 + C_SP + e);
    }
    return;
  }
  const int slot = p.slot[cl];
  const int rb = (slot >> 3) * 2 + rank, j = slot & 7;
  const int cta = rb * 8 + j;
  PROF_AT(threadIdx.x == 0, 0);

  if (threadIdx.x < 128) {
    uint32_t tag = load_epoch(p.epoch);
    asm volatile("setmaxnreg.dec.sync.aligned.u32 40;");
    const int warp = __shfl_sync(~0u, (int)(threadIdx.x >> 5), 0), lane = threadIdx.x & 31;
    if (threadIdx.x == 0) {
      if ((sm & 0x3FFFF) != SMEM_BASE) asm volatile("trap;");
      for (int i = 0; i < 4; i++) { mbar_init(bars + 8 * (B_FQ + i), 1); mbar_init(bars + 8 * (B_EQ + i), 16); }
      for (int i = 0; i < 6; i++) { mbar_init(bars + 8 * (B_FW + i), 1); mbar_init(bars + 8 * (B_EW + i), 16); }
      for (int i = 0; i < 4; i++) { mbar_init(bars + 8 * (B_FG + i), 1); mbar_init(bars + 8 * (B_EG + i), 16); }
      for (int i = 0; i < 6; i++) { mbar_init(bars + 8 * (B_FD + i), 1); mbar_init(bars + 8 * (B_ED + i), 16); }
      for (int i = 0; i < 2; i++) { mbar_init(bars + 8 * (B_STGF + i), 8); mbar_init(bars + 8 * (B_STGE + i), 1); }
      mbar_init(bars + 8 * B_MODB, 1);
      mbar_init(bars + 8 * (B_MODB + 1), 1);
      mbar_init(bars + 8 * B_MODA, 1);
      for (int i = 0; i < 11; i++) mbar_init(bars + 8 * (B_RDY + i), 1);
      asm volatile("fence.mbarrier_init.release.cluster;" ::: "memory");
    }
    __syncwarp();
    cluster_arrive_relaxed();
    tag += 1;
    const unsigned target = tag * 8;
    unsigned* cnt = p.cnt + rb * 32;
    cluster_wait();
    if (warp == 0) {
      const CUtensorMap* wgu = rank ? &p.wu : &p.wg;
      uint32_t st = sm + 16384, fb = bars + 8 * B_FQ, ph = 1;
      __nanosleep(BDELAY);
#pragma unroll 1
      for (int it = 0; it < 32; it++) {
        const int kb = qkv_kb(it, j), col = j * 128 + ((it < 4 ? it >= 2 : it >= 18) ? 64 : 0);
        if (BG && it == BG) mbar_wait(bars + 8 * B_MODA, 0);
        mbar_wait(fb + 8 * (B_EQ - B_FQ), ph);
        expect_tx_elect(fb, it < 4 ? 24576 : 40960);
        tma_load_mc(st + rank * 8192, &p.wqkv, fb, col + rank * 1024, kb * 64);
        tma_load_mc(st + 16384 + rank * 4096, &p.wqkv32, fb, col + 2048, kb * 64 + rank * 32);
        st += 49152; fb += 8;
        if ((it & 3) == 3) { st -= 4 * 49152; fb -= 32; ph ^= 1; }
      }
      fb = bars + 8 * B_FW; ph = 1;
#pragma unroll 1
      for (int it = 0, s = 0; it < 34; it++) {
        if (it < 6) wait_q_free(bars + 8 * B_EQ, it);
        if (it == 16) mbar_wait(bars + 8 * (B_FW + GW % 6), (GW / 6) & 1);
        mbar_wait(fb + 8 * (B_EW - B_FW), ph);
        expect_tx_elect(fb, (it == 8 || it == 18 || it == 19) ? 16384 : 32768);
        const int k0 = it < 16 ? wo_k(it, j) : (it < 20 ? 2 * j + (it & 1) : other_kb(it - 20, j)) * 64;
        if (it == 16 || it == 17) {
          tma_load_mc(st - 16384 + rank * 16384, wgu, fb, j * 448, k0);
          tma_load_mc(st - 8192 + rank * 16384, wgu, fb, j * 448 + 64, k0);
        } else {
          tma_load_mc(st + rank * 8192, it < 16 ? &p.wo : wgu, fb, it < 16 ? j * 128 + rank * 64 : j * 448 + 384, k0);
        }
        st += 32768; fb += 8;
        if (++s == 6) { s = 0; st -= 6 * 32768; fb -= 48; ph ^= 1; }
      }
      st = sm + 16384 + 3 * 49152; fb = bars + 8 * B_FG; ph = 1;
#pragma unroll 1
      for (int it = 0; it < 46; it++) {
        const int kb = it < 14 ? other_kb(it, j) : (it + 2) & 15, col = j * 448 + ((it + 2) >> 4) * 128;
        if (it < 4) wait_w_free(bars + 8 * B_EW, it);
        mbar_wait(fb + 8 * (B_EG - B_FG), ph);
        expect_tx_elect(fb, 49152);
        tma_load_mc(st + rank * 16384, wgu, fb, col, kb * 64);
        tma_load_mc(st + rank * 16384 + 8192, wgu, fb, col + 64, kb * 64);
        st += (it & 3) == 0 ? -3 * 49152 : 49152; fb += 8;
        if ((it & 3) == 3) { fb -= 32; ph ^= 1; }
      }
      st = sm + 16384 + 2 * 32768; fb = bars + 8 * B_FD; ph = 1;
#pragma unroll 1
      for (int it = 0, s = 0; it < 56 - KH; it++) {
        if (it < 6) wait_g_free(bars + 8 * B_EG, it);
        mbar_wait(fb + 8 * (B_ED - B_FD), ph);
        expect_tx_elect(fb, 32768);
        tma_load_mc(st + rank * 8192, &p.wd, fb, j * 128 + rank * 64, down_k(it));
        st += s == 3 ? -5 * 32768 : 32768; fb += 8;
        if (++s == 6) { s = 0; fb -= 48; ph ^= 1; }
      }
    } else if (warp == 1) {
      const int arow = rb * 128;
      uint32_t st = sm, fb = bars + 8 * B_FQ, ph = 0;
      cnt_wait(cnt + C_HA, target);
      PROF_AT(lane == 0, 16);
#pragma unroll 1
      for (int it = 4; it < 32; it++) {
        if (it == 11) mbar_wait(bars + 8 * (B_RDY + C_H), 0);
        mbar_wait(fb + 8 * (B_EQ - B_FQ), ph);
        tma_load(st, &p.h, fb, qkv_kb(it, j) * 64, arow);
        st += 49152; fb += 8;
        if ((it & 3) == 3) { st -= 4 * 49152; fb -= 32; ph ^= 1; }
      }
      fb = bars + 8 * B_FW; ph = 1;
#pragma unroll 1
      for (int it = 0, s = 0; it < 34; it++) {
        if (it < 16 || it >= 20) {
          if (it < 6) wait_q_free(bars + 8 * B_EQ, it);
          mbar_wait(fb + 8 * (B_EW - B_FW), ph);
          if (it == 0) mbar_wait(bars + 8 * (B_RDY + C_O), 0);
          if (it == 9 || it == 20) cnt_wait(cnt + (it == 9 ? C_O + 1 : C_H2A), target * 8);
          if (it == 27) mbar_wait(bars + 8 * (B_RDY + C_H2), 0);
          PROF_AT(lane == 0 && (it == 0 || it == 9 || it == 20), 17 + (it >> 3));
          if (it != 8) tma_load(st, it < 16 ? &p.o_ld : &p.h2, fb, it < 16 ? wo_k(it, j) : other_kb(it - 20, j) * 64, arow);
        }
        st += 32768; fb += 8;
        if (++s == 6) { s = 0; st -= 6 * 32768; fb -= 48; ph ^= 1; }
      }
      st = sm + 3 * 49152; fb = bars + 8 * B_FG; ph = 1;
#pragma unroll 1
      for (int it = 0; it < 46; it++) {
        if (it < 4) wait_w_free(bars + 8 * B_EW, it);
        mbar_wait(fb + 8 * (B_EG - B_FG), ph);
        tma_load(st, &p.h2, fb, (it < 14 ? other_kb(it, j) : (it + 2) & 15) * 64, arow);
        st += (it & 3) == 0 ? -3 * 49152 : 49152; fb += 8;
        if ((it & 3) == 3) { fb -= 32; ph ^= 1; }
      }
      st = sm + 2 * 32768; fb = bars + 8 * B_FD; ph = 1;
#pragma unroll 1
      for (int it = 0, s = 0; it < 56 - KH; it++) {
        if (it < 6) wait_g_free(bars + 8 * B_EG, it);
        mbar_wait(fb + 8 * (B_ED - B_FD), ph);
        const int u = it + KH, dep = it == 0 ? C_ACT : (u == 8 ? C_ACT + 1 : (u == 24 ? C_ACT + 2 : (u == 40 ? C_A0 : (u == 48 ? C_ACT + 3 : -1))));
        if (dep >= 0) mbar_wait(bars + 8 * (B_RDY + dep), 0);
        tma_load(st, &p.act, fb, down_k(it), arow);
        st += s == 3 ? -5 * 32768 : 32768; fb += 8;
        if (++s == 6) { s = 0; fb -= 48; ph ^= 1; }
      }
    } else if (warp == 2) {
      if (lane < 14) prefetch_map(&p.h + lane);
      __syncwarp();
      uint32_t ph1 = 0;
#pragma unroll 1
      for (int n = 0; n < 8; n++) {
        const int nch = (n == 1 || n == 2 || n == 4) ? 1 : 2;
#pragma unroll 1
        for (int ch = 0; ch < nch; ch++) {
          mbar_wait_watchdog(bars + 8 * (B_STGF + ch), ch ? ph1 : (n & 1));
          const uint32_t src = stg + ch * 16384;
          if (n == 2 || n == 3) {
          } else if (n == 1) {
#pragma unroll 1
            for (int q = 0; q < 8; q++) {
              tma_store2(&p.o_st, src + q * 2048, j * 128, rb * 128 + q * 16);
              if (q & 1) store_pause(true);
            }
          } else if (n >= 4 && n < 8) {
#pragma unroll 1
            for (int q = 0; q < 4; q++) {
              tma_store2(&p.act_st, src + q * 4096, j * 448 + (n == 4 ? 384 : (n - 5) * 128 + ch * 64), rb * 128 + q * 32);
              store_pause(true);
            }
          } else {
            tma_store2(&p.h, src, j * 128 + ch * 64, rb * 128);
            asm volatile("cp.async.bulk.commit_group;" ::: "memory");
            if (ch == 1) {
              asm volatile("cp.async.bulk.wait_group 1;" ::: "memory");
              __syncwarp();
              cnt_signal(cnt + C_HA);
            }
          }
          if (n >= 5 && ch == 0) arrive_elect(bars + 8 * B_STGE);
          if (n == 7 && ch == 0) {
            asm volatile("cp.async.bulk.wait_group 0;" ::: "memory");
            __syncwarp();
            cnt_signal(cnt + C_A0);
          }
        }
        asm volatile("cp.async.bulk.commit_group;" ::: "memory");
        asm volatile("cp.async.bulk.wait_group 0;" ::: "memory");
        __syncwarp();
        if (n != 2 && n != 3) cnt_signal(cnt + n);
        PROF_AT(lane == 0, n == 0 ? 33 : 23 + n);
        if (n == 0) {
#pragma unroll 1
          for (int t = 0; t < 34; t++) {
            ll_store(t < 32 ? p.halo + cta * 1024 + t * 32 + lane : (uint4*)(p.stats2 + cta * 128) + (t - 32) * 32 + lane, 0u, 0u, 0u);
            __nanosleep(40);
          }
          __syncwarp();
        }
        if (n < 5) arrive_elect(bars + 8 * B_STGE);
        if (nch == 2) { arrive_elect(bars + 8 * (B_STGE + 1)); ph1 ^= 1; }
      }
      mbar_wait_watchdog(bars + 8 * B_STGF, 0);
      PROF_AT(lane == 0, 31);
    } else {
      if (lane < 4) ll_store(p.modll + cta * 4 + lane, 0u, 0u, 0u);
      bar_sync(1, 288);
      {
        const uint4 t4 = lds128(sm + RED_OFF + lane * 16);
        float a[4] = {__uint_as_float(t4.x), __uint_as_float(t4.y), __uint_as_float(t4.z), __uint_as_float(t4.w)};
#pragma unroll
        for (int o = 4; o < 32; o <<= 1)
#pragma unroll
          for (int q = 0; q < 4; q++) a[q] += __shfl_xor_sync(~0u, a[q], o);
        if (lane < 4) ll_store(p.modll + cta * 4 + lane, pack2(a[0], a[1]), pack2(a[2], a[3]), tag);
        PROF_AT(lane == 0, 1);
        uint32_t m[4];
        const uint4* mp = p.modll + j * 32 + lane;
        ll_poll<2>([&](int i) { return mp + i * 256; }, tag, m);
        const uint32_t c0 = pack2(1.0f + bf_lo(m[2]), 1.0f + bf_hi(m[2])), c1 = pack2(1.0f + bf_lo(m[3]), 1.0f + bf_hi(m[3]));
        sts128(sm + MODB_OFF + lane * 16, c0, m[0], c1, m[1]);
        __syncwarp();
        arrive_elect(bars + 8 * B_MODA);
      }
#pragma unroll 1
      for (int n = C_H; n <= C_O; n++) {
        cnt_wait_lazy(cnt + n, target);
        arrive_elect(bars + 8 * (B_RDY + n));
      }
      {
        uint32_t m[6];
        const uint4* src = p.modll + 512 + j * 32 + lane;
        ll_poll<3, 500>([&](int i) { return src + i * 256; }, tag, m);
#pragma unroll
        for (int vec = 0; vec < 3; vec++) {
          const float add = vec == 2 ? 1.0f : 0.0f;
          sts128(sm + MODB_OFF + (vec * 128 + lane * 4) * 4, __float_as_uint(bf_round(bf_lo(m[2 * vec]) + add)), __float_as_uint(bf_round(bf_hi(m[2 * vec]) + add)),
                 __float_as_uint(bf_round(bf_lo(m[2 * vec + 1]) + add)), __float_as_uint(bf_round(bf_hi(m[2 * vec + 1]) + add)));
        }
        __syncwarp();
        if (lane == 0) mbar_arrive(bars + 8 * B_MODB);
        PROF_AT(lane == 0, 15);
      }
      __syncwarp();
#pragma unroll 1
      for (int q = C_H2; q < 9; q++) {
        const int n = q < 7 ? q : (q == 7 ? C_A0 : C_ACT + 3);
        cnt_wait_lazy(cnt + n, n == C_H2 ? target * 8 : target);
        arrive_elect(bars + 8 * (B_RDY + n));
      }
      {
        uint32_t m[2];
        const uint4* src = p.modll + 512 + 768 + j * 32 + lane;
        ll_poll<1>([&](int) { return src; }, tag, m);
        sts128(sm + MODB_OFF + (384 + lane * 4) * 4, m[0] << 16, m[0] & 0xffff0000u, m[1] << 16, m[1] & 0xffff0000u);
        cnt_wait_lazy(cnt + C_SP + (j >> 1), target);
        __syncwarp();
        if (lane == 0) mbar_arrive(bars + 8 * (B_MODB + 1));
      }
    }
  } else {
    uint32_t tag;

    {
      const int tid = threadIdx.x - 128, cw = tid >> 7, warp = (tid >> 5) & 3, lane = tid & 31;
      const int l16 = lane & 15, half = lane >> 4, w8 = cw * 4 + warp;
      const uint32_t cbuf = sm + 3 * 49152 + w8 * 512;
      if (lane <= 16) cp_async16(cbuf + lane * 16, lane < 16 ? (const void*)(p.c + w8 * 128 + lane * 8) : (const void*)p.epoch);
      asm volatile("cp.async.commit_group;" ::: "memory");
      const uint32_t xbuf = sm + 40960 + (cw * 2 + (l16 >> 3)) * 49152 + (warp * 16 + half) * 128;
      {
        const char* xp = (const char*)p.x + (uint32_t)((rb * 128 + (warp * 16 + half) * 2 + cw) * 2048 + j * 256 + l16 * 16);
#pragma unroll
        for (int i = 0; i < 8; i++) cp_async16(xbuf + i * 256 + (((l16 & 7) ^ ((i * 2 + half) & 7)) << 4), xp + i * 8192);
      }
      asm volatile("cp.async.commit_group;" ::: "memory");
      const uint32_t wbuf = sm + cw * 49152 + warp * 4096;
      {
        const char* wp = (const char*)p.wmod + (uint32_t)(cta * 32 + (lane & 1) * 16 + (w8 * 128 + (lane >> 1)) * 12288);
#pragma unroll
        for (int i = 0; i < 8; i++) cp_async16(wbuf + i * 512 + lane * 16, wp + i * 16 * 12288);
      }
      asm volatile("cp.async.commit_group;" ::: "memory");
      PROF_AT(tid == 0, 32);
      uint2* st1 = p.stats1 + (rb * 8 + j) * 128 + cw * 64 + warp * 16;
      if (lane < 8) ll_store((uint4*)st1 + lane, 0u, 0u, 0u);
      __syncwarp();
      cluster_arrive_relaxed();
      asm volatile("setmaxnreg.inc.sync.aligned.u32 232;");
      uint32_t sa[4][4];
      {
        asm volatile("cp.async.wait_group 2;" ::: "memory");
        __syncwarp();
        tag = lds32(cbuf + 256) + 1;
        const float2 cv = lds64f(cbuf + lane * 8);
        const uint32_t c0 = __float_as_uint(cv.x), c1 = __float_as_uint(cv.y);
        sts64f(cbuf + lane * 8, __uint_as_float(pack2(silu_f(bf_lo(c0)), silu_f(bf_hi(c0)))), __uint_as_float(pack2(silu_f(bf_lo(c1)), silu_f(bf_hi(c1)))));
        __syncwarp();
#pragma unroll
        for (int q = 0; q < 4; q++) ldmatrix4(sa[q][0], sa[q][1], sa[q][2], sa[q][3], cbuf + q * 64 + (lane >> 3) * 16);
      }
      cluster_wait();
      asm volatile("cp.async.wait_group 1;" ::: "memory");
      __syncwarp();
      uint32_t xl[16], xh[16];
      {
        const int srow = warp * 16 + (lane & 15);
#pragma unroll
        for (int q = 0; q < 8; q++)
          ldmatrix4(xl[2 * q], xh[2 * q], xl[2 * q + 1], xh[2 * q + 1],
                    sm + 40960 + (cw * 2 + (q >> 2)) * 49152 + srow * 128 + (((half + (q & 3) * 2) ^ (srow & 7)) << 4));
      }
      publish_stats(xl, xh, st1, lane, tag16(tag));
      PROF_AT(tid == 0, 50);
      asm volatile("cp.async.wait_group 0;" ::: "memory");
      __syncwarp();
      PROF_AT(tid == 0, 51);
      {
        uint32_t b[8][4];
#pragma unroll
        for (int ks = 0; ks < 8; ks++) ldmatrix4t(b[ks], wbuf + (ks * 16 + (lane & 15)) * 32 + (lane >> 4) * 16);
        float d0[4] = {0.f, 0.f, 0.f, 0.f}, d1[4] = {0.f, 0.f, 0.f, 0.f}, d2[4] = {0.f, 0.f, 0.f, 0.f}, d3[4] = {0.f, 0.f, 0.f, 0.f};
#pragma unroll
        for (int q = 0; q < 4; q++) {
          mma16816(d0, sa[q][0], sa[q][0], sa[q][1], sa[q][1], b[2 * q][0], b[2 * q][1]);
          mma16816(d1, sa[q][0], sa[q][0], sa[q][1], sa[q][1], b[2 * q][2], b[2 * q][3]);
          mma16816(d2, sa[q][2], sa[q][2], sa[q][3], sa[q][3], b[2 * q + 1][0], b[2 * q + 1][1]);
          mma16816(d3, sa[q][2], sa[q][2], sa[q][3], sa[q][3], b[2 * q + 1][2], b[2 * q + 1][3]);
        }
        d0[0] += d2[0]; d0[1] += d2[1]; d1[0] += d3[0]; d1[1] += d3[1];
        if (lane < 4) {
          sts64f(sm + RED_OFF + (w8 * 16 + lane * 2) * 4, d0[0], d0[1]);
          sts64f(sm + RED_OFF + (w8 * 16 + 8 + lane * 2) * 4, d1[0], d1[1]);
        }
        asm volatile("bar.arrive 1, 288;" ::: "memory");
      }
      {
        const int c = lane & 3;
        float rs[2], nb[2];
        stat_gather(p.stats1 + rb * 1024 + cw * 64 + warp * 16, tag16(tag), lane, rs, nb);
#pragma unroll
        for (int n = 0; n < 16; n++) {
          xl[n] = pack2(bf_lo(xl[n]) * rs[0] + nb[0], bf_hi(xl[n]) * rs[0] + nb[0]);
          xh[n] = pack2(bf_lo(xh[n]) * rs[1] + nb[1], bf_hi(xh[n]) * rs[1] + nb[1]);
        }
        const int srow = warp * 16 + l16;
        const uint32_t slab = stg + cw * 8192 + srow * 128;
#pragma unroll
        for (int q = 0; q < 8; q++)
          stmatrix4(slab + (q >> 2) * 16384 + (((half + (q & 3) * 2) ^ (srow & 7)) << 4), xl[2 * q], xh[2 * q], xl[2 * q + 1], xh[2 * q + 1]);
        PROF_AT(tid == 0, 52);
        mbar_wait(bars + 8 * B_MODA, 0);
        PROF_AT(tid == 0, 2);
#pragma unroll
        for (int q = 0; q < 8; q++) {
          const float2 m0 = lds64f(sm + MODB_OFF + (8 * q + c) * 8), m1 = lds64f(sm + MODB_OFF + (8 * q + 4 + c) * 8);
          const uint32_t c0 = __float_as_uint(m0.x), s0 = __float_as_uint(m0.y), c1 = __float_as_uint(m1.x), s1 = __float_as_uint(m1.y);
          stmatrix4(slab + (q >> 2) * 16384 + (((half + (q & 3) * 2) ^ (srow & 7)) << 4), fma_bf2(xl[2 * q], c0, s0), fma_bf2(xh[2 * q], c0, s0),
                    fma_bf2(xl[2 * q + 1], c1, s1), fma_bf2(xh[2 * q + 1], c1, s1));
          if ((q & 3) == 3) stage_done(bars + 8 * (B_STGF + (q >> 2)), lane);
        }
        wg_bar(cw);
      }
      PROF_AT(tid == 0, 3);
    }

    uint32_t xl[16], xh[16];
    {
      RING_IDS();
      uint32_t prev = 0;
      float acc1[96];
      {
        Ring g{bars + 8 * B_FQ, rbars + 8 * B_EQ, 0, 0u, 0u, releaser TR(0)};
        float acc0[96];
#pragma unroll 1
        for (int kb = 0; kb < 2; kb++) kblock<192, 4, 49152>(acc0, g, a_base + STG_OFF + kb * 16384, kb == 0, prev);
#pragma unroll 1
        for (int kb = 0; kb < 2; kb++) kblock<192, 4, 49152>(acc1, g, a_base + STG_OFF + kb * 16384, kb == 0, prev);
#pragma unroll 1
        for (int kb = 0; kb < 14; kb++) kblock<192, 4, 49152>(acc0, g, a_base + g.off, false, prev);
        PROF_AT(tid == 0, 4);
        attention<NPRE0, false>(acc0, p, 0, rb, cta, cw, warp, tag, stg, bars, prev, [&]() { kblock<192, 4, 49152>(acc1, g, a_base + g.off, false, prev); });
        PROF_AT(tid == 0, 5);
        {
          LANE_IDS();
#pragma unroll
          for (int q = 0; q < 8; q++)
            ldmatrix4(xl[2 * q], xh[2 * q], xl[2 * q + 1], xh[2 * q + 1], sm + 40960 + (cw * 2 + (q >> 2)) * 49152 + srow * 128 + ((sw0 ^ ((q & 3) * 2)) << 4));
#pragma unroll
          for (int q = 0; q < 16; q++) asm volatile("" : "+r"(xl[q]), "+r"(xh[q])::"memory");
        }
#pragma unroll 1
        for (int kb = 5 + NPRE0; kb < 14; kb++) kblock<192, 4, 49152>(acc1, g, a_base + g.off, false, prev);
        PROF_AT(tid == 0, 6);
      }
      float acc[64];
      Ring g{bars + 8 * B_FW, rbars + 8 * B_EW, 0, 0u, 0u, releaser TR(32)};
      attention<NPRE1, true>(acc1, p, 1, rb, cta, cw, warp, tag, stg, bars, prev, [&]() { kblock<128, 6, 32768>(acc, g, a_base + g.off, g.s == 0, prev); });
      PROF_AT(tid == 0, 7);
      LANE_IDS();
      unsigned* cnt = p.cnt + rb * 32;
      tma_store2(&p.o_st, stg + cw * 8192 + warp * 2048, j * 128 + 64, rb * 128 + cw * 64 + warp * 16);
      asm volatile("cp.async.bulk.commit_group;" ::: "memory");
#pragma unroll 1
      for (int kb = 1 + NPRE1; kb < 16; kb++) {
        if (kb == 8) wg_bar(cw);
        kblock<128, 6, 32768>(acc, g, a_base + (kb == 8 ? STG_OFF : g.off), false, prev);
        if (kb == OSIG + NPRE1) {
          asm volatile("cp.async.bulk.wait_group 0;" ::: "memory");
          __syncwarp();
          cnt_signal(cnt + C_O + 1);
        }
      }
      mbar_wait(bars + 8 * B_MODB, 0);
      float2 ga[16];
#pragma unroll
      for (int n = 0; n < 16; n++) ga[n] = lds64f(sm + MODB_OFF + (8 * n + 2 * c) * 4);
      tile_end(acc, prev);
      PROF_AT(tid == 0, 8);
#pragma unroll
      for (int n = 0; n < 16; n++) {
        acc[4 * n] = ga[n].x * acc[4 * n] + bf_lo(xl[n]); acc[4 * n + 1] = ga[n].y * acc[4 * n + 1] + bf_hi(xl[n]);
        acc[4 * n + 2] = ga[n].x * acc[4 * n + 2] + bf_lo(xh[n]); acc[4 * n + 3] = ga[n].y * acc[4 * n + 3] + bf_hi(xh[n]);
        xl[n] = pack2(acc[4 * n], acc[4 * n + 1]);
        xh[n] = pack2(acc[4 * n + 2], acc[4 * n + 3]);
      }
      publish_stats(xl, xh, p.stats2 + (rb * 8 + j) * 128 + cw * 64 + warp * 16, lane, tag16(tag));
      PROF_AT(tid == 0, 48);
      float2 sb[16], cb[16];
#pragma unroll
      for (int n = 0; n < 16; n++) {
        sb[n] = lds64f(sm + MODB_OFF + (128 + 8 * n + 2 * c) * 4);
        cb[n] = lds64f(sm + MODB_OFF + (256 + 8 * n + 2 * c) * 4);
      }
      mbar_wait(bars + 8 * B_STGE, 0);
      PROF_AT(tid == 0, 49);
      float nb[2], rstd[2];
      stat_gather(p.stats2 + rb * 1024 + cw * 64 + warp * 16, tag16(tag), lane, rstd, nb);
      PROF_AT(tid == 0, 9);
#pragma unroll
      for (int ch = 0; ch < 2; ch++) {
        uint32_t lo[8], hi[8];
#pragma unroll
        for (int t = 0; t < 8; t++) {
          const int n = ch * 8 + t;
          lo[t] = pack2((acc[4 * n] * rstd[0] + nb[0]) * cb[n].x + sb[n].x, (acc[4 * n + 1] * rstd[0] + nb[0]) * cb[n].y + sb[n].y);
          hi[t] = pack2((acc[4 * n + 2] * rstd[1] + nb[1]) * cb[n].x + sb[n].x, (acc[4 * n + 3] * rstd[1] + nb[1]) * cb[n].y + sb[n].y);
        }
        stage_slab(sm + ch * 32768 + cw * 8192, warp, lane, lo, hi);
        stage_done(bars + 8 * (B_STGF + ch), lane);
        tma_store2(&p.h2_st, sm + ch * 32768 + cw * 8192 + warp * 2048, j * 128 + ch * 64, rb * 128 + cw * 64 + warp * 16);
        asm volatile("cp.async.bulk.commit_group;" ::: "memory");
      }
      wg_bar(cw);
      PROF_AT(tid == 0, 10);
    }

    uint32_t pg[32], pu[32];
    {
      RING_IDS();
      float acc[128];
      uint32_t prev = 0;
      Ring g{bars + 8 * B_FG, rbars + 8 * B_EG, 0, 0u, 3 * 49152u, releaser TR(66)};
      {
        Ring w{bars + 8 * B_FW, rbars + 8 * B_EW, 4, 0u, 4 * 32768u, releaser TR(48)};
        float acn[64];
#pragma unroll 1
        for (int kb = 0; kb < 2; kb++) {
          kblock<256, 6, 32768>(acc, w, a_base + kb * 32768, kb == 0, prev, 0u);
          if (kb == 0) asm volatile("cp.async.bulk.wait_group 1;" ::: "memory");
          else asm volatile("cp.async.bulk.wait_group 0;" ::: "memory");
          __syncwarp();
          cnt_signal(p.cnt + rb * 32 + (kb == 0 ? C_H2A : C_H2));
        }
        {
          LANE_IDS();
#pragma unroll
          for (int q = 0; q < 8; q++)
            stmatrix4(slab + (q >> 2) * 16384 + ((sw0 ^ ((q & 3) * 2)) << 4), xl[2 * q], xh[2 * q], xl[2 * q + 1], xh[2 * q + 1]);
          __syncwarp();
        }
#pragma unroll 1
        for (int kb = 0; kb < 16; kb++) {
          kblock<128, 6, 32768>(acn, w, a_base + w.off, kb == 0, prev);
          if (kb == 4) {
            asm volatile("fence.proxy.async.shared::cta;" ::: "memory");
            __syncwarp();
          }
          if (kb == X1S + warp || kb == X1S + 4 + warp) {
            const int ch = kb != X1S + warp;
            tma_store3(&p.out, stg + ch * 16384 + cw * 8192 + warp * 2048, j * 128 + ch * 64, rb * 64 + warp * 16, cw);
            asm volatile("cp.async.bulk.commit_group;" ::: "memory");
          }
        }
        PROF_AT(tid == 0, 39);
        kblock<256, 4, 49152>(acc, g, a_base + g.off, false, prev);
        fence_regs(acn);
#pragma unroll
        for (int q = 0; q < 16; q++) {
          pg[q] = pack2(acn[2 * q], acn[2 * q + 1]);
          pu[q] = pack2(acn[32 + 2 * q], acn[32 + 2 * q + 1]);
          pg[16 + q] = 0; pu[16 + q] = 0;
        }
        asm volatile("cp.async.bulk.wait_group 0;" ::: "memory");
        kblock<256, 4, 49152>(acc, g, a_base + g.off, false, prev);
      }
      LANE_IDS();
#pragma unroll 1
      for (int t = 0; t < 3; t++) {
#pragma unroll 1
        for (int blk = 0; blk < (t == 0 ? 2 : 4); blk++) {
          g.s = 2;
#pragma unroll
          for (int i = 0; i < 4; i++) {
            g.off = ((i + 1) & 3) * 49152;
            kblock<256, 4, 49152>(acc, g, a_base + g.off, t > 0 && blk == 0 && i == 0, prev);
            if ((blk & 1) == 0 && i == 0) mbar_wait(bars + 8 * (B_STGE + (blk >> 1)), (t + 1 + (blk >> 1)) & 1);
            stmatrix2(slab + (blk >> 1) * 16384 + (((srow & 7) ^ ((blk & 1) * 4 + i)) << 4), swiglu2(pg[2 * i], pu[2 * i]), swiglu2(pg[2 * i + 1], pu[2 * i + 1]));
          }
#pragma unroll
          for (int q = 0; q < 24; q++) { pg[q] = pg[q + 8]; pu[q] = pu[q + 8]; }
          if (blk & 1) stage_done(bars + 8 * (B_STGF + (blk >> 1)), lane);
        }
#pragma unroll 1
        for (int kb = t == 0 ? 0 : 4; kb < 4; kb++) kblock<256, 4, 49152>(acc, g, a_base + g.off, false, prev);
        tile_end(acc, prev);
        PROF_AT(tid == 0, 36 + t);
#pragma unroll
        for (int q = 0; q < 32; q++) {
          pg[q] = pack2(acc[2 * q], acc[2 * q + 1]);
          pu[q] = pack2(acc[64 + 2 * q], acc[64 + 2 * q + 1]);
        }
      }
      PROF_AT(tid == 0, 11);
    }

    {
      RING_IDS();
      LANE_IDS();
      Ring g{bars + 8 * B_FD, rbars + 8 * B_ED, 0, 0u, 2 * 32768u, releaser TR(112)};
      float acc[64];
      uint32_t prev = 0;
#pragma unroll 1
      for (int blk = 0; blk < 4; blk++) {
#pragma unroll
        for (int i = 0; i < 8; i++) {
          kblock<128, 6, 32768>(acc, g, a_base + g.off, blk == 0 && i == 0, prev);
          if ((blk & 1) == 0 && i == 0) mbar_wait(bars + 8 * (B_STGE + (blk >> 1)), blk >> 1);
          stmatrix1(slab + (blk >> 1) * 16384 + (i & 1) * 1024 + (((srow & 7) ^ ((blk & 1) * 4 + (i >> 1))) << 4), swiglu2(pg[i], pu[i]));
        }
#pragma unroll
        for (int q = 0; q < 24; q++) { pg[q] = pg[q + 8]; pu[q] = pu[q + 8]; }
        if (blk & 1) stage_done(bars + 8 * (B_STGF + (blk >> 1)), lane);
      }
#pragma unroll 1
      for (int kb = 32; kb < 56 - KH; kb++) {
        if (kb == 50 - KH) g.releaser = false;
        if (TL && cw == 1 && kb == 56 - KH - TL) bar_sync(5, 256);
        kblock<128, 6, 32768>(acc, g, a_base + g.off, false, prev);
      }
      if (TL && cw == 0) asm volatile("bar.arrive 5, 256;" ::: "memory");
      mbar_wait(bars + 8 * (B_MODB + 1), 0);
      mbar_wait(bars + 8 * B_STGE, 1);
      mbar_wait(bars + 8 * (B_STGE + 1), 0);
      float2 gbv[16];
#pragma unroll
      for (int n = 0; n < 16; n++) gbv[n] = lds64f(sm + MODB_OFF + (384 + 8 * n + 2 * c) * 4);
      tile_end(acc, prev);
      PROF_AT(tid == 0, 13);
#pragma unroll
      for (int ch = 0; ch < 2; ch++) {
        uint32_t lo[8], hi[8];
#pragma unroll
        for (int t = 0; t < 8; t++) {
          const int n = ch * 8 + t;
          const float2 gb = gbv[n];
          lo[t] = pack2(gb.x * acc[4 * n], gb.y * acc[4 * n + 1]);
          hi[t] = pack2(gb.x * acc[4 * n + 2], gb.y * acc[4 * n + 3]);
        }
        stage_slab(stg + ch * 16384 + cw * 8192, warp, lane, lo, hi);
        asm volatile("fence.proxy.async.shared::cta;" ::: "memory");
        __syncwarp();
        tma_add3(&p.out, stg + ch * 16384 + cw * 8192 + warp * 2048, j * 128 + ch * 64, rb * 64 + warp * 16, cw);
      }
      asm volatile("cp.async.bulk.commit_group;" ::: "memory");
      if (lane == 0) mbar_arrive(bars + 8 * B_STGF);
      asm volatile("cp.async.bulk.wait_group.read 0;" ::: "memory");
      PROF_AT(tid == 0, 14);
    }
    if (blockIdx.x == 0 && threadIdx.x == 128) asm volatile("st.relaxed.gpu.global.u32 [%0], %1;" ::"l"(p.epoch), "r"(tag) : "memory");
  }
}

typedef CUresult (*EncodeFn)(CUtensorMap*, CUtensorMapDataType, cuuint32_t, void*, const cuuint64_t*, const cuuint64_t*,
                             const cuuint32_t*, const cuuint32_t*, CUtensorMapInterleave, CUtensorMapSwizzle,
                             CUtensorMapL2promotion, CUtensorMapFloatOOBfill);

void encode2d(EncodeFn fn, CUtensorMap* m, const void* ptr, uint64_t cols, uint64_t rows, uint32_t box_rows) {
  cuuint64_t dims[2] = {cols, rows};
  cuuint64_t strides[1] = {cols * 2};
  cuuint32_t box[2] = {64, box_rows};
  cuuint32_t es[2] = {1, 1};
  fn(m, CU_TENSOR_MAP_DATA_TYPE_BFLOAT16, 2, (void*)ptr, dims, strides, box, es, CU_TENSOR_MAP_INTERLEAVE_NONE,
     CU_TENSOR_MAP_SWIZZLE_128B, CU_TENSOR_MAP_L2_PROMOTION_L2_128B, CU_TENSOR_MAP_FLOAT_OOB_FILL_NONE);
}

}

extern "C" void kernel_launch(void* const* d_in, const int* in_sizes, int n_in, void* d_out, int out_size) {
  (void)in_sizes; (void)n_in; (void)out_size;
  void* fp = nullptr;
  cudaDriverEntryPointQueryResult qr;
  cudaGetDriverEntryPoint("cuTensorMapEncodeTiled", &fp, cudaEnableDefault, &qr);
  EncodeFn fn = (EncodeFn)fp;
  void *ph, *po, *ph2, *pact;
  cudaGetSymbolAddress(&ph, g_h);
  cudaGetSymbolAddress(&po, g_o);
  ph2 = ph;
  cudaGetSymbolAddress(&pact, g_act);
  Params p;
  encode2d(fn, &p.h, ph, DM, SEQ, 128);
  encode2d(fn, &p.o_ld, po, DM, SEQ, 128);
  encode2d(fn, &p.h2, ph2, DM, SEQ, 128);
  encode2d(fn, &p.act, pact, FF, SEQ, 128);
  encode2d(fn, &p.act_st, pact, FF, SEQ, 32);
  encode2d(fn, &p.wm, d_in[8], 6 * DM, DM, 64);
  encode2d(fn, &p.o_st, po, DM, SEQ, 16);
  encode2d(fn, &p.h2_st, ph2, DM, SEQ, 16);
  encode2d(fn, &p.wqkv, d_in[1], 3 * DM, DM, 64);
  encode2d(fn, &p.wqkv32, d_in[1], 3 * DM, DM, 32);
  encode2d(fn, &p.wo, d_in[2], DM, DM, 64);
  encode2d(fn, &p.wg, d_in[4], FF, DM, 64);
  encode2d(fn, &p.wu, d_in[5], FF, DM, 64);
  encode2d(fn, &p.wd, d_in[6], DM, FF, 64);
  {
    cuuint64_t dims[3] = {DM, SEQ / 2, 2};
    cuuint64_t strides[2] = {DM * 4, DM * 2};
    cuuint32_t box[3] = {64, 16, 1};
    cuuint32_t es[3] = {1, 1, 1};
    fn(&p.out, CU_TENSOR_MAP_DATA_TYPE_BFLOAT16, 3, d_out, dims, strides, box, es, CU_TENSOR_MAP_INTERLEAVE_NONE,
       CU_TENSOR_MAP_SWIZZLE_128B, CU_TENSOR_MAP_L2_PROMOTION_L2_128B, CU_TENSOR_MAP_FLOAT_OOB_FILL_NONE);
  }
  p.x = (const bf16*)d_in[0];
  p.c = (const bf16*)d_in[7];
  p.wmod = (const bf16*)d_in[8];
  for (int cl = 0; cl < 64; cl++) {
    const int grp = cl < 4 ? 0 : (cl < 36 ? (cl - 4) & 7 : 1 + (cl - 36) % 7);
    const int j = cl < 4 ? 4 + cl : (cl < 36 ? (cl - 4) >> 3 : 4 + (cl - 36) / 7);
    p.slot[cl] = (uint8_t)(grp * 8 + j);
  }
  void* q;
  cudaGetSymbolAddress(&q, g_modll); p.modll = (uint4*)q;
  cudaGetSymbolAddress(&q, g_halo); p.halo = (uint4*)q;
  cudaGetSymbolAddress(&q, g_stats); p.stats1 = (uint2*)q; p.stats2 = p.stats1 + SEQ * 8;
  cudaGetSymbolAddress(&q, g_cnt); p.cnt = (unsigned*)q;
  cudaGetSymbolAddress(&q, g_epoch); p.epoch = (unsigned*)q;

  cudaFuncSetAttribute(fused_kernel, cudaFuncAttributeMaxDynamicSharedMemorySize, SMEM_BYTES);
  cudaLaunchConfig_t cfg = {};
  cfg.gridDim = dim3(NCTA + 4);
  cfg.blockDim = dim3(384);
  cfg.dynamicSmemBytes = SMEM_BYTES;
  cfg.stream = cudaStreamPerThread;
  cudaLaunchAttribute at[1];
  at[0].id = cudaLaunchAttributeClusterDimension;
  at[0].val.clusterDim.x = 2; at[0].val.clusterDim.y = 1; at[0].val.clusterDim.z = 1;
  cfg.attrs = at;
  cfg.numAttrs = 1;
  cudaLaunchKernelEx(&cfg, fused_kernel, p);
}
```

```cpp
#include <cuda_runtime.h>
#include <cuda_bf16.h>
#include <cuda.h>
#include <stdint.h>

typedef __nv_bfloat16 bf16;

#define PAUSE 200
#define WMDELAY 500
#define BDELAY 1500
#define NPRE0 3
#define NPRE1 1
#define ALIAS 1
#define PFW 8000
#define KH 3

__device__ __forceinline__ void wgmma_ss_n128(float (&d)[64], uint32_t da, uint32_t db, int scale_d) {
  asm volatile("{\n.reg .pred p;\n.reg .b64 da, db;\nsetp.ne.b32 p, %66, 0;\n"
    "mov.b64 da, {%64, 0x40000040};\nmov.b64 db, {%65, 0x40000040};\n"
    "wgmma.mma_async.sync.aligned.m64n128k16.f32.bf16.bf16 "
    "{%0, %1, %2, %3, %4, %5, %6, %7, %8, %9, %10, %11, %12, %13, %14, %15, "
    "%16, %17, %18, %19, %20, %21, %22, %23, %24, %25, %26, %27, %28, %29, %30, %31, "
    "%32, %33, %34, %35, %36, %37, %38, %39, %40, %41, %42, %43, %44, %45, %46, %47, "
    "%48, %49, %50, %51, %52, %53, %54, %55, %56, %57, %58, %59, %60, %61, %62, %63}, "
    "da, db, p, 1, 1, 0, 1;\n}\n"
    : "+f"(d[0]), "+f"(d[1]), "+f"(d[2]), "+f"(d[3]), "+f"(d[4]), "+f"(d[5]), "+f"(d[6]), "+f"(d[7]),
      "+f"(d[8]), "+f"(d[9]), "+f"(d[10]), "+f"(d[11]), "+f"(d[12]), "+f"(d[13]), "+f"(d[14]), "+f"(d[15]),
      "+f"(d[16]), "+f"(d[17]), "+f"(d[18]), "+f"(d[19]), "+f"(d[20]), "+f"(d[21]), "+f"(d[22]), "+f"(d[23]),
      "+f"(d[24]), "+f"(d[25]), "+f"(d[26]), "+f"(d[27]), "+f"(d[28]), "+f"(d[29]), "+f"(d[30]), "+f"(d[31]),
      "+f"(d[32]), "+f"(d[33]), "+f"(d[34]), "+f"(d[35]), "+f"(d[36]), "+f"(d[37]), "+f"(d[38]), "+f"(d[39]),
      "+f"(d[40]), "+f"(d[41]), "+f"(d[42]), "+f"(d[43]), "+f"(d[44]), "+f"(d[45]), "+f"(d[46]), "+f"(d[47]),
      "+f"(d[48]), "+f"(d[49]), "+f"(d[50]), "+f"(d[51]), "+f"(d[52]), "+f"(d[53]), "+f"(d[54]), "+f"(d[55]),
      "+f"(d[56]), "+f"(d[57]), "+f"(d[58]), "+f"(d[59]), "+f"(d[60]), "+f"(d[61]), "+f"(d[62]), "+f"(d[63])
    : "r"(da), "r"(db), "r"(scale_d));
}

__device__ __forceinline__ void wgmma_ss_n192(float (&d)[96], uint32_t da, uint32_t db, int scale_d) {
  asm volatile("{\n.reg .pred p;\n.reg .b64 da, db;\nsetp.ne.b32 p, %98, 0;\n"
    "mov.b64 da, {%96, 0x40000040};\nmov.b64 db, {%97, 0x40000040};\n"
    "wgmma.mma_async.sync.aligned.m64n192k16.f32.bf16.bf16 "
    "{%0, %1, %2, %3, %4, %5, %6, %7, %8, %9, %10, %11, %12, %13, %14, %15, "
    "%16, %17, %18, %19, %20, %21, %22, %23, %24, %25, %26, %27, %28, %29, %30, %31, "
    "%32, %33, %34, %35, %36, %37, %38, %39, %40, %41, %42, %43, %44, %45, %46, %47, "
    "%48, %49, %50, %51, %52, %53, %54, %55, %56, %57, %58, %59, %60, %61, %62, %63, "
    "%64, %65, %66, %67, %68, %69, %70, %71, %72, %73, %74, %75, %76, %77, %78, %79, "
    "%80, %81, %82, %83, %84, %85, %86, %87, %88, %89, %90, %91, %92, %93, %94, %95}, "
    "da, db, p, 1, 1, 0, 1;\n}\n"
    : "+f"(d[0]), "+f"(d[1]), "+f"(d[2]), "+f"(d[3]), "+f"(d[4]), "+f"(d[5]), "+f"(d[6]), "+f"(d[7]),
      "+f"(d[8]), "+f"(d[9]), "+f"(d[10]), "+f"(d[11]), "+f"(d[12]), "+f"(d[13]), "+f"(d[14]), "+f"(d[15]),
      "+f"(d[16]), "+f"(d[17]), "+f"(d[18]), "+f"(d[19]), "+f"(d[20]), "+f"(d[21]), "+f"(d[22]), "+f"(d[23]),
      "+f"(d[24]), "+f"(d[25]), "+f"(d[26]), "+f"(d[27]), "+f"(d[28]), "+f"(d[29]), "+f"(d[30]), "+f"(d[31]),
      "+f"(d[32]), "+f"(d[33]), "+f"(d[34]), "+f"(d[35]), "+f"(d[36]), "+f"(d[37]), "+f"(d[38]), "+f"(d[39]),
      "+f"(d[40]), "+f"(d[41]), "+f"(d[42]), "+f"(d[43]), "+f"(d[44]), "+f"(d[45]), "+f"(d[46]), "+f"(d[47]),
      "+f"(d[48]), "+f"(d[49]), "+f"(d[50]), "+f"(d[51]), "+f"(d[52]), "+f"(d[53]), "+f"(d[54]), "+f"(d[55]),
      "+f"(d[56]), "+f"(d[57]), "+f"(d[58]), "+f"(d[59]), "+f"(d[60]), "+f"(d[61]), "+f"(d[62]), "+f"(d[63]),
      "+f"(d[64]), "+f"(d[65]), "+f"(d[66]), "+f"(d[67]), "+f"(d[68]), "+f"(d[69]), "+f"(d[70]), "+f"(d[71]),
      "+f"(d[72]), "+f"(d[73]), "+f"(d[74]), "+f"(d[75]), "+f"(d[76]), "+f"(d[77]), "+f"(d[78]), "+f"(d[79]),
      "+f"(d[80]), "+f"(d[81]), "+f"(d[82]), "+f"(d[83]), "+f"(d[84]), "+f"(d[85]), "+f"(d[86]), "+f"(d[87]),
      "+f"(d[88]), "+f"(d[89]), "+f"(d[90]), "+f"(d[91]), "+f"(d[92]), "+f"(d[93]), "+f"(d[94]), "+f"(d[95])
    : "r"(da), "r"(db), "r"(scale_d));
}

__device__ __forceinline__ void wgmma_ss_n256(float (&d)[128], uint32_t da, uint32_t db, int scale_d) {
  asm volatile("{\n.reg .pred p;\n.reg .b64 da, db;\nsetp.ne.b32 p, %130, 0;\n"
    "mov.b64 da, {%128, 0x40000040};\nmov.b64 db, {%129, 0x40000040};\n"
    "wgmma.mma_async.sync.aligned.m64n256k16.f32.bf16.bf16 "
    "{%0, %1, %2, %3, %4, %5, %6, %7, %8, %9, %10, %11, %12, %13, %14, %15, "
    "%16, %17, %18, %19, %20, %21, %22, %23, %24, %25, %26, %27, %28, %29, %30, %31, "
    "%32, %33, %34, %35, %36, %37, %38, %39, %40, %41, %42, %43, %44, %45, %46, %47, "
    "%48, %49, %50, %51, %52, %53, %54, %55, %56, %57, %58, %59, %60, %61, %62, %63, "
    "%64, %65, %66, %67, %68, %69, %70, %71, %72, %73, %74, %75, %76, %77, %78, %79, "
    "%80, %81, %82, %83, %84, %85, %86, %87, %88, %89, %90, %91, %92, %93, %94, %95, "
    "%96, %97, %98, %99, %100, %101, %102, %103, %104, %105, %106, %107, %108, %109, %110, %111, "
    "%112, %113, %114, %115, %116, %117, %118, %119, %120, %121, %122, %123, %124, %125, %126, %127}, "
    "da, db, p, 1, 1, 0, 1;\n}\n"
    : "+f"(d[0]), "+f"(d[1]), "+f"(d[2]), "+f"(d[3]), "+f"(d[4]), "+f"(d[5]), "+f"(d[6]), "+f"(d[7]),
      "+f"(d[8]), "+f"(d[9]), "+f"(d[10]), "+f"(d[11]), "+f"(d[12]), "+f"(d[13]), "+f"(d[14]), "+f"(d[15]),
      "+f"(d[16]), "+f"(d[17]), "+f"(d[18]), "+f"(d[19]), "+f"(d[20]), "+f"(d[21]), "+f"(d[22]), "+f"(d[23]),
      "+f"(d[24]), "+f"(d[25]), "+f"(d[26]), "+f"(d[27]), "+f"(d[28]), "+f"(d[29]), "+f"(d[30]), "+f"(d[31]),
      "+f"(d[32]), "+f"(d[33]), "+f"(d[34]), "+f"(d[35]), "+f"(d[36]), "+f"(d[37]), "+f"(d[38]), "+f"(d[39]),
      "+f"(d[40]), "+f"(d[41]), "+f"(d[42]), "+f"(d[43]), "+f"(d[44]), "+f"(d[45]), "+f"(d[46]), "+f"(d[47]),
      "+f"(d[48]), "+f"(d[49]), "+f"(d[50]), "+f"(d[51]), "+f"(d[52]), "+f"(d[53]), "+f"(d[54]), "+f"(d[55]),
      "+f"(d[56]), "+f"(d[57]), "+f"(d[58]), "+f"(d[59]), "+f"(d[60]), "+f"(d[61]), "+f"(d[62]), "+f"(d[63]),
      "+f"(d[64]), "+f"(d[65]), "+f"(d[66]), "+f"(d[67]), "+f"(d[68]), "+f"(d[69]), "+f"(d[70]), "+f"(d[71]),
      "+f"(d[72]), "+f"(d[73]), "+f"(d[74]), "+f"(d[75]), "+f"(d[76]), "+f"(d[77]), "+f"(d[78]), "+f"(d[79]),
      "+f"(d[80]), "+f"(d[81]), "+f"(d[82]), "+f"(d[83]), "+f"(d[84]), "+f"(d[85]), "+f"(d[86]), "+f"(d[87]),
      "+f"(d[88]), "+f"(d[89]), "+f"(d[90]), "+f"(d[91]), "+f"(d[92]), "+f"(d[93]), "+f"(d[94]), "+f"(d[95]),
      "+f"(d[96]), "+f"(d[97]), "+f"(d[98]), "+f"(d[99]), "+f"(d[100]), "+f"(d[101]), "+f"(d[102]), "+f"(d[103]),
      "+f"(d[104]), "+f"(d[105]), "+f"(d[106]), "+f"(d[107]), "+f"(d[108]), "+f"(d[109]), "+f"(d[110]), "+f"(d[111]),
      "+f"(d[112]), "+f"(d[113]), "+f"(d[114]), "+f"(d[115]), "+f"(d[116]), "+f"(d[117]), "+f"(d[118]), "+f"(d[119]),
      "+f"(d[120]), "+f"(d[121]), "+f"(d[122]), "+f"(d[123]), "+f"(d[124]), "+f"(d[125]), "+f"(d[126]), "+f"(d[127])
    : "r"(da), "r"(db), "r"(scale_d));
}

namespace {

constexpr int SEQ = 2048, DM = 1024, FF = 3584;
constexpr int NCTA = 128;

constexpr uint32_t STG_OFF = 196608;
constexpr uint32_t MISC_OFF = STG_OFF + 32768;
constexpr uint32_t SMEM_BYTES = MISC_OFF + 3072;
constexpr uint32_t RED_OFF = 2 * 49152;
constexpr uint32_t MODB_OFF = MISC_OFF + 512;

enum { B_FQ = 0, B_EQ = 4, B_FW = 8, B_EW = 14, B_FG = 20, B_EG = 24, B_FD = 28, B_ED = 34,
       B_STGF = 40, B_MODB = 42, B_MODA = 45, B_RDY = 46, B_STGE = 58, B_COUNT = 60 };
enum { C_H = 0, C_O = 1, C_H2 = 3, C_ACT = 4, C_HA = 8, C_H2A = 9, C_A0 = 10, C_SP = 12 };

struct Params {
  const bf16* x;
  const bf16* c;
  const bf16* wmod;
  unsigned* epoch;
  uint2* stats1;
  uint8_t slot[64];
  uint4* modll;
  uint4* halo;
  uint2* stats2;
  unsigned* cnt;
  CUtensorMap h, o_ld, o_st, h2, act, out, wqkv, wqkv32, wo, wg, wu, wd, act_st, h2_st, wm;
};

__device__ __align__(1024) bf16 g_h[SEQ * DM];
__device__ __align__(1024) bf16 g_o[SEQ * DM];
__device__ __align__(1024) bf16 g_act[SEQ * FF];
__device__ __align__(1024) uint4 g_modll[3072 / 2];
__device__ __align__(1024) uint4 g_halo[16 * 8 * 2 * 2 * 8 * 32];
__device__ __align__(1024) uint2 g_stats[2 * SEQ * 8];
__device__ __align__(1024) unsigned g_cnt[16 * 32];
__device__ uint4 g_epoch;
#define TR(off)

__device__ __forceinline__ uint32_t smem_u32(const void* p) { return (uint32_t)__cvta_generic_to_shared(p); }
__device__ __forceinline__ void mbar_init(uint32_t bar, uint32_t count) {
  asm volatile("mbarrier.init.shared::cta.b64 [%0], %1;" ::"r"(bar), "r"(count));
}
__device__ __forceinline__ void mbar_arrive(uint32_t bar) {
  asm volatile("mbarrier.arrive.shared::cta.b64 _, [%0];" ::"r"(bar) : "memory");
}
__device__ __forceinline__ void mbar_arrive_cluster(uint32_t cluster_addr) {
  asm volatile("mbarrier.arrive.shared::cluster.b64 _, [%0];" ::"r"(cluster_addr) : "memory");
}
__device__ __forceinline__ uint32_t mapa(uint32_t addr, uint32_t cta) {
  uint32_t r;
  asm volatile("mapa.shared::cluster.u32 %0, %1, %2;" : "=r"(r) : "r"(addr), "r"(cta));
  return r;
}
__device__ __forceinline__ void jitter() {}
__device__ __forceinline__ void mbar_wait(uint32_t bar, uint32_t parity) {
  jitter();
  asm volatile(
      "{\n.reg .pred p;\n"
      "WAIT_%=:\n"
      "mbarrier.try_wait.parity.shared::cta.b64 p, [%0], %1;\n"
      "@!p bra WAIT_%=;\n}\n" ::"r"(bar), "r"(parity) : "memory");
}
__device__ __forceinline__ void mbar_wait_watchdog(uint32_t bar, uint32_t parity) {
  jitter();
  asm volatile(
      "{\n.reg .pred p;\n.reg .u64 t0, t1;\nmov.u64 t0, %%globaltimer;\n"
      "WAIT_%=:\n"
      "mbarrier.try_wait.parity.shared::cta.b64 p, [%0], %1;\n"
      "@p bra DONE_%=;\n"
      "mov.u64 t1, %%globaltimer;\n"
      "sub.u64 t1, t1, t0;\n"
      "setp.lt.u64 p, t1, 2000000000;\n"
      "@p bra WAIT_%=;\n"
      "trap;\n"
      "DONE_%=:\n}\n" ::"r"(bar), "r"(parity) : "memory");
}
__device__ __forceinline__ void cnt_wait(const unsigned* p, unsigned target) {
  asm volatile(
      "{\n.reg .pred p;\n.reg .u32 v;\n.reg .s32 d;\n"
      "WAIT_%=:\n"
      "ld.relaxed.gpu.global.u32 v, [%0];\n"
      "sub.s32 d, v, %1;\n"
      "setp.lt.s32 p, d, 0;\n"
      "@p bra WAIT_%=;\n"
      "fence.proxy.async.global;\n"
      "}\n" ::"l"(p), "r"(target) : "memory");
}
__device__ __forceinline__ void cnt_wait_lazy(const unsigned* p, unsigned target) {
  asm volatile(
      "{\n.reg .pred p;\n.reg .u32 v;\n.reg .s32 d;\n"
      "WAIT_%=:\n"
      "nanosleep.u32 400;\n"
      "ld.relaxed.gpu.global.u32 v, [%0];\n"
      "sub.s32 d, v, %1;\n"
      "setp.lt.s32 p, d, 0;\n"
      "@p bra WAIT_%=;\n"
      "fence.proxy.async.global;\n"
      "}\n" ::"l"(p), "r"(target) : "memory");
}
__device__ __forceinline__ void cnt_signal(unsigned* p) {
  jitter();
  asm volatile("{\n.reg .pred p;\nelect.sync _|p, 0xffffffff;\n@p red.relaxed.gpu.global.add.u32 [%0], 1;\n}\n" ::"l"(p) : "memory");
}
__device__ __forceinline__ void ll_store(uint4* p, uint32_t a, uint32_t b, uint32_t tag) {
  asm volatile("st.relaxed.gpu.global.v2.b64 [%0], {%1, %2};" ::"l"(p), "l"((uint64_t)a | ((uint64_t)tag << 32)),
               "l"((uint64_t)b | ((uint64_t)tag << 32)) : "memory");
}
__device__ __forceinline__ uint4 ll_peek(const uint4* p) {
  uint4 v;
  asm volatile("ld.relaxed.gpu.global.v4.u32 {%0, %1, %2, %3}, [%4];" : "=r"(v.x), "=r"(v.y), "=r"(v.z), "=r"(v.w) : "l"(p) : "memory");
  return v;
}
template <int N, int SLEEP = 0, class F>
__device__ __forceinline__ void ll_poll(F addr, uint32_t tag, uint32_t (&out)[2 * N]) {
  for (;;) {
    uint4 v[N];
#pragma unroll
    for (int i = 0; i < N; i++) v[i] = ll_peek(addr(i));
    uint32_t bad = 0;
#pragma unroll
    for (int i = 0; i < N; i++) {
      bad |= (v[i].y ^ tag) | (v[i].w ^ tag);
      out[2 * i] = v[i].x;
      out[2 * i + 1] = v[i].z;
    }
    if (__all_sync(~0u, bad == 0)) break;
    if (SLEEP) __nanosleep(SLEEP);
  }
}
constexpr uint64_t POLICY_EVICT_FIRST = 0x12F0000000000000ull;
__device__ __forceinline__ void expect_tx_elect(uint32_t bar, uint32_t bytes) {
  asm volatile("{\n.reg .pred p;\nelect.sync _|p, 0xffffffff;\n@p mbarrier.arrive.expect_tx.shared::cta.b64 _, [%0], %1;\n}\n" ::"r"(bar), "r"(bytes) : "memory");
}
__device__ __forceinline__ void arrive_elect(uint32_t bar) {
  asm volatile("{\n.reg .pred p;\nelect.sync _|p, 0xffffffff;\n@p mbarrier.arrive.shared::cta.b64 _, [%0];\n}\n" ::"r"(bar) : "memory");
}
__device__ __forceinline__ void tma_load(uint32_t dst, const CUtensorMap* m, uint32_t bar, int c0, int c1) {
  asm volatile("{\n.reg .pred p;\nelect.sync _|p, 0xffffffff;\n"
               "@p cp.async.bulk.tensor.2d.shared::cluster.global.mbarrier::complete_tx::bytes [%0], [%1, {%3, %4}], [%2];\n}\n"
               ::"r"(dst), "l"(m), "r"(bar), "r"(c0), "r"(c1) : "memory");
}
__device__ __forceinline__ void tma_load_mc(uint32_t dst, const CUtensorMap* m, uint32_t bar, int c0, int c1) {
  asm volatile("{\n.reg .pred p;\nelect.sync _|p, 0xffffffff;\n"
               "@p cp.async.bulk.tensor.2d.shared::cluster.global.mbarrier::complete_tx::bytes.multicast::cluster.L2::cache_hint [%0], [%1, {%3, %4}], [%2], %5, %6;\n}\n"
               ::"r"(dst), "l"(m), "r"(bar), "r"(c0), "r"(c1), "h"((uint16_t)3), "l"(POLICY_EVICT_FIRST) : "memory");
}
__device__ __forceinline__ void tma_load_ef(uint32_t dst, const CUtensorMap* m, uint32_t bar, int c0, int c1) {
  asm volatile("{\n.reg .pred p;\nelect.sync _|p, 0xffffffff;\n"
               "@p cp.async.bulk.tensor.2d.shared::cluster.global.mbarrier::complete_tx::bytes.L2::cache_hint [%0], [%1, {%3, %4}], [%2], %5;\n}\n"
               ::"r"(dst), "l"(m), "r"(bar), "r"(c0), "r"(c1), "l"(POLICY_EVICT_FIRST) : "memory");
}
__device__ __forceinline__ void tma_store2(const CUtensorMap* m, uint32_t src, int c0, int c1) {
  asm volatile("{\n.reg .pred p;\nelect.sync _|p, 0xffffffff;\n"
               "@p cp.async.bulk.tensor.2d.global.shared::cta.bulk_group [%0, {%2, %3}], [%1];\n}\n"
               ::"l"(m), "r"(src), "r"(c0), "r"(c1) : "memory");
}
__device__ __forceinline__ void tma_store3(const CUtensorMap* m, uint32_t src, int c0, int c1, int c2) {
  asm volatile("{\n.reg .pred p;\nelect.sync _|p, 0xffffffff;\n"
               "@p cp.async.bulk.tensor.3d.global.shared::cta.bulk_group [%0, {%2, %3, %4}], [%1];\n}\n"
               ::"l"(m), "r"(src), "r"(c0), "r"(c1), "r"(c2) : "memory");
}
__device__ __forceinline__ void tma_add3(const CUtensorMap* m, uint32_t src, int c0, int c1, int c2) {
  asm volatile("{\n.reg .pred p;\nelect.sync _|p, 0xffffffff;\n"
               "@p cp.reduce.async.bulk.tensor.3d.global.shared::cta.add.bulk_group [%0, {%2, %3, %4}], [%1];\n}\n"
               ::"l"(m), "r"(src), "r"(c0), "r"(c1), "r"(c2) : "memory");
}
__device__ __forceinline__ void store_pause(bool sleep) {
  asm volatile("cp.async.bulk.commit_group;" ::: "memory");
  asm volatile("cp.async.bulk.wait_group.read 0;" ::: "memory");
  if (sleep) __nanosleep(PAUSE);
}
__device__ __forceinline__ void l2_prefetch_tile(const CUtensorMap* m, int c0, int c1) {
  asm volatile("{\n.reg .pred p;\nelect.sync _|p, 0xffffffff;\n@p cp.async.bulk.prefetch.tensor.2d.L2.global [%0, {%1, %2}];\n}\n"
               ::"l"(m), "r"(c0), "r"(c1) : "memory");
}
__device__ __forceinline__ void prefetch_map(const CUtensorMap* m) {
  asm volatile("prefetch.tensormap [%0];" ::"l"(m) : "memory");
}
__device__ __forceinline__ void wg_fence() { asm volatile("wgmma.fence.sync.aligned;" ::: "memory"); }
__device__ __forceinline__ void wg_commit() { asm volatile("wgmma.commit_group.sync.aligned;" ::: "memory"); }
template <int N>
__device__ __forceinline__ void wg_wait() { asm volatile("wgmma.wait_group.sync.aligned %0;" ::"n"(N) : "memory"); }
__device__ __forceinline__ void bar_sync(int id, int n) { asm volatile("bar.sync %0, %1;" ::"r"(id), "r"(n) : "memory"); }
__device__ __forceinline__ void wg_bar(int cw) {
  asm volatile("{\n.reg .pred p;\nsetp.ne.s32 p, %0, 0;\n@p bar.sync 3, 128;\n@!p bar.sync 2, 128;\n}\n" ::"r"(cw) : "memory");
}
__device__ __forceinline__ void skew_pre(int cw) { if (cw == 1) bar_sync(5, 256); }
__device__ __forceinline__ void skew_post(int cw) { if (cw == 0) asm volatile("bar.arrive 5, 256;" ::: "memory"); }
__device__ __forceinline__ void cluster_arrive_relaxed() { asm volatile("barrier.cluster.arrive.relaxed.aligned;" ::: "memory"); }
__device__ __forceinline__ void cluster_wait() { asm volatile("barrier.cluster.wait.acquire.aligned;" ::: "memory"); }
__device__ __forceinline__ uint32_t load_epoch(const unsigned* p) {
  uint32_t e;
  asm volatile("ld.relaxed.gpu.global.u32 %0, [%1];" : "=r"(e) : "l"(p) : "memory");
  return e;
}
__device__ __forceinline__ uint32_t pack2(float lo, float hi) {
  uint32_t r;
  asm("cvt.rn.bf16x2.f32 %0, %1, %2;" : "=r"(r) : "f"(hi), "f"(lo));
  return r;
}
__device__ __forceinline__ float bf_lo(uint32_t v) { return __uint_as_float(v << 16); }
__device__ __forceinline__ float bf_hi(uint32_t v) { return __uint_as_float(v & 0xffff0000u); }
__device__ __forceinline__ uint32_t fma_bf2(uint32_t a, uint32_t b, uint32_t c) {
  uint32_t d;
  asm("fma.rn.bf16x2 %0, %1, %2, %3;" : "=r"(d) : "r"(a), "r"(b), "r"(c));
  return d;
}
__device__ __forceinline__ float bf_round(float v) { return __bfloat162float(__float2bfloat16_rn(v)); }
__device__ __forceinline__ float silu_f(float v) { return __fdividef(v, 1.0f + __expf(-v)); }
__device__ __forceinline__ uint4 ldg_nc(const void* p) {
  uint4 v;
  asm volatile("ld.global.nc.L1::no_allocate.v4.u32 {%0, %1, %2, %3}, [%4];" : "=r"(v.x), "=r"(v.y), "=r"(v.z), "=r"(v.w) : "l"(p));
  return v;
}
__device__ __forceinline__ void stmatrix4(uint32_t addr, uint32_t a, uint32_t b, uint32_t c, uint32_t d) {
  asm volatile("stmatrix.sync.aligned.m8n8.x4.shared.b16 [%0], {%1, %2, %3, %4};" ::"r"(addr), "r"(a), "r"(b), "r"(c), "r"(d) : "memory");
}
__device__ __forceinline__ void stmatrix2(uint32_t addr, uint32_t a, uint32_t b) {
  asm volatile("stmatrix.sync.aligned.m8n8.x2.shared.b16 [%0], {%1, %2};" ::"r"(addr), "r"(a), "r"(b) : "memory");
}
__device__ __forceinline__ void stmatrix1(uint32_t addr, uint32_t a) {
  asm volatile("stmatrix.sync.aligned.m8n8.x1.shared.b16 [%0], {%1};" ::"r"(addr), "r"(a) : "memory");
}
__device__ __forceinline__ uint32_t movmatrix(uint32_t a) {
  uint32_t d;
  asm("movmatrix.sync.aligned.m8n8.trans.b16 %0, %1;" : "=r"(d) : "r"(a));
  return d;
}
__device__ __forceinline__ void mma16816(float (&d)[4], uint32_t a0, uint32_t a1, uint32_t a2, uint32_t a3, uint32_t b0, uint32_t b1) {
  asm("mma.sync.aligned.m16n8k16.row.col.f32.bf16.bf16.f32 {%0, %1, %2, %3}, {%4, %5, %6, %7}, {%8, %9}, {%0, %1, %2, %3};"
               : "+f"(d[0]), "+f"(d[1]), "+f"(d[2]), "+f"(d[3]) : "r"(a0), "r"(a1), "r"(a2), "r"(a3), "r"(b0), "r"(b1));
}
__device__ __forceinline__ void mma1688(float (&d)[4], uint32_t a0, uint32_t a1, uint32_t b0) {
  asm("mma.sync.aligned.m16n8k8.row.col.f32.bf16.bf16.f32 {%0, %1, %2, %3}, {%4, %5}, {%6}, {%0, %1, %2, %3};"
               : "+f"(d[0]), "+f"(d[1]), "+f"(d[2]), "+f"(d[3]) : "r"(a0), "r"(a1), "r"(b0));
}
__device__ __forceinline__ void ldmatrix4t(uint32_t (&b)[4], uint32_t addr) {
  asm volatile("ldmatrix.sync.aligned.m8n8.x4.trans.shared.b16 {%0, %1, %2, %3}, [%4];" : "=r"(b[0]), "=r"(b[1]), "=r"(b[2]), "=r"(b[3]) : "r"(addr) : "memory");
}
__device__ __forceinline__ void ldmatrix4(uint32_t& a, uint32_t& b, uint32_t& c, uint32_t& d, uint32_t addr) {
  asm volatile("ldmatrix.sync.aligned.m8n8.x4.shared.b16 {%0, %1, %2, %3}, [%4];" : "=r"(a), "=r"(b), "=r"(c), "=r"(d) : "r"(addr) : "memory");
}
__device__ __forceinline__ void cp_async16(uint32_t dst, const void* src) {
  asm volatile("cp.async.cg.shared.global.L2::cache_hint [%0], [%1], 16, %2;" ::"r"(dst), "l"(src), "l"(POLICY_EVICT_FIRST) : "memory");
}
__device__ __forceinline__ uint32_t lds32(uint32_t addr) {
  uint32_t v;
  asm volatile("ld.shared.u32 %0, [%1];" : "=r"(v) : "r"(addr) : "memory");
  return v;
}
__device__ __forceinline__ void sts64f(uint32_t addr, float a, float b) {
  asm volatile("st.shared.v2.f32 [%0], {%1, %2};" ::"r"(addr), "f"(a), "f"(b) : "memory");
}
constexpr float QK_SCALE = 0.17677669529663687f;
__device__ __forceinline__ float softmax8(float& p0, float& p1) {
  float m = fmaxf(p0, p1);
  m = fmaxf(m, __shfl_xor_sync(~0u, m, 1));
  m = fmaxf(m, __shfl_xor_sync(~0u, m, 2));
  asm("ex2.approx.ftz.f32 %0, %1;" : "=f"(p0) : "f"((p0 - m) * 1.4426950408889634f));
  asm("ex2.approx.ftz.f32 %0, %1;" : "=f"(p1) : "f"((p1 - m) * 1.4426950408889634f));
  float s = p0 + p1;
  s += __shfl_xor_sync(~0u, s, 1);
  s += __shfl_xor_sync(~0u, s, 2);
  float r;
  asm("rcp.approx.ftz.f32 %0, %1;" : "=f"(r) : "f"(s));
  return r;
}
__device__ __forceinline__ void sts128(uint32_t addr, uint32_t a, uint32_t b, uint32_t c, uint32_t d) {
  asm volatile("st.shared.v4.u32 [%0], {%1, %2, %3, %4};" ::"r"(addr), "r"(a), "r"(b), "r"(c), "r"(d) : "memory");
}
__device__ __forceinline__ uint4 lds128(uint32_t addr) {
  uint4 v;
  asm volatile("ld.shared.v4.u32 {%0, %1, %2, %3}, [%4];" : "=r"(v.x), "=r"(v.y), "=r"(v.z), "=r"(v.w) : "r"(addr) : "memory");
  return v;
}
__device__ __forceinline__ float2 lds64f(uint32_t addr) {
  float2 v;
  asm volatile("ld.shared.v2.f32 {%0, %1}, [%2];" : "=f"(v.x), "=f"(v.y) : "r"(addr) : "memory");
  return v;
}
#define PROF_AT(cond, slot) do {} while (0)

constexpr uint32_t SMEM_BASE = 1024;
constexpr uint32_t DESC_A = (1u << 16) | (SMEM_BASE >> 4);
constexpr uint32_t DESC_B = ((8192u >> 4) << 16) | (SMEM_BASE >> 4);

template <int BN> struct Wg;
template <> struct Wg<128> { static __device__ __forceinline__ void mma(float (&d)[64], uint32_t a, uint32_t b, int s) { wgmma_ss_n128(d, a, b, s); } };
template <> struct Wg<192> { static __device__ __forceinline__ void mma(float (&d)[96], uint32_t a, uint32_t b, int s) { wgmma_ss_n192(d, a, b, s); } };
template <> struct Wg<256> { static __device__ __forceinline__ void mma(float (&d)[128], uint32_t a, uint32_t b, int s) { wgmma_ss_n256(d, a, b, s); } };

struct Ring {
  uint32_t full0, rel0;
  int s;
  uint32_t ph;
  uint32_t off;
  bool releaser;
};

template <int N>
__device__ __forceinline__ void fence_regs(float (&a)[N]) {
#pragma unroll
  for (int i = 0; i < N; i++) asm volatile("" : "+f"(a[i])::"memory");
}

template <int BN, int NST, uint32_t STAGE>
__device__ __forceinline__ void kblock(float (&acc)[BN / 2], Ring& g, uint32_t a_addr, bool zero, uint32_t& prev, uint32_t b_rel = 16384) {
  mbar_wait(g.full0 + 8 * g.s, g.ph);
  const uint32_t da = DESC_A + (a_addr >> 4);
  const uint32_t db = DESC_B + ((g.off + b_rel) >> 4);
  wg_fence();
#pragma unroll
  for (int k = 0; k < 4; k++) Wg<BN>::mma(acc, da + k * 2, db + k * 128, !(zero && k == 0));
  wg_commit();
  wg_wait<1>();
  jitter();
  if (prev != 0) mbar_arrive_cluster(prev);
  prev = g.releaser ? g.rel0 + 8 * g.s : 0u;
  if (++g.s == NST) { g.s = 0; g.ph ^= 1; }
  g.off += STAGE;
  if (g.off == NST * STAGE) g.off = 0;
}
template <int N>
__device__ __forceinline__ void tile_end(float (&acc)[N], uint32_t& prev) {
  wg_wait<0>();
  if (prev != 0) mbar_arrive_cluster(prev);
  prev = 0;
  fence_regs(acc);
}

__device__ __forceinline__ int other_kb(int q, int j) {
  const int ch = q >= 7, jj = q - 7 * ch;
  return 2 * (jj < j ? jj : jj + 1) + ch;
}
__device__ __forceinline__ int qkv_kb(int it, int j) {
  return it < 4 ? 2 * j + (it & 1) : other_kb(it < 18 ? it - 4 : it - 18, j);
}
__device__ __forceinline__ int wo_k(int it, int j) {
  return it < 8 ? it * 128 : (it == 8 ? j : (it - 9 < j ? it - 9 : it - 8)) * 128 + 64;
}
__device__ __forceinline__ int down_k(int d) {
  const int u = d + KH;
  if (u < 8) return u * 448 + 384;
  if (u < 40) return (((u - 8) & 15) >> 1) * 448 + ((u - 8) >> 4) * 128 + (u & 1) * 64;
  return (u & 7) * 448 + 256 + (u >= 48 ? 64 : 0);
}
__device__ __forceinline__ void wait_q_free(uint32_t empty, int i) {
  mbar_wait(empty + 8 * ((i * 2) / 3), 1);
  mbar_wait(empty + 8 * ((i * 2 + 1) / 3), 1);
}
__device__ __forceinline__ void wait_w_free(uint32_t empty, int i) {
  const int t = (i + 3) & 3, w0 = (t * 3) / 2, w1 = (t * 3 + 2) / 2;
  mbar_wait(empty + 8 * w0, w0 < 4);
  mbar_wait(empty + 8 * w1, w1 < 4);
}
__device__ __forceinline__ void wait_g_free(uint32_t empty, int i) {
  const int s = i < 4 ? i + 2 : i - 4, b0 = ((s * 2) / 3 + 1) & 3, b1 = ((s * 2 + 1) / 3 + 1) & 3;
  mbar_wait(empty + 8 * b0, b0 < 2);
  mbar_wait(empty + 8 * b1, b1 < 2);
}

__device__ __forceinline__ void chan(float& m, float& q, float m2, float q2, float n) {
  const float d = m2 - m;
  m = 0.5f * (m + m2);
  q = q + q2 + d * d * (0.5f * n);
}

__device__ __forceinline__ uint32_t tag16(uint32_t tag) { return tag % 65535u + 1u; }
__device__ __forceinline__ void stat_store(uint2* slot, float m, float q, uint32_t t16) {
  const uint32_t a = ((__float_as_uint(m) + 0x80u) & 0xffffff00u) | (t16 & 0xffu), b = ((__float_as_uint(q) + 0x80u) & 0xffffff00u) | (t16 >> 8);
  asm volatile("st.relaxed.gpu.global.b64 [%0], %1;" ::"l"(slot), "l"((uint64_t)a | ((uint64_t)b << 32)) : "memory");
}
__device__ __forceinline__ void stat_gather(const uint2* rows, uint32_t t16, int lane, float (&rs)[2], float (&nb)[2]) {
  const uint4* sp = (const uint4*)(rows + (lane >> 3) * 128) + (lane & 7);
  const uint32_t want = (t16 & 0xffu) | ((t16 >> 8) << 8);
  uint4 a, b;
  for (;;) {
    a = ll_peek(sp);
    b = ll_peek(sp + 256);
    const uint32_t bad = (__byte_perm(a.x, a.y, 0x40) ^ want) | (__byte_perm(a.z, a.w, 0x40) ^ want) | (__byte_perm(b.x, b.y, 0x40) ^ want) |
                         (__byte_perm(b.z, b.w, 0x40) ^ want);
    if (__all_sync(~0u, (bad & 0xffffu) == 0)) break;
  }
  float m0 = __uint_as_float(a.x & 0xffffff00u), q0 = __uint_as_float(a.y & 0xffffff00u);
  float m1 = __uint_as_float(a.z & 0xffffff00u), q1 = __uint_as_float(a.w & 0xffffff00u);
  chan(m0, q0, __uint_as_float(b.x & 0xffffff00u), __uint_as_float(b.y & 0xffffff00u), 128.f);
  chan(m1, q1, __uint_as_float(b.z & 0xffffff00u), __uint_as_float(b.w & 0xffffff00u), 128.f);
  const bool hi = lane & 8;
  float m = hi ? m1 : m0, q = hi ? q1 : q0;
  chan(m, q, __shfl_xor_sync(~0u, hi ? m0 : m1, 8), __shfl_xor_sync(~0u, hi ? q0 : q1, 8), 256.f);
  chan(m, q, __shfl_xor_sync(~0u, m, 16), __shfl_xor_sync(~0u, q, 16), 512.f);
  const float rstd = rsqrtf(q * (1.0f / DM) + 1e-5f), nmr = -m * rstd;
  const int r = lane >> 2, src = (r >> 1) + (r & 1) * 8;
  rs[0] = __shfl_sync(~0u, rstd, src); nb[0] = __shfl_sync(~0u, nmr, src);
  rs[1] = __shfl_sync(~0u, rstd, src + 4); nb[1] = __shfl_sync(~0u, nmr, src + 4);
}

__device__ __forceinline__ void publish_stats(const uint32_t (&xl)[16], const uint32_t (&xh)[16], uint2* slot, int lane, uint32_t t16) {
  float ds[4] = {0.f, 0.f, 0.f, 0.f}, dl[4] = {0.f, 0.f, 0.f, 0.f}, dh[4] = {0.f, 0.f, 0.f, 0.f};
#pragma unroll
  for (int q = 0; q < 8; q++) {
    mma16816(ds, xl[2 * q], xh[2 * q], xl[2 * q + 1], xh[2 * q + 1], 0x3f803f80u, 0x3f803f80u);
    mma16816(dl, xl[2 * q], xh[2 * q], xl[2 * q + 1], xh[2 * q + 1], xl[2 * q], xl[2 * q + 1]);
    mma16816(dh, xl[2 * q], xh[2 * q], xl[2 * q + 1], xh[2 * q + 1], xh[2 * q], xh[2 * q + 1]);
  }
  const int r = lane >> 2;
  if ((lane & 3) == (r >> 1)) {
    const float ml = ds[0] * (1.0f / 128), mh = ds[2] * (1.0f / 128);
    const float ql = fmaxf(((r & 1) ? dl[1] : dl[0]) - ds[0] * ml, 0.f), qh = fmaxf(((r & 1) ? dh[3] : dh[2]) - ds[2] * mh, 0.f);
    stat_store(slot + r, ml, ql, t16);
    stat_store(slot + r + 8, mh, qh, t16);
  }
  __syncwarp();
}

__device__ __forceinline__ void stage_slab(uint32_t chunk, int warp, int lane, const uint32_t (&lo)[8], const uint32_t (&hi)[8]) {
  const int row = warp * 16 + (lane & 7) + ((lane >> 3) & 1) * 8;
  const uint32_t rbase = chunk + row * 128;
#pragma unroll
  for (int q = 0; q < 4; q++) {
    const int grp = 2 * q + (lane >> 4);
    stmatrix4(rbase + ((grp ^ (row & 7)) << 4), lo[2 * q], hi[2 * q], lo[2 * q + 1], hi[2 * q + 1]);
  }
}
__device__ __forceinline__ float silu_mul(float g, float u) {
  float e, r;
  asm("ex2.approx.ftz.f32 %0, %1;" : "=f"(e) : "f"(g * -1.4426950408889634f));
  asm("rcp.approx.ftz.f32 %0, %1;" : "=f"(r) : "f"(1.0f + e));
  return g * r * u;
}
__device__ __forceinline__ uint32_t swiglu2(uint32_t g2, uint32_t u2) {
  asm volatile("" : "+r"(g2));
  return pack2(silu_mul(bf_lo(g2), bf_lo(u2)), silu_mul(bf_hi(g2), bf_hi(u2)));
}
__device__ __forceinline__ void stage_done(uint32_t bar, int lane) {
  asm volatile("fence.proxy.async.shared::cta;" ::: "memory");
  __syncwarp();
  if (lane == 0) mbar_arrive(bar);
}

__device__ __forceinline__ int fresh_tid() {
  int t;
  asm volatile("mov.u32 %0, %%tid.x;" : "=r"(t));
  return t;
}
#define RING_IDS()                                                                                           \
  const int tid = fresh_tid() - 128;                                                                         \
  const int cw = __shfl_sync(~0u, tid >> 7, 0), warp = __shfl_sync(~0u, (tid >> 5) & 3, 0);                  \
  const bool releaser = (tid & 31) < 2;                                                                      \
  const uint32_t rbars = mapa(bars, tid & 1);                                                                \
  const uint32_t a_base = cw * 8192
#define LANE_IDS()                                                                                           \
  const int lane = fresh_tid() & 31, r = lane >> 2, c = lane & 3;                                            \
  const int srow = warp * 16 + (lane & 7) + ((lane >> 3) & 1) * 8;                                           \
  const uint32_t slab = stg + cw * 8192 + srow * 128, sw0 = (lane >> 4) ^ (srow & 7);                        \
  (void)r; (void)c; (void)slab; (void)sw0

template <int NPRE, bool EAGER, class Step>
__device__ __forceinline__ void attention(float (&acc)[96], const Params& p, int rho, int rb, int cta, int cw, int warp, uint32_t tag,
                                          uint32_t stg, uint32_t bars, uint32_t& prev, Step step) {
  uint32_t ql[8], qh[8], k0[8], k1[8], v0[8], v1[8], hp[16];
  if (EAGER) {
    tile_end(acc, prev);
  } else {
    step();
    fence_regs(acc);
  }
#pragma unroll
  for (int t = 0; t < 8; t++) {
    k0[t] = pack2(acc[4 * (8 + t)], acc[4 * (8 + t) + 1]);
    k1[t] = pack2(acc[4 * (8 + t) + 2], acc[4 * (8 + t) + 3]);
    v0[t] = pack2(acc[4 * (16 + t)], acc[4 * (16 + t) + 1]);
    v1[t] = pack2(acc[4 * (16 + t) + 2], acc[4 * (16 + t) + 3]);
    asm volatile("" : "+r"(k0[t]), "+r"(k1[t]), "+r"(v0[t]), "+r"(v1[t]));
  }
  const int lane = fresh_tid() & 31, r = lane >> 2, c = lane & 3;
#pragma unroll
  for (int t = 0; t < 8; t++) v1[t] = movmatrix(v1[t]);
  mbar_wait(bars + 8 * B_STGE, rho);
  mbar_wait(bars + 8 * (B_STGE + 1), 0);
  const uint32_t xch = stg + 16384 + (cw * 4 + warp) * 2048 + lane * 16;
  if (warp < 3) {
    sts128(xch, k1[0], k1[1], k1[2], k1[3]);
    sts128(xch + 512, k1[4], k1[5], k1[6], k1[7]);
    sts128(xch + 1024, v1[0], v1[1], v1[2], v1[3]);
    sts128(xch + 1536, v1[4], v1[5], v1[6], v1[7]);
  } else if (rb < 15) {
    uint4* dst = p.halo + ((cta * 2 + rho) * 2 + cw) * 256 + lane;
#pragma unroll
    for (int t = 0; t < 4; t++) {
      ll_store(dst + t * 32, k1[2 * t], k1[2 * t + 1], tag);
      ll_store(dst + (4 + t) * 32, v1[2 * t], v1[2 * t + 1], tag);
    }
  }
#pragma unroll
  for (int t = 0; t < 8; t++) {
    v0[t] = movmatrix(v0[t]);
    ql[t] = pack2(acc[4 * t], acc[4 * t + 1]);
    qh[t] = pack2(acc[4 * t + 2], acc[4 * t + 3]);
    asm volatile("" : "+r"(v0[t]), "+r"(ql[t]), "+r"(qh[t]));
  }
#pragma unroll 1
  for (int i = 0; i < NPRE; i++) step();
  const uint4* src = p.halo + (((cta - 8) * 2 + rho) * 2 + cw) * 256 + lane;
  uint4 early[8] = {};
  if (warp == 0 && rb > 0) {
#pragma unroll
    for (int i = 0; i < 8; i++) early[i] = ll_peek(src + i * 32);
  }
  step();
  wg_bar(cw);
  if (warp > 0) {
#pragma unroll
    for (int t = 0; t < 4; t++) {
      const uint4 a = lds128(xch - 2048 + t * 512);
      hp[4 * t] = a.x; hp[4 * t + 1] = a.y; hp[4 * t + 2] = a.z; hp[4 * t + 3] = a.w;
    }
  } else if (rb > 0) {
    uint32_t bad = 0;
#pragma unroll
    for (int i = 0; i < 8; i++) {
      bad |= (early[i].y ^ tag) | (early[i].w ^ tag);
      hp[2 * i] = early[i].x;
      hp[2 * i + 1] = early[i].z;
    }
    if (!__all_sync(~0u, bad == 0)) ll_poll<8>([&](int i) { return src + i * 32; }, tag, hp);
  } else {
#pragma unroll
    for (int t = 0; t < 16; t++) hp[t] = 0;
  }
  wg_wait<0>();
  if (prev != 0) mbar_arrive_cluster(prev);
  prev = 0;
#pragma unroll
  for (int t = 0; t < 8; t++) asm volatile("" : "+r"(ql[t])::"memory");
  const bool up0 = 2 * c > r, up1 = 2 * c + 1 > r;
  const bool first = (rb == 0) && (warp == 0);
  uint32_t a0[2], a2[2], a3[2], a5[2];
  float il[2], ih[2];
#pragma unroll
  for (int h = 0; h < 2; h++) {
    float sp[4] = {0.f, 0.f, 0.f, 0.f}, s0[4] = {0.f, 0.f, 0.f, 0.f}, s1[4] = {0.f, 0.f, 0.f, 0.f};
#pragma unroll
    for (int ks = 0; ks < 2; ks++) {
      const int t = 4 * h + 2 * ks;
      mma16816(sp, ql[t], qh[t], ql[t + 1], qh[t + 1], hp[t], hp[t + 1]);
      mma16816(s0, ql[t], qh[t], ql[t + 1], qh[t + 1], k0[t], k0[t + 1]);
      mma16816(s1, ql[t], qh[t], ql[t + 1], qh[t + 1], k1[t], k1[t + 1]);
    }
    float p0 = (up0 ? sp[0] : s0[0]) * QK_SCALE, p1 = (up1 ? sp[1] : s0[1]) * QK_SCALE;
    float p2 = (up0 ? s0[2] : s1[2]) * QK_SCALE, p3 = (up1 ? s0[3] : s1[3]) * QK_SCALE;
    if (first && up0) p0 = -1000000000.0f;
    if (first && up1) p1 = -1000000000.0f;
    il[h] = softmax8(p0, p1);
    ih[h] = softmax8(p2, p3);
    a0[h] = pack2(up0 ? p0 : 0.f, up1 ? p1 : 0.f);
    a2[h] = pack2(up0 ? 0.f : p0, up1 ? 0.f : p1);
    a3[h] = pack2(up0 ? p2 : 0.f, up1 ? p3 : 0.f);
    a5[h] = pack2(up0 ? 0.f : p2, up1 ? 0.f : p3);
  }
  float o[8][4];
#pragma unroll
  for (int t = 0; t < 8; t++) {
#pragma unroll
    for (int q = 0; q < 4; q++) o[t][q] = 0.f;
    mma1688(o[t], 0u, a5[t >> 2], v1[t]);
    mma16816(o[t], a0[t >> 2], 0u, a2[t >> 2], a3[t >> 2], hp[8 + t], v0[t]);
  }
#pragma unroll
  for (int t = 0; t < 8; t++) fence_regs(o[t]);
  if (!EAGER) step();
  uint32_t ol[8], oh[8];
#pragma unroll
  for (int t = 0; t < 8; t++) {
    ol[t] = pack2(o[t][0] * il[t >> 2], o[t][1] * il[t >> 2]);
    oh[t] = pack2(o[t][2] * ih[t >> 2], o[t][3] * ih[t >> 2]);
  }
  if (!EAGER) step();
  stage_slab(stg + cw * 8192, warp, lane, ol, oh);
  stage_done(bars + 8 * B_STGF, lane);
  if (!EAGER) step();
}

__global__ void __launch_bounds__(384, 1) fused_kernel(const __grid_constant__ Params p) {
  extern __shared__ __align__(1024) uint8_t smem_raw[];
  const uint32_t sm = smem_u32(smem_raw);
  const uint32_t bars = sm + MISC_OFF;
  const uint32_t stg = sm + STG_OFF;
  const int rank = blockIdx.x & 1;
  const int cl = blockIdx.x >> 1;
  if (cl >= NCTA / 2) {
    const int e = blockIdx.x - NCTA, wid = __shfl_sync(~0u, (int)(threadIdx.x >> 5), 0), lane = threadIdx.x & 31;
    if (threadIdx.x == 0) {
      for (int i = 0; i < 6; i++) { mbar_init(bars + 8 * i, 1); mbar_init(bars + 8 * (6 + i), 8); }
      for (int i = 0; i < 8; i++) { mbar_init(bars + 8 * (16 + i), 1); mbar_init(bars + 8 * (24 + i), 4); }
      mbar_init(bars + 8 * 12, 1);
      asm volatile("fence.mbarrier_init.release.cluster;" ::: "memory");
    }
    const uint32_t tag = load_epoch(p.epoch) + 1;
    if (threadIdx.x < 256) ll_store(p.modll + 512 + (threadIdx.x >> 6) * 256 + e * 64 + (threadIdx.x & 63), 0u, 0u, 0u);
    for (int i = threadIdx.x; i < 1536; i += 384) {
      uint4 o = make_uint4(0u, 0u, 0u, 0u);
      if (i < 1024 && (i & 63) < 8) {
        const uint4 cv = ldg_nc(p.c + (i >> 6) * 64 + (i & 7) * 8);
        o = make_uint4(pack2(silu_f(bf_lo(cv.x)), silu_f(bf_hi(cv.x))), pack2(silu_f(bf_lo(cv.y)), silu_f(bf_hi(cv.y))),
                       pack2(silu_f(bf_lo(cv.z)), silu_f(bf_hi(cv.z))), pack2(silu_f(bf_lo(cv.w)), silu_f(bf_hi(cv.w))));
      }
      sts128(stg + i * 16, o.x, o.y, o.z, o.w);
    }
    asm volatile("fence.proxy.async.shared::cta;" ::: "memory");
    __syncthreads();
    if (wid == 0) {
      __nanosleep(WMDELAY);
      uint32_t ph = 1;
#pragma unroll 1
      for (int it = 0, s = 0; it < 64; it++) {
        mbar_wait(bars + 8 * (6 + s), ph);
        expect_tx_elect(bars + 8 * s, 32768);
#pragma unroll
        for (int q = 0; q < 4; q++) tma_load_ef(sm + s * 32768 + q * 8192, &p.wm, bars + 8 * s, 2048 + (it >> 4) * 1024 + e * 256 + q * 64, (it & 15) * 64);
        if (++s == 6) { s = 0; ph ^= 1; }
      }
    } else if (wid == 1) {
      __nanosleep(PFW);
#pragma unroll 1
      for (int i = 0; i < 64; i++) {
        l2_prefetch_tile(&p.wo, (i & 15) * 64, (e * 4 + (i >> 4)) * 64);
      }
#pragma unroll 1
      for (int i = 0; i < 80; i++) {
        if (i < 64) l2_prefetch_tile((i & 1) ? &p.wu : &p.wg, ((i >> 1) & 7) * 448 + 384, ((i >> 4) * 4 + e) * 64);
        else l2_prefetch_tile((i & 2) ? &p.wu : &p.wg, (e * 2 + ((i >> 3) & 1)) * 448 + (i & 1) * 64, (e * 4 + ((i >> 2) & 3)) * 64);
      }
    } else if (wid >= 4) {
      const int hf = (wid >> 2) - 1;
      uint32_t ph = 0;
      int s = 0;
#pragma unroll 1
      for (int v = 0; v < 4; v++) {
        float acc[64];
#pragma unroll 1
        for (int kb = 0; kb < 16; kb++) {
          mbar_wait_watchdog(bars + 8 * s, ph);
          const uint32_t da = DESC_A + ((STG_OFF + kb * 1024) >> 4), db = DESC_B + ((s * 32768 + hf * 16384) >> 4);
          wg_fence();
#pragma unroll
          for (int k = 0; k < 4; k++) wgmma_ss_n128(acc, da + k * 2, db + k * 128, (kb | k) != 0);
          wg_commit();
          wg_wait<0>();
          if (lane == 0) mbar_arrive(bars + 8 * (6 + s));
          if (++s == 6) { s = 0; ph ^= 1; }
        }
        fence_regs(acc);
        if ((wid & 3) == 0) {
#pragma unroll
          for (int n = 0; n < 16; n++) {
            const uint32_t mine = pack2(acc[4 * n], acc[4 * n + 1]), next = __shfl_down_sync(~0u, mine, 1);
            if (lane < 4 && (lane & 1) == 0) ll_store(p.modll + 512 + v * 256 + e * 64 + hf * 32 + n * 2 + (lane >> 1), mine, next, tag);
            if (lane < 4) sts64f(sm + MODB_OFF + (hf * 128 + n * 8 + lane * 2) * 4, bf_lo(mine), bf_hi(mine));
          }
        }
      }
    }
    __syncthreads();
    if (wid == 0 || wid == 2) {
      const int w = wid >> 1;
      if (w == 0) {
        expect_tx_elect(bars + 8 * 12, KH * 32768);
#pragma unroll 1
        for (int q = 0; q < 4 * KH; q++) tma_load_ef(sm + q * 8192, &p.wd, bars + 8 * 12, e * 256 + (q & 3) * 64, (q >> 2) * 448 + 384);
      }
      cnt_wait_lazy(p.cnt + C_ACT, tag * 8);
      if (w == 1) __nanosleep(900);
      uint32_t ph = 1, ready = 0;
#pragma unroll 1
      for (int it = 0, s = 0; it < 16 * KH; it++) {
        const int rb = it / KH, kc = it - rb * KH;
        while (!((ready >> rb) & 1)) {
          ready = __ballot_sync(~0u, (int)(load_epoch(p.cnt + (lane & 15) * 32 + C_ACT) - tag * 8) >= 0);
          asm volatile("fence.proxy.async.global;" ::: "memory");
        }
        const uint32_t fb = bars + 8 * (16 + w * 4 + s), dst = sm + 98304 + w * 32768 + s * 8192;
        mbar_wait(fb + 64, ph);
        expect_tx_elect(fb, 8192);
        tma_load(dst, &p.act_st, fb, kc * 448 + 384, rb * 128 + w * 64);
        tma_load(dst + 4096, &p.act_st, fb, kc * 448 + 384, rb * 128 + w * 64 + 32);
        if (++s == 4) { s = 0; ph ^= 1; }
      }
    } else if (wid >= 4) {
      const int w = (wid >> 2) - 1, warp = wid & 3;
      const uint32_t out_stg = (w ? stg : sm + 163840) + warp * 2048;
      const uint32_t slab = out_stg + (lane & 15) * 128, sw0 = (lane >> 4) ^ (lane & 7);
      mbar_wait_watchdog(bars + 8 * 12, 0);
#pragma unroll 1
      for (int i = threadIdx.x - 128; i < KH * 2048; i += 256) {
        const uint32_t gp = sm + MODB_OFF + (((i >> 9) & 3) * 64 + ((i ^ (i >> 3)) & 7) * 8) * 4;
        const uint4 v = lds128(sm + i * 16), ga = lds128(gp), gc = lds128(gp + 16);
        sts128(sm + i * 16, pack2(bf_lo(v.x) * __uint_as_float(ga.x), bf_hi(v.x) * __uint_as_float(ga.y)),
               pack2(bf_lo(v.y) * __uint_as_float(ga.z), bf_hi(v.y) * __uint_as_float(ga.w)),
               pack2(bf_lo(v.z) * __uint_as_float(gc.x), bf_hi(v.z) * __uint_as_float(gc.y)),
               pack2(bf_lo(v.w) * __uint_as_float(gc.z), bf_hi(v.w) * __uint_as_float(gc.w)));
      }
      asm volatile("fence.proxy.async.shared::cta;" ::: "memory");
      bar_sync(1, 256);
      uint32_t ph = 0;
      int s = 0;
#pragma unroll 1
      for (int rb = 0; rb < 16; rb++) {
        float acc[128];
#pragma unroll 1
        for (int kc = 0; kc < KH; kc++) {
          mbar_wait_watchdog(bars + 8 * (16 + w * 4 + s), ph);
          const uint32_t da = DESC_A + ((98304 + w * 32768 + s * 8192) >> 4), db = DESC_B + ((kc * 32768) >> 4);
          wg_fence();
#pragma unroll
          for (int k = 0; k < 4; k++) wgmma_ss_n256(acc, da + k * 2, db + k * 128, (kc | k) != 0);
          wg_commit();
          wg_wait<1>();
          if (kc > 0 && lane == 0) mbar_arrive(bars + 8 * (24 + w * 4 + ((s + 3) & 3)));
          if (++s == 4) { s = 0; ph ^= 1; }
        }
        asm volatile("cp.async.bulk.wait_group 0;" ::: "memory");
        __syncwarp();
        if (rb > 0) cnt_signal(p.cnt + (rb - 1) * 32 + C_SP + e);
        wg_wait<0>();
        fence_regs(acc);
        __syncwarp();
        if (lane == 0) mbar_arrive(bars + 8 * (24 + w * 4 + ((s + 3) & 3)));
#pragma unroll
        for (int q = 0; q < 16; q++)
          stmatrix4(slab + (q >> 2) * 8192 + ((sw0 ^ ((q & 3) * 2)) << 4), pack2(acc[8 * q], acc[8 * q + 1]), pack2(acc[8 * q + 2], acc[8 * q + 3]),
                    pack2(acc[8 * q + 4], acc[8 * q + 5]), pack2(acc[8 * q + 6], acc[8 * q + 7]));
        asm volatile("fence.proxy.async.shared::cta;" ::: "memory");
        __syncwarp();
#pragma unroll
        for (int ch = 0; ch < 4; ch++) tma_add3(&p.out, out_stg + ch * 8192, e * 256 + ch * 64, rb * 64 + warp * 16, w);
        asm volatile("cp.async.bulk.commit_group;" ::: "memory");
      }
      asm volatile("cp.async.bulk.wait_group 0;" ::: "memory");
      __syncwarp();
      cnt_signal(p.cnt + 15 * 32 + C_SP + e);
    }
    return;
  }
  const int slot = p.slot[cl];
  const int rb = (slot >> 3) * 2 + rank, j = slot & 7;
  const int cta = rb * 8 + j;
  PROF_AT(threadIdx.x == 0, 0);

  if (threadIdx.x < 128) {
    uint32_t tag = load_epoch(p.epoch);
    asm volatile("setmaxnreg.dec.sync.aligned.u32 40;");
    const int warp = __shfl_sync(~0u, (int)(threadIdx.x >> 5), 0), lane = threadIdx.x & 31;
    if (threadIdx.x == 0) {
      if ((sm & 0x3FFFF) != SMEM_BASE) asm volatile("trap;");
      for (int i = 0; i < 4; i++) { mbar_init(bars + 8 * (B_FQ + i), 1); mbar_init(bars + 8 * (B_EQ + i), 16); }
      for (int i = 0; i < 6; i++) { mbar_init(bars + 8 * (B_FW + i), 1); mbar_init(bars + 8 * (B_EW + i), 16); }
      for (int i = 0; i < 4; i++) { mbar_init(bars + 8 * (B_FG + i), 1); mbar_init(bars + 8 * (B_EG + i), 16); }
      for (int i = 0; i < 6; i++) { mbar_init(bars + 8 * (B_FD + i), 1); mbar_init(bars + 8 * (B_ED + i), 16); }
      for (int i = 0; i < 2; i++) { mbar_init(bars + 8 * (B_STGF + i), 8); mbar_init(bars + 8 * (B_STGE + i), 1); }
      mbar_init(bars + 8 * B_MODB, 1);
      mbar_init(bars + 8 * (B_MODB + 1), 1);
      mbar_init(bars + 8 * B_MODA, 1);
      for (int i = 0; i < 11; i++) mbar_init(bars + 8 * (B_RDY + i), 1);
      asm volatile("fence.mbarrier_init.release.cluster;" ::: "memory");
    }
    __syncwarp();
    cluster_arrive_relaxed();
    tag += 1;
    const unsigned target = tag * 8;
    unsigned* cnt = p.cnt + rb * 32;
    cluster_wait();
    if (warp == 0) {
      const CUtensorMap* wgu = rank ? &p.wu : &p.wg;
      uint32_t st = sm + 16384, fb = bars + 8 * B_FQ, ph = 1;
      __nanosleep(BDELAY);
#pragma unroll 1
      for (int it = 0; it < 32; it++) {
        const int kb = qkv_kb(it, j), col = j * 128 + ((it < 4 ? it >= 2 : it >= 18) ? 64 : 0);
        if (it == 2) mbar_wait(bars + 8 * B_MODA, 0);
        mbar_wait(fb + 8 * (B_EQ - B_FQ), ph);
        expect_tx_elect(fb, it < 4 ? 24576 : 40960);
        tma_load_mc(st + rank * 8192, &p.wqkv, fb, col + rank * 1024, kb * 64);
        tma_load_mc(st + 16384 + rank * 4096, &p.wqkv32, fb, col + 2048, kb * 64 + rank * 32);
        st += 49152; fb += 8;
        if ((it & 3) == 3) { st -= 4 * 49152; fb -= 32; ph ^= 1; }
      }
      fb = bars + 8 * B_FW; ph = 1;
#pragma unroll 1
      for (int it = 0, s = 0; it < 34; it++) {
        if (it < 6) wait_q_free(bars + 8 * B_EQ, it);
        if (it == 16) mbar_wait(bars + 8 * (B_FW + 3), 0);
        mbar_wait(fb + 8 * (B_EW - B_FW), ph);
        expect_tx_elect(fb, (it == 8 || it == 18 || it == 19) ? 16384 : 32768);
        const int k0 = it < 16 ? wo_k(it, j) : (it < 20 ? 2 * j + (it & 1) : other_kb(it - 20, j)) * 64;
        if (it == 16 || it == 17) {
          tma_load_mc(st - 16384 + rank * 16384, wgu, fb, j * 448, k0);
          tma_load_mc(st - 8192 + rank * 16384, wgu, fb, j * 448 + 64, k0);
        } else {
          tma_load_mc(st + rank * 8192, it < 16 ? &p.wo : wgu, fb, it < 16 ? j * 128 + rank * 64 : j * 448 + 384, k0);
        }
        st += 32768; fb += 8;
        if (++s == 6) { s = 0; st -= 6 * 32768; fb -= 48; ph ^= 1; }
      }
      st = sm + 16384 + 3 * 49152; fb = bars + 8 * B_FG; ph = 1;
#pragma unroll 1
      for (int it = 0; it < 46; it++) {
        const int kb = it < 14 ? other_kb(it, j) : (it + 2) & 15, col = j * 448 + ((it + 2) >> 4) * 128;
        if (it < 4) wait_w_free(bars + 8 * B_EW, it);
        mbar_wait(fb + 8 * (B_EG - B_FG), ph);
        expect_tx_elect(fb, 49152);
        tma_load_mc(st + rank * 16384, wgu, fb, col, kb * 64);
        tma_load_mc(st + rank * 16384 + 8192, wgu, fb, col + 64, kb * 64);
        st += (it & 3) == 0 ? -3 * 49152 : 49152; fb += 8;
        if ((it & 3) == 3) { fb -= 32; ph ^= 1; }
      }
      st = sm + 16384 + 2 * 32768; fb = bars + 8 * B_FD; ph = 1;
#pragma unroll 1
      for (int it = 0, s = 0; it < 56 - KH; it++) {
        if (it < 6) wait_g_free(bars + 8 * B_EG, it);
        mbar_wait(fb + 8 * (B_ED - B_FD), ph);
        expect_tx_elect(fb, 32768);
        tma_load_mc(st + rank * 8192, &p.wd, fb, j * 128 + rank * 64, down_k(it));
        st += s == 3 ? -5 * 32768 : 32768; fb += 8;
        if (++s == 6) { s = 0; fb -= 48; ph ^= 1; }
      }
    } else if (warp == 1) {
      const int arow = rb * 128;
      uint32_t st = sm, fb = bars + 8 * B_FQ, ph = 0;
      cnt_wait(cnt + C_HA, target);
      PROF_AT(lane == 0, 16);
#pragma unroll 1
      for (int it = 4; it < 32; it++) {
        if (it == 11) mbar_wait(bars + 8 * (B_RDY + C_H), 0);
        mbar_wait(fb + 8 * (B_EQ - B_FQ), ph);
        tma_load(st, &p.h, fb, qkv_kb(it, j) * 64, arow);
        st += 49152; fb += 8;
        if ((it & 3) == 3) { st -= 4 * 49152; fb -= 32; ph ^= 1; }
      }
      fb = bars + 8 * B_FW; ph = 1;
#pragma unroll 1
      for (int it = 0, s = 0; it < 34; it++) {
        if (it < 16 || it >= 20) {
          if (it < 6) wait_q_free(bars + 8 * B_EQ, it);
          mbar_wait(fb + 8 * (B_EW - B_FW), ph);
          if (it == 0) mbar_wait(bars + 8 * (B_RDY + C_O), 0);
          if (it == 9 || it == 20) cnt_wait(cnt + (it == 9 ? C_O + 1 : C_H2A), target * 8);
          if (it == 27) mbar_wait(bars + 8 * (B_RDY + C_H2), 0);
          PROF_AT(lane == 0 && (it == 0 || it == 9 || it == 20), 17 + (it >> 3));
          if (it != 8) tma_load(st, it < 16 ? &p.o_ld : &p.h2, fb, it < 16 ? wo_k(it, j) : other_kb(it - 20, j) * 64, arow);
        }
        st += 32768; fb += 8;
        if (++s == 6) { s = 0; st -= 6 * 32768; fb -= 48; ph ^= 1; }
      }
      st = sm + 3 * 49152; fb = bars + 8 * B_FG; ph = 1;
#pragma unroll 1
      for (int it = 0; it < 46; it++) {
        if (it < 4) wait_w_free(bars + 8 * B_EW, it);
        mbar_wait(fb + 8 * (B_EG - B_FG), ph);
        tma_load(st, &p.h2, fb, (it < 14 ? other_kb(it, j) : (it + 2) & 15) * 64, arow);
        st += (it & 3) == 0 ? -3 * 49152 : 49152; fb += 8;
        if ((it & 3) == 3) { fb -= 32; ph ^= 1; }
      }
      st = sm + 2 * 32768; fb = bars + 8 * B_FD; ph = 1;
#pragma unroll 1
      for (int it = 0, s = 0; it < 56 - KH; it++) {
        if (it < 6) wait_g_free(bars + 8 * B_EG, it);
        mbar_wait(fb + 8 * (B_ED - B_FD), ph);
        const int u = it + KH, dep = it == 0 ? C_ACT : (u == 8 ? C_ACT + 1 : (u == 24 ? C_ACT + 2 : (u == 40 ? C_A0 : (u == 48 ? C_ACT + 3 : -1))));
        if (dep >= 0) mbar_wait(bars + 8 * (B_RDY + dep), 0);
        tma_load(st, &p.act, fb, down_k(it), arow);
        st += s == 3 ? -5 * 32768 : 32768; fb += 8;
        if (++s == 6) { s = 0; fb -= 48; ph ^= 1; }
      }
    } else if (warp == 2) {
      if (lane < 14) prefetch_map(&p.h + lane);
      __syncwarp();
      uint32_t ph1 = 0;
#pragma unroll 1
      for (int n = 0; n < 8; n++) {
        const int nch = (n == 1 || n == 2 || n == 4) ? 1 : 2;
#pragma unroll 1
        for (int ch = 0; ch < nch; ch++) {
          mbar_wait_watchdog(bars + 8 * (B_STGF + ch), ch ? ph1 : (n & 1));
          const uint32_t src = stg + ch * 16384;
          if (n == 2 || n == 3) {
          } else if (n == 1) {
#pragma unroll 1
            for (int q = 0; q < 8; q++) {
              tma_store2(&p.o_st, src + q * 2048, j * 128, rb * 128 + q * 16);
              if (q & 1) store_pause(true);
            }
          } else if (n >= 4 && n < 8) {
#pragma unroll 1
            for (int q = 0; q < 4; q++) {
              tma_store2(&p.act_st, src + q * 4096, j * 448 + (n == 4 ? 384 : (n - 5) * 128 + ch * 64), rb * 128 + q * 32);
              store_pause(true);
            }
          } else {
            tma_store2(&p.h, src, j * 128 + ch * 64, rb * 128);
            asm volatile("cp.async.bulk.commit_group;" ::: "memory");
            if (ch == 1) {
              asm volatile("cp.async.bulk.wait_group 1;" ::: "memory");
              __syncwarp();
              cnt_signal(cnt + C_HA);
            }
          }
          if (n >= 5 && ch == 0) arrive_elect(bars + 8 * B_STGE);
          if (n == 7 && ch == 0) {
            asm volatile("cp.async.bulk.wait_group 0;" ::: "memory");
            __syncwarp();
            cnt_signal(cnt + C_A0);
          }
        }
        asm volatile("cp.async.bulk.commit_group;" ::: "memory");
        asm volatile("cp.async.bulk.wait_group 0;" ::: "memory");
        __syncwarp();
        if (n != 2 && n != 3) cnt_signal(cnt + n);
        PROF_AT(lane == 0, n == 0 ? 33 : 23 + n);
        if (n == 0) {
#pragma unroll 1
          for (int t = 0; t < 34; t++) {
            ll_store(t < 32 ? p.halo + cta * 1024 + t * 32 + lane : (uint4*)(p.stats2 + cta * 128) + (t - 32) * 32 + lane, 0u, 0u, 0u);
            __nanosleep(40);
          }
          __syncwarp();
        }
        if (n < 5) arrive_elect(bars + 8 * B_STGE);
        if (nch == 2) { arrive_elect(bars + 8 * (B_STGE + 1)); ph1 ^= 1; }
      }
      mbar_wait_watchdog(bars + 8 * B_STGF, 0);
      PROF_AT(lane == 0, 31);
    } else {
      if (lane < 4) ll_store(p.modll + cta * 4 + lane, 0u, 0u, 0u);
      bar_sync(1, 288);
      {
        const uint4 t4 = lds128(sm + RED_OFF + lane * 16);
        float a[4] = {__uint_as_float(t4.x), __uint_as_float(t4.y), __uint_as_float(t4.z), __uint_as_float(t4.w)};
#pragma unroll
        for (int o = 4; o < 32; o <<= 1)
#pragma unroll
          for (int q = 0; q < 4; q++) a[q] += __shfl_xor_sync(~0u, a[q], o);
        if (lane < 4) ll_store(p.modll + cta * 4 + lane, pack2(a[0], a[1]), pack2(a[2], a[3]), tag);
        PROF_AT(lane == 0, 1);
        uint32_t m[4];
        const uint4* mp = p.modll + j * 32 + lane;
        ll_poll<2>([&](int i) { return mp + i * 256; }, tag, m);
        const uint32_t c0 = pack2(1.0f + bf_lo(m[2]), 1.0f + bf_hi(m[2])), c1 = pack2(1.0f + bf_lo(m[3]), 1.0f + bf_hi(m[3]));
        sts128(sm + MODB_OFF + lane * 16, c0, m[0], c1, m[1]);
        __syncwarp();
        arrive_elect(bars + 8 * B_MODA);
      }
#pragma unroll 1
      for (int n = C_H; n <= C_O; n++) {
        cnt_wait_lazy(cnt + n, target);
        arrive_elect(bars + 8 * (B_RDY + n));
      }
      {
        uint32_t m[6];
        const uint4* src = p.modll + 512 + j * 32 + lane;
        ll_poll<3, 500>([&](int i) { return src + i * 256; }, tag, m);
#pragma unroll
        for (int vec = 0; vec < 3; vec++) {
          const float add = vec == 2 ? 1.0f : 0.0f;
          sts128(sm + MODB_OFF + (vec * 128 + lane * 4) * 4, __float_as_uint(bf_round(bf_lo(m[2 * vec]) + add)), __float_as_uint(bf_round(bf_hi(m[2 * vec]) + add)),
                 __float_as_uint(bf_round(bf_lo(m[2 * vec + 1]) + add)), __float_as_uint(bf_round(bf_hi(m[2 * vec + 1]) + add)));
        }
        __syncwarp();
        if (lane == 0) mbar_arrive(bars + 8 * B_MODB);
        PROF_AT(lane == 0, 15);
      }
      __syncwarp();
#pragma unroll 1
      for (int q = C_H2; q < 9; q++) {
        const int n = q < 7 ? q : (q == 7 ? C_A0 : C_ACT + 3);
        cnt_wait_lazy(cnt + n, n == C_H2 ? target * 8 : target);
        arrive_elect(bars + 8 * (B_RDY + n));
      }
      {
        uint32_t m[2];
        const uint4* src = p.modll + 512 + 768 + j * 32 + lane;
        ll_poll<1>([&](int) { return src; }, tag, m);
        sts128(sm + MODB_OFF + (384 + lane * 4) * 4, m[0] << 16, m[0] & 0xffff0000u, m[1] << 16, m[1] & 0xffff0000u);
        cnt_wait_lazy(cnt + C_SP + (j >> 1), target);
        __syncwarp();
        if (lane == 0) mbar_arrive(bars + 8 * (B_MODB + 1));
      }
    }
  } else {
    uint32_t tag;

    {
      const int tid = threadIdx.x - 128, cw = tid >> 7, warp = (tid >> 5) & 3, lane = tid & 31;
      const int l16 = lane & 15, half = lane >> 4, w8 = cw * 4 + warp;
      const uint32_t cbuf = sm + 3 * 49152 + w8 * 512;
      if (lane <= 16) cp_async16(cbuf + lane * 16, lane < 16 ? (const void*)(p.c + w8 * 128 + lane * 8) : (const void*)p.epoch);
      asm volatile("cp.async.commit_group;" ::: "memory");
      const uint32_t xbuf = sm + 40960 + (cw * 2 + (l16 >> 3)) * 49152 + (warp * 16 + half) * 128;
      {
        const char* xp = (const char*)p.x + (uint32_t)((rb * 128 + (warp * 16 + half) * 2 + cw) * 2048 + j * 256 + l16 * 16);
#pragma unroll
        for (int i = 0; i < 8; i++) cp_async16(xbuf + i * 256 + (((l16 & 7) ^ ((i * 2 + half) & 7)) << 4), xp + i * 8192);
      }
      asm volatile("cp.async.commit_group;" ::: "memory");
      const uint32_t wbuf = sm + cw * 49152 + warp * 4096;
      {
        const char* wp = (const char*)p.wmod + (uint32_t)(cta * 32 + (lane & 1) * 16 + (w8 * 128 + (lane >> 1)) * 12288);
#pragma unroll
        for (int i = 0; i < 8; i++) cp_async16(wbuf + i * 512 + lane * 16, wp + i * 16 * 12288);
      }
      asm volatile("cp.async.commit_group;" ::: "memory");
      PROF_AT(tid == 0, 32);
      uint2* st1 = p.stats1 + (rb * 8 + j) * 128 + cw * 64 + warp * 16;
      if (lane < 8) ll_store((uint4*)st1 + lane, 0u, 0u, 0u);
      __syncwarp();
      cluster_arrive_relaxed();
      asm volatile("setmaxnreg.inc.sync.aligned.u32 232;");
      uint32_t sa[4][4];
      {
        asm volatile("cp.async.wait_group 2;" ::: "memory");
        __syncwarp();
        tag = lds32(cbuf + 256) + 1;
        const float2 cv = lds64f(cbuf + lane * 8);
        const uint32_t c0 = __float_as_uint(cv.x), c1 = __float_as_uint(cv.y);
        sts64f(cbuf + lane * 8, __uint_as_float(pack2(silu_f(bf_lo(c0)), silu_f(bf_hi(c0)))), __uint_as_float(pack2(silu_f(bf_lo(c1)), silu_f(bf_hi(c1)))));
        __syncwarp();
#pragma unroll
        for (int q = 0; q < 4; q++) ldmatrix4(sa[q][0], sa[q][1], sa[q][2], sa[q][3], cbuf + q * 64 + (lane >> 3) * 16);
      }
      cluster_wait();
      asm volatile("cp.async.wait_group 1;" ::: "memory");
      __syncwarp();
      uint32_t xl[16], xh[16];
      {
        const int srow = warp * 16 + (lane & 15);
#pragma unroll
        for (int q = 0; q < 8; q++)
          ldmatrix4(xl[2 * q], xh[2 * q], xl[2 * q + 1], xh[2 * q + 1],
                    sm + 40960 + (cw * 2 + (q >> 2)) * 49152 + srow * 128 + (((half + (q & 3) * 2) ^ (srow & 7)) << 4));
      }
      publish_stats(xl, xh, st1, lane, tag16(tag));
      PROF_AT(tid == 0, 50);
      asm volatile("cp.async.wait_group 0;" ::: "memory");
      __syncwarp();
      PROF_AT(tid == 0, 51);
      {
        uint32_t b[8][4];
#pragma unroll
        for (int ks = 0; ks < 8; ks++) ldmatrix4t(b[ks], wbuf + (ks * 16 + (lane & 15)) * 32 + (lane >> 4) * 16);
        float d0[4] = {0.f, 0.f, 0.f, 0.f}, d1[4] = {0.f, 0.f, 0.f, 0.f}, d2[4] = {0.f, 0.f, 0.f, 0.f}, d3[4] = {0.f, 0.f, 0.f, 0.f};
#pragma unroll
        for (int q = 0; q < 4; q++) {
          mma16816(d0, sa[q][0], sa[q][0], sa[q][1], sa[q][1], b[2 * q][0], b[2 * q][1]);
          mma16816(d1, sa[q][0], sa[q][0], sa[q][1], sa[q][1], b[2 * q][2], b[2 * q][3]);
          mma16816(d2, sa[q][2], sa[q][2], sa[q][3], sa[q][3], b[2 * q + 1][0], b[2 * q + 1][1]);
          mma16816(d3, sa[q][2], sa[q][2], sa[q][3], sa[q][3], b[2 * q + 1][2], b[2 * q + 1][3]);
        }
        d0[0] += d2[0]; d0[1] += d2[1]; d1[0] += d3[0]; d1[1] += d3[1];
        if (lane < 4) {
          sts64f(sm + RED_OFF + (w8 * 16 + lane * 2) * 4, d0[0], d0[1]);
          sts64f(sm + RED_OFF + (w8 * 16 + 8 + lane * 2) * 4, d1[0], d1[1]);
        }
        asm volatile("bar.arrive 1, 288;" ::: "memory");
      }
      {
        const int c = lane & 3;
        float rs[2], nb[2];
        stat_gather(p.stats1 + rb * 1024 + cw * 64 + warp * 16, tag16(tag), lane, rs, nb);
#pragma unroll
        for (int n = 0; n < 16; n++) {
          xl[n] = pack2(bf_lo(xl[n]) * rs[0] + nb[0], bf_hi(xl[n]) * rs[0] + nb[0]);
          xh[n] = pack2(bf_lo(xh[n]) * rs[1] + nb[1], bf_hi(xh[n]) * rs[1] + nb[1]);
        }
        const int srow = warp * 16 + l16;
        const uint32_t slab = stg + cw * 8192 + srow * 128;
#pragma unroll
        for (int q = 0; q < 8; q++)
          stmatrix4(slab + (q >> 2) * 16384 + (((half + (q & 3) * 2) ^ (srow & 7)) << 4), xl[2 * q], xh[2 * q], xl[2 * q + 1], xh[2 * q + 1]);
        PROF_AT(tid == 0, 52);
        mbar_wait(bars + 8 * B_MODA, 0);
        PROF_AT(tid == 0, 2);
#pragma unroll
        for (int q = 0; q < 8; q++) {
          const float2 m0 = lds64f(sm + MODB_OFF + (8 * q + c) * 8), m1 = lds64f(sm + MODB_OFF + (8 * q + 4 + c) * 8);
          const uint32_t c0 = __float_as_uint(m0.x), s0 = __float_as_uint(m0.y), c1 = __float_as_uint(m1.x), s1 = __float_as_uint(m1.y);
          stmatrix4(slab + (q >> 2) * 16384 + (((half + (q & 3) * 2) ^ (srow & 7)) << 4), fma_bf2(xl[2 * q], c0, s0), fma_bf2(xh[2 * q], c0, s0),
                    fma_bf2(xl[2 * q + 1], c1, s1), fma_bf2(xh[2 * q + 1], c1, s1));
          if ((q & 3) == 3) stage_done(bars + 8 * (B_STGF + (q >> 2)), lane);
        }
        wg_bar(cw);
      }
      PROF_AT(tid == 0, 3);
    }

    uint32_t xl[16], xh[16];
    {
      RING_IDS();
      uint32_t prev = 0;
      float acc1[96];
      {
        Ring g{bars + 8 * B_FQ, rbars + 8 * B_EQ, 0, 0u, 0u, releaser TR(0)};
        float acc0[96];
#pragma unroll 1
        for (int kb = 0; kb < 2; kb++) kblock<192, 4, 49152>(acc0, g, a_base + STG_OFF + kb * 16384, kb == 0, prev);
#pragma unroll 1
        for (int kb = 0; kb < 2; kb++) kblock<192, 4, 49152>(acc1, g, a_base + STG_OFF + kb * 16384, kb == 0, prev);
#pragma unroll 1
        for (int kb = 0; kb < 14; kb++) kblock<192, 4, 49152>(acc0, g, a_base + g.off, false, prev);
        PROF_AT(tid == 0, 4);
        attention<NPRE0, false>(acc0, p, 0, rb, cta, cw, warp, tag, stg, bars, prev, [&]() { kblock<192, 4, 49152>(acc1, g, a_base + g.off, false, prev); });
        PROF_AT(tid == 0, 5);
        {
          LANE_IDS();
#pragma unroll
          for (int q = 0; q < 8; q++)
            ldmatrix4(xl[2 * q], xh[2 * q], xl[2 * q + 1], xh[2 * q + 1], sm + 40960 + (cw * 2 + (q >> 2)) * 49152 + srow * 128 + ((sw0 ^ ((q & 3) * 2)) << 4));
#pragma unroll
          for (int q = 0; q < 16; q++) asm volatile("" : "+r"(xl[q]), "+r"(xh[q])::"memory");
        }
#pragma unroll 1
        for (int kb = 5 + NPRE0; kb < 14; kb++) kblock<192, 4, 49152>(acc1, g, a_base + g.off, false, prev);
        PROF_AT(tid == 0, 6);
      }
      float acc[64];
      Ring g{bars + 8 * B_FW, rbars + 8 * B_EW, 0, 0u, 0u, releaser TR(32)};
      attention<NPRE1, true>(acc1, p, 1, rb, cta, cw, warp, tag, stg, bars, prev, [&]() { kblock<128, 6, 32768>(acc, g, a_base + g.off, g.s == 0, prev); });
      PROF_AT(tid == 0, 7);
      LANE_IDS();
      unsigned* cnt = p.cnt + rb * 32;
      tma_store2(&p.o_st, stg + cw * 8192 + warp * 2048, j * 128 + 64, rb * 128 + cw * 64 + warp * 16);
      asm volatile("cp.async.bulk.commit_group;" ::: "memory");
#pragma unroll 1
      for (int kb = 1 + NPRE1; kb < 16; kb++) {
        if (kb == 8) wg_bar(cw);
        kblock<128, 6, 32768>(acc, g, a_base + (kb == 8 ? STG_OFF : g.off), false, prev);
        if (kb == 3 + NPRE1) {
          asm volatile("cp.async.bulk.wait_group 0;" ::: "memory");
          __syncwarp();
          cnt_signal(cnt + C_O + 1);
        }
      }
      mbar_wait(bars + 8 * B_MODB, 0);
      float2 ga[16];
#pragma unroll
      for (int n = 0; n < 16; n++) ga[n] = lds64f(sm + MODB_OFF + (8 * n + 2 * c) * 4);
      tile_end(acc, prev);
      PROF_AT(tid == 0, 8);
#pragma unroll
      for (int n = 0; n < 16; n++) {
        acc[4 * n] = ga[n].x * acc[4 * n] + bf_lo(xl[n]); acc[4 * n + 1] = ga[n].y * acc[4 * n + 1] + bf_hi(xl[n]);
        acc[4 * n + 2] = ga[n].x * acc[4 * n + 2] + bf_lo(xh[n]); acc[4 * n + 3] = ga[n].y * acc[4 * n + 3] + bf_hi(xh[n]);
        xl[n] = pack2(acc[4 * n], acc[4 * n + 1]);
        xh[n] = pack2(acc[4 * n + 2], acc[4 * n + 3]);
      }
      publish_stats(xl, xh, p.stats2 + (rb * 8 + j) * 128 + cw * 64 + warp * 16, lane, tag16(tag));
      PROF_AT(tid == 0, 48);
      float2 sb[16], cb[16];
#pragma unroll
      for (int n = 0; n < 16; n++) {
        sb[n] = lds64f(sm + MODB_OFF + (128 + 8 * n + 2 * c) * 4);
        cb[n] = lds64f(sm + MODB_OFF + (256 + 8 * n + 2 * c) * 4);
      }
      mbar_wait(bars + 8 * B_STGE, 0);
      PROF_AT(tid == 0, 49);
      float nb[2], rstd[2];
      stat_gather(p.stats2 + rb * 1024 + cw * 64 + warp * 16, tag16(tag), lane, rstd, nb);
      PROF_AT(tid == 0, 9);
#pragma unroll
      for (int ch = 0; ch < 2; ch++) {
        uint32_t lo[8], hi[8];
#pragma unroll
        for (int t = 0; t < 8; t++) {
          const int n = ch * 8 + t;
          lo[t] = pack2((acc[4 * n] * rstd[0] + nb[0]) * cb[n].x + sb[n].x, (acc[4 * n + 1] * rstd[0] + nb[0]) * cb[n].y + sb[n].y);
          hi[t] = pack2((acc[4 * n + 2] * rstd[1] + nb[1]) * cb[n].x + sb[n].x, (acc[4 * n + 3] * rstd[1] + nb[1]) * cb[n].y + sb[n].y);
        }
        stage_slab(sm + ch * 32768 + cw * 8192, warp, lane, lo, hi);
        stage_done(bars + 8 * (B_STGF + ch), lane);
        tma_store2(&p.h2_st, sm + ch * 32768 + cw * 8192 + warp * 2048, j * 128 + ch * 64, rb * 128 + cw * 64 + warp * 16);
        asm volatile("cp.async.bulk.commit_group;" ::: "memory");
      }
      wg_bar(cw);
      PROF_AT(tid == 0, 10);
    }

    uint32_t pg[32], pu[32];
    {
      RING_IDS();
      float acc[128];
      uint32_t prev = 0;
      Ring g{bars + 8 * B_FG, rbars + 8 * B_EG, 0, 0u, 3 * 49152u, releaser TR(66)};
      {
        Ring w{bars + 8 * B_FW, rbars + 8 * B_EW, 4, 0u, 4 * 32768u, releaser TR(48)};
        float acn[64];
#pragma unroll 1
        for (int kb = 0; kb < 2; kb++) {
          kblock<256, 6, 32768>(acc, w, a_base + kb * 32768, kb == 0, prev, 0u);
          if (kb == 0) asm volatile("cp.async.bulk.wait_group 1;" ::: "memory");
          else asm volatile("cp.async.bulk.wait_group 0;" ::: "memory");
          __syncwarp();
          cnt_signal(p.cnt + rb * 32 + (kb == 0 ? C_H2A : C_H2));
        }
        {
          LANE_IDS();
#pragma unroll
          for (int q = 0; q < 8; q++)
            stmatrix4(slab + (q >> 2) * 16384 + ((sw0 ^ ((q & 3) * 2)) << 4), xl[2 * q], xh[2 * q], xl[2 * q + 1], xh[2 * q + 1]);
          __syncwarp();
        }
#pragma unroll 1
        for (int kb = 0; kb < 16; kb++) {
          kblock<128, 6, 32768>(acn, w, a_base + w.off, kb == 0, prev);
          if (kb == 4) {
            asm volatile("fence.proxy.async.shared::cta;" ::: "memory");
            __syncwarp();
          }
          if (kb == 6 + warp || kb == 10 + warp) {
            const int ch = kb != 6 + warp;
            tma_store3(&p.out, stg + ch * 16384 + cw * 8192 + warp * 2048, j * 128 + ch * 64, rb * 64 + warp * 16, cw);
            asm volatile("cp.async.bulk.commit_group;" ::: "memory");
          }
        }
        PROF_AT(tid == 0, 39);
        kblock<256, 4, 49152>(acc, g, a_base + g.off, false, prev);
        fence_regs(acn);
#pragma unroll
        for (int q = 0; q < 16; q++) {
          pg[q] = pack2(acn[2 * q], acn[2 * q + 1]);
          pu[q] = pack2(acn[32 + 2 * q], acn[32 + 2 * q + 1]);
          pg[16 + q] = 0; pu[16 + q] = 0;
        }
        asm volatile("cp.async.bulk.wait_group 0;" ::: "memory");
        kblock<256, 4, 49152>(acc, g, a_base + g.off, false, prev);
      }
      LANE_IDS();
#pragma unroll 1
      for (int t = 0; t < 3; t++) {
#pragma unroll 1
        for (int blk = 0; blk < (t == 0 ? 2 : 4); blk++) {
          g.s = 2;
#pragma unroll
          for (int i = 0; i < 4; i++) {
            g.off = ((i + 1) & 3) * 49152;
            if (i == 3 && blk == 3) skew_pre(cw);
            kblock<256, 4, 49152>(acc, g, a_base + g.off, t > 0 && blk == 0 && i == 0, prev);
            if (i == 3 && blk == 3) skew_post(cw);
            if ((blk & 1) == 0 && i == 0) mbar_wait(bars + 8 * (B_STGE + (blk >> 1)), (t + 1 + (blk >> 1)) & 1);
            stmatrix2(slab + (blk >> 1) * 16384 + (((srow & 7) ^ ((blk & 1) * 4 + i)) << 4), swiglu2(pg[2 * i], pu[2 * i]), swiglu2(pg[2 * i + 1], pu[2 * i + 1]));
          }
#pragma unroll
          for (int q = 0; q < 24; q++) { pg[q] = pg[q + 8]; pu[q] = pu[q + 8]; }
          if (blk & 1) stage_done(bars + 8 * (B_STGF + (blk >> 1)), lane);
        }
#pragma unroll 1
        for (int kb = t == 0 ? 0 : 4; kb < 4; kb++) {
          if (kb == 3) skew_pre(cw);
          kblock<256, 4, 49152>(acc, g, a_base + g.off, false, prev);
          if (kb == 3) skew_post(cw);
        }
        tile_end(acc, prev);
        PROF_AT(tid == 0, 36 + t);
#pragma unroll
        for (int q = 0; q < 32; q++) {
          pg[q] = pack2(acc[2 * q], acc[2 * q + 1]);
          pu[q] = pack2(acc[64 + 2 * q], acc[64 + 2 * q + 1]);
        }
      }
      PROF_AT(tid == 0, 11);
    }

    {
      RING_IDS();
      LANE_IDS();
      Ring g{bars + 8 * B_FD, rbars + 8 * B_ED, 0, 0u, 2 * 32768u, releaser TR(112)};
      float acc[64];
      uint32_t prev = 0;
#pragma unroll 1
      for (int blk = 0; blk < 4; blk++) {
#pragma unroll
        for (int i = 0; i < 8; i++) {
          kblock<128, 6, 32768>(acc, g, a_base + g.off, blk == 0 && i == 0, prev);
          if ((blk & 1) == 0 && i == 0) mbar_wait(bars + 8 * (B_STGE + (blk >> 1)), blk >> 1);
          stmatrix1(slab + (blk >> 1) * 16384 + (i & 1) * 1024 + (((srow & 7) ^ ((blk & 1) * 4 + (i >> 1))) << 4), swiglu2(pg[i], pu[i]));
        }
#pragma unroll
        for (int q = 0; q < 24; q++) { pg[q] = pg[q + 8]; pu[q] = pu[q + 8]; }
        if (blk & 1) stage_done(bars + 8 * (B_STGF + (blk >> 1)), lane);
      }
#pragma unroll 1
      for (int kb = 32; kb < 56 - KH; kb++) {
        if (kb == 50 - KH) g.releaser = false;
        if (kb == 52 - KH) skew_pre(cw);
        kblock<128, 6, 32768>(acc, g, a_base + g.off, false, prev);
      }
      skew_post(cw);
      mbar_wait(bars + 8 * (B_MODB + 1), 0);
      mbar_wait(bars + 8 * B_STGE, 1);
      mbar_wait(bars + 8 * (B_STGE + 1), 0);
      float2 gbv[16];
#pragma unroll
      for (int n = 0; n < 16; n++) gbv[n] = lds64f(sm + MODB_OFF + (384 + 8 * n + 2 * c) * 4);
      tile_end(acc, prev);
      PROF_AT(tid == 0, 13);
#pragma unroll
      for (int ch = 0; ch < 2; ch++) {
        uint32_t lo[8], hi[8];
#pragma unroll
        for (int t = 0; t < 8; t++) {
          const int n = ch * 8 + t;
          const float2 gb = gbv[n];
          lo[t] = pack2(gb.x * acc[4 * n], gb.y * acc[4 * n + 1]);
          hi[t] = pack2(gb.x * acc[4 * n + 2], gb.y * acc[4 * n + 3]);
        }
        stage_slab(stg + ch * 16384 + cw * 8192, warp, lane, lo, hi);
        asm volatile("fence.proxy.async.shared::cta;" ::: "memory");
        __syncwarp();
        tma_add3(&p.out, stg + ch * 16384 + cw * 8192 + warp * 2048, j * 128 + ch * 64, rb * 64 + warp * 16, cw);
      }
      asm volatile("cp.async.bulk.commit_group;" ::: "memory");
      if (lane == 0) mbar_arrive(bars + 8 * B_STGF);
      asm volatile("cp.async.bulk.wait_group.read 0;" ::: "memory");
      PROF_AT(tid == 0, 14);
    }
    if (blockIdx.x == 0 && threadIdx.x == 128) asm volatile("st.relaxed.gpu.global.u32 [%0], %1;" ::"l"(p.epoch), "r"(tag) : "memory");
  }
}

typedef CUresult (*EncodeFn)(CUtensorMap*, CUtensorMapDataType, cuuint32_t, void*, const cuuint64_t*, const cuuint64_t*,
                             const cuuint32_t*, const cuuint32_t*, CUtensorMapInterleave, CUtensorMapSwizzle,
                             CUtensorMapL2promotion, CUtensorMapFloatOOBfill);

void encode2d(EncodeFn fn, CUtensorMap* m, const void* ptr, uint64_t cols, uint64_t rows, uint32_t box_rows) {
  cuuint64_t dims[2] = {cols, rows};
  cuuint64_t strides[1] = {cols * 2};
  cuuint32_t box[2] = {64, box_rows};
  cuuint32_t es[2] = {1, 1};
  fn(m, CU_TENSOR_MAP_DATA_TYPE_BFLOAT16, 2, (void*)ptr, dims, strides, box, es, CU_TENSOR_MAP_INTERLEAVE_NONE,
     CU_TENSOR_MAP_SWIZZLE_128B, CU_TENSOR_MAP_L2_PROMOTION_L2_128B, CU_TENSOR_MAP_FLOAT_OOB_FILL_NONE);
}

}

extern "C" void kernel_launch(void* const* d_in, const int* in_sizes, int n_in, void* d_out, int out_size) {
  (void)in_sizes; (void)n_in; (void)out_size;
  void* fp = nullptr;
  cudaDriverEntryPointQueryResult qr;
  cudaGetDriverEntryPoint("cuTensorMapEncodeTiled", &fp, cudaEnableDefault, &qr);
  EncodeFn fn = (EncodeFn)fp;
  void *ph, *po, *ph2, *pact;
  cudaGetSymbolAddress(&ph, g_h);
  cudaGetSymbolAddress(&po, g_o);
  ph2 = ph;
  cudaGetSymbolAddress(&pact, g_act);
  Params p;
  encode2d(fn, &p.h, ph, DM, SEQ, 128);
  encode2d(fn, &p.o_ld, po, DM, SEQ, 128);
  encode2d(fn, &p.h2, ph2, DM, SEQ, 128);
  encode2d(fn, &p.act, pact, FF, SEQ, 128);
  encode2d(fn, &p.act_st, pact, FF, SEQ, 32);
  encode2d(fn, &p.wm, d_in[8], 6 * DM, DM, 64);
  encode2d(fn, &p.o_st, po, DM, SEQ, 16);
  encode2d(fn, &p.h2_st, ph2, DM, SEQ, 16);
  encode2d(fn, &p.wqkv, d_in[1], 3 * DM, DM, 64);
  encode2d(fn, &p.wqkv32, d_in[1], 3 * DM, DM, 32);
  encode2d(fn, &p.wo, d_in[2], DM, DM, 64);
  encode2d(fn, &p.wg, d_in[4], FF, DM, 64);
  encode2d(fn, &p.wu, d_in[5], FF, DM, 64);
  encode2d(fn, &p.wd, d_in[6], DM, FF, 64);
  {
    cuuint64_t dims[3] = {DM, SEQ / 2, 2};
    cuuint64_t strides[2] = {DM * 4, DM * 2};
    cuuint32_t box[3] = {64, 16, 1};
    cuuint32_t es[3] = {1, 1, 1};
    fn(&p.out, CU_TENSOR_MAP_DATA_TYPE_BFLOAT16, 3, d_out, dims, strides, box, es, CU_TENSOR_MAP_INTERLEAVE_NONE,
       CU_TENSOR_MAP_SWIZZLE_128B, CU_TENSOR_MAP_L2_PROMOTION_L2_128B, CU_TENSOR_MAP_FLOAT_OOB_FILL_NONE);
  }
  p.x = (const bf16*)d_in[0];
  p.c = (const bf16*)d_in[7];
  p.wmod = (const bf16*)d_in[8];
  for (int cl = 0; cl < 64; cl++) {
    const int grp = cl < 4 ? 0 : (cl < 36 ? (cl - 4) & 7 : 1 + (cl - 36) % 7);
    const int j = cl < 4 ? 4 + cl : (cl < 36 ? (cl - 4) >> 3 : 4 + (cl - 36) / 7);
    p.slot[cl] = (uint8_t)(grp * 8 + j);
  }
  void* q;
  cudaGetSymbolAddress(&q, g_modll); p.modll = (uint4*)q;
  cudaGetSymbolAddress(&q, g_halo); p.halo = (uint4*)q;
  cudaGetSymbolAddress(&q, g_stats); p.stats1 = (uint2*)q; p.stats2 = p.stats1 + SEQ * 8;
  cudaGetSymbolAddress(&q, g_cnt); p.cnt = (unsigned*)q;
  cudaGetSymbolAddress(&q, g_epoch); p.epoch = (unsigned*)q;

  cudaFuncSetAttribute(fused_kernel, cudaFuncAttributeMaxDynamicSharedMemorySize, SMEM_BYTES);
  cudaLaunchConfig_t cfg = {};
  cfg.gridDim = dim3(NCTA + 4);
  cfg.blockDim = dim3(384);
  cfg.dynamicSmemBytes = SMEM_BYTES;
  cfg.stream = cudaStreamPerThread;
  cudaLaunchAttribute at[1];
  at[0].id = cudaLaunchAttributeClusterDimension;
  at[0].val.clusterDim.x = 2; at[0].val.clusterDim.y = 1; at[0].val.clusterDim.z = 1;
  cfg.attrs = at;
  cfg.numAttrs = 1;
  cudaLaunchKernelEx(&cfg, fused_kernel, p);
}
```

```cpp
#include <cuda_runtime.h>
#include <cuda_bf16.h>
#include <cuda.h>
#include <stdint.h>

typedef __nv_bfloat16 bf16;

#define PAUSE 200
#define WMDELAY 500
#define BDELAY 1500
#define NPRE0 3
#define NPRE1 1
#define ALIAS 1
#define PFW 8000
#define KH 3

__device__ __forceinline__ void wgmma_ss_n128(float (&d)[64], uint32_t da, uint32_t db, int scale_d) {
  asm volatile("{\n.reg .pred p;\n.reg .b64 da, db;\nsetp.ne.b32 p, %66, 0;\n"
    "mov.b64 da, {%64, 0x40000040};\nmov.b64 db, {%65, 0x40000040};\n"
    "wgmma.mma_async.sync.aligned.m64n128k16.f32.bf16.bf16 "
    "{%0, %1, %2, %3, %4, %5, %6, %7, %8, %9, %10, %11, %12, %13, %14, %15, "
    "%16, %17, %18, %19, %20, %21, %22, %23, %24, %25, %26, %27, %28, %29, %30, %31, "
    "%32, %33, %34, %35, %36, %37, %38, %39, %40, %41, %42, %43, %44, %45, %46, %47, "
    "%48, %49, %50, %51, %52, %53, %54, %55, %56, %57, %58, %59, %60, %61, %62, %63}, "
    "da, db, p, 1, 1, 0, 1;\n}\n"
    : "+f"(d[0]), "+f"(d[1]), "+f"(d[2]), "+f"(d[3]), "+f"(d[4]), "+f"(d[5]), "+f"(d[6]), "+f"(d[7]),
      "+f"(d[8]), "+f"(d[9]), "+f"(d[10]), "+f"(d[11]), "+f"(d[12]), "+f"(d[13]), "+f"(d[14]), "+f"(d[15]),
      "+f"(d[16]), "+f"(d[17]), "+f"(d[18]), "+f"(d[19]), "+f"(d[20]), "+f"(d[21]), "+f"(d[22]), "+f"(d[23]),
      "+f"(d[24]), "+f"(d[25]), "+f"(d[26]), "+f"(d[27]), "+f"(d[28]), "+f"(d[29]), "+f"(d[30]), "+f"(d[31]),
      "+f"(d[32]), "+f"(d[33]), "+f"(d[34]), "+f"(d[35]), "+f"(d[36]), "+f"(d[37]), "+f"(d[38]), "+f"(d[39]),
      "+f"(d[40]), "+f"(d[41]), "+f"(d[42]), "+f"(d[43]), "+f"(d[44]), "+f"(d[45]), "+f"(d[46]), "+f"(d[47]),
      "+f"(d[48]), "+f"(d[49]), "+f"(d[50]), "+f"(d[51]), "+f"(d[52]), "+f"(d[53]), "+f"(d[54]), "+f"(d[55]),
      "+f"(d[56]), "+f"(d[57]), "+f"(d[58]), "+f"(d[59]), "+f"(d[60]), "+f"(d[61]), "+f"(d[62]), "+f"(d[63])
    : "r"(da), "r"(db), "r"(scale_d));
}

__device__ __forceinline__ void wgmma_ss_n192(float (&d)[96], uint32_t da, uint32_t db, int scale_d) {
  asm volatile("{\n.reg .pred p;\n.reg .b64 da, db;\nsetp.ne.b32 p, %98, 0;\n"
    "mov.b64 da, {%96, 0x40000040};\nmov.b64 db, {%97, 0x40000040};\n"
    "wgmma.mma_async.sync.aligned.m64n192k16.f32.bf16.bf16 "
    "{%0, %1, %2, %3, %4, %5, %6, %7, %8, %9, %10, %11, %12, %13, %14, %15, "
    "%16, %17, %18, %19, %20, %21, %22, %23, %24, %25, %26, %27, %28, %29, %30, %31, "
    "%32, %33, %34, %35, %36, %37, %38, %39, %40, %41, %42, %43, %44, %45, %46, %47, "
    "%48, %49, %50, %51, %52, %53, %54, %55, %56, %57, %58, %59, %60, %61, %62, %63, "
    "%64, %65, %66, %67, %68, %69, %70, %71, %72, %73, %74, %75, %76, %77, %78, %79, "
    "%80, %81, %82, %83, %84, %85, %86, %87, %88, %89, %90, %91, %92, %93, %94, %95}, "
    "da, db, p, 1, 1, 0, 1;\n}\n"
    : "+f"(d[0]), "+f"(d[1]), "+f"(d[2]), "+f"(d[3]), "+f"(d[4]), "+f"(d[5]), "+f"(d[6]), "+f"(d[7]),
      "+f"(d[8]), "+f"(d[9]), "+f"(d[10]), "+f"(d[11]), "+f"(d[12]), "+f"(d[13]), "+f"(d[14]), "+f"(d[15]),
      "+f"(d[16]), "+f"(d[17]), "+f"(d[18]), "+f"(d[19]), "+f"(d[20]), "+f"(d[21]), "+f"(d[22]), "+f"(d[23]),
      "+f"(d[24]), "+f"(d[25]), "+f"(d[26]), "+f"(d[27]), "+f"(d[28]), "+f"(d[29]), "+f"(d[30]), "+f"(d[31]),
      "+f"(d[32]), "+f"(d[33]), "+f"(d[34]), "+f"(d[35]), "+f"(d[36]), "+f"(d[37]), "+f"(d[38]), "+f"(d[39]),
      "+f"(d[40]), "+f"(d[41]), "+f"(d[42]), "+f"(d[43]), "+f"(d[44]), "+f"(d[45]), "+f"(d[46]), "+f"(d[47]),
      "+f"(d[48]), "+f"(d[49]), "+f"(d[50]), "+f"(d[51]), "+f"(d[52]), "+f"(d[53]), "+f"(d[54]), "+f"(d[55]),
      "+f"(d[56]), "+f"(d[57]), "+f"(d[58]), "+f"(d[59]), "+f"(d[60]), "+f"(d[61]), "+f"(d[62]), "+f"(d[63]),
      "+f"(d[64]), "+f"(d[65]), "+f"(d[66]), "+f"(d[67]), "+f"(d[68]), "+f"(d[69]), "+f"(d[70]), "+f"(d[71]),
      "+f"(d[72]), "+f"(d[73]), "+f"(d[74]), "+f"(d[75]), "+f"(d[76]), "+f"(d[77]), "+f"(d[78]), "+f"(d[79]),
      "+f"(d[80]), "+f"(d[81]), "+f"(d[82]), "+f"(d[83]), "+f"(d[84]), "+f"(d[85]), "+f"(d[86]), "+f"(d[87]),
      "+f"(d[88]), "+f"(d[89]), "+f"(d[90]), "+f"(d[91]), "+f"(d[92]), "+f"(d[93]), "+f"(d[94]), "+f"(d[95])
    : "r"(da), "r"(db), "r"(scale_d));
}

__device__ __forceinline__ void wgmma_ss_n256(float (&d)[128], uint32_t da, uint32_t db, int scale_d) {
  asm volatile("{\n.reg .pred p;\n.reg .b64 da, db;\nsetp.ne.b32 p, %130, 0;\n"
    "mov.b64 da, {%128, 0x40000040};\nmov.b64 db, {%129, 0x40000040};\n"
    "wgmma.mma_async.sync.aligned.m64n256k16.f32.bf16.bf16 "
    "{%0, %1, %2, %3, %4, %5, %6, %7, %8, %9, %10, %11, %12, %13, %14, %15, "
    "%16, %17, %18, %19, %20, %21, %22, %23, %24, %25, %26, %27, %28, %29, %30, %31, "
    "%32, %33, %34, %35, %36, %37, %38, %39, %40, %41, %42, %43, %44, %45, %46, %47, "
    "%48, %49, %50, %51, %52, %53, %54, %55, %56, %57, %58, %59, %60, %61, %62, %63, "
    "%64, %65, %66, %67, %68, %69, %70, %71, %72, %73, %74, %75, %76, %77, %78, %79, "
    "%80, %81, %82, %83, %84, %85, %86, %87, %88, %89, %90, %91, %92, %93, %94, %95, "
    "%96, %97, %98, %99, %100, %101, %102, %103, %104, %105, %106, %107, %108, %109, %110, %111, "
    "%112, %113, %114, %115, %116, %117, %118, %119, %120, %121, %122, %123, %124, %125, %126, %127}, "
    "da, db, p, 1, 1, 0, 1;\n}\n"
    : "+f"(d[0]), "+f"(d[1]), "+f"(d[2]), "+f"(d[3]), "+f"(d[4]), "+f"(d[5]), "+f"(d[6]), "+f"(d[7]),
      "+f"(d[8]), "+f"(d[9]), "+f"(d[10]), "+f"(d[11]), "+f"(d[12]), "+f"(d[13]), "+f"(d[14]), "+f"(d[15]),
      "+f"(d[16]), "+f"(d[17]), "+f"(d[18]), "+f"(d[19]), "+f"(d[20]), "+f"(d[21]), "+f"(d[22]), "+f"(d[23]),
      "+f"(d[24]), "+f"(d[25]), "+f"(d[26]), "+f"(d[27]), "+f"(d[28]), "+f"(d[29]), "+f"(d[30]), "+f"(d[31]),
      "+f"(d[32]), "+f"(d[33]), "+f"(d[34]), "+f"(d[35]), "+f"(d[36]), "+f"(d[37]), "+f"(d[38]), "+f"(d[39]),
      "+f"(d[40]), "+f"(d[41]), "+f"(d[42]), "+f"(d[43]), "+f"(d[44]), "+f"(d[45]), "+f"(d[46]), "+f"(d[47]),
      "+f"(d[48]), "+f"(d[49]), "+f"(d[50]), "+f"(d[51]), "+f"(d[52]), "+f"(d[53]), "+f"(d[54]), "+f"(d[55]),
      "+f"(d[56]), "+f"(d[57]), "+f"(d[58]), "+f"(d[59]), "+f"(d[60]), "+f"(d[61]), "+f"(d[62]), "+f"(d[63]),
      "+f"(d[64]), "+f"(d[65]), "+f"(d[66]), "+f"(d[67]), "+f"(d[68]), "+f"(d[69]), "+f"(d[70]), "+f"(d[71]),
      "+f"(d[72]), "+f"(d[73]), "+f"(d[74]), "+f"(d[75]), "+f"(d[76]), "+f"(d[77]), "+f"(d[78]), "+f"(d[79]),
      "+f"(d[80]), "+f"(d[81]), "+f"(d[82]), "+f"(d[83]), "+f"(d[84]), "+f"(d[85]), "+f"(d[86]), "+f"(d[87]),
      "+f"(d[88]), "+f"(d[89]), "+f"(d[90]), "+f"(d[91]), "+f"(d[92]), "+f"(d[93]), "+f"(d[94]), "+f"(d[95]),
      "+f"(d[96]), "+f"(d[97]), "+f"(d[98]), "+f"(d[99]), "+f"(d[100]), "+f"(d[101]), "+f"(d[102]), "+f"(d[103]),
      "+f"(d[104]), "+f"(d[105]), "+f"(d[106]), "+f"(d[107]), "+f"(d[108]), "+f"(d[109]), "+f"(d[110]), "+f"(d[111]),
      "+f"(d[112]), "+f"(d[113]), "+f"(d[114]), "+f"(d[115]), "+f"(d[116]), "+f"(d[117]), "+f"(d[118]), "+f"(d[119]),
      "+f"(d[120]), "+f"(d[121]), "+f"(d[122]), "+f"(d[123]), "+f"(d[124]), "+f"(d[125]), "+f"(d[126]), "+f"(d[127])
    : "r"(da), "r"(db), "r"(scale_d));
}

namespace {

constexpr int SEQ = 2048, DM = 1024, FF = 3584;
constexpr int NCTA = 128;

constexpr uint32_t STG_OFF = 196608;
constexpr uint32_t MISC_OFF = STG_OFF + 32768;
constexpr uint32_t SMEM_BYTES = MISC_OFF + 3072;
constexpr uint32_t RED_OFF = 2 * 49152;
constexpr uint32_t MODB_OFF = MISC_OFF + 512;

enum { B_FQ = 0, B_EQ = 4, B_FW = 8, B_EW = 14, B_FG = 20, B_EG = 24, B_FD = 28, B_ED = 34,
       B_STGF = 40, B_MODB = 42, B_MODA = 45, B_RDY = 46, B_STGE = 58, B_COUNT = 60 };
enum { C_H = 0, C_O = 1, C_H2 = 3, C_ACT = 4, C_HA = 8, C_H2A = 9, C_A0 = 10, C_SP = 12 };

struct Params {
  uint4* modll;
  uint4* halo;
  uint2* stats2;
  unsigned* cnt;
  CUtensorMap h, o_ld, o_st, h2, act, out, wqkv, wqkv32, wo, wg, wu, wd, act_st, h2_st, wm;
};

__device__ __align__(1024) bf16 g_h[SEQ * DM];
__device__ __align__(1024) bf16 g_o[SEQ * DM];
__device__ __align__(1024) bf16 g_act[SEQ * FF];
__device__ __align__(1024) uint4 g_modll[3072 / 2];
__device__ __align__(1024) uint4 g_halo[16 * 8 * 2 * 2 * 8 * 32];
__device__ __align__(1024) uint2 g_stats[2 * SEQ * 8];
__device__ __align__(1024) unsigned g_cnt[16 * 32];
__device__ uint4 g_epoch;
#define TR(off)

__device__ __forceinline__ uint32_t smem_u32(const void* p) { return (uint32_t)__cvta_generic_to_shared(p); }
__device__ __forceinline__ void mbar_init(uint32_t bar, uint32_t count) {
  asm volatile("mbarrier.init.shared::cta.b64 [%0], %1;" ::"r"(bar), "r"(count));
}
__device__ __forceinline__ void mbar_arrive(uint32_t bar) {
  asm volatile("mbarrier.arrive.shared::cta.b64 _, [%0];" ::"r"(bar) : "memory");
}
__device__ __forceinline__ void mbar_arrive_cluster(uint32_t cluster_addr) {
  asm volatile("mbarrier.arrive.shared::cluster.b64 _, [%0];" ::"r"(cluster_addr) : "memory");
}
__device__ __forceinline__ uint32_t mapa(uint32_t addr, uint32_t cta) {
  uint32_t r;
  asm volatile("mapa.shared::cluster.u32 %0, %1, %2;" : "=r"(r) : "r"(addr), "r"(cta));
  return r;
}
__device__ __forceinline__ void jitter() {}
__device__ __forceinline__ void mbar_wait(uint32_t bar, uint32_t parity) {
  jitter();
  asm volatile(
      "{\n.reg .pred p;\n"
      "WAIT_%=:\n"
      "mbarrier.try_wait.parity.shared::cta.b64 p, [%0], %1;\n"
      "@!p bra WAIT_%=;\n}\n" ::"r"(bar), "r"(parity) : "memory");
}
__device__ __forceinline__ void mbar_wait_watchdog(uint32_t bar, uint32_t parity) {
  jitter();
  asm volatile(
      "{\n.reg .pred p;\n.reg .u64 t0, t1;\nmov.u64 t0, %%globaltimer;\n"
      "WAIT_%=:\n"
      "mbarrier.try_wait.parity.shared::cta.b64 p, [%0], %1;\n"
      "@p bra DONE_%=;\n"
      "mov.u64 t1, %%globaltimer;\n"
      "sub.u64 t1, t1, t0;\n"
      "setp.lt.u64 p, t1, 2000000000;\n"
      "@p bra WAIT_%=;\n"
      "trap;\n"
      "DONE_%=:\n}\n" ::"r"(bar), "r"(parity) : "memory");
}
__device__ __forceinline__ void cnt_wait(const unsigned* p, unsigned target) {
  asm volatile(
      "{\n.reg .pred p;\n.reg .u32 v;\n.reg .s32 d;\n"
      "WAIT_%=:\n"
      "ld.relaxed.gpu.global.u32 v, [%0];\n"
      "sub.s32 d, v, %1;\n"
      "setp.lt.s32 p, d, 0;\n"
      "@p bra WAIT_%=;\n"
      "fence.proxy.async.global;\n"
      "}\n" ::"l"(p), "r"(target) : "memory");
}
__device__ __forceinline__ void cnt_wait_lazy(const unsigned* p, unsigned target) {
  asm volatile(
      "{\n.reg .pred p;\n.reg .u32 v;\n.reg .s32 d;\n"
      "WAIT_%=:\n"
      "nanosleep.u32 400;\n"
      "ld.relaxed.gpu.global.u32 v, [%0];\n"
      "sub.s32 d, v, %1;\n"
      "setp.lt.s32 p, d, 0;\n"
      "@p bra WAIT_%=;\n"
      "fence.proxy.async.global;\n"
      "}\n" ::"l"(p), "r"(target) : "memory");
}
__device__ __forceinline__ void cnt_signal(unsigned* p) {
  jitter();
  asm volatile("{\n.reg .pred p;\nelect.sync _|p, 0xffffffff;\n@p red.relaxed.gpu.global.add.u32 [%0], 1;\n}\n" ::"l"(p) : "memory");
}
__device__ __forceinline__ void ll_store(uint4* p, uint32_t a, uint32_t b, uint32_t tag) {
  asm volatile("st.relaxed.gpu.global.v2.b64 [%0], {%1, %2};" ::"l"(p), "l"((uint64_t)a | ((uint64_t)tag << 32)),
               "l"((uint64_t)b | ((uint64_t)tag << 32)) : "memory");
}
__device__ __forceinline__ uint4 ll_peek(const uint4* p) {
  uint4 v;
  asm volatile("ld.relaxed.gpu.global.v4.u32 {%0, %1, %2, %3}, [%4];" : "=r"(v.x), "=r"(v.y), "=r"(v.z), "=r"(v.w) : "l"(p) : "memory");
  return v;
}
template <int N, int SLEEP = 0, class F>
__device__ __forceinline__ void ll_poll(F addr, uint32_t tag, uint32_t (&out)[2 * N]) {
  for (;;) {
    uint4 v[N];
#pragma unroll
    for (int i = 0; i < N; i++) v[i] = ll_peek(addr(i));
    uint32_t bad = 0;
#pragma unroll
    for (int i = 0; i < N; i++) {
      bad |= (v[i].y ^ tag) | (v[i].w ^ tag);
      out[2 * i] = v[i].x;
      out[2 * i + 1] = v[i].z;
    }
    if (__all_sync(~0u, bad == 0)) break;
    if (SLEEP) __nanosleep(SLEEP);
  }
}
constexpr uint64_t POLICY_EVICT_FIRST = 0x12F0000000000000ull;
__device__ __forceinline__ void expect_tx_elect(uint32_t bar, uint32_t bytes) {
  asm volatile("{\n.reg .pred p;\nelect.sync _|p, 0xffffffff;\n@p mbarrier.arrive.expect_tx.shared::cta.b64 _, [%0], %1;\n}\n" ::"r"(bar), "r"(bytes) : "memory");
}
__device__ __forceinline__ void arrive_elect(uint32_t bar) {
  asm volatile("{\n.reg .pred p;\nelect.sync _|p, 0xffffffff;\n@p mbarrier.arrive.shared::cta.b64 _, [%0];\n}\n" ::"r"(bar) : "memory");
}
__device__ __forceinline__ void tma_load(uint32_t dst, const CUtensorMap* m, uint32_t bar, int c0, int c1) {
  asm volatile("{\n.reg .pred p;\nelect.sync _|p, 0xffffffff;\n"
               "@p cp.async.bulk.tensor.2d.shared::cluster.global.mbarrier::complete_tx::bytes [%0], [%1, {%3, %4}], [%2];\n}\n"
               ::"r"(dst), "l"(m), "r"(bar), "r"(c0), "r"(c1) : "memory");
}
__device__ __forceinline__ void tma_load_mc(uint32_t dst, const CUtensorMap* m, uint32_t bar, int c0, int c1) {
  asm volatile("{\n.reg .pred p;\nelect.sync _|p, 0xffffffff;\n"
               "@p cp.async.bulk.tensor.2d.shared::cluster.global.mbarrier::complete_tx::bytes.multicast::cluster.L2::cache_hint [%0], [%1, {%3, %4}], [%2], %5, %6;\n}\n"
               ::"r"(dst), "l"(m), "r"(bar), "r"(c0), "r"(c1), "h"((uint16_t)3), "l"(POLICY_EVICT_FIRST) : "memory");
}
__device__ __forceinline__ void tma_load_ef(uint32_t dst, const CUtensorMap* m, uint32_t bar, int c0, int c1) {
  asm volatile("{\n.reg .pred p;\nelect.sync _|p, 0xffffffff;\n"
               "@p cp.async.bulk.tensor.2d.shared::cluster.global.mbarrier::complete_tx::bytes.L2::cache_hint [%0], [%1, {%3, %4}], [%2], %5;\n}\n"
               ::"r"(dst), "l"(m), "r"(bar), "r"(c0), "r"(c1), "l"(POLICY_EVICT_FIRST) : "memory");
}
__device__ __forceinline__ void tma_store2(const CUtensorMap* m, uint32_t src, int c0, int c1) {
  asm volatile("{\n.reg .pred p;\nelect.sync _|p, 0xffffffff;\n"
               "@p cp.async.bulk.tensor.2d.global.shared::cta.bulk_group [%0, {%2, %3}], [%1];\n}\n"
               ::"l"(m), "r"(src), "r"(c0), "r"(c1) : "memory");
}
__device__ __forceinline__ void tma_store3(const CUtensorMap* m, uint32_t src, int c0, int c1, int c2) {
  asm volatile("{\n.reg .pred p;\nelect.sync _|p, 0xffffffff;\n"
               "@p cp.async.bulk.tensor.3d.global.shared::cta.bulk_group [%0, {%2, %3, %4}], [%1];\n}\n"
               ::"l"(m), "r"(src), "r"(c0), "r"(c1), "r"(c2) : "memory");
}
__device__ __forceinline__ void tma_add3(const CUtensorMap* m, uint32_t src, int c0, int c1, int c2) {
  asm volatile("{\n.reg .pred p;\nelect.sync _|p, 0xffffffff;\n"
               "@p cp.reduce.async.bulk.tensor.3d.global.shared::cta.add.bulk_group [%0, {%2, %3, %4}], [%1];\n}\n"
               ::"l"(m), "r"(src), "r"(c0), "r"(c1), "r"(c2) : "memory");
}
__device__ __forceinline__ void store_pause(bool sleep) {
  asm volatile("cp.async.bulk.commit_group;" ::: "memory");
  asm volatile("cp.async.bulk.wait_group.read 0;" ::: "memory");
  if (sleep) __nanosleep(PAUSE);
}
__device__ __forceinline__ void l2_prefetch_tile(const CUtensorMap* m, int c0, int c1) {
  asm volatile("{\n.reg .pred p;\nelect.sync _|p, 0xffffffff;\n@p cp.async.bulk.prefetch.tensor.2d.L2.global [%0, {%1, %2}];\n}\n"
               ::"l"(m), "r"(c0), "r"(c1) : "memory");
}
__device__ __forceinline__ void prefetch_map(const CUtensorMap* m) {
  asm volatile("prefetch.tensormap [%0];" ::"l"(m) : "memory");
}
__device__ __forceinline__ void wg_fence() { asm volatile("wgmma.fence.sync.aligned;" ::: "memory"); }
__device__ __forceinline__ void wg_commit() { asm volatile("wgmma.commit_group.sync.aligned;" ::: "memory"); }
template <int N>
__device__ __forceinline__ void wg_wait() { asm volatile("wgmma.wait_group.sync.aligned %0;" ::"n"(N) : "memory"); }
__device__ __forceinline__ void bar_sync(int id, int n) { asm volatile("bar.sync %0, %1;" ::"r"(id), "r"(n) : "memory"); }
__device__ __forceinline__ void wg_bar(int cw) {
  asm volatile("{\n.reg .pred p;\nsetp.ne.s32 p, %0, 0;\n@p bar.sync 3, 128;\n@!p bar.sync 2, 128;\n}\n" ::"r"(cw) : "memory");
}
__device__ __forceinline__ void skew_pre(int cw) { if (cw == 1) bar_sync(5, 256); }
__device__ __forceinline__ void skew_post(int cw) { if (cw == 0) asm volatile("bar.arrive 5, 256;" ::: "memory"); }
__device__ __forceinline__ void cluster_arrive_relaxed() { asm volatile("barrier.cluster.arrive.relaxed.aligned;" ::: "memory"); }
__device__ __forceinline__ void cluster_wait() { asm volatile("barrier.cluster.wait.acquire.aligned;" ::: "memory"); }
__device__ __forceinline__ uint32_t load_epoch(const unsigned* p) {
  uint32_t e;
  asm volatile("ld.relaxed.gpu.global.u32 %0, [%1];" : "=r"(e) : "l"(p) : "memory");
  return e;
}
__device__ __forceinline__ uint32_t pack2(float lo, float hi) {
  uint32_t r;
  asm("cvt.rn.bf16x2.f32 %0, %1, %2;" : "=r"(r) : "f"(hi), "f"(lo));
  return r;
}
__device__ __forceinline__ float bf_lo(uint32_t v) { return __uint_as_float(v << 16); }
__device__ __forceinline__ float bf_hi(uint32_t v) { return __uint_as_float(v & 0xffff0000u); }
__device__ __forceinline__ uint32_t fma_bf2(uint32_t a, uint32_t b, uint32_t c) {
  uint32_t d;
  asm("fma.rn.bf16x2 %0, %1, %2, %3;" : "=r"(d) : "r"(a), "r"(b), "r"(c));
  return d;
}
__device__ __forceinline__ float bf_round(float v) { return __bfloat162float(__float2bfloat16_rn(v)); }
__device__ __forceinline__ float silu_f(float v) { return __fdividef(v, 1.0f + __expf(-v)); }
__device__ __forceinline__ uint4 ldg_nc(const void* p) {
  uint4 v;
  asm volatile("ld.global.nc.L1::no_allocate.v4.u32 {%0, %1, %2, %3}, [%4];" : "=r"(v.x), "=r"(v.y), "=r"(v.z), "=r"(v.w) : "l"(p));
  return v;
}
__device__ __forceinline__ void stmatrix4(uint32_t addr, uint32_t a, uint32_t b, uint32_t c, uint32_t d) {
  asm volatile("stmatrix.sync.aligned.m8n8.x4.shared.b16 [%0], {%1, %2, %3, %4};" ::"r"(addr), "r"(a), "r"(b), "r"(c), "r"(d) : "memory");
}
__device__ __forceinline__ void stmatrix2(uint32_t addr, uint32_t a, uint32_t b) {
  asm volatile("stmatrix.sync.aligned.m8n8.x2.shared.b16 [%0], {%1, %2};" ::"r"(addr), "r"(a), "r"(b) : "memory");
}
__device__ __forceinline__ void stmatrix1(uint32_t addr, uint32_t a) {
  asm volatile("stmatrix.sync.aligned.m8n8.x1.shared.b16 [%0], {%1};" ::"r"(addr), "r"(a) : "memory");
}
__device__ __forceinline__ uint32_t movmatrix(uint32_t a) {
  uint32_t d;
  asm("movmatrix.sync.aligned.m8n8.trans.b16 %0, %1;" : "=r"(d) : "r"(a));
  return d;
}
__device__ __forceinline__ void mma16816(float (&d)[4], uint32_t a0, uint32_t a1, uint32_t a2, uint32_t a3, uint32_t b0, uint32_t b1) {
  asm("mma.sync.aligned.m16n8k16.row.col.f32.bf16.bf16.f32 {%0, %1, %2, %3}, {%4, %5, %6, %7}, {%8, %9}, {%0, %1, %2, %3};"
               : "+f"(d[0]), "+f"(d[1]), "+f"(d[2]), "+f"(d[3]) : "r"(a0), "r"(a1), "r"(a2), "r"(a3), "r"(b0), "r"(b1));
}
__device__ __forceinline__ void mma1688(float (&d)[4], uint32_t a0, uint32_t a1, uint32_t b0) {
  asm("mma.sync.aligned.m16n8k8.row.col.f32.bf16.bf16.f32 {%0, %1, %2, %3}, {%4, %5}, {%6}, {%0, %1, %2, %3};"
               : "+f"(d[0]), "+f"(d[1]), "+f"(d[2]), "+f"(d[3]) : "r"(a0), "r"(a1), "r"(b0));
}
__device__ __forceinline__ void ldmatrix4t(uint32_t (&b)[4], uint32_t addr) {
  asm volatile("ldmatrix.sync.aligned.m8n8.x4.trans.shared.b16 {%0, %1, %2, %3}, [%4];" : "=r"(b[0]), "=r"(b[1]), "=r"(b[2]), "=r"(b[3]) : "r"(addr) : "memory");
}
__device__ __forceinline__ void ldmatrix4(uint32_t& a, uint32_t& b, uint32_t& c, uint32_t& d, uint32_t addr) {
  asm volatile("ldmatrix.sync.aligned.m8n8.x4.shared.b16 {%0, %1, %2, %3}, [%4];" : "=r"(a), "=r"(b), "=r"(c), "=r"(d) : "r"(addr) : "memory");
}
__device__ __forceinline__ void cp_async16(uint32_t dst, const void* src) {
  asm volatile("cp.async.cg.shared.global.L2::cache_hint [%0], [%1], 16, %2;" ::"r"(dst), "l"(src), "l"(POLICY_EVICT_FIRST) : "memory");
}
__device__ __forceinline__ uint32_t lds32(uint32_t addr) {
  uint32_t v;
  asm volatile("ld.shared.u32 %0, [%1];" : "=r"(v) : "r"(addr) : "memory");
  return v;
}
__device__ __forceinline__ void sts64f(uint32_t addr, float a, float b) {
  asm volatile("st.shared.v2.f32 [%0], {%1, %2};" ::"r"(addr), "f"(a), "f"(b) : "memory");
}
constexpr float QK_SCALE = 0.17677669529663687f;
__device__ __forceinline__ float softmax8(float& p0, float& p1) {
  float m = fmaxf(p0, p1);
  m = fmaxf(m, __shfl_xor_sync(~0u, m, 1));
  m = fmaxf(m, __shfl_xor_sync(~0u, m, 2));
  asm("ex2.approx.ftz.f32 %0, %1;" : "=f"(p0) : "f"((p0 - m) * 1.4426950408889634f));
  asm("ex2.approx.ftz.f32 %0, %1;" : "=f"(p1) : "f"((p1 - m) * 1.4426950408889634f));
  float s = p0 + p1;
  s += __shfl_xor_sync(~0u, s, 1);
  s += __shfl_xor_sync(~0u, s, 2);
  float r;
  asm("rcp.approx.ftz.f32 %0, %1;" : "=f"(r) : "f"(s));
  return r;
}
__device__ __forceinline__ void sts128(uint32_t addr, uint32_t a, uint32_t b, uint32_t c, uint32_t d) {
  asm volatile("st.shared.v4.u32 [%0], {%1, %2, %3, %4};" ::"r"(addr), "r"(a), "r"(b), "r"(c), "r"(d) : "memory");
}
__device__ __forceinline__ uint4 lds128(uint32_t addr) {
  uint4 v;
  asm volatile("ld.shared.v4.u32 {%0, %1, %2, %3}, [%4];" : "=r"(v.x), "=r"(v.y), "=r"(v.z), "=r"(v.w) : "r"(addr) : "memory");
  return v;
}
__device__ __forceinline__ float2 lds64f(uint32_t addr) {
  float2 v;
  asm volatile("ld.shared.v2.f32 {%0, %1}, [%2];" : "=f"(v.x), "=f"(v.y) : "r"(addr) : "memory");
  return v;
}
#define PROF_AT(cond, slot) do {} while (0)

constexpr uint32_t SMEM_BASE = 1024;
constexpr uint32_t DESC_A = (1u << 16) | (SMEM_BASE >> 4);
constexpr uint32_t DESC_B = ((8192u >> 4) << 16) | (SMEM_BASE >> 4);

template <int BN> struct Wg;
template <> struct Wg<128> { static __device__ __forceinline__ void mma(float (&d)[64], uint32_t a, uint32_t b, int s) { wgmma_ss_n128(d, a, b, s); } };
template <> struct Wg<192> { static __device__ __forceinline__ void mma(float (&d)[96], uint32_t a, uint32_t b, int s) { wgmma_ss_n192(d, a, b, s); } };
template <> struct Wg<256> { static __device__ __forceinline__ void mma(float (&d)[128], uint32_t a, uint32_t b, int s) { wgmma_ss_n256(d, a, b, s); } };

struct Ring {
  uint32_t full0, rel0;
  int s;
  uint32_t ph;
  uint32_t off;
  bool releaser;
};

template <int N>
__device__ __forceinline__ void fence_regs(float (&a)[N]) {
#pragma unroll
  for (int i = 0; i < N; i++) asm volatile("" : "+f"(a[i])::"memory");
}

template <int BN, int NST, uint32_t STAGE>
__device__ __forceinline__ void kblock(float (&acc)[BN / 2], Ring& g, uint32_t a_addr, bool zero, uint32_t& prev, uint32_t b_rel = 16384) {
  mbar_wait(g.full0 + 8 * g.s, g.ph);
  const uint32_t da = DESC_A + (a_addr >> 4);
  const uint32_t db = DESC_B + ((g.off + b_rel) >> 4);
  wg_fence();
#pragma unroll
  for (int k = 0; k < 4; k++) Wg<BN>::mma(acc, da + k * 2, db + k * 128, !(zero && k == 0));
  wg_commit();
  wg_wait<1>();
  jitter();
  if (prev != 0) mbar_arrive_cluster(prev);
  prev = g.releaser ? g.rel0 + 8 * g.s : 0u;
  if (++g.s == NST) { g.s = 0; g.ph ^= 1; }
  g.off += STAGE;
  if (g.off == NST * STAGE) g.off = 0;
}
template <int N>
__device__ __forceinline__ void tile_end(float (&acc)[N], uint32_t& prev) {
  wg_wait<0>();
  if (prev != 0) mbar_arrive_cluster(prev);
  prev = 0;
  fence_regs(acc);
}

__device__ __forceinline__ int other_kb(int q, int j) {
  const int ch = q >= 7, jj = q - 7 * ch;
  return 2 * (jj < j ? jj : jj + 1) + ch;
}
__device__ __forceinline__ int qkv_kb(int it, int j) {
  return it < 4 ? 2 * j + (it & 1) : other_kb(it < 18 ? it - 4 : it - 18, j);
}
__device__ __forceinline__ int wo_k(int it, int j) {
  return it < 8 ? it * 128 : (it == 8 ? j : (it - 9 < j ? it - 9 : it - 8)) * 128 + 64;
}
__device__ __forceinline__ int down_k(int d) {
  const int u = d + KH;
  if (u < 8) return u * 448 + 384;
  if (u < 40) return (((u - 8) & 15) >> 1) * 448 + ((u - 8) >> 4) * 128 + (u & 1) * 64;
  return (u & 7) * 448 + 256 + (u >= 48 ? 64 : 0);
}
__device__ __forceinline__ void wait_q_free(uint32_t empty, int i) {
  mbar_wait(empty + 8 * ((i * 2) / 3), 1);
  mbar_wait(empty + 8 * ((i * 2 + 1) / 3), 1);
}
__device__ __forceinline__ void wait_w_free(uint32_t empty, int i) {
  const int t = (i + 3) & 3, w0 = (t * 3) / 2, w1 = (t * 3 + 2) / 2;
  mbar_wait(empty + 8 * w0, w0 < 4);
  mbar_wait(empty + 8 * w1, w1 < 4);
}
__device__ __forceinline__ void wait_g_free(uint32_t empty, int i) {
  const int s = i < 4 ? i + 2 : i - 4, b0 = ((s * 2) / 3 + 1) & 3, b1 = ((s * 2 + 1) / 3 + 1) & 3;
  mbar_wait(empty + 8 * b0, b0 < 2);
  mbar_wait(empty + 8 * b1, b1 < 2);
}

__device__ __forceinline__ void chan(float& m, float& q, float m2, float q2, float n) {
  const float d = m2 - m;
  m = 0.5f * (m + m2);
  q = q + q2 + d * d * (0.5f * n);
}

__device__ __forceinline__ uint32_t tag16(uint32_t tag) { return tag % 65535u + 1u; }
__device__ __forceinline__ void stat_store(uint2* slot, float m, float q, uint32_t t16) {
  const uint32_t a = ((__float_as_uint(m) + 0x80u) & 0xffffff00u) | (t16 & 0xffu), b = ((__float_as_uint(q) + 0x80u) & 0xffffff00u) | (t16 >> 8);
  asm volatile("st.relaxed.gpu.global.b64 [%0], %1;" ::"l"(slot), "l"((uint64_t)a | ((uint64_t)b << 32)) : "memory");
}
__device__ __forceinline__ void stat_gather(const uint2* rows, uint32_t t16, int lane, float (&rs)[2], float (&nb)[2]) {
  const uint4* sp = (const uint4*)(rows + (lane >> 3) * 128) + (lane & 7);
  const uint32_t want = (t16 & 0xffu) | ((t16 >> 8) << 8);
  uint4 a, b;
  for (;;) {
    a = ll_peek(sp);
    b = ll_peek(sp + 256);
    const uint32_t bad = (__byte_perm(a.x, a.y, 0x40) ^ want) | (__byte_perm(a.z, a.w, 0x40) ^ want) | (__byte_perm(b.x, b.y, 0x40) ^ want) |
                         (__byte_perm(b.z, b.w, 0x40) ^ want);
    if (__all_sync(~0u, (bad & 0xffffu) == 0)) break;
  }
  float m0 = __uint_as_float(a.x & 0xffffff00u), q0 = __uint_as_float(a.y & 0xffffff00u);
  float m1 = __uint_as_float(a.z & 0xffffff00u), q1 = __uint_as_float(a.w & 0xffffff00u);
  chan(m0, q0, __uint_as_float(b.x & 0xffffff00u), __uint_as_float(b.y & 0xffffff00u), 128.f);
  chan(m1, q1, __uint_as_float(b.z & 0xffffff00u), __uint_as_float(b.w & 0xffffff00u), 128.f);
  const bool hi = lane & 8;
  float m = hi ? m1 : m0, q = hi ? q1 : q0;
  chan(m, q, __shfl_xor_sync(~0u, hi ? m0 : m1, 8), __shfl_xor_sync(~0u, hi ? q0 : q1, 8), 256.f);
  chan(m, q, __shfl_xor_sync(~0u, m, 16), __shfl_xor_sync(~0u, q, 16), 512.f);
  const float rstd = rsqrtf(q * (1.0f / DM) + 1e-5f), nmr = -m * rstd;
  const int r = lane >> 2, src = (r >> 1) + (r & 1) * 8;
  rs[0] = __shfl_sync(~0u, rstd, src); nb[0] = __shfl_sync(~0u, nmr, src);
  rs[1] = __shfl_sync(~0u, rstd, src + 4); nb[1] = __shfl_sync(~0u, nmr, src + 4);
}

__device__ __forceinline__ void publish_stats(const uint32_t (&xl)[16], const uint32_t (&xh)[16], uint2* slot, int lane, uint32_t t16) {
  float ds[4] = {0.f, 0.f, 0.f, 0.f}, dl[4] = {0.f, 0.f, 0.f, 0.f}, dh[4] = {0.f, 0.f, 0.f, 0.f};
#pragma unroll
  for (int q = 0; q < 8; q++) {
    mma16816(ds, xl[2 * q], xh[2 * q], xl[2 * q + 1], xh[2 * q + 1], 0x3f803f80u, 0x3f803f80u);
    mma16816(dl, xl[2 * q], xh[2 * q], xl[2 * q + 1], xh[2 * q + 1], xl[2 * q], xl[2 * q + 1]);
    mma16816(dh, xl[2 * q], xh[2 * q], xl[2 * q + 1], xh[2 * q + 1], xh[2 * q], xh[2 * q + 1]);
  }
  const int r = lane >> 2;
  if ((lane & 3) == (r >> 1)) {
    const float ml = ds[0] * (1.0f / 128), mh = ds[2] * (1.0f / 128);
    const float ql = fmaxf(((r & 1) ? dl[1] : dl[0]) - ds[0] * ml, 0.f), qh = fmaxf(((r & 1) ? dh[3] : dh[2]) - ds[2] * mh, 0.f);
    stat_store(slot + r, ml, ql, t16);
    stat_store(slot + r + 8, mh, qh, t16);
  }
  __syncwarp();
}

__device__ __forceinline__ void stage_slab(uint32_t chunk, int warp, int lane, const uint32_t (&lo)[8], const uint32_t (&hi)[8]) {
  const int row = warp * 16 + (lane & 7) + ((lane >> 3) & 1) * 8;
  const uint32_t rbase = chunk + row * 128;
#pragma unroll
  for (int q = 0; q < 4; q++) {
    const int grp = 2 * q + (lane >> 4);
    stmatrix4(rbase + ((grp ^ (row & 7)) << 4), lo[2 * q], hi[2 * q], lo[2 * q + 1], hi[2 * q + 1]);
  }
}
__device__ __forceinline__ float silu_mul(float g, float u) {
  float e, r;
  asm("ex2.approx.ftz.f32 %0, %1;" : "=f"(e) : "f"(g * -1.4426950408889634f));
  asm("rcp.approx.ftz.f32 %0, %1;" : "=f"(r) : "f"(1.0f + e));
  return g * r * u;
}
__device__ __forceinline__ uint32_t swiglu2(uint32_t g2, uint32_t u2) {
  asm volatile("" : "+r"(g2));
  return pack2(silu_mul(bf_lo(g2), bf_lo(u2)), silu_mul(bf_hi(g2), bf_hi(u2)));
}
__device__ __forceinline__ void stage_done(uint32_t bar, int lane) {
  asm volatile("fence.proxy.async.shared::cta;" ::: "memory");
  __syncwarp();
  if (lane == 0) mbar_arrive(bar);
}

__device__ __forceinline__ int fresh_tid() {
  int t;
  asm volatile("mov.u32 %0, %%tid.x;" : "=r"(t));
  return t;
}
#define RING_IDS()                                                                                           \
  const int tid = fresh_tid() - 128;                                                                         \
  const int cw = __shfl_sync(~0u, tid >> 7, 0), warp = __shfl_sync(~0u, (tid >> 5) & 3, 0);                  \
  const bool releaser = (tid & 31) < 2;                                                                      \
  const uint32_t rbars = mapa(bars, tid & 1);                                                                \
  const uint32_t a_base = cw * 8192
#define LANE_IDS()                                                                                           \
  const int lane = fresh_tid() & 31, r = lane >> 2, c = lane & 3;                                            \
  const int srow = warp * 16 + (lane & 7) + ((lane >> 3) & 1) * 8;                                           \
  const uint32_t slab = stg + cw * 8192 + srow * 128, sw0 = (lane >> 4) ^ (srow & 7);                        \
  (void)r; (void)c; (void)slab; (void)sw0

template <int NPRE, bool EAGER, class Step>
__device__ __forceinline__ void attention(float (&acc)[96], const Params& p, int rho, int rb, int cta, int cw, int warp, uint32_t tag,
                                          uint32_t stg, uint32_t bars, uint32_t& prev, Step step) {
  uint32_t ql[8], qh[8], k0[8], k1[8], v0[8], v1[8], hp[16];
  if (EAGER) {
    tile_end(acc, prev);
  } else {
    step();
    fence_regs(acc);
  }
#pragma unroll
  for (int t = 0; t < 8; t++) {
    k0[t] = pack2(acc[4 * (8 + t)], acc[4 * (8 + t) + 1]);
    k1[t] = pack2(acc[4 * (8 + t) + 2], acc[4 * (8 + t) + 3]);
    v0[t] = pack2(acc[4 * (16 + t)], acc[4 * (16 + t) + 1]);
    v1[t] = pack2(acc[4 * (16 + t) + 2], acc[4 * (16 + t) + 3]);
    asm volatile("" : "+r"(k0[t]), "+r"(k1[t]), "+r"(v0[t]), "+r"(v1[t]));
  }
  const int lane = fresh_tid() & 31, r = lane >> 2, c = lane & 3;
#pragma unroll
  for (int t = 0; t < 8; t++) v1[t] = movmatrix(v1[t]);
  mbar_wait(bars + 8 * B_STGE, rho);
  mbar_wait(bars + 8 * (B_STGE + 1), 0);
  const uint32_t xch = stg + 16384 + (cw * 4 + warp) * 2048 + lane * 16;
  if (warp < 3) {
    sts128(xch, k1[0], k1[1], k1[2], k1[3]);
    sts128(xch + 512, k1[4], k1[5], k1[6], k1[7]);
    sts128(xch + 1024, v1[0], v1[1], v1[2], v1[3]);
    sts128(xch + 1536, v1[4], v1[5], v1[6], v1[7]);
  } else if (rb < 15) {
    uint4* dst = p.halo + ((cta * 2 + rho) * 2 + cw) * 256 + lane;
#pragma unroll
    for (int t = 0; t < 4; t++) {
      ll_store(dst + t * 32, k1[2 * t], k1[2 * t + 1], tag);
      ll_store(dst + (4 + t) * 32, v1[2 * t], v1[2 * t + 1], tag);
    }
  }
#pragma unroll
  for (int t = 0; t < 8; t++) {
    v0[t] = movmatrix(v0[t]);
    ql[t] = pack2(acc[4 * t], acc[4 * t + 1]);
    qh[t] = pack2(acc[4 * t + 2], acc[4 * t + 3]);
    asm volatile("" : "+r"(v0[t]), "+r"(ql[t]), "+r"(qh[t]));
  }
#pragma unroll 1
  for (int i = 0; i < NPRE; i++) step();
  const uint4* src = p.halo + (((cta - 8) * 2 + rho) * 2 + cw) * 256 + lane;
  uint4 early[8] = {};
  if (warp == 0 && rb > 0) {
#pragma unroll
    for (int i = 0; i < 8; i++) early[i] = ll_peek(src + i * 32);
  }
  step();
  wg_bar(cw);
  if (warp > 0) {
#pragma unroll
    for (int t = 0; t < 4; t++) {
      const uint4 a = lds128(xch - 2048 + t * 512);
      hp[4 * t] = a.x; hp[4 * t + 1] = a.y; hp[4 * t + 2] = a.z; hp[4 * t + 3] = a.w;
    }
  } else if (rb > 0) {
    uint32_t bad = 0;
#pragma unroll
    for (int i = 0; i < 8; i++) {
      bad |= (early[i].y ^ tag) | (early[i].w ^ tag);
      hp[2 * i] = early[i].x;
      hp[2 * i + 1] = early[i].z;
    }
    if (!__all_sync(~0u, bad == 0)) ll_poll<8>([&](int i) { return src + i * 32; }, tag, hp);
  } else {
#pragma unroll
    for (int t = 0; t < 16; t++) hp[t] = 0;
  }
  wg_wait<0>();
  if (prev != 0) mbar_arrive_cluster(prev);
  prev = 0;
#pragma unroll
  for (int t = 0; t < 8; t++) asm volatile("" : "+r"(ql[t])::"memory");
  const bool up0 = 2 * c > r, up1 = 2 * c + 1 > r;
  const bool first = (rb == 0) && (warp == 0);
  uint32_t a0[2], a2[2], a3[2], a5[2];
  float il[2], ih[2];
#pragma unroll
  for (int h = 0; h < 2; h++) {
    float sp[4] = {0.f, 0.f, 0.f, 0.f}, s0[4] = {0.f, 0.f, 0.f, 0.f}, s1[4] = {0.f, 0.f, 0.f, 0.f};
#pragma unroll
    for (int ks = 0; ks < 2; ks++) {
      const int t = 4 * h + 2 * ks;
      mma16816(sp, ql[t], qh[t], ql[t + 1], qh[t + 1], hp[t], hp[t + 1]);
      mma16816(s0, ql[t], qh[t], ql[t + 1], qh[t + 1], k0[t], k0[t + 1]);
      mma16816(s1, ql[t], qh[t], ql[t + 1], qh[t + 1], k1[t], k1[t + 1]);
    }
    float p0 = (up0 ? sp[0] : s0[0]) * QK_SCALE, p1 = (up1 ? sp[1] : s0[1]) * QK_SCALE;
    float p2 = (up0 ? s0[2] : s1[2]) * QK_SCALE, p3 = (up1 ? s0[3] : s1[3]) * QK_SCALE;
    if (first && up0) p0 = -1000000000.0f;
    if (first && up1) p1 = -1000000000.0f;
    il[h] = softmax8(p0, p1);
    ih[h] = softmax8(p2, p3);
    a0[h] = pack2(up0 ? p0 : 0.f, up1 ? p1 : 0.f);
    a2[h] = pack2(up0 ? 0.f : p0, up1 ? 0.f : p1);
    a3[h] = pack2(up0 ? p2 : 0.f, up1 ? p3 : 0.f);
    a5[h] = pack2(up0 ? 0.f : p2, up1 ? 0.f : p3);
  }
  float o[8][4];
#pragma unroll
  for (int t = 0; t < 8; t++) {
#pragma unroll
    for (int q = 0; q < 4; q++) o[t][q] = 0.f;
    mma1688(o[t], 0u, a5[t >> 2], v1[t]);
    mma16816(o[t], a0[t >> 2], 0u, a2[t >> 2], a3[t >> 2], hp[8 + t], v0[t]);
  }
#pragma unroll
  for (int t = 0; t < 8; t++) fence_regs(o[t]);
  if (!EAGER) step();
  uint32_t ol[8], oh[8];
#pragma unroll
  for (int t = 0; t < 8; t++) {
    ol[t] = pack2(o[t][0] * il[t >> 2], o[t][1] * il[t >> 2]);
    oh[t] = pack2(o[t][2] * ih[t >> 2], o[t][3] * ih[t >> 2]);
  }
  if (!EAGER) step();
  stage_slab(stg + cw * 8192, warp, lane, ol, oh);
  stage_done(bars + 8 * B_STGF, lane);
  if (!EAGER) step();
}

__global__ void __launch_bounds__(384, 1) fused_kernel(const bf16* __restrict__ gx, const bf16* __restrict__ gwmod, const bf16* __restrict__ gc,
                                                          unsigned* gepoch, uint2* gstats1, const __grid_constant__ Params p) {
  extern __shared__ __align__(1024) uint8_t smem_raw[];
  const uint32_t sm = smem_u32(smem_raw);
  const uint32_t bars = sm + MISC_OFF;
  const uint32_t stg = sm + STG_OFF;
  const int rank = blockIdx.x & 1;
  const int cl = blockIdx.x >> 1;
  if (cl >= NCTA / 2) {
    const int e = blockIdx.x - NCTA, wid = __shfl_sync(~0u, (int)(threadIdx.x >> 5), 0), lane = threadIdx.x & 31;
    if (threadIdx.x == 0) {
      for (int i = 0; i < 6; i++) { mbar_init(bars + 8 * i, 1); mbar_init(bars + 8 * (6 + i), 8); }
      for (int i = 0; i < 8; i++) { mbar_init(bars + 8 * (16 + i), 1); mbar_init(bars + 8 * (24 + i), 4); }
      mbar_init(bars + 8 * 12, 1);
      asm volatile("fence.mbarrier_init.release.cluster;" ::: "memory");
    }
    const uint32_t tag = load_epoch(gepoch) + 1;
    if (threadIdx.x < 256) ll_store(p.modll + 512 + (threadIdx.x >> 6) * 256 + e * 64 + (threadIdx.x & 63), 0u, 0u, 0u);
    for (int i = threadIdx.x; i < 1536; i += 384) {
      uint4 o = make_uint4(0u, 0u, 0u, 0u);
      if (i < 1024 && (i & 63) < 8) {
        const uint4 cv = ldg_nc(gc + (i >> 6) * 64 + (i & 7) * 8);
        o = make_uint4(pack2(silu_f(bf_lo(cv.x)), silu_f(bf_hi(cv.x))), pack2(silu_f(bf_lo(cv.y)), silu_f(bf_hi(cv.y))),
                       pack2(silu_f(bf_lo(cv.z)), silu_f(bf_hi(cv.z))), pack2(silu_f(bf_lo(cv.w)), silu_f(bf_hi(cv.w))));
      }
      sts128(stg + i * 16, o.x, o.y, o.z, o.w);
    }
    asm volatile("fence.proxy.async.shared::cta;" ::: "memory");
    __syncthreads();
    if (wid == 0) {
      __nanosleep(WMDELAY);
      uint32_t ph = 1;
#pragma unroll 1
      for (int it = 0, s = 0; it < 64; it++) {
        mbar_wait(bars + 8 * (6 + s), ph);
        expect_tx_elect(bars + 8 * s, 32768);
#pragma unroll
        for (int q = 0; q < 4; q++) tma_load_ef(sm + s * 32768 + q * 8192, &p.wm, bars + 8 * s, 2048 + (it >> 4) * 1024 + e * 256 + q * 64, (it & 15) * 64);
        if (++s == 6) { s = 0; ph ^= 1; }
      }
    } else if (wid == 1) {
      __nanosleep(PFW);
#pragma unroll 1
      for (int i = 0; i < 64; i++) {
        l2_prefetch_tile(&p.wo, (i & 15) * 64, (e * 4 + (i >> 4)) * 64);
      }
#pragma unroll 1
      for (int i = 0; i < 80; i++) {
        if (i < 64) l2_prefetch_tile((i & 1) ? &p.wu : &p.wg, ((i >> 1) & 7) * 448 + 384, ((i >> 4) * 4 + e) * 64);
        else l2_prefetch_tile((i & 2) ? &p.wu : &p.wg, (e * 2 + ((i >> 3) & 1)) * 448 + (i & 1) * 64, (e * 4 + ((i >> 2) & 3)) * 64);
      }
    } else if (wid >= 4) {
      const int hf = (wid >> 2) - 1;
      uint32_t ph = 0;
      int s = 0;
#pragma unroll 1
      for (int v = 0; v < 4; v++) {
        float acc[64];
#pragma unroll 1
        for (int kb = 0; kb < 16; kb++) {
          mbar_wait_watchdog(bars + 8 * s, ph);
          const uint32_t da = DESC_A + ((STG_OFF + kb * 1024) >> 4), db = DESC_B + ((s * 32768 + hf * 16384) >> 4);
          wg_fence();
#pragma unroll
          for (int k = 0; k < 4; k++) wgmma_ss_n128(acc, da + k * 2, db + k * 128, (kb | k) != 0);
          wg_commit();
          wg_wait<0>();
          if (lane == 0) mbar_arrive(bars + 8 * (6 + s));
          if (++s == 6) { s = 0; ph ^= 1; }
        }
        fence_regs(acc);
        if ((wid & 3) == 0) {
#pragma unroll
          for (int n = 0; n < 16; n++) {
            const uint32_t mine = pack2(acc[4 * n], acc[4 * n + 1]), next = __shfl_down_sync(~0u, mine, 1);
            if (lane < 4 && (lane & 1) == 0) ll_store(p.modll + 512 + v * 256 + e * 64 + hf * 32 + n * 2 + (lane >> 1), mine, next, tag);
            if (lane < 4) sts64f(sm + MODB_OFF + (hf * 128 + n * 8 + lane * 2) * 4, bf_lo(mine), bf_hi(mine));
          }
        }
      }
    }
    __syncthreads();
    if (wid == 0 || wid == 2) {
      const int w = wid >> 1;
      if (w == 0) {
        expect_tx_elect(bars + 8 * 12, KH * 32768);
#pragma unroll 1
        for (int q = 0; q < 4 * KH; q++) tma_load_ef(sm + q * 8192, &p.wd, bars + 8 * 12, e * 256 + (q & 3) * 64, (q >> 2) * 448 + 384);
      }
      cnt_wait_lazy(p.cnt + C_ACT, tag * 8);
      if (w == 1) __nanosleep(900);
      uint32_t ph = 1, ready = 0;
#pragma unroll 1
      for (int it = 0, s = 0; it < 16 * KH; it++) {
        const int rb = it / KH, kc = it - rb * KH;
        while (!((ready >> rb) & 1)) {
          ready = __ballot_sync(~0u, (int)(load_epoch(p.cnt + (lane & 15) * 32 + C_ACT) - tag * 8) >= 0);
          asm volatile("fence.proxy.async.global;" ::: "memory");
        }
        const uint32_t fb = bars + 8 * (16 + w * 4 + s), dst = sm + 98304 + w * 32768 + s * 8192;
        mbar_wait(fb + 64, ph);
        expect_tx_elect(fb, 8192);
        tma_load(dst, &p.act_st, fb, kc * 448 + 384, rb * 128 + w * 64);
        tma_load(dst + 4096, &p.act_st, fb, kc * 448 + 384, rb * 128 + w * 64 + 32);
        if (++s == 4) { s = 0; ph ^= 1; }
      }
    } else if (wid >= 4) {
      const int w = (wid >> 2) - 1, warp = wid & 3;
      const uint32_t out_stg = (w ? stg : sm + 163840) + warp * 2048;
      const uint32_t slab = out_stg + (lane & 15) * 128, sw0 = (lane >> 4) ^ (lane & 7);
      mbar_wait_watchdog(bars + 8 * 12, 0);
#pragma unroll 1
      for (int i = threadIdx.x - 128; i < KH * 2048; i += 256) {
        const uint32_t gp = sm + MODB_OFF + (((i >> 9) & 3) * 64 + ((i ^ (i >> 3)) & 7) * 8) * 4;
        const uint4 v = lds128(sm + i * 16), ga = lds128(gp), gc = lds128(gp + 16);
        sts128(sm + i * 16, pack2(bf_lo(v.x) * __uint_as_float(ga.x), bf_hi(v.x) * __uint_as_float(ga.y)),
               pack2(bf_lo(v.y) * __uint_as_float(ga.z), bf_hi(v.y) * __uint_as_float(ga.w)),
               pack2(bf_lo(v.z) * __uint_as_float(gc.x), bf_hi(v.z) * __uint_as_float(gc.y)),
               pack2(bf_lo(v.w) * __uint_as_float(gc.z), bf_hi(v.w) * __uint_as_float(gc.w)));
      }
      asm volatile("fence.proxy.async.shared::cta;" ::: "memory");
      bar_sync(1, 256);
      uint32_t ph = 0;
      int s = 0;
#pragma unroll 1
      for (int rb = 0; rb < 16; rb++) {
        float acc[128];
#pragma unroll 1
        for (int kc = 0; kc < KH; kc++) {
          mbar_wait_watchdog(bars + 8 * (16 + w * 4 + s), ph);
          const uint32_t da = DESC_A + ((98304 + w * 32768 + s * 8192) >> 4), db = DESC_B + ((kc * 32768) >> 4);
          wg_fence();
#pragma unroll
          for (int k = 0; k < 4; k++) wgmma_ss_n256(acc, da + k * 2, db + k * 128, (kc | k) != 0);
          wg_commit();
          wg_wait<1>();
          if (kc > 0 && lane == 0) mbar_arrive(bars + 8 * (24 + w * 4 + ((s + 3) & 3)));
          if (++s == 4) { s = 0; ph ^= 1; }
        }
        asm volatile("cp.async.bulk.wait_group 0;" ::: "memory");
        __syncwarp();
        if (rb > 0) cnt_signal(p.cnt + (rb - 1) * 32 + C_SP + e);
        wg_wait<0>();
        fence_regs(acc);
        __syncwarp();
        if (lane == 0) mbar_arrive(bars + 8 * (24 + w * 4 + ((s + 3) & 3)));
#pragma unroll
        for (int q = 0; q < 16; q++)
          stmatrix4(slab + (q >> 2) * 8192 + ((sw0 ^ ((q & 3) * 2)) << 4), pack2(acc[8 * q], acc[8 * q + 1]), pack2(acc[8 * q + 2], acc[8 * q + 3]),
                    pack2(acc[8 * q + 4], acc[8 * q + 5]), pack2(acc[8 * q + 6], acc[8 * q + 7]));
        asm volatile("fence.proxy.async.shared::cta;" ::: "memory");
        __syncwarp();
#pragma unroll
        for (int ch = 0; ch < 4; ch++) tma_add3(&p.out, out_stg + ch * 8192, e * 256 + ch * 64, rb * 64 + warp * 16, w);
        asm volatile("cp.async.bulk.commit_group;" ::: "memory");
      }
      asm volatile("cp.async.bulk.wait_group 0;" ::: "memory");
      __syncwarp();
      cnt_signal(p.cnt + 15 * 32 + C_SP + e);
    }
    return;
  }
  const int q7 = ((cl - 36) * 37) >> 8;
  const int j = cl < 4 ? 4 + cl : (cl < 36 ? (cl - 4) >> 3 : 4 + q7);
  const int rb = (cl < 4 ? 0 : (cl < 36 ? (cl - 4) & 7 : cl - 35 - 7 * q7)) * 2 + rank;
  const int cta = rb * 8 + j;
  PROF_AT(threadIdx.x == 0, 0);

  if (threadIdx.x < 128) {
    uint32_t tag = load_epoch(gepoch);
    asm volatile("setmaxnreg.dec.sync.aligned.u32 40;");
    const int warp = __shfl_sync(~0u, (int)(threadIdx.x >> 5), 0), lane = threadIdx.x & 31;
    if (threadIdx.x == 0) {
      if ((sm & 0x3FFFF) != SMEM_BASE) asm volatile("trap;");
      for (int i = 0; i < 4; i++) { mbar_init(bars + 8 * (B_FQ + i), 1); mbar_init(bars + 8 * (B_EQ + i), 16); }
      for (int i = 0; i < 6; i++) { mbar_init(bars + 8 * (B_FW + i), 1); mbar_init(bars + 8 * (B_EW + i), 16); }
      for (int i = 0; i < 4; i++) { mbar_init(bars + 8 * (B_FG + i), 1); mbar_init(bars + 8 * (B_EG + i), 16); }
      for (int i = 0; i < 6; i++) { mbar_init(bars + 8 * (B_FD + i), 1); mbar_init(bars + 8 * (B_ED + i), 16); }
      for (int i = 0; i < 2; i++) { mbar_init(bars + 8 * (B_STGF + i), 8); mbar_init(bars + 8 * (B_STGE + i), 1); }
      mbar_init(bars + 8 * B_MODB, 1);
      mbar_init(bars + 8 * (B_MODB + 1), 1);
      mbar_init(bars + 8 * B_MODA, 1);
      for (int i = 0; i < 11; i++) mbar_init(bars + 8 * (B_RDY + i), 1);
      asm volatile("fence.mbarrier_init.release.cluster;" ::: "memory");
    }
    __syncwarp();
    cluster_arrive_relaxed();
    tag += 1;
    const unsigned target = tag * 8;
    unsigned* cnt = p.cnt + rb * 32;
    cluster_wait();
    if (warp == 0) {
      const CUtensorMap* wgu = rank ? &p.wu : &p.wg;
      uint32_t st = sm + 16384, fb = bars + 8 * B_FQ, ph = 1;
      __nanosleep(BDELAY);
#pragma unroll 1
      for (int it = 0; it < 32; it++) {
        const int kb = qkv_kb(it, j), col = j * 128 + ((it < 4 ? it >= 2 : it >= 18) ? 64 : 0);
        if (it == 2) mbar_wait(bars + 8 * B_MODA, 0);
        mbar_wait(fb + 8 * (B_EQ - B_FQ), ph);
        expect_tx_elect(fb, it < 4 ? 24576 : 40960);
        tma_load_mc(st + rank * 8192, &p.wqkv, fb, col + rank * 1024, kb * 64);
        tma_load_mc(st + 16384 + rank * 4096, &p.wqkv32, fb, col + 2048, kb * 64 + rank * 32);
        st += 49152; fb += 8;
        if ((it & 3) == 3) { st -= 4 * 49152; fb -= 32; ph ^= 1; }
      }
      fb = bars + 8 * B_FW; ph = 1;
#pragma unroll 1
      for (int it = 0, s = 0; it < 34; it++) {
        if (it < 6) wait_q_free(bars + 8 * B_EQ, it);
        if (it == 16) mbar_wait(bars + 8 * (B_FW + 3), 0);
        mbar_wait(fb + 8 * (B_EW - B_FW), ph);
        expect_tx_elect(fb, (it == 8 || it == 18 || it == 19) ? 16384 : 32768);
        const int k0 = it < 16 ? wo_k(it, j) : (it < 20 ? 2 * j + (it & 1) : other_kb(it - 20, j)) * 64;
        if (it == 16 || it == 17) {
          tma_load_mc(st - 16384 + rank * 16384, wgu, fb, j * 448, k0);
          tma_load_mc(st - 8192 + rank * 16384, wgu, fb, j * 448 + 64, k0);
        } else {
          tma_load_mc(st + rank * 8192, it < 16 ? &p.wo : wgu, fb, it < 16 ? j * 128 + rank * 64 : j * 448 + 384, k0);
        }
        st += 32768; fb += 8;
        if (++s == 6) { s = 0; st -= 6 * 32768; fb -= 48; ph ^= 1; }
      }
      st = sm + 16384 + 3 * 49152; fb = bars + 8 * B_FG; ph = 1;
#pragma unroll 1
      for (int it = 0; it < 46; it++) {
        const int kb = it < 14 ? other_kb(it, j) : (it + 2) & 15, col = j * 448 + ((it + 2) >> 4) * 128;
        if (it < 4) wait_w_free(bars + 8 * B_EW, it);
        mbar_wait(fb + 8 * (B_EG - B_FG), ph);
        expect_tx_elect(fb, 49152);
        tma_load_mc(st + rank * 16384, wgu, fb, col, kb * 64);
        tma_load_mc(st + rank * 16384 + 8192, wgu, fb, col + 64, kb * 64);
        st += (it & 3) == 0 ? -3 * 49152 : 49152; fb += 8;
        if ((it & 3) == 3) { fb -= 32; ph ^= 1; }
      }
      st = sm + 16384 + 2 * 32768; fb = bars + 8 * B_FD; ph = 1;
#pragma unroll 1
      for (int it = 0, s = 0; it < 56 - KH; it++) {
        if (it < 6) wait_g_free(bars + 8 * B_EG, it);
        mbar_wait(fb + 8 * (B_ED - B_FD), ph);
        expect_tx_elect(fb, 32768);
        tma_load_mc(st + rank * 8192, &p.wd, fb, j * 128 + rank * 64, down_k(it));
        st += s == 3 ? -5 * 32768 : 32768; fb += 8;
        if (++s == 6) { s = 0; fb -= 48; ph ^= 1; }
      }
    } else if (warp == 1) {
      const int arow = rb * 128;
      uint32_t st = sm, fb = bars + 8 * B_FQ, ph = 0;
      cnt_wait(cnt + C_HA, target);
      PROF_AT(lane == 0, 16);
#pragma unroll 1
      for (int it = 4; it < 32; it++) {
        if (it == 11) mbar_wait(bars + 8 * (B_RDY + C_H), 0);
        mbar_wait(fb + 8 * (B_EQ - B_FQ), ph);
        tma_load(st, &p.h, fb, qkv_kb(it, j) * 64, arow);
        st += 49152; fb += 8;
        if ((it & 3) == 3) { st -= 4 * 49152; fb -= 32; ph ^= 1; }
      }
      fb = bars + 8 * B_FW; ph = 1;
#pragma unroll 1
      for (int it = 0, s = 0; it < 34; it++) {
        if (it < 16 || it >= 20) {
          if (it < 6) wait_q_free(bars + 8 * B_EQ, it);
          mbar_wait(fb + 8 * (B_EW - B_FW), ph);
          if (it == 0) mbar_wait(bars + 8 * (B_RDY + C_O), 0);
          if (it == 9 || it == 20) cnt_wait(cnt + (it == 9 ? C_O + 1 : C_H2A), target * 8);
          if (it == 27) mbar_wait(bars + 8 * (B_RDY + C_H2), 0);
          PROF_AT(lane == 0 && (it == 0 || it == 9 || it == 20), 17 + (it >> 3));
          if (it != 8) tma_load(st, it < 16 ? &p.o_ld : &p.h2, fb, it < 16 ? wo_k(it, j) : other_kb(it - 20, j) * 64, arow);
        }
        st += 32768; fb += 8;
        if (++s == 6) { s = 0; st -= 6 * 32768; fb -= 48; ph ^= 1; }
      }
      st = sm + 3 * 49152; fb = bars + 8 * B_FG; ph = 1;
#pragma unroll 1
      for (int it = 0; it < 46; it++) {
        if (it < 4) wait_w_free(bars + 8 * B_EW, it);
        mbar_wait(fb + 8 * (B_EG - B_FG), ph);
        tma_load(st, &p.h2, fb, (it < 14 ? other_kb(it, j) : (it + 2) & 15) * 64, arow);
        st += (it & 3) == 0 ? -3 * 49152 : 49152; fb += 8;
        if ((it & 3) == 3) { fb -= 32; ph ^= 1; }
      }
      st = sm + 2 * 32768; fb = bars + 8 * B_FD; ph = 1;
#pragma unroll 1
      for (int it = 0, s = 0; it < 56 - KH; it++) {
        if (it < 6) wait_g_free(bars + 8 * B_EG, it);
        mbar_wait(fb + 8 * (B_ED - B_FD), ph);
        const int u = it + KH, dep = it == 0 ? C_ACT : (u == 8 ? C_ACT + 1 : (u == 24 ? C_ACT + 2 : (u == 40 ? C_A0 : (u == 48 ? C_ACT + 3 : -1))));
        if (dep >= 0) mbar_wait(bars + 8 * (B_RDY + dep), 0);
        tma_load(st, &p.act, fb, down_k(it), arow);
        st += s == 3 ? -5 * 32768 : 32768; fb += 8;
        if (++s == 6) { s = 0; fb -= 48; ph ^= 1; }
      }
    } else if (warp == 2) {
      if (lane < 14) prefetch_map(&p.h + lane);
      __syncwarp();
      uint32_t ph1 = 0;
#pragma unroll 1
      for (int n = 0; n < 8; n++) {
        const int nch = (n == 1 || n == 2 || n == 4) ? 1 : 2;
#pragma unroll 1
        for (int ch = 0; ch < nch; ch++) {
          mbar_wait_watchdog(bars + 8 * (B_STGF + ch), ch ? ph1 : (n & 1));
          const uint32_t src = stg + ch * 16384;
          if (n == 2 || n == 3) {
          } else if (n == 1) {
#pragma unroll 1
            for (int q = 0; q < 8; q++) {
              tma_store2(&p.o_st, src + q * 2048, j * 128, rb * 128 + q * 16);
              if (q & 1) store_pause(true);
            }
          } else if (n >= 4 && n < 8) {
#pragma unroll 1
            for (int q = 0; q < 4; q++) {
              tma_store2(&p.act_st, src + q * 4096, j * 448 + (n == 4 ? 384 : (n - 5) * 128 + ch * 64), rb * 128 + q * 32);
              store_pause(true);
            }
          } else {
            tma_store2(&p.h, src, j * 128 + ch * 64, rb * 128);
            asm volatile("cp.async.bulk.commit_group;" ::: "memory");
            if (ch == 1) {
              asm volatile("cp.async.bulk.wait_group 1;" ::: "memory");
              __syncwarp();
              cnt_signal(cnt + C_HA);
            }
          }
          if (n >= 5 && ch == 0) arrive_elect(bars + 8 * B_STGE);
          if (n == 7 && ch == 0) {
            asm volatile("cp.async.bulk.wait_group 0;" ::: "memory");
            __syncwarp();
            cnt_signal(cnt + C_A0);
          }
        }
        asm volatile("cp.async.bulk.commit_group;" ::: "memory");
        asm volatile("cp.async.bulk.wait_group 0;" ::: "memory");
        __syncwarp();
        if (n != 2 && n != 3) cnt_signal(cnt + n);
        PROF_AT(lane == 0, n == 0 ? 33 : 23 + n);
        if (n == 0) {
#pragma unroll 1
          for (int t = 0; t < 34; t++) {
            ll_store(t < 32 ? p.halo + cta * 1024 + t * 32 + lane : (uint4*)(p.stats2 + cta * 128) + (t - 32) * 32 + lane, 0u, 0u, 0u);
            __nanosleep(40);
          }
          __syncwarp();
        }
        if (n < 5) arrive_elect(bars + 8 * B_STGE);
        if (nch == 2) { arrive_elect(bars + 8 * (B_STGE + 1)); ph1 ^= 1; }
      }
      mbar_wait_watchdog(bars + 8 * B_STGF, 0);
      PROF_AT(lane == 0, 31);
    } else {
      if (lane < 4) ll_store(p.modll + cta * 4 + lane, 0u, 0u, 0u);
      bar_sync(1, 288);
      {
        const uint4 t4 = lds128(sm + RED_OFF + lane * 16);
        float a[4] = {__uint_as_float(t4.x), __uint_as_float(t4.y), __uint_as_float(t4.z), __uint_as_float(t4.w)};
#pragma unroll
        for (int o = 4; o < 32; o <<= 1)
#pragma unroll
          for (int q = 0; q < 4; q++) a[q] += __shfl_xor_sync(~0u, a[q], o);
        if (lane < 4) ll_store(p.modll + cta * 4 + lane, pack2(a[0], a[1]), pack2(a[2], a[3]), tag);
        PROF_AT(lane == 0, 1);
        uint32_t m[4];
        const uint4* mp = p.modll + j * 32 + lane;
        ll_poll<2>([&](int i) { return mp + i * 256; }, tag, m);
        const uint32_t c0 = pack2(1.0f + bf_lo(m[2]), 1.0f + bf_hi(m[2])), c1 = pack2(1.0f + bf_lo(m[3]), 1.0f + bf_hi(m[3]));
        sts128(sm + MODB_OFF + lane * 16, c0, m[0], c1, m[1]);
        __syncwarp();
        arrive_elect(bars + 8 * B_MODA);
      }
#pragma unroll 1
      for (int n = C_H; n <= C_O; n++) {
        cnt_wait_lazy(cnt + n, target);
        arrive_elect(bars + 8 * (B_RDY + n));
      }
      {
        uint32_t m[6];
        const uint4* src = p.modll + 512 + j * 32 + lane;
        ll_poll<3, 500>([&](int i) { return src + i * 256; }, tag, m);
#pragma unroll
        for (int vec = 0; vec < 3; vec++) {
          const float add = vec == 2 ? 1.0f : 0.0f;
          sts128(sm + MODB_OFF + (vec * 128 + lane * 4) * 4, __float_as_uint(bf_round(bf_lo(m[2 * vec]) + add)), __float_as_uint(bf_round(bf_hi(m[2 * vec]) + add)),
                 __float_as_uint(bf_round(bf_lo(m[2 * vec + 1]) + add)), __float_as_uint(bf_round(bf_hi(m[2 * vec + 1]) + add)));
        }
        __syncwarp();
        if (lane == 0) mbar_arrive(bars + 8 * B_MODB);
        PROF_AT(lane == 0, 15);
      }
      __syncwarp();
#pragma unroll 1
      for (int q = C_H2; q < 9; q++) {
        const int n = q < 7 ? q : (q == 7 ? C_A0 : C_ACT + 3);
        cnt_wait_lazy(cnt + n, n == C_H2 ? target * 8 : target);
        arrive_elect(bars + 8 * (B_RDY + n));
      }
      {
        uint32_t m[2];
        const uint4* src = p.modll + 512 + 768 + j * 32 + lane;
        ll_poll<1>([&](int) { return src; }, tag, m);
        sts128(sm + MODB_OFF + (384 + lane * 4) * 4, m[0] << 16, m[0] & 0xffff0000u, m[1] << 16, m[1] & 0xffff0000u);
        cnt_wait_lazy(cnt + C_SP + (j >> 1), target);
        __syncwarp();
        if (lane == 0) mbar_arrive(bars + 8 * (B_MODB + 1));
      }
    }
  } else {
    uint32_t tag;

    {
      const int tid = threadIdx.x - 128, cw = tid >> 7, warp = (tid >> 5) & 3, lane = tid & 31;
      const int l16 = lane & 15, half = lane >> 4, w8 = cw * 4 + warp;
      const uint32_t cbuf = sm + 3 * 49152 + w8 * 512;
      if (lane <= 16) cp_async16(cbuf + lane * 16, lane < 16 ? (const void*)(gc + w8 * 128 + lane * 8) : (const void*)gepoch);
      asm volatile("cp.async.commit_group;" ::: "memory");
      const uint32_t xbuf = sm + 40960 + (cw * 2 + (l16 >> 3)) * 49152 + (warp * 16 + half) * 128;
      {
        const char* xp = (const char*)gx + (uint32_t)((rb * 128 + (warp * 16 + half) * 2 + cw) * 2048 + j * 256 + l16 * 16);
#pragma unroll
        for (int i = 0; i < 8; i++) cp_async16(xbuf + i * 256 + (((l16 & 7) ^ ((i * 2 + half) & 7)) << 4), xp + i * 8192);
      }
      asm volatile("cp.async.commit_group;" ::: "memory");
      const uint32_t wbuf = sm + cw * 49152 + warp * 4096;
      {
        const char* wp = (const char*)gwmod + (uint32_t)(cta * 32 + (lane & 1) * 16 + (w8 * 128 + (lane >> 1)) * 12288);
#pragma unroll
        for (int i = 0; i < 8; i++) cp_async16(wbuf + i * 512 + lane * 16, wp + i * 16 * 12288);
      }
      asm volatile("cp.async.commit_group;" ::: "memory");
      PROF_AT(tid == 0, 32);
      uint2* st1 = gstats1 + (rb * 8 + j) * 128 + cw * 64 + warp * 16;
      if (lane < 8) ll_store((uint4*)st1 + lane, 0u, 0u, 0u);
      __syncwarp();
      cluster_arrive_relaxed();
      asm volatile("setmaxnreg.inc.sync.aligned.u32 232;");
      uint32_t sa[4][4];
      {
        asm volatile("cp.async.wait_group 2;" ::: "memory");
        __syncwarp();
        tag = lds32(cbuf + 256) + 1;
        const float2 cv = lds64f(cbuf + lane * 8);
        const uint32_t c0 = __float_as_uint(cv.x), c1 = __float_as_uint(cv.y);
        sts64f(cbuf + lane * 8, __uint_as_float(pack2(silu_f(bf_lo(c0)), silu_f(bf_hi(c0)))), __uint_as_float(pack2(silu_f(bf_lo(c1)), silu_f(bf_hi(c1)))));
        __syncwarp();
#pragma unroll
        for (int q = 0; q < 4; q++) ldmatrix4(sa[q][0], sa[q][1], sa[q][2], sa[q][3], cbuf + q * 64 + (lane >> 3) * 16);
      }
      cluster_wait();
      asm volatile("cp.async.wait_group 1;" ::: "memory");
      __syncwarp();
      uint32_t xl[16], xh[16];
      {
        const int srow = warp * 16 + (lane & 15);
#pragma unroll
        for (int q = 0; q < 8; q++)
          ldmatrix4(xl[2 * q], xh[2 * q], xl[2 * q + 1], xh[2 * q + 1],
                    sm + 40960 + (cw * 2 + (q >> 2)) * 49152 + srow * 128 + (((half + (q & 3) * 2) ^ (srow & 7)) << 4));
      }
      publish_stats(xl, xh, st1, lane, tag16(tag));
      PROF_AT(tid == 0, 50);
      asm volatile("cp.async.wait_group 0;" ::: "memory");
      __syncwarp();
      PROF_AT(tid == 0, 51);
      {
        uint32_t b[8][4];
#pragma unroll
        for (int ks = 0; ks < 8; ks++) ldmatrix4t(b[ks], wbuf + (ks * 16 + (lane & 15)) * 32 + (lane >> 4) * 16);
        float d0[4] = {0.f, 0.f, 0.f, 0.f}, d1[4] = {0.f, 0.f, 0.f, 0.f}, d2[4] = {0.f, 0.f, 0.f, 0.f}, d3[4] = {0.f, 0.f, 0.f, 0.f};
#pragma unroll
        for (int q = 0; q < 4; q++) {
          mma16816(d0, sa[q][0], sa[q][0], sa[q][1], sa[q][1], b[2 * q][0], b[2 * q][1]);
          mma16816(d1, sa[q][0], sa[q][0], sa[q][1], sa[q][1], b[2 * q][2], b[2 * q][3]);
          mma16816(d2, sa[q][2], sa[q][2], sa[q][3], sa[q][3], b[2 * q + 1][0], b[2 * q + 1][1]);
          mma16816(d3, sa[q][2], sa[q][2], sa[q][3], sa[q][3], b[2 * q + 1][2], b[2 * q + 1][3]);
        }
        d0[0] += d2[0]; d0[1] += d2[1]; d1[0] += d3[0]; d1[1] += d3[1];
        if (lane < 4) {
          sts64f(sm + RED_OFF + (w8 * 16 + lane * 2) * 4, d0[0], d0[1]);
          sts64f(sm + RED_OFF + (w8 * 16 + 8 + lane * 2) * 4, d1[0], d1[1]);
        }
        asm volatile("bar.arrive 1, 288;" ::: "memory");
      }
      {
        const int c = lane & 3;
        float rs[2], nb[2];
        stat_gather(gstats1 + rb * 1024 + cw * 64 + warp * 16, tag16(tag), lane, rs, nb);
#pragma unroll
        for (int n = 0; n < 16; n++) {
          xl[n] = pack2(bf_lo(xl[n]) * rs[0] + nb[0], bf_hi(xl[n]) * rs[0] + nb[0]);
          xh[n] = pack2(bf_lo(xh[n]) * rs[1] + nb[1], bf_hi(xh[n]) * rs[1] + nb[1]);
        }
        const int srow = warp * 16 + l16;
        const uint32_t slab = stg + cw * 8192 + srow * 128;
#pragma unroll
        for (int q = 0; q < 8; q++)
          stmatrix4(slab + (q >> 2) * 16384 + (((half + (q & 3) * 2) ^ (srow & 7)) << 4), xl[2 * q], xh[2 * q], xl[2 * q + 1], xh[2 * q + 1]);
        PROF_AT(tid == 0, 52);
        mbar_wait(bars + 8 * B_MODA, 0);
        PROF_AT(tid == 0, 2);
#pragma unroll
        for (int q = 0; q < 8; q++) {
          const float2 m0 = lds64f(sm + MODB_OFF + (8 * q + c) * 8), m1 = lds64f(sm + MODB_OFF + (8 * q + 4 + c) * 8);
          const uint32_t c0 = __float_as_uint(m0.x), s0 = __float_as_uint(m0.y), c1 = __float_as_uint(m1.x), s1 = __float_as_uint(m1.y);
          stmatrix4(slab + (q >> 2) * 16384 + (((half + (q & 3) * 2) ^ (srow & 7)) << 4), fma_bf2(xl[2 * q], c0, s0), fma_bf2(xh[2 * q], c0, s0),
                    fma_bf2(xl[2 * q + 1], c1, s1), fma_bf2(xh[2 * q + 1], c1, s1));
          if ((q & 3) == 3) stage_done(bars + 8 * (B_STGF + (q >> 2)), lane);
        }
        wg_bar(cw);
      }
      PROF_AT(tid == 0, 3);
    }

    uint32_t xl[16], xh[16];
    {
      RING_IDS();
      uint32_t prev = 0;
      float acc1[96];
      {
        Ring g{bars + 8 * B_FQ, rbars + 8 * B_EQ, 0, 0u, 0u, releaser TR(0)};
        float acc0[96];
#pragma unroll 1
        for (int kb = 0; kb < 2; kb++) kblock<192, 4, 49152>(acc0, g, a_base + STG_OFF + kb * 16384, kb == 0, prev);
#pragma unroll 1
        for (int kb = 0; kb < 2; kb++) kblock<192, 4, 49152>(acc1, g, a_base + STG_OFF + kb * 16384, kb == 0, prev);
#pragma unroll 1
        for (int kb = 0; kb < 14; kb++) kblock<192, 4, 49152>(acc0, g, a_base + g.off, false, prev);
        PROF_AT(tid == 0, 4);
        attention<NPRE0, false>(acc0, p, 0, rb, cta, cw, warp, tag, stg, bars, prev, [&]() { kblock<192, 4, 49152>(acc1, g, a_base + g.off, false, prev); });
        PROF_AT(tid == 0, 5);
        {
          LANE_IDS();
#pragma unroll
          for (int q = 0; q < 8; q++)
            ldmatrix4(xl[2 * q], xh[2 * q], xl[2 * q + 1], xh[2 * q + 1], sm + 40960 + (cw * 2 + (q >> 2)) * 49152 + srow * 128 + ((sw0 ^ ((q & 3) * 2)) << 4));
#pragma unroll
          for (int q = 0; q < 16; q++) asm volatile("" : "+r"(xl[q]), "+r"(xh[q])::"memory");
        }
#pragma unroll 1
        for (int kb = 5 + NPRE0; kb < 14; kb++) kblock<192, 4, 49152>(acc1, g, a_base + g.off, false, prev);
        PROF_AT(tid == 0, 6);
      }
      float acc[64];
      Ring g{bars + 8 * B_FW, rbars + 8 * B_EW, 0, 0u, 0u, releaser TR(32)};
      attention<NPRE1, true>(acc1, p, 1, rb, cta, cw, warp, tag, stg, bars, prev, [&]() { kblock<128, 6, 32768>(acc, g, a_base + g.off, g.s == 0, prev); });
      PROF_AT(tid == 0, 7);
      LANE_IDS();
      unsigned* cnt = p.cnt + rb * 32;
      tma_store2(&p.o_st, stg + cw * 8192 + warp * 2048, j * 128 + 64, rb * 128 + cw * 64 + warp * 16);
      asm volatile("cp.async.bulk.commit_group;" ::: "memory");
#pragma unroll 1
      for (int kb = 1 + NPRE1; kb < 16; kb++) {
        if (kb == 8) wg_bar(cw);
        kblock<128, 6, 32768>(acc, g, a_base + (kb == 8 ? STG_OFF : g.off), false, prev);
        if (kb == 3 + NPRE1) {
          asm volatile("cp.async.bulk.wait_group 0;" ::: "memory");
          __syncwarp();
          cnt_signal(cnt + C_O + 1);
        }
      }
      mbar_wait(bars + 8 * B_MODB, 0);
      float2 ga[16];
#pragma unroll
      for (int n = 0; n < 16; n++) ga[n] = lds64f(sm + MODB_OFF + (8 * n + 2 * c) * 4);
      tile_end(acc, prev);
      PROF_AT(tid == 0, 8);
#pragma unroll
      for (int n = 0; n < 16; n++) {
        acc[4 * n] = ga[n].x * acc[4 * n] + bf_lo(xl[n]); acc[4 * n + 1] = ga[n].y * acc[4 * n + 1] + bf_hi(xl[n]);
        acc[4 * n + 2] = ga[n].x * acc[4 * n + 2] + bf_lo(xh[n]); acc[4 * n + 3] = ga[n].y * acc[4 * n + 3] + bf_hi(xh[n]);
        xl[n] = pack2(acc[4 * n], acc[4 * n + 1]);
        xh[n] = pack2(acc[4 * n + 2], acc[4 * n + 3]);
      }
      publish_stats(xl, xh, p.stats2 + (rb * 8 + j) * 128 + cw * 64 + warp * 16, lane, tag16(tag));
      PROF_AT(tid == 0, 48);
      float2 sb[16], cb[16];
#pragma unroll
      for (int n = 0; n < 16; n++) {
        sb[n] = lds64f(sm + MODB_OFF + (128 + 8 * n + 2 * c) * 4);
        cb[n] = lds64f(sm + MODB_OFF + (256 + 8 * n + 2 * c) * 4);
      }
      mbar_wait(bars + 8 * B_STGE, 0);
      PROF_AT(tid == 0, 49);
      float nb[2], rstd[2];
      stat_gather(p.stats2 + rb * 1024 + cw * 64 + warp * 16, tag16(tag), lane, rstd, nb);
      PROF_AT(tid == 0, 9);
#pragma unroll
      for (int ch = 0; ch < 2; ch++) {
        uint32_t lo[8], hi[8];
#pragma unroll
        for (int t = 0; t < 8; t++) {
          const int n = ch * 8 + t;
          lo[t] = pack2((acc[4 * n] * rstd[0] + nb[0]) * cb[n].x + sb[n].x, (acc[4 * n + 1] * rstd[0] + nb[0]) * cb[n].y + sb[n].y);
          hi[t] = pack2((acc[4 * n + 2] * rstd[1] + nb[1]) * cb[n].x + sb[n].x, (acc[4 * n + 3] * rstd[1] + nb[1]) * cb[n].y + sb[n].y);
        }
        stage_slab(sm + ch * 32768 + cw * 8192, warp, lane, lo, hi);
        stage_done(bars + 8 * (B_STGF + ch), lane);
        tma_store2(&p.h2_st, sm + ch * 32768 + cw * 8192 + warp * 2048, j * 128 + ch * 64, rb * 128 + cw * 64 + warp * 16);
        asm volatile("cp.async.bulk.commit_group;" ::: "memory");
      }
      wg_bar(cw);
      PROF_AT(tid == 0, 10);
    }

    uint32_t pg[32], pu[32];
    {
      RING_IDS();
      float acc[128];
      uint32_t prev = 0;
      Ring g{bars + 8 * B_FG, rbars + 8 * B_EG, 0, 0u, 3 * 49152u, releaser TR(66)};
      {
        Ring w{bars + 8 * B_FW, rbars + 8 * B_EW, 4, 0u, 4 * 32768u, releaser TR(48)};
        float acn[64];
#pragma unroll 1
        for (int kb = 0; kb < 2; kb++) {
          kblock<256, 6, 32768>(acc, w, a_base + kb * 32768, kb == 0, prev, 0u);
          if (kb == 0) asm volatile("cp.async.bulk.wait_group 1;" ::: "memory");
          else asm volatile("cp.async.bulk.wait_group 0;" ::: "memory");
          __syncwarp();
          cnt_signal(p.cnt + rb * 32 + (kb == 0 ? C_H2A : C_H2));
        }
        {
          LANE_IDS();
#pragma unroll
          for (int q = 0; q < 8; q++)
            stmatrix4(slab + (q >> 2) * 16384 + ((sw0 ^ ((q & 3) * 2)) << 4), xl[2 * q], xh[2 * q], xl[2 * q + 1], xh[2 * q + 1]);
          __syncwarp();
        }
#pragma unroll 1
        for (int kb = 0; kb < 16; kb++) {
          kblock<128, 6, 32768>(acn, w, a_base + w.off, kb == 0, prev);
          if (kb == 4) {
            asm volatile("fence.proxy.async.shared::cta;" ::: "memory");
            __syncwarp();
          }
          if (kb == 6 + warp || kb == 10 + warp) {
            const int ch = kb != 6 + warp;
            tma_store3(&p.out, stg + ch * 16384 + cw * 8192 + warp * 2048, j * 128 + ch * 64, rb * 64 + warp * 16, cw);
            asm volatile("cp.async.bulk.commit_group;" ::: "memory");
          }
        }
        PROF_AT(tid == 0, 39);
        kblock<256, 4, 49152>(acc, g, a_base + g.off, false, prev);
        fence_regs(acn);
#pragma unroll
        for (int q = 0; q < 16; q++) {
          pg[q] = pack2(acn[2 * q], acn[2 * q + 1]);
          pu[q] = pack2(acn[32 + 2 * q], acn[32 + 2 * q + 1]);
          pg[16 + q] = 0; pu[16 + q] = 0;
        }
        asm volatile("cp.async.bulk.wait_group 0;" ::: "memory");
        kblock<256, 4, 49152>(acc, g, a_base + g.off, false, prev);
      }
      LANE_IDS();
#pragma unroll 1
      for (int t = 0; t < 3; t++) {
#pragma unroll 1
        for (int blk = 0; blk < (t == 0 ? 2 : 4); blk++) {
          g.s = 2;
#pragma unroll
          for (int i = 0; i < 4; i++) {
            g.off = ((i + 1) & 3) * 49152;
            if (i == 3 && blk == 3) skew_pre(cw);
            kblock<256, 4, 49152>(acc, g, a_base + g.off, t > 0 && blk == 0 && i == 0, prev);
            if (i == 3 && blk == 3) skew_post(cw);
            if ((blk & 1) == 0 && i == 0) mbar_wait(bars + 8 * (B_STGE + (blk >> 1)), (t + 1 + (blk >> 1)) & 1);
            stmatrix2(slab + (blk >> 1) * 16384 + (((srow & 7) ^ ((blk & 1) * 4 + i)) << 4), swiglu2(pg[2 * i], pu[2 * i]), swiglu2(pg[2 * i + 1], pu[2 * i + 1]));
          }
#pragma unroll
          for (int q = 0; q < 24; q++) { pg[q] = pg[q + 8]; pu[q] = pu[q + 8]; }
          if (blk & 1) stage_done(bars + 8 * (B_STGF + (blk >> 1)), lane);
        }
#pragma unroll 1
        for (int kb = t == 0 ? 0 : 4; kb < 4; kb++) {
          if (kb == 3) skew_pre(cw);
          kblock<256, 4, 49152>(acc, g, a_base + g.off, false, prev);
          if (kb == 3) skew_post(cw);
        }
        tile_end(acc, prev);
        PROF_AT(tid == 0, 36 + t);
#pragma unroll
        for (int q = 0; q < 32; q++) {
          pg[q] = pack2(acc[2 * q], acc[2 * q + 1]);
          pu[q] = pack2(acc[64 + 2 * q], acc[64 + 2 * q + 1]);
        }
      }
      PROF_AT(tid == 0, 11);
    }

    {
      RING_IDS();
      LANE_IDS();
      Ring g{bars + 8 * B_FD, rbars + 8 * B_ED, 0, 0u, 2 * 32768u, releaser TR(112)};
      float acc[64];
      uint32_t prev = 0;
#pragma unroll 1
      for (int blk = 0; blk < 4; blk++) {
#pragma unroll
        for (int i = 0; i < 8; i++) {
          kblock<128, 6, 32768>(acc, g, a_base + g.off, blk == 0 && i == 0, prev);
          if ((blk & 1) == 0 && i == 0) mbar_wait(bars + 8 * (B_STGE + (blk >> 1)), blk >> 1);
          stmatrix1(slab + (blk >> 1) * 16384 + (i & 1) * 1024 + (((srow & 7) ^ ((blk & 1) * 4 + (i >> 1))) << 4), swiglu2(pg[i], pu[i]));
        }
#pragma unroll
        for (int q = 0; q < 24; q++) { pg[q] = pg[q + 8]; pu[q] = pu[q + 8]; }
        if (blk & 1) stage_done(bars + 8 * (B_STGF + (blk >> 1)), lane);
      }
#pragma unroll 1
      for (int kb = 32; kb < 56 - KH; kb++) {
        if (kb == 50 - KH) g.releaser = false;
        if (kb == 52 - KH) skew_pre(cw);
        kblock<128, 6, 32768>(acc, g, a_base + g.off, false, prev);
      }
      skew_post(cw);
      mbar_wait(bars + 8 * (B_MODB + 1), 0);
      mbar_wait(bars + 8 * B_STGE, 1);
      mbar_wait(bars + 8 * (B_STGE + 1), 0);
      float2 gbv[16];
#pragma unroll
      for (int n = 0; n < 16; n++) gbv[n] = lds64f(sm + MODB_OFF + (384 + 8 * n + 2 * c) * 4);
      tile_end(acc, prev);
      PROF_AT(tid == 0, 13);
#pragma unroll
      for (int ch = 0; ch < 2; ch++) {
        uint32_t lo[8], hi[8];
#pragma unroll
        for (int t = 0; t < 8; t++) {
          const int n = ch * 8 + t;
          const float2 gb = gbv[n];
          lo[t] = pack2(gb.x * acc[4 * n], gb.y * acc[4 * n + 1]);
          hi[t] = pack2(gb.x * acc[4 * n + 2], gb.y * acc[4 * n + 3]);
        }
        stage_slab(stg + ch * 16384 + cw * 8192, warp, lane, lo, hi);
        asm volatile("fence.proxy.async.shared::cta;" ::: "memory");
        __syncwarp();
        tma_add3(&p.out, stg + ch * 16384 + cw * 8192 + warp * 2048, j * 128 + ch * 64, rb * 64 + warp * 16, cw);
      }
      asm volatile("cp.async.bulk.commit_group;" ::: "memory");
      if (lane == 0) mbar_arrive(bars + 8 * B_STGF);
      asm volatile("cp.async.bulk.wait_group.read 0;" ::: "memory");
      PROF_AT(tid == 0, 14);
    }
    if (blockIdx.x == 0 && threadIdx.x == 128) asm volatile("st.relaxed.gpu.global.u32 [%0], %1;" ::"l"(gepoch), "r"(tag) : "memory");
  }
}

typedef CUresult (*EncodeFn)(CUtensorMap*, CUtensorMapDataType, cuuint32_t, void*, const cuuint64_t*, const cuuint64_t*,
                             const cuuint32_t*, const cuuint32_t*, CUtensorMapInterleave, CUtensorMapSwizzle,
                             CUtensorMapL2promotion, CUtensorMapFloatOOBfill);

void encode2d(EncodeFn fn, CUtensorMap* m, const void* ptr, uint64_t cols, uint64_t rows, uint32_t box_rows) {
  cuuint64_t dims[2] = {cols, rows};
  cuuint64_t strides[1] = {cols * 2};
  cuuint32_t box[2] = {64, box_rows};
  cuuint32_t es[2] = {1, 1};
  fn(m, CU_TENSOR_MAP_DATA_TYPE_BFLOAT16, 2, (void*)ptr, dims, strides, box, es, CU_TENSOR_MAP_INTERLEAVE_NONE,
     CU_TENSOR_MAP_SWIZZLE_128B, CU_TENSOR_MAP_L2_PROMOTION_L2_128B, CU_TENSOR_MAP_FLOAT_OOB_FILL_NONE);
}

}

extern "C" void kernel_launch(void* const* d_in, const int* in_sizes, int n_in, void* d_out, int out_size) {
  (void)in_sizes; (void)n_in; (void)out_size;
  void* fp = nullptr;
  cudaDriverEntryPointQueryResult qr;
  cudaGetDriverEntryPoint("cuTensorMapEncodeTiled", &fp, cudaEnableDefault, &qr);
  EncodeFn fn = (EncodeFn)fp;
  void *ph, *po, *ph2, *pact;
  cudaGetSymbolAddress(&ph, g_h);
  cudaGetSymbolAddress(&po, g_o);
  ph2 = ph;
  cudaGetSymbolAddress(&pact, g_act);
  Params p;
  encode2d(fn, &p.h, ph, DM, SEQ, 128);
  encode2d(fn, &p.o_ld, po, DM, SEQ, 128);
  encode2d(fn, &p.h2, ph2, DM, SEQ, 128);
  encode2d(fn, &p.act, pact, FF, SEQ, 128);
  encode2d(fn, &p.act_st, pact, FF, SEQ, 32);
  encode2d(fn, &p.wm, d_in[8], 6 * DM, DM, 64);
  encode2d(fn, &p.o_st, po, DM, SEQ, 16);
  encode2d(fn, &p.h2_st, ph2, DM, SEQ, 16);
  encode2d(fn, &p.wqkv, d_in[1], 3 * DM, DM, 64);
  encode2d(fn, &p.wqkv32, d_in[1], 3 * DM, DM, 32);
  encode2d(fn, &p.wo, d_in[2], DM, DM, 64);
  encode2d(fn, &p.wg, d_in[4], FF, DM, 64);
  encode2d(fn, &p.wu, d_in[5], FF, DM, 64);
  encode2d(fn, &p.wd, d_in[6], DM, FF, 64);
  {
    cuuint64_t dims[3] = {DM, SEQ / 2, 2};
    cuuint64_t strides[2] = {DM * 4, DM * 2};
    cuuint32_t box[3] = {64, 16, 1};
    cuuint32_t es[3] = {1, 1, 1};
    fn(&p.out, CU_TENSOR_MAP_DATA_TYPE_BFLOAT16, 3, d_out, dims, strides, box, es, CU_TENSOR_MAP_INTERLEAVE_NONE,
       CU_TENSOR_MAP_SWIZZLE_128B, CU_TENSOR_MAP_L2_PROMOTION_L2_128B, CU_TENSOR_MAP_FLOAT_OOB_FILL_NONE);
  }
  void* q;
  cudaGetSymbolAddress(&q, g_modll); p.modll = (uint4*)q;
  cudaGetSymbolAddress(&q, g_halo); p.halo = (uint4*)q;
  cudaGetSymbolAddress(&q, g_stats); uint2* stats1 = (uint2*)q; p.stats2 = stats1 + SEQ * 8;
  cudaGetSymbolAddress(&q, g_cnt); p.cnt = (unsigned*)q;
  cudaGetSymbolAddress(&q, g_epoch); unsigned* epoch = (unsigned*)q;

  cudaFuncSetAttribute(fused_kernel, cudaFuncAttributeMaxDynamicSharedMemorySize, SMEM_BYTES);
  cudaLaunchConfig_t cfg = {};
  cfg.gridDim = dim3(NCTA + 4);
  cfg.blockDim = dim3(384);
  cfg.dynamicSmemBytes = SMEM_BYTES;
  cfg.stream = cudaStreamPerThread;
  cudaLaunchAttribute at[1];
  at[0].id = cudaLaunchAttributeClusterDimension;
  at[0].val.clusterDim.x = 2; at[0].val.clusterDim.y = 1; at[0].val.clusterDim.z = 1;
  cfg.attrs = at;
  cfg.numAttrs = 1;
  cudaLaunchKernelEx(&cfg, fused_kernel, (const bf16*)d_in[0], (const bf16*)d_in[8], (const bf16*)d_in[7], epoch, stats1, p);
}
```

```cpp
#include <cuda_runtime.h>
#include <cuda_bf16.h>
#include <cuda.h>
#include <stdint.h>

typedef __nv_bfloat16 bf16;

#define PAUSE 200
#define WMDELAY 500
#define BDELAY 1500
#define NPRE0 3
#define NPRE1 1
#define ALIAS 1
#define PFW 8000
#define KH 3

__device__ __forceinline__ void wgmma_ss_n128(float (&d)[64], uint32_t da, uint32_t db, int scale_d) {
  asm volatile("{\n.reg .pred p;\n.reg .b64 da, db;\nsetp.ne.b32 p, %66, 0;\n"
    "mov.b64 da, {%64, 0x40000040};\nmov.b64 db, {%65, 0x40000040};\n"
    "wgmma.mma_async.sync.aligned.m64n128k16.f32.bf16.bf16 "
    "{%0, %1, %2, %3, %4, %5, %6, %7, %8, %9, %10, %11, %12, %13, %14, %15, "
    "%16, %17, %18, %19, %20, %21, %22, %23, %24, %25, %26, %27, %28, %29, %30, %31, "
    "%32, %33, %34, %35, %36, %37, %38, %39, %40, %41, %42, %43, %44, %45, %46, %47, "
    "%48, %49, %50, %51, %52, %53, %54, %55, %56, %57, %58, %59, %60, %61, %62, %63}, "
    "da, db, p, 1, 1, 0, 1;\n}\n"
    : "+f"(d[0]), "+f"(d[1]), "+f"(d[2]), "+f"(d[3]), "+f"(d[4]), "+f"(d[5]), "+f"(d[6]), "+f"(d[7]),
      "+f"(d[8]), "+f"(d[9]), "+f"(d[10]), "+f"(d[11]), "+f"(d[12]), "+f"(d[13]), "+f"(d[14]), "+f"(d[15]),
      "+f"(d[16]), "+f"(d[17]), "+f"(d[18]), "+f"(d[19]), "+f"(d[20]), "+f"(d[21]), "+f"(d[22]), "+f"(d[23]),
      "+f"(d[24]), "+f"(d[25]), "+f"(d[26]), "+f"(d[27]), "+f"(d[28]), "+f"(d[29]), "+f"(d[30]), "+f"(d[31]),
      "+f"(d[32]), "+f"(d[33]), "+f"(d[34]), "+f"(d[35]), "+f"(d[36]), "+f"(d[37]), "+f"(d[38]), "+f"(d[39]),
      "+f"(d[40]), "+f"(d[41]), "+f"(d[42]), "+f"(d[43]), "+f"(d[44]), "+f"(d[45]), "+f"(d[46]), "+f"(d[47]),
      "+f"(d[48]), "+f"(d[49]), "+f"(d[50]), "+f"(d[51]), "+f"(d[52]), "+f"(d[53]), "+f"(d[54]), "+f"(d[55]),
      "+f"(d[56]), "+f"(d[57]), "+f"(d[58]), "+f"(d[59]), "+f"(d[60]), "+f"(d[61]), "+f"(d[62]), "+f"(d[63])
    : "r"(da), "r"(db), "r"(scale_d));
}

__device__ __forceinline__ void wgmma_ss_n192(float (&d)[96], uint32_t da, uint32_t db, int scale_d) {
  asm volatile("{\n.reg .pred p;\n.reg .b64 da, db;\nsetp.ne.b32 p, %98, 0;\n"
    "mov.b64 da, {%96, 0x40000040};\nmov.b64 db, {%97, 0x40000040};\n"
    "wgmma.mma_async.sync.aligned.m64n192k16.f32.bf16.bf16 "
    "{%0, %1, %2, %3, %4, %5, %6, %7, %8, %9, %10, %11, %12, %13, %14, %15, "
    "%16, %17, %18, %19, %20, %21, %22, %23, %24, %25, %26, %27, %28, %29, %30, %31, "
    "%32, %33, %34, %35, %36, %37, %38, %39, %40, %41, %42, %43, %44, %45, %46, %47, "
    "%48, %49, %50, %51, %52, %53, %54, %55, %56, %57, %58, %59, %60, %61, %62, %63, "
    "%64, %65, %66, %67, %68, %69, %70, %71, %72, %73, %74, %75, %76, %77, %78, %79, "
    "%80, %81, %82, %83, %84, %85, %86, %87, %88, %89, %90, %91, %92, %93, %94, %95}, "
    "da, db, p, 1, 1, 0, 1;\n}\n"
    : "+f"(d[0]), "+f"(d[1]), "+f"(d[2]), "+f"(d[3]), "+f"(d[4]), "+f"(d[5]), "+f"(d[6]), "+f"(d[7]),
      "+f"(d[8]), "+f"(d[9]), "+f"(d[10]), "+f"(d[11]), "+f"(d[12]), "+f"(d[13]), "+f"(d[14]), "+f"(d[15]),
      "+f"(d[16]), "+f"(d[17]), "+f"(d[18]), "+f"(d[19]), "+f"(d[20]), "+f"(d[21]), "+f"(d[22]), "+f"(d[23]),
      "+f"(d[24]), "+f"(d[25]), "+f"(d[26]), "+f"(d[27]), "+f"(d[28]), "+f"(d[29]), "+f"(d[30]), "+f"(d[31]),
      "+f"(d[32]), "+f"(d[33]), "+f"(d[34]), "+f"(d[35]), "+f"(d[36]), "+f"(d[37]), "+f"(d[38]), "+f"(d[39]),
      "+f"(d[40]), "+f"(d[41]), "+f"(d[42]), "+f"(d[43]), "+f"(d[44]), "+f"(d[45]), "+f"(d[46]), "+f"(d[47]),
      "+f"(d[48]), "+f"(d[49]), "+f"(d[50]), "+f"(d[51]), "+f"(d[52]), "+f"(d[53]), "+f"(d[54]), "+f"(d[55]),
      "+f"(d[56]), "+f"(d[57]), "+f"(d[58]), "+f"(d[59]), "+f"(d[60]), "+f"(d[61]), "+f"(d[62]), "+f"(d[63]),
      "+f"(d[64]), "+f"(d[65]), "+f"(d[66]), "+f"(d[67]), "+f"(d[68]), "+f"(d[69]), "+f"(d[70]), "+f"(d[71]),
      "+f"(d[72]), "+f"(d[73]), "+f"(d[74]), "+f"(d[75]), "+f"(d[76]), "+f"(d[77]), "+f"(d[78]), "+f"(d[79]),
      "+f"(d[80]), "+f"(d[81]), "+f"(d[82]), "+f"(d[83]), "+f"(d[84]), "+f"(d[85]), "+f"(d[86]), "+f"(d[87]),
      "+f"(d[88]), "+f"(d[89]), "+f"(d[90]), "+f"(d[91]), "+f"(d[92]), "+f"(d[93]), "+f"(d[94]), "+f"(d[95])
    : "r"(da), "r"(db), "r"(scale_d));
}

__device__ __forceinline__ void wgmma_ss_n256(float (&d)[128], uint32_t da, uint32_t db, int scale_d) {
  asm volatile("{\n.reg .pred p;\n.reg .b64 da, db;\nsetp.ne.b32 p, %130, 0;\n"
    "mov.b64 da, {%128, 0x40000040};\nmov.b64 db, {%129, 0x40000040};\n"
    "wgmma.mma_async.sync.aligned.m64n256k16.f32.bf16.bf16 "
    "{%0, %1, %2, %3, %4, %5, %6, %7, %8, %9, %10, %11, %12, %13, %14, %15, "
    "%16, %17, %18, %19, %20, %21, %22, %23, %24, %25, %26, %27, %28, %29, %30, %31, "
    "%32, %33, %34, %35, %36, %37, %38, %39, %40, %41, %42, %43, %44, %45, %46, %47, "
    "%48, %49, %50, %51, %52, %53, %54, %55, %56, %57, %58, %59, %60, %61, %62, %63, "
    "%64, %65, %66, %67, %68, %69, %70, %71, %72, %73, %74, %75, %76, %77, %78, %79, "
    "%80, %81, %82, %83, %84, %85, %86, %87, %88, %89, %90, %91, %92, %93, %94, %95, "
    "%96, %97, %98, %99, %100, %101, %102, %103, %104, %105, %106, %107, %108, %109, %110, %111, "
    "%112, %113, %114, %115, %116, %117, %118, %119, %120, %121, %122, %123, %124, %125, %126, %127}, "
    "da, db, p, 1, 1, 0, 1;\n}\n"
    : "+f"(d[0]), "+f"(d[1]), "+f"(d[2]), "+f"(d[3]), "+f"(d[4]), "+f"(d[5]), "+f"(d[6]), "+f"(d[7]),
      "+f"(d[8]), "+f"(d[9]), "+f"(d[10]), "+f"(d[11]), "+f"(d[12]), "+f"(d[13]), "+f"(d[14]), "+f"(d[15]),
      "+f"(d[16]), "+f"(d[17]), "+f"(d[18]), "+f"(d[19]), "+f"(d[20]), "+f"(d[21]), "+f"(d[22]), "+f"(d[23]),
      "+f"(d[24]), "+f"(d[25]), "+f"(d[26]), "+f"(d[27]), "+f"(d[28]), "+f"(d[29]), "+f"(d[30]), "+f"(d[31]),
      "+f"(d[32]), "+f"(d[33]), "+f"(d[34]), "+f"(d[35]), "+f"(d[36]), "+f"(d[37]), "+f"(d[38]), "+f"(d[39]),
      "+f"(d[40]), "+f"(d[41]), "+f"(d[42]), "+f"(d[43]), "+f"(d[44]), "+f"(d[45]), "+f"(d[46]), "+f"(d[47]),
      "+f"(d[48]), "+f"(d[49]), "+f"(d[50]), "+f"(d[51]), "+f"(d[52]), "+f"(d[53]), "+f"(d[54]), "+f"(d[55]),
      "+f"(d[56]), "+f"(d[57]), "+f"(d[58]), "+f"(d[59]), "+f"(d[60]), "+f"(d[61]), "+f"(d[62]), "+f"(d[63]),
      "+f"(d[64]), "+f"(d[65]), "+f"(d[66]), "+f"(d[67]), "+f"(d[68]), "+f"(d[69]), "+f"(d[70]), "+f"(d[71]),
      "+f"(d[72]), "+f"(d[73]), "+f"(d[74]), "+f"(d[75]), "+f"(d[76]), "+f"(d[77]), "+f"(d[78]), "+f"(d[79]),
      "+f"(d[80]), "+f"(d[81]), "+f"(d[82]), "+f"(d[83]), "+f"(d[84]), "+f"(d[85]), "+f"(d[86]), "+f"(d[87]),
      "+f"(d[88]), "+f"(d[89]), "+f"(d[90]), "+f"(d[91]), "+f"(d[92]), "+f"(d[93]), "+f"(d[94]), "+f"(d[95]),
      "+f"(d[96]), "+f"(d[97]), "+f"(d[98]), "+f"(d[99]), "+f"(d[100]), "+f"(d[101]), "+f"(d[102]), "+f"(d[103]),
      "+f"(d[104]), "+f"(d[105]), "+f"(d[106]), "+f"(d[107]), "+f"(d[108]), "+f"(d[109]), "+f"(d[110]), "+f"(d[111]),
      "+f"(d[112]), "+f"(d[113]), "+f"(d[114]), "+f"(d[115]), "+f"(d[116]), "+f"(d[117]), "+f"(d[118]), "+f"(d[119]),
      "+f"(d[120]), "+f"(d[121]), "+f"(d[122]), "+f"(d[123]), "+f"(d[124]), "+f"(d[125]), "+f"(d[126]), "+f"(d[127])
    : "r"(da), "r"(db), "r"(scale_d));
}

namespace {

constexpr int SEQ = 2048, DM = 1024, FF = 3584;
constexpr int NCTA = 128;

constexpr uint32_t STG_OFF = 196608;
constexpr uint32_t MISC_OFF = STG_OFF + 32768;
constexpr uint32_t SMEM_BYTES = MISC_OFF + 3072;
constexpr uint32_t RED_OFF = 2 * 49152;
constexpr uint32_t MODB_OFF = MISC_OFF + 512;

enum { B_FQ = 0, B_EQ = 4, B_FW = 8, B_EW = 14, B_FG = 20, B_EG = 24, B_FD = 28, B_ED = 34,
       B_STGF = 40, B_MODB = 42, B_MODA = 45, B_RDY = 46, B_STGE = 58, B_COUNT = 60 };
enum { C_H = 0, C_O = 1, C_H2 = 3, C_ACT = 4, C_HA = 8, C_H2A = 9, C_A0 = 10, C_SP = 12 };

struct Params {
  uint4* modll;
  uint4* halo;
  uint2* stats2;
  unsigned* cnt;
  CUtensorMap h, o_ld, o_st, h2, act, out, wqkv, wqkv32, wo, wg, wu, wd, act_st, h2_st, wm;
};

__device__ __align__(1024) bf16 g_h[SEQ * DM];
__device__ __align__(1024) bf16 g_o[SEQ * DM];
__device__ __align__(1024) bf16 g_act[SEQ * FF];
__device__ __align__(1024) uint4 g_modll[3072 / 2];
__device__ __align__(1024) uint4 g_halo[16 * 8 * 2 * 2 * 8 * 32];
__device__ __align__(1024) uint2 g_stats[2 * SEQ * 8];
__device__ __align__(1024) unsigned g_cnt[16 * 32];
__device__ uint4 g_epoch;
#define TR(off)

__device__ __forceinline__ uint32_t smem_u32(const void* p) { return (uint32_t)__cvta_generic_to_shared(p); }
__device__ __forceinline__ void mbar_init(uint32_t bar, uint32_t count) {
  asm volatile("mbarrier.init.shared::cta.b64 [%0], %1;" ::"r"(bar), "r"(count));
}
__device__ __forceinline__ void mbar_arrive(uint32_t bar) {
  asm volatile("mbarrier.arrive.shared::cta.b64 _, [%0];" ::"r"(bar) : "memory");
}
__device__ __forceinline__ void mbar_arrive_cluster(uint32_t cluster_addr) {
  asm volatile("mbarrier.arrive.shared::cluster.b64 _, [%0];" ::"r"(cluster_addr) : "memory");
}
__device__ __forceinline__ uint32_t mapa(uint32_t addr, uint32_t cta) {
  uint32_t r;
  asm volatile("mapa.shared::cluster.u32 %0, %1, %2;" : "=r"(r) : "r"(addr), "r"(cta));
  return r;
}
__device__ __forceinline__ void jitter() {}
__device__ __forceinline__ void mbar_wait(uint32_t bar, uint32_t parity) {
  jitter();
  asm volatile(
      "{\n.reg .pred p;\n"
      "WAIT_%=:\n"
      "mbarrier.try_wait.parity.shared::cta.b64 p, [%0], %1;\n"
      "@!p bra WAIT_%=;\n}\n" ::"r"(bar), "r"(parity) : "memory");
}
__device__ __forceinline__ void mbar_wait_watchdog(uint32_t bar, uint32_t parity) {
  jitter();
  asm volatile(
      "{\n.reg .pred p;\n.reg .u64 t0, t1;\nmov.u64 t0, %%globaltimer;\n"
      "WAIT_%=:\n"
      "mbarrier.try_wait.parity.shared::cta.b64 p, [%0], %1;\n"
      "@p bra DONE_%=;\n"
      "mov.u64 t1, %%globaltimer;\n"
      "sub.u64 t1, t1, t0;\n"
      "setp.lt.u64 p, t1, 2000000000;\n"
      "@p bra WAIT_%=;\n"
      "trap;\n"
      "DONE_%=:\n}\n" ::"r"(bar), "r"(parity) : "memory");
}
__device__ __forceinline__ void cnt_wait(const unsigned* p, unsigned target) {
  asm volatile(
      "{\n.reg .pred p;\n.reg .u32 v;\n.reg .s32 d;\n"
      "WAIT_%=:\n"
      "ld.relaxed.gpu.global.u32 v, [%0];\n"
      "sub.s32 d, v, %1;\n"
      "setp.lt.s32 p, d, 0;\n"
      "@p bra WAIT_%=;\n"
      "fence.proxy.async.global;\n"
      "}\n" ::"l"(p), "r"(target) : "memory");
}
__device__ __forceinline__ void cnt_wait_lazy(const unsigned* p, unsigned target) {
  asm volatile(
      "{\n.reg .pred p;\n.reg .u32 v;\n.reg .s32 d;\n"
      "WAIT_%=:\n"
      "nanosleep.u32 400;\n"
      "ld.relaxed.gpu.global.u32 v, [%0];\n"
      "sub.s32 d, v, %1;\n"
      "setp.lt.s32 p, d, 0;\n"
      "@p bra WAIT_%=;\n"
      "fence.proxy.async.global;\n"
      "}\n" ::"l"(p), "r"(target) : "memory");
}
__device__ __forceinline__ void cnt_signal(unsigned* p) {
  jitter();
  asm volatile("{\n.reg .pred p;\nelect.sync _|p, 0xffffffff;\n@p red.relaxed.gpu.global.add.u32 [%0], 1;\n}\n" ::"l"(p) : "memory");
}
__device__ __forceinline__ void ll_store(uint4* p, uint32_t a, uint32_t b, uint32_t tag) {
  asm volatile("st.relaxed.gpu.global.v2.b64 [%0], {%1, %2};" ::"l"(p), "l"((uint64_t)a | ((uint64_t)tag << 32)),
               "l"((uint64_t)b | ((uint64_t)tag << 32)) : "memory");
}
__device__ __forceinline__ uint4 ll_peek(const uint4* p) {
  uint4 v;
  asm volatile("ld.relaxed.gpu.global.v4.u32 {%0, %1, %2, %3}, [%4];" : "=r"(v.x), "=r"(v.y), "=r"(v.z), "=r"(v.w) : "l"(p) : "memory");
  return v;
}
template <int N, int SLEEP = 0, class F>
__device__ __forceinline__ void ll_poll(F addr, uint32_t tag, uint32_t (&out)[2 * N]) {
  for (;;) {
    uint4 v[N];
#pragma unroll
    for (int i = 0; i < N; i++) v[i] = ll_peek(addr(i));
    uint32_t bad = 0;
#pragma unroll
    for (int i = 0; i < N; i++) {
      bad |= (v[i].y ^ tag) | (v[i].w ^ tag);
      out[2 * i] = v[i].x;
      out[2 * i + 1] = v[i].z;
    }
    if (__all_sync(~0u, bad == 0)) break;
    if (SLEEP) __nanosleep(SLEEP);
  }
}
constexpr uint64_t POLICY_EVICT_FIRST = 0x12F0000000000000ull;
__device__ __forceinline__ void expect_tx_elect(uint32_t bar, uint32_t bytes) {
  asm volatile("{\n.reg .pred p;\nelect.sync _|p, 0xffffffff;\n@p mbarrier.arrive.expect_tx.shared::cta.b64 _, [%0], %1;\n}\n" ::"r"(bar), "r"(bytes) : "memory");
}
__device__ __forceinline__ void arrive_elect(uint32_t bar) {
  asm volatile("{\n.reg .pred p;\nelect.sync _|p, 0xffffffff;\n@p mbarrier.arrive.shared::cta.b64 _, [%0];\n}\n" ::"r"(bar) : "memory");
}
__device__ __forceinline__ void tma_load(uint32_t dst, const CUtensorMap* m, uint32_t bar, int c0, int c1) {
  asm volatile("{\n.reg .pred p;\nelect.sync _|p, 0xffffffff;\n"
               "@p cp.async.bulk.tensor.2d.shared::cluster.global.mbarrier::complete_tx::bytes [%0], [%1, {%3, %4}], [%2];\n}\n"
               ::"r"(dst), "l"(m), "r"(bar), "r"(c0), "r"(c1) : "memory");
}
__device__ __forceinline__ void tma_load_mc(uint32_t dst, const CUtensorMap* m, uint32_t bar, int c0, int c1) {
  asm volatile("{\n.reg .pred p;\nelect.sync _|p, 0xffffffff;\n"
               "@p cp.async.bulk.tensor.2d.shared::cluster.global.mbarrier::complete_tx::bytes.multicast::cluster.L2::cache_hint [%0], [%1, {%3, %4}], [%2], %5, %6;\n}\n"
               ::"r"(dst), "l"(m), "r"(bar), "r"(c0), "r"(c1), "h"((uint16_t)3), "l"(POLICY_EVICT_FIRST) : "memory");
}
__device__ __forceinline__ void tma_load_ef(uint32_t dst, const CUtensorMap* m, uint32_t bar, int c0, int c1) {
  asm volatile("{\n.reg .pred p;\nelect.sync _|p, 0xffffffff;\n"
               "@p cp.async.bulk.tensor.2d.shared::cluster.global.mbarrier::complete_tx::bytes.L2::cache_hint [%0], [%1, {%3, %4}], [%2], %5;\n}\n"
               ::"r"(dst), "l"(m), "r"(bar), "r"(c0), "r"(c1), "l"(POLICY_EVICT_FIRST) : "memory");
}
__device__ __forceinline__ void tma_store2(const CUtensorMap* m, uint32_t src, int c0, int c1) {
  asm volatile("{\n.reg .pred p;\nelect.sync _|p, 0xffffffff;\n"
               "@p cp.async.bulk.tensor.2d.global.shared::cta.bulk_group [%0, {%2, %3}], [%1];\n}\n"
               ::"l"(m), "r"(src), "r"(c0), "r"(c1) : "memory");
}
__device__ __forceinline__ void tma_store3(const CUtensorMap* m, uint32_t src, int c0, int c1, int c2) {
  asm volatile("{\n.reg .pred p;\nelect.sync _|p, 0xffffffff;\n"
               "@p cp.async.bulk.tensor.3d.global.shared::cta.bulk_group [%0, {%2, %3, %4}], [%1];\n}\n"
               ::"l"(m), "r"(src), "r"(c0), "r"(c1), "r"(c2) : "memory");
}
__device__ __forceinline__ void tma_add3(const CUtensorMap* m, uint32_t src, int c0, int c1, int c2) {
  asm volatile("{\n.reg .pred p;\nelect.sync _|p, 0xffffffff;\n"
               "@p cp.reduce.async.bulk.tensor.3d.global.shared::cta.add.bulk_group [%0, {%2, %3, %4}], [%1];\n}\n"
               ::"l"(m), "r"(src), "r"(c0), "r"(c1), "r"(c2) : "memory");
}
__device__ __forceinline__ void store_pause(bool sleep) {
  asm volatile("cp.async.bulk.commit_group;" ::: "memory");
  asm volatile("cp.async.bulk.wait_group.read 0;" ::: "memory");
  if (sleep) __nanosleep(PAUSE);
}
__device__ __forceinline__ void l2_prefetch_tile(const CUtensorMap* m, int c0, int c1) {
  asm volatile("{\n.reg .pred p;\nelect.sync _|p, 0xffffffff;\n@p cp.async.bulk.prefetch.tensor.2d.L2.global [%0, {%1, %2}];\n}\n"
               ::"l"(m), "r"(c0), "r"(c1) : "memory");
}
__device__ __forceinline__ void prefetch_map(const CUtensorMap* m) {
  asm volatile("prefetch.tensormap [%0];" ::"l"(m) : "memory");
}
__device__ __forceinline__ void wg_fence() { asm volatile("wgmma.fence.sync.aligned;" ::: "memory"); }
__device__ __forceinline__ void wg_commit() { asm volatile("wgmma.commit_group.sync.aligned;" ::: "memory"); }
template <int N>
__device__ __forceinline__ void wg_wait() { asm volatile("wgmma.wait_group.sync.aligned %0;" ::"n"(N) : "memory"); }
__device__ __forceinline__ void bar_sync(int id, int n) { asm volatile("bar.sync %0, %1;" ::"r"(id), "r"(n) : "memory"); }
__device__ __forceinline__ void wg_bar(int cw) {
  asm volatile("{\n.reg .pred p;\nsetp.ne.s32 p, %0, 0;\n@p bar.sync 3, 128;\n@!p bar.sync 2, 128;\n}\n" ::"r"(cw) : "memory");
}
__device__ __forceinline__ void skew_pre(int cw) { if (cw == 1) bar_sync(5, 256); }
__device__ __forceinline__ void skew_post(int cw) { if (cw == 0) asm volatile("bar.arrive 5, 256;" ::: "memory"); }
__device__ __forceinline__ void cluster_arrive_relaxed() { asm volatile("barrier.cluster.arrive.relaxed.aligned;" ::: "memory"); }
__device__ __forceinline__ void cluster_wait() { asm volatile("barrier.cluster.wait.acquire.aligned;" ::: "memory"); }
__device__ __forceinline__ uint32_t load_epoch(const unsigned* p) {
  uint32_t e;
  asm volatile("ld.relaxed.gpu.global.u32 %0, [%1];" : "=r"(e) : "l"(p) : "memory");
  return e;
}
__device__ __forceinline__ uint32_t pack2(float lo, float hi) {
  uint32_t r;
  asm("cvt.rn.bf16x2.f32 %0, %1, %2;" : "=r"(r) : "f"(hi), "f"(lo));
  return r;
}
__device__ __forceinline__ float bf_lo(uint32_t v) { return __uint_as_float(v << 16); }
__device__ __forceinline__ float bf_hi(uint32_t v) { return __uint_as_float(v & 0xffff0000u); }
__device__ __forceinline__ uint32_t fma_bf2(uint32_t a, uint32_t b, uint32_t c) {
  uint32_t d;
  asm("fma.rn.bf16x2 %0, %1, %2, %3;" : "=r"(d) : "r"(a), "r"(b), "r"(c));
  return d;
}
__device__ __forceinline__ float bf_round(float v) { return __bfloat162float(__float2bfloat16_rn(v)); }
__device__ __forceinline__ float silu_f(float v) { return __fdividef(v, 1.0f + __expf(-v)); }
__device__ __forceinline__ uint4 ldg_nc(const void* p) {
  uint4 v;
  asm volatile("ld.global.nc.L1::no_allocate.v4.u32 {%0, %1, %2, %3}, [%4];" : "=r"(v.x), "=r"(v.y), "=r"(v.z), "=r"(v.w) : "l"(p));
  return v;
}
__device__ __forceinline__ void stmatrix4(uint32_t addr, uint32_t a, uint32_t b, uint32_t c, uint32_t d) {
  asm volatile("stmatrix.sync.aligned.m8n8.x4.shared.b16 [%0], {%1, %2, %3, %4};" ::"r"(addr), "r"(a), "r"(b), "r"(c), "r"(d) : "memory");
}
__device__ __forceinline__ void stmatrix2(uint32_t addr, uint32_t a, uint32_t b) {
  asm volatile("stmatrix.sync.aligned.m8n8.x2.shared.b16 [%0], {%1, %2};" ::"r"(addr), "r"(a), "r"(b) : "memory");
}
__device__ __forceinline__ void stmatrix1(uint32_t addr, uint32_t a) {
  asm volatile("stmatrix.sync.aligned.m8n8.x1.shared.b16 [%0], {%1};" ::"r"(addr), "r"(a) : "memory");
}
__device__ __forceinline__ uint32_t movmatrix(uint32_t a) {
  uint32_t d;
  asm("movmatrix.sync.aligned.m8n8.trans.b16 %0, %1;" : "=r"(d) : "r"(a));
  return d;
}
__device__ __forceinline__ void mma16816(float (&d)[4], uint32_t a0, uint32_t a1, uint32_t a2, uint32_t a3, uint32_t b0, uint32_t b1) {
  asm("mma.sync.aligned.m16n8k16.row.col.f32.bf16.bf16.f32 {%0, %1, %2, %3}, {%4, %5, %6, %7}, {%8, %9}, {%0, %1, %2, %3};"
               : "+f"(d[0]), "+f"(d[1]), "+f"(d[2]), "+f"(d[3]) : "r"(a0), "r"(a1), "r"(a2), "r"(a3), "r"(b0), "r"(b1));
}
__device__ __forceinline__ void mma1688(float (&d)[4], uint32_t a0, uint32_t a1, uint32_t b0) {
  asm("mma.sync.aligned.m16n8k8.row.col.f32.bf16.bf16.f32 {%0, %1, %2, %3}, {%4, %5}, {%6}, {%0, %1, %2, %3};"
               : "+f"(d[0]), "+f"(d[1]), "+f"(d[2]), "+f"(d[3]) : "r"(a0), "r"(a1), "r"(b0));
}
__device__ __forceinline__ void ldmatrix4t(uint32_t (&b)[4], uint32_t addr) {
  asm volatile("ldmatrix.sync.aligned.m8n8.x4.trans.shared.b16 {%0, %1, %2, %3}, [%4];" : "=r"(b[0]), "=r"(b[1]), "=r"(b[2]), "=r"(b[3]) : "r"(addr) : "memory");
}
__device__ __forceinline__ void ldmatrix4(uint32_t& a, uint32_t& b, uint32_t& c, uint32_t& d, uint32_t addr) {
  asm volatile("ldmatrix.sync.aligned.m8n8.x4.shared.b16 {%0, %1, %2, %3}, [%4];" : "=r"(a), "=r"(b), "=r"(c), "=r"(d) : "r"(addr) : "memory");
}
__device__ __forceinline__ void cp_async16(uint32_t dst, const void* src) {
  asm volatile("cp.async.cg.shared.global.L2::cache_hint [%0], [%1], 16, %2;" ::"r"(dst), "l"(src), "l"(POLICY_EVICT_FIRST) : "memory");
}
__device__ __forceinline__ uint32_t lds32(uint32_t addr) {
  uint32_t v;
  asm volatile("ld.shared.u32 %0, [%1];" : "=r"(v) : "r"(addr) : "memory");
  return v;
}
__device__ __forceinline__ void sts64f(uint32_t addr, float a, float b) {
  asm volatile("st.shared.v2.f32 [%0], {%1, %2};" ::"r"(addr), "f"(a), "f"(b) : "memory");
}
constexpr float QK_SCALE = 0.17677669529663687f;
__device__ __forceinline__ float softmax8(float& p0, float& p1) {
  float m = fmaxf(p0, p1);
  m = fmaxf(m, __shfl_xor_sync(~0u, m, 1));
  m = fmaxf(m, __shfl_xor_sync(~0u, m, 2));
  asm("ex2.approx.ftz.f32 %0, %1;" : "=f"(p0) : "f"((p0 - m) * 1.4426950408889634f));
  asm("ex2.approx.ftz.f32 %0, %1;" : "=f"(p1) : "f"((p1 - m) * 1.4426950408889634f));
  float s = p0 + p1;
  s += __shfl_xor_sync(~0u, s, 1);
  s += __shfl_xor_sync(~0u, s, 2);
  float r;
  asm("rcp.approx.ftz.f32 %0, %1;" : "=f"(r) : "f"(s));
  return r;
}
__device__ __forceinline__ void sts128(uint32_t addr, uint32_t a, uint32_t b, uint32_t c, uint32_t d) {
  asm volatile("st.shared.v4.u32 [%0], {%1, %2, %3, %4};" ::"r"(addr), "r"(a), "r"(b), "r"(c), "r"(d) : "memory");
}
__device__ __forceinline__ uint4 lds128(uint32_t addr) {
  uint4 v;
  asm volatile("ld.shared.v4.u32 {%0, %1, %2, %3}, [%4];" : "=r"(v.x), "=r"(v.y), "=r"(v.z), "=r"(v.w) : "r"(addr) : "memory");
  return v;
}
__device__ __forceinline__ float2 lds64f(uint32_t addr) {
  float2 v;
  asm volatile("ld.shared.v2.f32 {%0, %1}, [%2];" : "=f"(v.x), "=f"(v.y) : "r"(addr) : "memory");
  return v;
}
#define PROF_AT(cond, slot) do {} while (0)

constexpr uint32_t SMEM_BASE = 1024;
constexpr uint32_t DESC_A = (1u << 16) | (SMEM_BASE >> 4);
constexpr uint32_t DESC_B = ((8192u >> 4) << 16) | (SMEM_BASE >> 4);

template <int BN> struct Wg;
template <> struct Wg<128> { static __device__ __forceinline__ void mma(float (&d)[64], uint32_t a, uint32_t b, int s) { wgmma_ss_n128(d, a, b, s); } };
template <> struct Wg<192> { static __device__ __forceinline__ void mma(float (&d)[96], uint32_t a, uint32_t b, int s) { wgmma_ss_n192(d, a, b, s); } };
template <> struct Wg<256> { static __device__ __forceinline__ void mma(float (&d)[128], uint32_t a, uint32_t b, int s) { wgmma_ss_n256(d, a, b, s); } };

struct Ring {
  uint32_t full0, rel0;
  int s;
  uint32_t ph;
  uint32_t off;
  bool releaser;
};

template <int N>
__device__ __forceinline__ void fence_regs(float (&a)[N]) {
#pragma unroll
  for (int i = 0; i < N; i++) asm volatile("" : "+f"(a[i])::"memory");
}

template <int BN, int NST, uint32_t STAGE>
__device__ __forceinline__ void kblock(float (&acc)[BN / 2], Ring& g, uint32_t a_addr, bool zero, uint32_t& prev, uint32_t b_rel = 16384) {
  mbar_wait(g.full0 + 8 * g.s, g.ph);
  const uint32_t da = DESC_A + (a_addr >> 4);
  const uint32_t db = DESC_B + ((g.off + b_rel) >> 4);
  wg_fence();
#pragma unroll
  for (int k = 0; k < 4; k++) Wg<BN>::mma(acc, da + k * 2, db + k * 128, !(zero && k == 0));
  wg_commit();
  wg_wait<1>();
  jitter();
  if (prev != 0) mbar_arrive_cluster(prev);
  prev = g.releaser ? g.rel0 + 8 * g.s : 0u;
  if (++g.s == NST) { g.s = 0; g.ph ^= 1; }
  g.off += STAGE;
  if (g.off == NST * STAGE) g.off = 0;
}
template <int N>
__device__ __forceinline__ void tile_end(float (&acc)[N], uint32_t& prev) {
  wg_wait<0>();
  if (prev != 0) mbar_arrive_cluster(prev);
  prev = 0;
  fence_regs(acc);
}

__device__ __forceinline__ int other_kb(int q, int j) {
  const int ch = q >= 7, jj = q - 7 * ch;
  return 2 * (jj < j ? jj : jj + 1) + ch;
}
__device__ __forceinline__ int qkv_kb(int it, int j) {
  return it < 4 ? 2 * j + (it & 1) : other_kb(it < 18 ? it - 4 : it - 18, j);
}
__device__ __forceinline__ int wo_k(int it, int j) {
  return it < 8 ? it * 128 : (it == 8 ? j : (it - 9 < j ? it - 9 : it - 8)) * 128 + 64;
}
__device__ __forceinline__ int down_k(int d) {
  const int u = d + KH;
  if (u < 8) return u * 448 + 384;
  if (u < 40) return (((u - 8) & 15) >> 1) * 448 + ((u - 8) >> 4) * 128 + (u & 1) * 64;
  return (u & 7) * 448 + 256 + (u >= 48 ? 64 : 0);
}
__device__ __forceinline__ void wait_q_free(uint32_t empty, int i) {
  mbar_wait(empty + 8 * ((i * 2) / 3), 1);
  mbar_wait(empty + 8 * ((i * 2 + 1) / 3), 1);
}
__device__ __forceinline__ void wait_w_free(uint32_t empty, int i) {
  const int t = (i + 3) & 3, w0 = (t * 3) / 2, w1 = (t * 3 + 2) / 2;
  mbar_wait(empty + 8 * w0, w0 < 4);
  mbar_wait(empty + 8 * w1, w1 < 4);
}
__device__ __forceinline__ void wait_g_free(uint32_t empty, int i) {
  const int s = i < 4 ? i + 2 : i - 4, b0 = ((s * 2) / 3 + 1) & 3, b1 = ((s * 2 + 1) / 3 + 1) & 3;
  mbar_wait(empty + 8 * b0, b0 < 2);
  mbar_wait(empty + 8 * b1, b1 < 2);
}

__device__ __forceinline__ void chan(float& m, float& q, float m2, float q2, float n) {
  const float d = m2 - m;
  m = 0.5f * (m + m2);
  q = q + q2 + d * d * (0.5f * n);
}

__device__ __forceinline__ uint32_t tag16(uint32_t tag) { return tag % 65535u + 1u; }
__device__ __forceinline__ void stat_store(uint2* slot, float m, float q, uint32_t t16) {
  const uint32_t a = ((__float_as_uint(m) + 0x80u) & 0xffffff00u) | (t16 & 0xffu), b = ((__float_as_uint(q) + 0x80u) & 0xffffff00u) | (t16 >> 8);
  asm volatile("st.relaxed.gpu.global.b64 [%0], %1;" ::"l"(slot), "l"((uint64_t)a | ((uint64_t)b << 32)) : "memory");
}
__device__ __forceinline__ void stat_gather(const uint2* rows, uint32_t t16, int lane, float (&rs)[2], float (&nb)[2]) {
  const uint4* sp = (const uint4*)(rows + (lane >> 3) * 128) + (lane & 7);
  const uint32_t want = (t16 & 0xffu) | ((t16 >> 8) << 8);
  uint4 a, b;
  for (;;) {
    a = ll_peek(sp);
    b = ll_peek(sp + 256);
    const uint32_t bad = (__byte_perm(a.x, a.y, 0x40) ^ want) | (__byte_perm(a.z, a.w, 0x40) ^ want) | (__byte_perm(b.x, b.y, 0x40) ^ want) |
                         (__byte_perm(b.z, b.w, 0x40) ^ want);
    if (__all_sync(~0u, (bad & 0xffffu) == 0)) break;
  }
  float m0 = __uint_as_float(a.x & 0xffffff00u), q0 = __uint_as_float(a.y & 0xffffff00u);
  float m1 = __uint_as_float(a.z & 0xffffff00u), q1 = __uint_as_float(a.w & 0xffffff00u);
  chan(m0, q0, __uint_as_float(b.x & 0xffffff00u), __uint_as_float(b.y & 0xffffff00u), 128.f);
  chan(m1, q1, __uint_as_float(b.z & 0xffffff00u), __uint_as_float(b.w & 0xffffff00u), 128.f);
  const bool hi = lane & 8;
  float m = hi ? m1 : m0, q = hi ? q1 : q0;
  chan(m, q, __shfl_xor_sync(~0u, hi ? m0 : m1, 8), __shfl_xor_sync(~0u, hi ? q0 : q1, 8), 256.f);
  chan(m, q, __shfl_xor_sync(~0u, m, 16), __shfl_xor_sync(~0u, q, 16), 512.f);
  const float rstd = rsqrtf(q * (1.0f / DM) + 1e-5f), nmr = -m * rstd;
  const int r = lane >> 2, src = (r >> 1) + (r & 1) * 8;
  rs[0] = __shfl_sync(~0u, rstd, src); nb[0] = __shfl_sync(~0u, nmr, src);
  rs[1] = __shfl_sync(~0u, rstd, src + 4); nb[1] = __shfl_sync(~0u, nmr, src + 4);
}

__device__ __forceinline__ void publish_stats(const uint32_t (&xl)[16], const uint32_t (&xh)[16], uint2* slot, int lane, uint32_t t16) {
  float ds[4] = {0.f, 0.f, 0.f, 0.f}, dl[4] = {0.f, 0.f, 0.f, 0.f}, dh[4] = {0.f, 0.f, 0.f, 0.f};
#pragma unroll
  for (int q = 0; q < 8; q++) {
    mma16816(ds, xl[2 * q], xh[2 * q], xl[2 * q + 1], xh[2 * q + 1], 0x3f803f80u, 0x3f803f80u);
    mma16816(dl, xl[2 * q], xh[2 * q], xl[2 * q + 1], xh[2 * q + 1], xl[2 * q], xl[2 * q + 1]);
    mma16816(dh, xl[2 * q], xh[2 * q], xl[2 * q + 1], xh[2 * q + 1], xh[2 * q], xh[2 * q + 1]);
  }
  const int r = lane >> 2;
  if ((lane & 3) == (r >> 1)) {
    const float ml = ds[0] * (1.0f / 128), mh = ds[2] * (1.0f / 128);
    const float ql = fmaxf(((r & 1) ? dl[1] : dl[0]) - ds[0] * ml, 0.f), qh = fmaxf(((r & 1) ? dh[3] : dh[2]) - ds[2] * mh, 0.f);
    stat_store(slot + r, ml, ql, t16);
    stat_store(slot + r + 8, mh, qh, t16);
  }
  __syncwarp();
}

__device__ __forceinline__ void stage_slab(uint32_t chunk, int warp, int lane, const uint32_t (&lo)[8], const uint32_t (&hi)[8]) {
  const int row = warp * 16 + (lane & 7) + ((lane >> 3) & 1) * 8;
  const uint32_t rbase = chunk + row * 128;
#pragma unroll
  for (int q = 0; q < 4; q++) {
    const int grp = 2 * q + (lane >> 4);
    stmatrix4(rbase + ((grp ^ (row & 7)) << 4), lo[2 * q], hi[2 * q], lo[2 * q + 1], hi[2 * q + 1]);
  }
}
__device__ __forceinline__ float silu_mul(float g, float u) {
  float e, r;
  asm("ex2.approx.ftz.f32 %0, %1;" : "=f"(e) : "f"(g * -1.4426950408889634f));
  asm("rcp.approx.ftz.f32 %0, %1;" : "=f"(r) : "f"(1.0f + e));
  return g * r * u;
}
__device__ __forceinline__ uint32_t swiglu2(uint32_t g2, uint32_t u2) {
  asm volatile("" : "+r"(g2));
  return pack2(silu_mul(bf_lo(g2), bf_lo(u2)), silu_mul(bf_hi(g2), bf_hi(u2)));
}
__device__ __forceinline__ void stage_done(uint32_t bar, int lane) {
  asm volatile("fence.proxy.async.shared::cta;" ::: "memory");
  __syncwarp();
  if (lane == 0) mbar_arrive(bar);
}

__device__ __forceinline__ int fresh_tid() {
  int t;
  asm volatile("mov.u32 %0, %%tid.x;" : "=r"(t));
  return t;
}
#define RING_IDS()                                                                                           \
  const int tid = fresh_tid() - 128;                                                                         \
  const int cw = __shfl_sync(~0u, tid >> 7, 0), warp = __shfl_sync(~0u, (tid >> 5) & 3, 0);                  \
  const bool releaser = (tid & 31) < 2;                                                                      \
  const uint32_t rbars = mapa(bars, tid & 1);                                                                \
  const uint32_t a_base = cw * 8192
#define LANE_IDS()                                                                                           \
  const int lane = fresh_tid() & 31, r = lane >> 2, c = lane & 3;                                            \
  const int srow = warp * 16 + (lane & 7) + ((lane >> 3) & 1) * 8;                                           \
  const uint32_t slab = stg + cw * 8192 + srow * 128, sw0 = (lane >> 4) ^ (srow & 7);                        \
  (void)r; (void)c; (void)slab; (void)sw0

template <int NPRE, bool EAGER, class Step>
__device__ __forceinline__ void attention(float (&acc)[96], const Params& p, int rho, int rb, int cta, int cw, int warp, uint32_t tag,
                                          uint32_t stg, uint32_t bars, uint32_t& prev, Step step) {
  uint32_t ql[8], qh[8], k0[8], k1[8], v0[8], v1[8], hp[16];
  if (EAGER) {
    tile_end(acc, prev);
  } else {
    step();
    fence_regs(acc);
  }
#pragma unroll
  for (int t = 0; t < 8; t++) {
    k0[t] = pack2(acc[4 * (8 + t)], acc[4 * (8 + t) + 1]);
    k1[t] = pack2(acc[4 * (8 + t) + 2], acc[4 * (8 + t) + 3]);
    v0[t] = pack2(acc[4 * (16 + t)], acc[4 * (16 + t) + 1]);
    v1[t] = pack2(acc[4 * (16 + t) + 2], acc[4 * (16 + t) + 3]);
    asm volatile("" : "+r"(k0[t]), "+r"(k1[t]), "+r"(v0[t]), "+r"(v1[t]));
  }
  const int lane = fresh_tid() & 31, r = lane >> 2, c = lane & 3;
#pragma unroll
  for (int t = 0; t < 8; t++) v1[t] = movmatrix(v1[t]);
  mbar_wait(bars + 8 * B_STGE, rho);
  mbar_wait(bars + 8 * (B_STGE + 1), 0);
  const uint32_t xch = stg + 16384 + (cw * 4 + warp) * 2048 + lane * 16;
  if (warp < 3) {
    sts128(xch, k1[0], k1[1], k1[2], k1[3]);
    sts128(xch + 512, k1[4], k1[5], k1[6], k1[7]);
    sts128(xch + 1024, v1[0], v1[1], v1[2], v1[3]);
    sts128(xch + 1536, v1[4], v1[5], v1[6], v1[7]);
  } else if (rb < 15) {
    uint4* dst = p.halo + ((cta * 2 + rho) * 2 + cw) * 256 + lane;
#pragma unroll
    for (int t = 0; t < 4; t++) {
      ll_store(dst + t * 32, k1[2 * t], k1[2 * t + 1], tag);
      ll_store(dst + (4 + t) * 32, v1[2 * t], v1[2 * t + 1], tag);
    }
  }
#pragma unroll
  for (int t = 0; t < 8; t++) {
    v0[t] = movmatrix(v0[t]);
    ql[t] = pack2(acc[4 * t], acc[4 * t + 1]);
    qh[t] = pack2(acc[4 * t + 2], acc[4 * t + 3]);
    asm volatile("" : "+r"(v0[t]), "+r"(ql[t]), "+r"(qh[t]));
  }
#pragma unroll 1
  for (int i = 0; i < NPRE; i++) step();
  const uint4* src = p.halo + (((cta - 8) * 2 + rho) * 2 + cw) * 256 + lane;
  uint4 early[8] = {};
  if (warp == 0 && rb > 0) {
#pragma unroll
    for (int i = 0; i < 8; i++) early[i] = ll_peek(src + i * 32);
  }
  step();
  wg_bar(cw);
  if (warp > 0) {
#pragma unroll
    for (int t = 0; t < 4; t++) {
      const uint4 a = lds128(xch - 2048 + t * 512);
      hp[4 * t] = a.x; hp[4 * t + 1] = a.y; hp[4 * t + 2] = a.z; hp[4 * t + 3] = a.w;
    }
  } else if (rb > 0) {
    uint32_t bad = 0;
#pragma unroll
    for (int i = 0; i < 8; i++) {
      bad |= (early[i].y ^ tag) | (early[i].w ^ tag);
      hp[2 * i] = early[i].x;
      hp[2 * i + 1] = early[i].z;
    }
    if (!__all_sync(~0u, bad == 0)) ll_poll<8>([&](int i) { return src + i * 32; }, tag, hp);
  } else {
#pragma unroll
    for (int t = 0; t < 16; t++) hp[t] = 0;
  }
  wg_wait<0>();
  if (prev != 0) mbar_arrive_cluster(prev);
  prev = 0;
#pragma unroll
  for (int t = 0; t < 8; t++) asm volatile("" : "+r"(ql[t])::"memory");
  const bool up0 = 2 * c > r, up1 = 2 * c + 1 > r;
  const bool first = (rb == 0) && (warp == 0);
  uint32_t a0[2], a2[2], a3[2], a5[2];
  float il[2], ih[2];
#pragma unroll
  for (int h = 0; h < 2; h++) {
    float sp[4] = {0.f, 0.f, 0.f, 0.f}, s0[4] = {0.f, 0.f, 0.f, 0.f}, s1[4] = {0.f, 0.f, 0.f, 0.f};
#pragma unroll
    for (int ks = 0; ks < 2; ks++) {
      const int t = 4 * h + 2 * ks;
      mma16816(sp, ql[t], qh[t], ql[t + 1], qh[t + 1], hp[t], hp[t + 1]);
      mma16816(s0, ql[t], qh[t], ql[t + 1], qh[t + 1], k0[t], k0[t + 1]);
      mma16816(s1, ql[t], qh[t], ql[t + 1], qh[t + 1], k1[t], k1[t + 1]);
    }
    float p0 = (up0 ? sp[0] : s0[0]) * QK_SCALE, p1 = (up1 ? sp[1] : s0[1]) * QK_SCALE;
    float p2 = (up0 ? s0[2] : s1[2]) * QK_SCALE, p3 = (up1 ? s0[3] : s1[3]) * QK_SCALE;
    if (first && up0) p0 = -1000000000.0f;
    if (first && up1) p1 = -1000000000.0f;
    il[h] = softmax8(p0, p1);
    ih[h] = softmax8(p2, p3);
    a0[h] = pack2(up0 ? p0 : 0.f, up1 ? p1 : 0.f);
    a2[h] = pack2(up0 ? 0.f : p0, up1 ? 0.f : p1);
    a3[h] = pack2(up0 ? p2 : 0.f, up1 ? p3 : 0.f);
    a5[h] = pack2(up0 ? 0.f : p2, up1 ? 0.f : p3);
  }
  float o[8][4];
#pragma unroll
  for (int t = 0; t < 8; t++) {
#pragma unroll
    for (int q = 0; q < 4; q++) o[t][q] = 0.f;
    mma1688(o[t], 0u, a5[t >> 2], v1[t]);
    mma16816(o[t], a0[t >> 2], 0u, a2[t >> 2], a3[t >> 2], hp[8 + t], v0[t]);
  }
#pragma unroll
  for (int t = 0; t < 8; t++) fence_regs(o[t]);
  if (!EAGER) step();
  uint32_t ol[8], oh[8];
#pragma unroll
  for (int t = 0; t < 8; t++) {
    ol[t] = pack2(o[t][0] * il[t >> 2], o[t][1] * il[t >> 2]);
    oh[t] = pack2(o[t][2] * ih[t >> 2], o[t][3] * ih[t >> 2]);
  }
  if (!EAGER) step();
  stage_slab(stg + cw * 8192, warp, lane, ol, oh);
  stage_done(bars + 8 * B_STGF, lane);
  if (!EAGER) step();
}

__global__ void __launch_bounds__(384, 1) fused_kernel(const bf16* __restrict__ gx, const bf16* __restrict__ gwmod, const bf16* __restrict__ gc,
                                                          unsigned* gepoch, uint2* gstats1, const __grid_constant__ Params p) {
  extern __shared__ __align__(1024) uint8_t smem_raw[];
  const uint32_t sm = smem_u32(smem_raw);
  const uint32_t bars = sm + MISC_OFF;
  const uint32_t stg = sm + STG_OFF;
  const int rank = blockIdx.x & 1;
  const int cl = blockIdx.x >> 1;
  if (cl >= NCTA / 2) {
    const int e = blockIdx.x - NCTA, wid = __shfl_sync(~0u, (int)(threadIdx.x >> 5), 0), lane = threadIdx.x & 31;
    if (threadIdx.x == 0) {
      for (int i = 0; i < 6; i++) { mbar_init(bars + 8 * i, 1); mbar_init(bars + 8 * (6 + i), 8); }
      for (int i = 0; i < 8; i++) { mbar_init(bars + 8 * (16 + i), 1); mbar_init(bars + 8 * (24 + i), 4); }
      mbar_init(bars + 8 * 12, 1);
      asm volatile("fence.mbarrier_init.release.cluster;" ::: "memory");
    }
    const uint32_t tag = load_epoch(gepoch) + 1;
    if (threadIdx.x < 256) ll_store(p.modll + 512 + (threadIdx.x >> 6) * 256 + e * 64 + (threadIdx.x & 63), 0u, 0u, 0u);
    for (int i = threadIdx.x; i < 1536; i += 384) {
      uint4 o = make_uint4(0u, 0u, 0u, 0u);
      if (i < 1024 && (i & 63) < 8) {
        const uint4 cv = ldg_nc(gc + (i >> 6) * 64 + (i & 7) * 8);
        o = make_uint4(pack2(silu_f(bf_lo(cv.x)), silu_f(bf_hi(cv.x))), pack2(silu_f(bf_lo(cv.y)), silu_f(bf_hi(cv.y))),
                       pack2(silu_f(bf_lo(cv.z)), silu_f(bf_hi(cv.z))), pack2(silu_f(bf_lo(cv.w)), silu_f(bf_hi(cv.w))));
      }
      sts128(stg + i * 16, o.x, o.y, o.z, o.w);
    }
    asm volatile("fence.proxy.async.shared::cta;" ::: "memory");
    __syncthreads();
    if (wid == 0) {
      __nanosleep(WMDELAY);
      uint32_t ph = 1;
#pragma unroll 1
      for (int it = 0, s = 0; it < 64; it++) {
        mbar_wait(bars + 8 * (6 + s), ph);
        expect_tx_elect(bars + 8 * s, 32768);
#pragma unroll
        for (int q = 0; q < 4; q++) tma_load_ef(sm + s * 32768 + q * 8192, &p.wm, bars + 8 * s, 2048 + (it >> 4) * 1024 + e * 256 + q * 64, (it & 15) * 64);
        if (++s == 6) { s = 0; ph ^= 1; }
      }
    } else if (wid == 1) {
      __nanosleep(PFW);
#pragma unroll 1
      for (int i = 0; i < 64; i++) {
        l2_prefetch_tile(&p.wo, (i & 15) * 64, (e * 4 + (i >> 4)) * 64);
      }
#pragma unroll 1
      for (int i = 0; i < 80; i++) {
        if (i < 64) l2_prefetch_tile((i & 1) ? &p.wu : &p.wg, ((i >> 1) & 7) * 448 + 384, ((i >> 4) * 4 + e) * 64);
        else l2_prefetch_tile((i & 2) ? &p.wu : &p.wg, (e * 2 + ((i >> 3) & 1)) * 448 + (i & 1) * 64, (e * 4 + ((i >> 2) & 3)) * 64);
      }
    } else if (wid >= 4) {
      const int hf = (wid >> 2) - 1;
      uint32_t ph = 0;
      int s = 0;
#pragma unroll 1
      for (int v = 0; v < 4; v++) {
        float acc[64];
#pragma unroll 1
        for (int kb = 0; kb < 16; kb++) {
          mbar_wait_watchdog(bars + 8 * s, ph);
          const uint32_t da = DESC_A + ((STG_OFF + kb * 1024) >> 4), db = DESC_B + ((s * 32768 + hf * 16384) >> 4);
          wg_fence();
#pragma unroll
          for (int k = 0; k < 4; k++) wgmma_ss_n128(acc, da + k * 2, db + k * 128, (kb | k) != 0);
          wg_commit();
          wg_wait<0>();
          if (lane == 0) mbar_arrive(bars + 8 * (6 + s));
          if (++s == 6) { s = 0; ph ^= 1; }
        }
        fence_regs(acc);
        if ((wid & 3) == 0) {
#pragma unroll
          for (int n = 0; n < 16; n++) {
            const uint32_t mine = pack2(acc[4 * n], acc[4 * n + 1]), next = __shfl_down_sync(~0u, mine, 1);
            if (lane < 4 && (lane & 1) == 0) ll_store(p.modll + 512 + v * 256 + e * 64 + hf * 32 + n * 2 + (lane >> 1), mine, next, tag);
            if (lane < 4) sts64f(sm + MODB_OFF + (hf * 128 + n * 8 + lane * 2) * 4, bf_lo(mine), bf_hi(mine));
          }
        }
      }
    }
    __syncthreads();
    if (wid == 0 || wid == 2) {
      const int w = wid >> 1;
      if (w == 0) {
        expect_tx_elect(bars + 8 * 12, KH * 32768);
#pragma unroll 1
        for (int q = 0; q < 4 * KH; q++) tma_load_ef(sm + q * 8192, &p.wd, bars + 8 * 12, e * 256 + (q & 3) * 64, (q >> 2) * 448 + 384);
      }
      cnt_wait_lazy(p.cnt + C_ACT, tag * 8);
      if (w == 1) __nanosleep(900);
      uint32_t ph = 1, ready = 0;
#pragma unroll 1
      for (int it = 0, s = 0; it < 16 * KH; it++) {
        const int rb = it / KH, kc = it - rb * KH;
        while (!((ready >> rb) & 1)) {
          ready = __ballot_sync(~0u, (int)(load_epoch(p.cnt + (lane & 15) * 32 + C_ACT) - tag * 8) >= 0);
          asm volatile("fence.proxy.async.global;" ::: "memory");
        }
        const uint32_t fb = bars + 8 * (16 + w * 4 + s), dst = sm + 98304 + w * 32768 + s * 8192;
        mbar_wait(fb + 64, ph);
        expect_tx_elect(fb, 8192);
        tma_load(dst, &p.act_st, fb, kc * 448 + 384, rb * 128 + w * 64);
        tma_load(dst + 4096, &p.act_st, fb, kc * 448 + 384, rb * 128 + w * 64 + 32);
        if (++s == 4) { s = 0; ph ^= 1; }
      }
    } else if (wid >= 4) {
      const int w = (wid >> 2) - 1, warp = wid & 3;
      const uint32_t out_stg = (w ? stg : sm + 163840) + warp * 2048;
      const uint32_t slab = out_stg + (lane & 15) * 128, sw0 = (lane >> 4) ^ (lane & 7);
      mbar_wait_watchdog(bars + 8 * 12, 0);
#pragma unroll 1
      for (int i = threadIdx.x - 128; i < KH * 2048; i += 256) {
        const uint32_t gp = sm + MODB_OFF + (((i >> 9) & 3) * 64 + ((i ^ (i >> 3)) & 7) * 8) * 4;
        const uint4 v = lds128(sm + i * 16), ga = lds128(gp), gc = lds128(gp + 16);
        sts128(sm + i * 16, pack2(bf_lo(v.x) * __uint_as_float(ga.x), bf_hi(v.x) * __uint_as_float(ga.y)),
               pack2(bf_lo(v.y) * __uint_as_float(ga.z), bf_hi(v.y) * __uint_as_float(ga.w)),
               pack2(bf_lo(v.z) * __uint_as_float(gc.x), bf_hi(v.z) * __uint_as_float(gc.y)),
               pack2(bf_lo(v.w) * __uint_as_float(gc.z), bf_hi(v.w) * __uint_as_float(gc.w)));
      }
      asm volatile("fence.proxy.async.shared::cta;" ::: "memory");
      bar_sync(1, 256);
      uint32_t ph = 0;
      int s = 0;
#pragma unroll 1
      for (int rb = 0; rb < 16; rb++) {
        float acc[128];
#pragma unroll 1
        for (int kc = 0; kc < KH; kc++) {
          mbar_wait_watchdog(bars + 8 * (16 + w * 4 + s), ph);
          const uint32_t da = DESC_A + ((98304 + w * 32768 + s * 8192) >> 4), db = DESC_B + ((kc * 32768) >> 4);
          wg_fence();
#pragma unroll
          for (int k = 0; k < 4; k++) wgmma_ss_n256(acc, da + k * 2, db + k * 128, (kc | k) != 0);
          wg_commit();
          wg_wait<1>();
          if (kc > 0 && lane == 0) mbar_arrive(bars + 8 * (24 + w * 4 + ((s + 3) & 3)));
          if (++s == 4) { s = 0; ph ^= 1; }
        }
        asm volatile("cp.async.bulk.wait_group 0;" ::: "memory");
        __syncwarp();
        if (rb > 0) cnt_signal(p.cnt + (rb - 1) * 32 + C_SP + e);
        wg_wait<0>();
        fence_regs(acc);
        __syncwarp();
        if (lane == 0) mbar_arrive(bars + 8 * (24 + w * 4 + ((s + 3) & 3)));
#pragma unroll
        for (int q = 0; q < 16; q++)
          stmatrix4(slab + (q >> 2) * 8192 + ((sw0 ^ ((q & 3) * 2)) << 4), pack2(acc[8 * q], acc[8 * q + 1]), pack2(acc[8 * q + 2], acc[8 * q + 3]),
                    pack2(acc[8 * q + 4], acc[8 * q + 5]), pack2(acc[8 * q + 6], acc[8 * q + 7]));
        asm volatile("fence.proxy.async.shared::cta;" ::: "memory");
        __syncwarp();
#pragma unroll
        for (int ch = 0; ch < 4; ch++) tma_add3(&p.out, out_stg + ch * 8192, e * 256 + ch * 64, rb * 64 + warp * 16, w);
        asm volatile("cp.async.bulk.commit_group;" ::: "memory");
      }
      asm volatile("cp.async.bulk.wait_group 0;" ::: "memory");
      __syncwarp();
      cnt_signal(p.cnt + 15 * 32 + C_SP + e);
    }
    return;
  }
  const int q7 = ((cl - 36) * 37) >> 8;
  const int j = cl < 4 ? 4 + cl : (cl < 36 ? (cl - 4) >> 3 : 4 + q7);
  const int rb = (cl < 4 ? 0 : (cl < 36 ? (cl - 4) & 7 : cl - 35 - 7 * q7)) * 2 + rank;
  const int cta = rb * 8 + j;
  PROF_AT(threadIdx.x == 0, 0);

  if (threadIdx.x < 128) {
    asm volatile("setmaxnreg.dec.sync.aligned.u32 40;");
    const int warp = __shfl_sync(~0u, (int)(threadIdx.x >> 5), 0), lane = threadIdx.x & 31;
    if (threadIdx.x == 0) {
      const uint32_t ep = load_epoch(gepoch);
      if ((sm & 0x3FFFF) != SMEM_BASE) asm volatile("trap;");
      for (int i = 0; i < 4; i++) { mbar_init(bars + 8 * (B_FQ + i), 1); mbar_init(bars + 8 * (B_EQ + i), 16); }
      for (int i = 0; i < 6; i++) { mbar_init(bars + 8 * (B_FW + i), 1); mbar_init(bars + 8 * (B_EW + i), 16); }
      for (int i = 0; i < 4; i++) { mbar_init(bars + 8 * (B_FG + i), 1); mbar_init(bars + 8 * (B_EG + i), 16); }
      for (int i = 0; i < 6; i++) { mbar_init(bars + 8 * (B_FD + i), 1); mbar_init(bars + 8 * (B_ED + i), 16); }
      for (int i = 0; i < 2; i++) { mbar_init(bars + 8 * (B_STGF + i), 8); mbar_init(bars + 8 * (B_STGE + i), 1); }
      mbar_init(bars + 8 * B_MODB, 1);
      mbar_init(bars + 8 * (B_MODB + 1), 1);
      mbar_init(bars + 8 * B_MODA, 1);
      for (int i = 0; i < 11; i++) mbar_init(bars + 8 * (B_RDY + i), 1);
      asm volatile("st.shared.u32 [%0], %1;" ::"r"(bars + 8 * B_COUNT), "r"(ep + 1) : "memory");
      asm volatile("fence.mbarrier_init.release.cluster;\nfence.acq_rel.cta;" ::: "memory");
    }
    __syncwarp();
    cluster_arrive_relaxed();
    unsigned* cnt = p.cnt + rb * 32;
    cluster_wait();
    const uint32_t tag = lds32(bars + 8 * B_COUNT);
    const unsigned target = tag * 8;
    if (warp == 0) {
      const CUtensorMap* wgu = rank ? &p.wu : &p.wg;
      uint32_t st = sm + 16384, fb = bars + 8 * B_FQ, ph = 1;
      __nanosleep(BDELAY);
#pragma unroll 1
      for (int it = 0; it < 32; it++) {
        const int kb = qkv_kb(it, j), col = j * 128 + ((it < 4 ? it >= 2 : it >= 18) ? 64 : 0);
        if (it == 2) mbar_wait(bars + 8 * B_MODA, 0);
        mbar_wait(fb + 8 * (B_EQ - B_FQ), ph);
        expect_tx_elect(fb, it < 4 ? 24576 : 40960);
        tma_load_mc(st + rank * 8192, &p.wqkv, fb, col + rank * 1024, kb * 64);
        tma_load_mc(st + 16384 + rank * 4096, &p.wqkv32, fb, col + 2048, kb * 64 + rank * 32);
        st += 49152; fb += 8;
        if ((it & 3) == 3) { st -= 4 * 49152; fb -= 32; ph ^= 1; }
      }
      fb = bars + 8 * B_FW; ph = 1;
#pragma unroll 1
      for (int it = 0, s = 0; it < 34; it++) {
        if (it < 6) wait_q_free(bars + 8 * B_EQ, it);
        if (it == 16) mbar_wait(bars + 8 * (B_FW + 3), 0);
        mbar_wait(fb + 8 * (B_EW - B_FW), ph);
        expect_tx_elect(fb, (it == 8 || it == 18 || it == 19) ? 16384 : 32768);
        const int k0 = it < 16 ? wo_k(it, j) : (it < 20 ? 2 * j + (it & 1) : other_kb(it - 20, j)) * 64;
        if (it == 16 || it == 17) {
          tma_load_mc(st - 16384 + rank * 16384, wgu, fb, j * 448, k0);
          tma_load_mc(st - 8192 + rank * 16384, wgu, fb, j * 448 + 64, k0);
        } else {
          tma_load_mc(st + rank * 8192, it < 16 ? &p.wo : wgu, fb, it < 16 ? j * 128 + rank * 64 : j * 448 + 384, k0);
        }
        st += 32768; fb += 8;
        if (++s == 6) { s = 0; st -= 6 * 32768; fb -= 48; ph ^= 1; }
      }
      st = sm + 16384 + 3 * 49152; fb = bars + 8 * B_FG; ph = 1;
#pragma unroll 1
      for (int it = 0; it < 46; it++) {
        const int kb = it < 14 ? other_kb(it, j) : (it + 2) & 15, col = j * 448 + ((it + 2) >> 4) * 128;
        if (it < 4) wait_w_free(bars + 8 * B_EW, it);
        mbar_wait(fb + 8 * (B_EG - B_FG), ph);
        expect_tx_elect(fb, 49152);
        tma_load_mc(st + rank * 16384, wgu, fb, col, kb * 64);
        tma_load_mc(st + rank * 16384 + 8192, wgu, fb, col + 64, kb * 64);
        st += (it & 3) == 0 ? -3 * 49152 : 49152; fb += 8;
        if ((it & 3) == 3) { fb -= 32; ph ^= 1; }
      }
      st = sm + 16384 + 2 * 32768; fb = bars + 8 * B_FD; ph = 1;
#pragma unroll 1
      for (int it = 0, s = 0; it < 56 - KH; it++) {
        if (it < 6) wait_g_free(bars + 8 * B_EG, it);
        mbar_wait(fb + 8 * (B_ED - B_FD), ph);
        expect_tx_elect(fb, 32768);
        tma_load_mc(st + rank * 8192, &p.wd, fb, j * 128 + rank * 64, down_k(it));
        st += s == 3 ? -5 * 32768 : 32768; fb += 8;
        if (++s == 6) { s = 0; fb -= 48; ph ^= 1; }
      }
    } else if (warp == 1) {
      const int arow = rb * 128;
      uint32_t st = sm, fb = bars + 8 * B_FQ, ph = 0;
      cnt_wait(cnt + C_HA, target);
      PROF_AT(lane == 0, 16);
#pragma unroll 1
      for (int it = 4; it < 32; it++) {
        if (it == 11) mbar_wait(bars + 8 * (B_RDY + C_H), 0);
        mbar_wait(fb + 8 * (B_EQ - B_FQ), ph);
        tma_load(st, &p.h, fb, qkv_kb(it, j) * 64, arow);
        st += 49152; fb += 8;
        if ((it & 3) == 3) { st -= 4 * 49152; fb -= 32; ph ^= 1; }
      }
      fb = bars + 8 * B_FW; ph = 1;
#pragma unroll 1
      for (int it = 0, s = 0; it < 34; it++) {
        if (it < 16 || it >= 20) {
          if (it < 6) wait_q_free(bars + 8 * B_EQ, it);
          mbar_wait(fb + 8 * (B_EW - B_FW), ph);
          if (it == 0) mbar_wait(bars + 8 * (B_RDY + C_O), 0);
          if (it == 9 || it == 20) cnt_wait(cnt + (it == 9 ? C_O + 1 : C_H2A), target * 8);
          if (it == 27) mbar_wait(bars + 8 * (B_RDY + C_H2), 0);
          PROF_AT(lane == 0 && (it == 0 || it == 9 || it == 20), 17 + (it >> 3));
          if (it != 8) tma_load(st, it < 16 ? &p.o_ld : &p.h2, fb, it < 16 ? wo_k(it, j) : other_kb(it - 20, j) * 64, arow);
        }
        st += 32768; fb += 8;
        if (++s == 6) { s = 0; st -= 6 * 32768; fb -= 48; ph ^= 1; }
      }
      st = sm + 3 * 49152; fb = bars + 8 * B_FG; ph = 1;
#pragma unroll 1
      for (int it = 0; it < 46; it++) {
        if (it < 4) wait_w_free(bars + 8 * B_EW, it);
        mbar_wait(fb + 8 * (B_EG - B_FG), ph);
        tma_load(st, &p.h2, fb, (it < 14 ? other_kb(it, j) : (it + 2) & 15) * 64, arow);
        st += (it & 3) == 0 ? -3 * 49152 : 49152; fb += 8;
        if ((it & 3) == 3) { fb -= 32; ph ^= 1; }
      }
      st = sm + 2 * 32768; fb = bars + 8 * B_FD; ph = 1;
#pragma unroll 1
      for (int it = 0, s = 0; it < 56 - KH; it++) {
        if (it < 6) wait_g_free(bars + 8 * B_EG, it);
        mbar_wait(fb + 8 * (B_ED - B_FD), ph);
        const int u = it + KH, dep = it == 0 ? C_ACT : (u == 8 ? C_ACT + 1 : (u == 24 ? C_ACT + 2 : (u == 40 ? C_A0 : (u == 48 ? C_ACT + 3 : -1))));
        if (dep >= 0) mbar_wait(bars + 8 * (B_RDY + dep), 0);
        tma_load(st, &p.act, fb, down_k(it), arow);
        st += s == 3 ? -5 * 32768 : 32768; fb += 8;
        if (++s == 6) { s = 0; fb -= 48; ph ^= 1; }
      }
    } else if (warp == 2) {
      if (lane < 14) prefetch_map(&p.h + lane);
      __syncwarp();
      uint32_t ph1 = 0;
#pragma unroll 1
      for (int n = 0; n < 8; n++) {
        const int nch = (n == 1 || n == 2 || n == 4) ? 1 : 2;
#pragma unroll 1
        for (int ch = 0; ch < nch; ch++) {
          mbar_wait_watchdog(bars + 8 * (B_STGF + ch), ch ? ph1 : (n & 1));
          const uint32_t src = stg + ch * 16384;
          if (n == 2 || n == 3) {
          } else if (n == 1) {
#pragma unroll 1
            for (int q = 0; q < 8; q++) {
              tma_store2(&p.o_st, src + q * 2048, j * 128, rb * 128 + q * 16);
              if (q & 1) store_pause(true);
            }
          } else if (n >= 4 && n < 8) {
#pragma unroll 1
            for (int q = 0; q < 4; q++) {
              tma_store2(&p.act_st, src + q * 4096, j * 448 + (n == 4 ? 384 : (n - 5) * 128 + ch * 64), rb * 128 + q * 32);
              store_pause(true);
            }
          } else {
            tma_store2(&p.h, src, j * 128 + ch * 64, rb * 128);
            asm volatile("cp.async.bulk.commit_group;" ::: "memory");
            if (ch == 1) {
              asm volatile("cp.async.bulk.wait_group 1;" ::: "memory");
              __syncwarp();
              cnt_signal(cnt + C_HA);
            }
          }
          if (n >= 5 && ch == 0) arrive_elect(bars + 8 * B_STGE);
          if (n == 7 && ch == 0) {
            asm volatile("cp.async.bulk.wait_group 0;" ::: "memory");
            __syncwarp();
            cnt_signal(cnt + C_A0);
          }
        }
        asm volatile("cp.async.bulk.commit_group;" ::: "memory");
        asm volatile("cp.async.bulk.wait_group 0;" ::: "memory");
        __syncwarp();
        if (n != 2 && n != 3) cnt_signal(cnt + n);
        PROF_AT(lane == 0, n == 0 ? 33 : 23 + n);
        if (n == 0) {
#pragma unroll 1
          for (int t = 0; t < 34; t++) {
            ll_store(t < 32 ? p.halo + cta * 1024 + t * 32 + lane : (uint4*)(p.stats2 + cta * 128) + (t - 32) * 32 + lane, 0u, 0u, 0u);
            __nanosleep(40);
          }
          __syncwarp();
        }
        if (n < 5) arrive_elect(bars + 8 * B_STGE);
        if (nch == 2) { arrive_elect(bars + 8 * (B_STGE + 1)); ph1 ^= 1; }
      }
      mbar_wait_watchdog(bars + 8 * B_STGF, 0);
      PROF_AT(lane == 0, 31);
    } else {
      if (lane < 4) ll_store(p.modll + cta * 4 + lane, 0u, 0u, 0u);
      bar_sync(1, 288);
      {
        const uint4 t4 = lds128(sm + RED_OFF + lane * 16);
        float a[4] = {__uint_as_float(t4.x), __uint_as_float(t4.y), __uint_as_float(t4.z), __uint_as_float(t4.w)};
#pragma unroll
        for (int o = 4; o < 32; o <<= 1)
#pragma unroll
          for (int q = 0; q < 4; q++) a[q] += __shfl_xor_sync(~0u, a[q], o);
        if (lane < 4) ll_store(p.modll + cta * 4 + lane, pack2(a[0], a[1]), pack2(a[2], a[3]), tag);
        PROF_AT(lane == 0, 1);
        uint32_t m[4];
        const uint4* mp = p.modll + j * 32 + lane;
        ll_poll<2>([&](int i) { return mp + i * 256; }, tag, m);
        const uint32_t c0 = pack2(1.0f + bf_lo(m[2]), 1.0f + bf_hi(m[2])), c1 = pack2(1.0f + bf_lo(m[3]), 1.0f + bf_hi(m[3]));
        sts128(sm + MODB_OFF + lane * 16, c0, m[0], c1, m[1]);
        __syncwarp();
        arrive_elect(bars + 8 * B_MODA);
      }
#pragma unroll 1
      for (int n = C_H; n <= C_O; n++) {
        cnt_wait_lazy(cnt + n, target);
        arrive_elect(bars + 8 * (B_RDY + n));
      }
      {
        uint32_t m[6];
        const uint4* src = p.modll + 512 + j * 32 + lane;
        ll_poll<3, 500>([&](int i) { return src + i * 256; }, tag, m);
#pragma unroll
        for (int vec = 0; vec < 3; vec++) {
          const float add = vec == 2 ? 1.0f : 0.0f;
          sts128(sm + MODB_OFF + (vec * 128 + lane * 4) * 4, __float_as_uint(bf_round(bf_lo(m[2 * vec]) + add)), __float_as_uint(bf_round(bf_hi(m[2 * vec]) + add)),
                 __float_as_uint(bf_round(bf_lo(m[2 * vec + 1]) + add)), __float_as_uint(bf_round(bf_hi(m[2 * vec + 1]) + add)));
        }
        __syncwarp();
        if (lane == 0) mbar_arrive(bars + 8 * B_MODB);
        PROF_AT(lane == 0, 15);
      }
      __syncwarp();
#pragma unroll 1
      for (int q = C_H2; q < 9; q++) {
        const int n = q < 7 ? q : (q == 7 ? C_A0 : C_ACT + 3);
        cnt_wait_lazy(cnt + n, n == C_H2 ? target * 8 : target);
        arrive_elect(bars + 8 * (B_RDY + n));
      }
      {
        uint32_t m[2];
        const uint4* src = p.modll + 512 + 768 + j * 32 + lane;
        ll_poll<1>([&](int) { return src; }, tag, m);
        sts128(sm + MODB_OFF + (384 + lane * 4) * 4, m[0] << 16, m[0] & 0xffff0000u, m[1] << 16, m[1] & 0xffff0000u);
        cnt_wait_lazy(cnt + C_SP + (j >> 1), target);
        __syncwarp();
        if (lane == 0) mbar_arrive(bars + 8 * (B_MODB + 1));
      }
    }
  } else {
    uint32_t tag;

    {
      const int tid = threadIdx.x - 128, cw = tid >> 7, warp = (tid >> 5) & 3, lane = tid & 31;
      const int l16 = lane & 15, half = lane >> 4, w8 = cw * 4 + warp;
      const uint32_t cbuf = sm + 3 * 49152 + w8 * 512;
      if (lane < 16) cp_async16(cbuf + lane * 16, gc + w8 * 128 + lane * 8);
      asm volatile("cp.async.commit_group;" ::: "memory");
      const uint32_t xbuf = sm + 40960 + (cw * 2 + (l16 >> 3)) * 49152 + (warp * 16 + half) * 128;
      {
        const char* xp = (const char*)gx + (uint32_t)((rb * 128 + (warp * 16 + half) * 2 + cw) * 2048 + j * 256 + l16 * 16);
#pragma unroll
        for (int i = 0; i < 8; i++) cp_async16(xbuf + i * 256 + (((l16 & 7) ^ ((i * 2 + half) & 7)) << 4), xp + i * 8192);
      }
      asm volatile("cp.async.commit_group;" ::: "memory");
      const uint32_t wbuf = sm + cw * 49152 + warp * 4096;
      {
        const char* wp = (const char*)gwmod + (uint32_t)(cta * 32 + (lane & 1) * 16 + (w8 * 128 + (lane >> 1)) * 12288);
#pragma unroll
        for (int i = 0; i < 8; i++) cp_async16(wbuf + i * 512 + lane * 16, wp + i * 16 * 12288);
      }
      asm volatile("cp.async.commit_group;" ::: "memory");
      PROF_AT(tid == 0, 32);
      uint2* st1 = gstats1 + (rb * 8 + j) * 128 + cw * 64 + warp * 16;
      if (lane < 8) ll_store((uint4*)st1 + lane, 0u, 0u, 0u);
      __syncwarp();
      cluster_arrive_relaxed();
      asm volatile("setmaxnreg.inc.sync.aligned.u32 232;");
      uint32_t sa[4][4];
      {
        asm volatile("cp.async.wait_group 2;" ::: "memory");
        __syncwarp();
        const float2 cv = lds64f(cbuf + lane * 8);
        const uint32_t c0 = __float_as_uint(cv.x), c1 = __float_as_uint(cv.y);
        sts64f(cbuf + lane * 8, __uint_as_float(pack2(silu_f(bf_lo(c0)), silu_f(bf_hi(c0)))), __uint_as_float(pack2(silu_f(bf_lo(c1)), silu_f(bf_hi(c1)))));
        __syncwarp();
#pragma unroll
        for (int q = 0; q < 4; q++) ldmatrix4(sa[q][0], sa[q][1], sa[q][2], sa[q][3], cbuf + q * 64 + (lane >> 3) * 16);
      }
      cluster_wait();
      tag = lds32(bars + 8 * B_COUNT);
      asm volatile("cp.async.wait_group 1;" ::: "memory");
      __syncwarp();
      uint32_t xl[16], xh[16];
      {
        const int srow = warp * 16 + (lane & 15);
#pragma unroll
        for (int q = 0; q < 8; q++)
          ldmatrix4(xl[2 * q], xh[2 * q], xl[2 * q + 1], xh[2 * q + 1],
                    sm + 40960 + (cw * 2 + (q >> 2)) * 49152 + srow * 128 + (((half + (q & 3) * 2) ^ (srow & 7)) << 4));
      }
      publish_stats(xl, xh, st1, lane, tag16(tag));
      PROF_AT(tid == 0, 50);
      asm volatile("cp.async.wait_group 0;" ::: "memory");
      __syncwarp();
      PROF_AT(tid == 0, 51);
      {
        uint32_t b[8][4];
#pragma unroll
        for (int ks = 0; ks < 8; ks++) ldmatrix4t(b[ks], wbuf + (ks * 16 + (lane & 15)) * 32 + (lane >> 4) * 16);
        float d0[4] = {0.f, 0.f, 0.f, 0.f}, d1[4] = {0.f, 0.f, 0.f, 0.f}, d2[4] = {0.f, 0.f, 0.f, 0.f}, d3[4] = {0.f, 0.f, 0.f, 0.f};
#pragma unroll
        for (int q = 0; q < 4; q++) {
          mma16816(d0, sa[q][0], sa[q][0], sa[q][1], sa[q][1], b[2 * q][0], b[2 * q][1]);
          mma16816(d1, sa[q][0], sa[q][0], sa[q][1], sa[q][1], b[2 * q][2], b[2 * q][3]);
          mma16816(d2, sa[q][2], sa[q][2], sa[q][3], sa[q][3], b[2 * q + 1][0], b[2 * q + 1][1]);
          mma16816(d3, sa[q][2], sa[q][2], sa[q][3], sa[q][3], b[2 * q + 1][2], b[2 * q + 1][3]);
        }
        d0[0] += d2[0]; d0[1] += d2[1]; d1[0] += d3[0]; d1[1] += d3[1];
        if (lane < 4) {
          sts64f(sm + RED_OFF + (w8 * 16 + lane * 2) * 4, d0[0], d0[1]);
          sts64f(sm + RED_OFF + (w8 * 16 + 8 + lane * 2) * 4, d1[0], d1[1]);
        }
        asm volatile("bar.arrive 1, 288;" ::: "memory");
      }
      {
        const int c = lane & 3;
        float rs[2], nb[2];
        stat_gather(gstats1 + rb * 1024 + cw * 64 + warp * 16, tag16(tag), lane, rs, nb);
#pragma unroll
        for (int n = 0; n < 16; n++) {
          xl[n] = pack2(bf_lo(xl[n]) * rs[0] + nb[0], bf_hi(xl[n]) * rs[0] + nb[0]);
          xh[n] = pack2(bf_lo(xh[n]) * rs[1] + nb[1], bf_hi(xh[n]) * rs[1] + nb[1]);
        }
        const int srow = warp * 16 + l16;
        const uint32_t slab = stg + cw * 8192 + srow * 128;
#pragma unroll
        for (int q = 0; q < 8; q++)
          stmatrix4(slab + (q >> 2) * 16384 + (((half + (q & 3) * 2) ^ (srow & 7)) << 4), xl[2 * q], xh[2 * q], xl[2 * q + 1], xh[2 * q + 1]);
        PROF_AT(tid == 0, 52);
        mbar_wait(bars + 8 * B_MODA, 0);
        PROF_AT(tid == 0, 2);
#pragma unroll
        for (int q = 0; q < 8; q++) {
          const float2 m0 = lds64f(sm + MODB_OFF + (8 * q + c) * 8), m1 = lds64f(sm + MODB_OFF + (8 * q + 4 + c) * 8);
          const uint32_t c0 = __float_as_uint(m0.x), s0 = __float_as_uint(m0.y), c1 = __float_as_uint(m1.x), s1 = __float_as_uint(m1.y);
          stmatrix4(slab + (q >> 2) * 16384 + (((half + (q & 3) * 2) ^ (srow & 7)) << 4), fma_bf2(xl[2 * q], c0, s0), fma_bf2(xh[2 * q], c0, s0),
                    fma_bf2(xl[2 * q + 1], c1, s1), fma_bf2(xh[2 * q + 1], c1, s1));
          if ((q & 3) == 3) stage_done(bars + 8 * (B_STGF + (q >> 2)), lane);
        }
        wg_bar(cw);
      }
      PROF_AT(tid == 0, 3);
    }

    uint32_t xl[16], xh[16];
    {
      RING_IDS();
      uint32_t prev = 0;
      float acc1[96];
      {
        Ring g{bars + 8 * B_FQ, rbars + 8 * B_EQ, 0, 0u, 0u, releaser TR(0)};
        float acc0[96];
#pragma unroll 1
        for (int kb = 0; kb < 2; kb++) kblock<192, 4, 49152>(acc0, g, a_base + STG_OFF + kb * 16384, kb == 0, prev);
#pragma unroll 1
        for (int kb = 0; kb < 2; kb++) kblock<192, 4, 49152>(acc1, g, a_base + STG_OFF + kb * 16384, kb == 0, prev);
#pragma unroll 1
        for (int kb = 0; kb < 14; kb++) kblock<192, 4, 49152>(acc0, g, a_base + g.off, false, prev);
        PROF_AT(tid == 0, 4);
        attention<NPRE0, false>(acc0, p, 0, rb, cta, cw, warp, tag, stg, bars, prev, [&]() { kblock<192, 4, 49152>(acc1, g, a_base + g.off, false, prev); });
        PROF_AT(tid == 0, 5);
        {
          LANE_IDS();
#pragma unroll
          for (int q = 0; q < 8; q++)
            ldmatrix4(xl[2 * q], xh[2 * q], xl[2 * q + 1], xh[2 * q + 1], sm + 40960 + (cw * 2 + (q >> 2)) * 49152 + srow * 128 + ((sw0 ^ ((q & 3) * 2)) << 4));
#pragma unroll
          for (int q = 0; q < 16; q++) asm volatile("" : "+r"(xl[q]), "+r"(xh[q])::"memory");
        }
#pragma unroll 1
        for (int kb = 5 + NPRE0; kb < 14; kb++) kblock<192, 4, 49152>(acc1, g, a_base + g.off, false, prev);
        PROF_AT(tid == 0, 6);
      }
      float acc[64];
      Ring g{bars + 8 * B_FW, rbars + 8 * B_EW, 0, 0u, 0u, releaser TR(32)};
      attention<NPRE1, true>(acc1, p, 1, rb, cta, cw, warp, tag, stg, bars, prev, [&]() { kblock<128, 6, 32768>(acc, g, a_base + g.off, g.s == 0, prev); });
      PROF_AT(tid == 0, 7);
      LANE_IDS();
      unsigned* cnt = p.cnt + rb * 32;
      tma_store2(&p.o_st, stg + cw * 8192 + warp * 2048, j * 128 + 64, rb * 128 + cw * 64 + warp * 16);
      asm volatile("cp.async.bulk.commit_group;" ::: "memory");
#pragma unroll 1
      for (int kb = 1 + NPRE1; kb < 16; kb++) {
        if (kb == 8) wg_bar(cw);
        kblock<128, 6, 32768>(acc, g, a_base + (kb == 8 ? STG_OFF : g.off), false, prev);
        if (kb == 3 + NPRE1) {
          asm volatile("cp.async.bulk.wait_group 0;" ::: "memory");
          __syncwarp();
          cnt_signal(cnt + C_O + 1);
        }
      }
      mbar_wait(bars + 8 * B_MODB, 0);
      float2 ga[16];
#pragma unroll
      for (int n = 0; n < 16; n++) ga[n] = lds64f(sm + MODB_OFF + (8 * n + 2 * c) * 4);
      tile_end(acc, prev);
      PROF_AT(tid == 0, 8);
#pragma unroll
      for (int n = 0; n < 16; n++) {
        acc[4 * n] = ga[n].x * acc[4 * n] + bf_lo(xl[n]); acc[4 * n + 1] = ga[n].y * acc[4 * n + 1] + bf_hi(xl[n]);
        acc[4 * n + 2] = ga[n].x * acc[4 * n + 2] + bf_lo(xh[n]); acc[4 * n + 3] = ga[n].y * acc[4 * n + 3] + bf_hi(xh[n]);
        xl[n] = pack2(acc[4 * n], acc[4 * n + 1]);
        xh[n] = pack2(acc[4 * n + 2], acc[4 * n + 3]);
      }
      publish_stats(xl, xh, p.stats2 + (rb * 8 + j) * 128 + cw * 64 + warp * 16, lane, tag16(tag));
      PROF_AT(tid == 0, 48);
      float2 sb[16], cb[16];
#pragma unroll
      for (int n = 0; n < 16; n++) {
        sb[n] = lds64f(sm + MODB_OFF + (128 + 8 * n + 2 * c) * 4);
        cb[n] = lds64f(sm + MODB_OFF + (256 + 8 * n + 2 * c) * 4);
      }
      mbar_wait(bars + 8 * B_STGE, 0);
      PROF_AT(tid == 0, 49);
      float nb[2], rstd[2];
      stat_gather(p.stats2 + rb * 1024 + cw * 64 + warp * 16, tag16(tag), lane, rstd, nb);
      PROF_AT(tid == 0, 9);
#pragma unroll
      for (int ch = 0; ch < 2; ch++) {
        uint32_t lo[8], hi[8];
#pragma unroll
        for (int t = 0; t < 8; t++) {
          const int n = ch * 8 + t;
          lo[t] = pack2((acc[4 * n] * rstd[0] + nb[0]) * cb[n].x + sb[n].x, (acc[4 * n + 1] * rstd[0] + nb[0]) * cb[n].y + sb[n].y);
          hi[t] = pack2((acc[4 * n + 2] * rstd[1] + nb[1]) * cb[n].x + sb[n].x, (acc[4 * n + 3] * rstd[1] + nb[1]) * cb[n].y + sb[n].y);
        }
        stage_slab(sm + ch * 32768 + cw * 8192, warp, lane, lo, hi);
        stage_done(bars + 8 * (B_STGF + ch), lane);
        tma_store2(&p.h2_st, sm + ch * 32768 + cw * 8192 + warp * 2048, j * 128 + ch * 64, rb * 128 + cw * 64 + warp * 16);
        asm volatile("cp.async.bulk.commit_group;" ::: "memory");
      }
      wg_bar(cw);
      PROF_AT(tid == 0, 10);
    }

    uint32_t pg[32], pu[32];
    {
      RING_IDS();
      float acc[128];
      uint32_t prev = 0;
      Ring g{bars + 8 * B_FG, rbars + 8 * B_EG, 0, 0u, 3 * 49152u, releaser TR(66)};
      {
        Ring w{bars + 8 * B_FW, rbars + 8 * B_EW, 4, 0u, 4 * 32768u, releaser TR(48)};
        float acn[64];
#pragma unroll 1
        for (int kb = 0; kb < 2; kb++) {
          kblock<256, 6, 32768>(acc, w, a_base + kb * 32768, kb == 0, prev, 0u);
          if (kb == 0) asm volatile("cp.async.bulk.wait_group 1;" ::: "memory");
          else asm volatile("cp.async.bulk.wait_group 0;" ::: "memory");
          __syncwarp();
          cnt_signal(p.cnt + rb * 32 + (kb == 0 ? C_H2A : C_H2));
        }
        {
          LANE_IDS();
#pragma unroll
          for (int q = 0; q < 8; q++)
            stmatrix4(slab + (q >> 2) * 16384 + ((sw0 ^ ((q & 3) * 2)) << 4), xl[2 * q], xh[2 * q], xl[2 * q + 1], xh[2 * q + 1]);
          __syncwarp();
        }
#pragma unroll 1
        for (int kb = 0; kb < 16; kb++) {
          kblock<128, 6, 32768>(acn, w, a_base + w.off, kb == 0, prev);
          if (kb == 4) {
            asm volatile("fence.proxy.async.shared::cta;" ::: "memory");
            __syncwarp();
          }
          if (kb == 6 + warp || kb == 10 + warp) {
            const int ch = kb != 6 + warp;
            tma_store3(&p.out, stg + ch * 16384 + cw * 8192 + warp * 2048, j * 128 + ch * 64, rb * 64 + warp * 16, cw);
            asm volatile("cp.async.bulk.commit_group;" ::: "memory");
          }
        }
        PROF_AT(tid == 0, 39);
        kblock<256, 4, 49152>(acc, g, a_base + g.off, false, prev);
        fence_regs(acn);
#pragma unroll
        for (int q = 0; q < 16; q++) {
          pg[q] = pack2(acn[2 * q], acn[2 * q + 1]);
          pu[q] = pack2(acn[32 + 2 * q], acn[32 + 2 * q + 1]);
          pg[16 + q] = 0; pu[16 + q] = 0;
        }
        asm volatile("cp.async.bulk.wait_group 0;" ::: "memory");
        kblock<256, 4, 49152>(acc, g, a_base + g.off, false, prev);
      }
      LANE_IDS();
#pragma unroll 1
      for (int t = 0; t < 3; t++) {
#pragma unroll 1
        for (int blk = 0; blk < (t == 0 ? 2 : 4); blk++) {
          g.s = 2;
#pragma unroll
          for (int i = 0; i < 4; i++) {
            g.off = ((i + 1) & 3) * 49152;
            if (i == 3 && blk == 3) skew_pre(cw);
            kblock<256, 4, 49152>(acc, g, a_base + g.off, t > 0 && blk == 0 && i == 0, prev);
            if (i == 3 && blk == 3) skew_post(cw);
            if ((blk & 1) == 0 && i == 0) mbar_wait(bars + 8 * (B_STGE + (blk >> 1)), (t + 1 + (blk >> 1)) & 1);
            stmatrix2(slab + (blk >> 1) * 16384 + (((srow & 7) ^ ((blk & 1) * 4 + i)) << 4), swiglu2(pg[2 * i], pu[2 * i]), swiglu2(pg[2 * i + 1], pu[2 * i + 1]));
          }
#pragma unroll
          for (int q = 0; q < 24; q++) { pg[q] = pg[q + 8]; pu[q] = pu[q + 8]; }
          if (blk & 1) stage_done(bars + 8 * (B_STGF + (blk >> 1)), lane);
        }
#pragma unroll 1
        for (int kb = t == 0 ? 0 : 4; kb < 4; kb++) {
          if (kb == 3) skew_pre(cw);
          kblock<256, 4, 49152>(acc, g, a_base + g.off, false, prev);
          if (kb == 3) skew_post(cw);
        }
        tile_end(acc, prev);
        PROF_AT(tid == 0, 36 + t);
#pragma unroll
        for (int q = 0; q < 32; q++) {
          pg[q] = pack2(acc[2 * q], acc[2 * q + 1]);
          pu[q] = pack2(acc[64 + 2 * q], acc[64 + 2 * q + 1]);
        }
      }
      PROF_AT(tid == 0, 11);
    }

    {
      RING_IDS();
      LANE_IDS();
      Ring g{bars + 8 * B_FD, rbars + 8 * B_ED, 0, 0u, 2 * 32768u, releaser TR(112)};
      float acc[64];
      uint32_t prev = 0;
#pragma unroll 1
      for (int blk = 0; blk < 4; blk++) {
#pragma unroll
        for (int i = 0; i < 8; i++) {
          kblock<128, 6, 32768>(acc, g, a_base + g.off, blk == 0 && i == 0, prev);
          if ((blk & 1) == 0 && i == 0) mbar_wait(bars + 8 * (B_STGE + (blk >> 1)), blk >> 1);
          stmatrix1(slab + (blk >> 1) * 16384 + (i & 1) * 1024 + (((srow & 7) ^ ((blk & 1) * 4 + (i >> 1))) << 4), swiglu2(pg[i], pu[i]));
        }
#pragma unroll
        for (int q = 0; q < 24; q++) { pg[q] = pg[q + 8]; pu[q] = pu[q + 8]; }
        if (blk & 1) stage_done(bars + 8 * (B_STGF + (blk >> 1)), lane);
      }
#pragma unroll 1
      for (int kb = 32; kb < 56 - KH; kb++) {
        if (kb == 50 - KH) g.releaser = false;
        if (kb == 52 - KH) skew_pre(cw);
        kblock<128, 6, 32768>(acc, g, a_base + g.off, false, prev);
      }
      skew_post(cw);
      mbar_wait(bars + 8 * (B_MODB + 1), 0);
      mbar_wait(bars + 8 * B_STGE, 1);
      mbar_wait(bars + 8 * (B_STGE + 1), 0);
      float2 gbv[16];
#pragma unroll
      for (int n = 0; n < 16; n++) gbv[n] = lds64f(sm + MODB_OFF + (384 + 8 * n + 2 * c) * 4);
      tile_end(acc, prev);
      PROF_AT(tid == 0, 13);
#pragma unroll
      for (int ch = 0; ch < 2; ch++) {
        uint32_t lo[8], hi[8];
#pragma unroll
        for (int t = 0; t < 8; t++) {
          const int n = ch * 8 + t;
          const float2 gb = gbv[n];
          lo[t] = pack2(gb.x * acc[4 * n], gb.y * acc[4 * n + 1]);
          hi[t] = pack2(gb.x * acc[4 * n + 2], gb.y * acc[4 * n + 3]);
        }
        stage_slab(stg + ch * 16384 + cw * 8192, warp, lane, lo, hi);
        asm volatile("fence.proxy.async.shared::cta;" ::: "memory");
        __syncwarp();
        tma_add3(&p.out, stg + ch * 16384 + cw * 8192 + warp * 2048, j * 128 + ch * 64, rb * 64 + warp * 16, cw);
      }
      asm volatile("cp.async.bulk.commit_group;" ::: "memory");
      if (lane == 0) mbar_arrive(bars + 8 * B_STGF);
      asm volatile("cp.async.bulk.wait_group.read 0;" ::: "memory");
      PROF_AT(tid == 0, 14);
    }
    if (blockIdx.x == 0 && threadIdx.x == 128) asm volatile("st.relaxed.gpu.global.u32 [%0], %1;" ::"l"(gepoch), "r"(tag) : "memory");
  }
}

typedef CUresult (*EncodeFn)(CUtensorMap*, CUtensorMapDataType, cuuint32_t, void*, const cuuint64_t*, const cuuint64_t*,
                             const cuuint32_t*, const cuuint32_t*, CUtensorMapInterleave, CUtensorMapSwizzle,
                             CUtensorMapL2promotion, CUtensorMapFloatOOBfill);

void encode2d(EncodeFn fn, CUtensorMap* m, const void* ptr, uint64_t cols, uint64_t rows, uint32_t box_rows) {
  cuuint64_t dims[2] = {cols, rows};
  cuuint64_t strides[1] = {cols * 2};
  cuuint32_t box[2] = {64, box_rows};
  cuuint32_t es[2] = {1, 1};
  fn(m, CU_TENSOR_MAP_DATA_TYPE_BFLOAT16, 2, (void*)ptr, dims, strides, box, es, CU_TENSOR_MAP_INTERLEAVE_NONE,
     CU_TENSOR_MAP_SWIZZLE_128B, CU_TENSOR_MAP_L2_PROMOTION_L2_128B, CU_TENSOR_MAP_FLOAT_OOB_FILL_NONE);
}

}

extern "C" void kernel_launch(void* const* d_in, const int* in_sizes, int n_in, void* d_out, int out_size) {
  (void)in_sizes; (void)n_in; (void)out_size;
  void* fp = nullptr;
  cudaDriverEntryPointQueryResult qr;
  cudaGetDriverEntryPoint("cuTensorMapEncodeTiled", &fp, cudaEnableDefault, &qr);
  EncodeFn fn = (EncodeFn)fp;
  void *ph, *po, *ph2, *pact;
  cudaGetSymbolAddress(&ph, g_h);
  cudaGetSymbolAddress(&po, g_o);
  ph2 = ph;
  cudaGetSymbolAddress(&pact, g_act);
  Params p;
  encode2d(fn, &p.h, ph, DM, SEQ, 128);
  encode2d(fn, &p.o_ld, po, DM, SEQ, 128);
  encode2d(fn, &p.h2, ph2, DM, SEQ, 128);
  encode2d(fn, &p.act, pact, FF, SEQ, 128);
  encode2d(fn, &p.act_st, pact, FF, SEQ, 32);
  encode2d(fn, &p.wm, d_in[8], 6 * DM, DM, 64);
  encode2d(fn, &p.o_st, po, DM, SEQ, 16);
  encode2d(fn, &p.h2_st, ph2, DM, SEQ, 16);
  encode2d(fn, &p.wqkv, d_in[1], 3 * DM, DM, 64);
  encode2d(fn, &p.wqkv32, d_in[1], 3 * DM, DM, 32);
  encode2d(fn, &p.wo, d_in[2], DM, DM, 64);
  encode2d(fn, &p.wg, d_in[4], FF, DM, 64);
  encode2d(fn, &p.wu, d_in[5], FF, DM, 64);
  encode2d(fn, &p.wd, d_in[6], DM, FF, 64);
  {
    cuuint64_t dims[3] = {DM, SEQ / 2, 2};
    cuuint64_t strides[2] = {DM * 4, DM * 2};
    cuuint32_t box[3] = {64, 16, 1};
    cuuint32_t es[3] = {1, 1, 1};
    fn(&p.out, CU_TENSOR_MAP_DATA_TYPE_BFLOAT16, 3, d_out, dims, strides, box, es, CU_TENSOR_MAP_INTERLEAVE_NONE,
       CU_TENSOR_MAP_SWIZZLE_128B, CU_TENSOR_MAP_L2_PROMOTION_L2_128B, CU_TENSOR_MAP_FLOAT_OOB_FILL_NONE);
  }
  void* q;
  cudaGetSymbolAddress(&q, g_modll); p.modll = (uint4*)q;
  cudaGetSymbolAddress(&q, g_halo); p.halo = (uint4*)q;
  cudaGetSymbolAddress(&q, g_stats); uint2* stats1 = (uint2*)q; p.stats2 = stats1 + SEQ * 8;
  cudaGetSymbolAddress(&q, g_cnt); p.cnt = (unsigned*)q;
  cudaGetSymbolAddress(&q, g_epoch); unsigned* epoch = (unsigned*)q;

  cudaFuncSetAttribute(fused_kernel, cudaFuncAttributeMaxDynamicSharedMemorySize, SMEM_BYTES);
  cudaLaunchConfig_t cfg = {};
  cfg.gridDim = dim3(NCTA + 4);
  cfg.blockDim = dim3(384);
  cfg.dynamicSmemBytes = SMEM_BYTES;
  cfg.stream = cudaStreamPerThread;
  cudaLaunchAttribute at[1];
  at[0].id = cudaLaunchAttributeClusterDimension;
  at[0].val.clusterDim.x = 2; at[0].val.clusterDim.y = 1; at[0].val.clusterDim.z = 1;
  cfg.attrs = at;
  cfg.numAttrs = 1;
  cudaLaunchKernelEx(&cfg, fused_kernel, (const bf16*)d_in[0], (const bf16*)d_in[8], (const bf16*)d_in[7], epoch, stats1, p);
}
```

```cpp
#include <cuda_runtime.h>
#include <cuda_bf16.h>
#include <cuda.h>
#include <stdint.h>

typedef __nv_bfloat16 bf16;

#define PAUSE 200
#define WMDELAY 500
#define BDELAY 1500
#define NPRE0 3
#define NPRE1 1
#define ALIAS 1
#define PFW 8000
#define KH 3

__device__ __forceinline__ void wgmma_ss_n128(float (&d)[64], uint32_t da, uint32_t db, int scale_d) {
  asm volatile("{\n.reg .pred p;\n.reg .b64 da, db;\nsetp.ne.b32 p, %66, 0;\n"
    "mov.b64 da, {%64, 0x40000040};\nmov.b64 db, {%65, 0x40000040};\n"
    "wgmma.mma_async.sync.aligned.m64n128k16.f32.bf16.bf16 "
    "{%0, %1, %2, %3, %4, %5, %6, %7, %8, %9, %10, %11, %12, %13, %14, %15, "
    "%16, %17, %18, %19, %20, %21, %22, %23, %24, %25, %26, %27, %28, %29, %30, %31, "
    "%32, %33, %34, %35, %36, %37, %38, %39, %40, %41, %42, %43, %44, %45, %46, %47, "
    "%48, %49, %50, %51, %52, %53, %54, %55, %56, %57, %58, %59, %60, %61, %62, %63}, "
    "da, db, p, 1, 1, 0, 1;\n}\n"
    : "+f"(d[0]), "+f"(d[1]), "+f"(d[2]), "+f"(d[3]), "+f"(d[4]), "+f"(d[5]), "+f"(d[6]), "+f"(d[7]),
      "+f"(d[8]), "+f"(d[9]), "+f"(d[10]), "+f"(d[11]), "+f"(d[12]), "+f"(d[13]), "+f"(d[14]), "+f"(d[15]),
      "+f"(d[16]), "+f"(d[17]), "+f"(d[18]), "+f"(d[19]), "+f"(d[20]), "+f"(d[21]), "+f"(d[22]), "+f"(d[23]),
      "+f"(d[24]), "+f"(d[25]), "+f"(d[26]), "+f"(d[27]), "+f"(d[28]), "+f"(d[29]), "+f"(d[30]), "+f"(d[31]),
      "+f"(d[32]), "+f"(d[33]), "+f"(d[34]), "+f"(d[35]), "+f"(d[36]), "+f"(d[37]), "+f"(d[38]), "+f"(d[39]),
      "+f"(d[40]), "+f"(d[41]), "+f"(d[42]), "+f"(d[43]), "+f"(d[44]), "+f"(d[45]), "+f"(d[46]), "+f"(d[47]),
      "+f"(d[48]), "+f"(d[49]), "+f"(d[50]), "+f"(d[51]), "+f"(d[52]), "+f"(d[53]), "+f"(d[54]), "+f"(d[55]),
      "+f"(d[56]), "+f"(d[57]), "+f"(d[58]), "+f"(d[59]), "+f"(d[60]), "+f"(d[61]), "+f"(d[62]), "+f"(d[63])
    : "r"(da), "r"(db), "r"(scale_d));
}

__device__ __forceinline__ void wgmma_ss_n192(float (&d)[96], uint32_t da, uint32_t db, int scale_d) {
  asm volatile("{\n.reg .pred p;\n.reg .b64 da, db;\nsetp.ne.b32 p, %98, 0;\n"
    "mov.b64 da, {%96, 0x40000040};\nmov.b64 db, {%97, 0x40000040};\n"
    "wgmma.mma_async.sync.aligned.m64n192k16.f32.bf16.bf16 "
    "{%0, %1, %2, %3, %4, %5, %6, %7, %8, %9, %10, %11, %12, %13, %14, %15, "
    "%16, %17, %18, %19, %20, %21, %22, %23, %24, %25, %26, %27, %28, %29, %30, %31, "
    "%32, %33, %34, %35, %36, %37, %38, %39, %40, %41, %42, %43, %44, %45, %46, %47, "
    "%48, %49, %50, %51, %52, %53, %54, %55, %56, %57, %58, %59, %60, %61, %62, %63, "
    "%64, %65, %66, %67, %68, %69, %70, %71, %72, %73, %74, %75, %76, %77, %78, %79, "
    "%80, %81, %82, %83, %84, %85, %86, %87, %88, %89, %90, %91, %92, %93, %94, %95}, "
    "da, db, p, 1, 1, 0, 1;\n}\n"
    : "+f"(d[0]), "+f"(d[1]), "+f"(d[2]), "+f"(d[3]), "+f"(d[4]), "+f"(d[5]), "+f"(d[6]), "+f"(d[7]),
      "+f"(d[8]), "+f"(d[9]), "+f"(d[10]), "+f"(d[11]), "+f"(d[12]), "+f"(d[13]), "+f"(d[14]), "+f"(d[15]),
      "+f"(d[16]), "+f"(d[17]), "+f"(d[18]), "+f"(d[19]), "+f"(d[20]), "+f"(d[21]), "+f"(d[22]), "+f"(d[23]),
      "+f"(d[24]), "+f"(d[25]), "+f"(d[26]), "+f"(d[27]), "+f"(d[28]), "+f"(d[29]), "+f"(d[30]), "+f"(d[31]),
      "+f"(d[32]), "+f"(d[33]), "+f"(d[34]), "+f"(d[35]), "+f"(d[36]), "+f"(d[37]), "+f"(d[38]), "+f"(d[39]),
      "+f"(d[40]), "+f"(d[41]), "+f"(d[42]), "+f"(d[43]), "+f"(d[44]), "+f"(d[45]), "+f"(d[46]), "+f"(d[47]),
      "+f"(d[48]), "+f"(d[49]), "+f"(d[50]), "+f"(d[51]), "+f"(d[52]), "+f"(d[53]), "+f"(d[54]), "+f"(d[55]),
      "+f"(d[56]), "+f"(d[57]), "+f"(d[58]), "+f"(d[59]), "+f"(d[60]), "+f"(d[61]), "+f"(d[62]), "+f"(d[63]),
      "+f"(d[64]), "+f"(d[65]), "+f"(d[66]), "+f"(d[67]), "+f"(d[68]), "+f"(d[69]), "+f"(d[70]), "+f"(d[71]),
      "+f"(d[72]), "+f"(d[73]), "+f"(d[74]), "+f"(d[75]), "+f"(d[76]), "+f"(d[77]), "+f"(d[78]), "+f"(d[79]),
      "+f"(d[80]), "+f"(d[81]), "+f"(d[82]), "+f"(d[83]), "+f"(d[84]), "+f"(d[85]), "+f"(d[86]), "+f"(d[87]),
      "+f"(d[88]), "+f"(d[89]), "+f"(d[90]), "+f"(d[91]), "+f"(d[92]), "+f"(d[93]), "+f"(d[94]), "+f"(d[95])
    : "r"(da), "r"(db), "r"(scale_d));
}

__device__ __forceinline__ void wgmma_ss_n256(float (&d)[128], uint32_t da, uint32_t db, int scale_d) {
  asm volatile("{\n.reg .pred p;\n.reg .b64 da, db;\nsetp.ne.b32 p, %130, 0;\n"
    "mov.b64 da, {%128, 0x40000040};\nmov.b64 db, {%129, 0x40000040};\n"
    "wgmma.mma_async.sync.aligned.m64n256k16.f32.bf16.bf16 "
    "{%0, %1, %2, %3, %4, %5, %6, %7, %8, %9, %10, %11, %12, %13, %14, %15, "
    "%16, %17, %18, %19, %20, %21, %22, %23, %24, %25, %26, %27, %28, %29, %30, %31, "
    "%32, %33, %34, %35, %36, %37, %38, %39, %40, %41, %42, %43, %44, %45, %46, %47, "
    "%48, %49, %50, %51, %52, %53, %54, %55, %56, %57, %58, %59, %60, %61, %62, %63, "
    "%64, %65, %66, %67, %68, %69, %70, %71, %72, %73, %74, %75, %76, %77, %78, %79, "
    "%80, %81, %82, %83, %84, %85, %86, %87, %88, %89, %90, %91, %92, %93, %94, %95, "
    "%96, %97, %98, %99, %100, %101, %102, %103, %104, %105, %106, %107, %108, %109, %110, %111, "
    "%112, %113, %114, %115, %116, %117, %118, %119, %120, %121, %122, %123, %124, %125, %126, %127}, "
    "da, db, p, 1, 1, 0, 1;\n}\n"
    : "+f"(d[0]), "+f"(d[1]), "+f"(d[2]), "+f"(d[3]), "+f"(d[4]), "+f"(d[5]), "+f"(d[6]), "+f"(d[7]),
      "+f"(d[8]), "+f"(d[9]), "+f"(d[10]), "+f"(d[11]), "+f"(d[12]), "+f"(d[13]), "+f"(d[14]), "+f"(d[15]),
      "+f"(d[16]), "+f"(d[17]), "+f"(d[18]), "+f"(d[19]), "+f"(d[20]), "+f"(d[21]), "+f"(d[22]), "+f"(d[23]),
      "+f"(d[24]), "+f"(d[25]), "+f"(d[26]), "+f"(d[27]), "+f"(d[28]), "+f"(d[29]), "+f"(d[30]), "+f"(d[31]),
      "+f"(d[32]), "+f"(d[33]), "+f"(d[34]), "+f"(d[35]), "+f"(d[36]), "+f"(d[37]), "+f"(d[38]), "+f"(d[39]),
      "+f"(d[40]), "+f"(d[41]), "+f"(d[42]), "+f"(d[43]), "+f"(d[44]), "+f"(d[45]), "+f"(d[46]), "+f"(d[47]),
      "+f"(d[48]), "+f"(d[49]), "+f"(d[50]), "+f"(d[51]), "+f"(d[52]), "+f"(d[53]), "+f"(d[54]), "+f"(d[55]),
      "+f"(d[56]), "+f"(d[57]), "+f"(d[58]), "+f"(d[59]), "+f"(d[60]), "+f"(d[61]), "+f"(d[62]), "+f"(d[63]),
      "+f"(d[64]), "+f"(d[65]), "+f"(d[66]), "+f"(d[67]), "+f"(d[68]), "+f"(d[69]), "+f"(d[70]), "+f"(d[71]),
      "+f"(d[72]), "+f"(d[73]), "+f"(d[74]), "+f"(d[75]), "+f"(d[76]), "+f"(d[77]), "+f"(d[78]), "+f"(d[79]),
      "+f"(d[80]), "+f"(d[81]), "+f"(d[82]), "+f"(d[83]), "+f"(d[84]), "+f"(d[85]), "+f"(d[86]), "+f"(d[87]),
      "+f"(d[88]), "+f"(d[89]), "+f"(d[90]), "+f"(d[91]), "+f"(d[92]), "+f"(d[93]), "+f"(d[94]), "+f"(d[95]),
      "+f"(d[96]), "+f"(d[97]), "+f"(d[98]), "+f"(d[99]), "+f"(d[100]), "+f"(d[101]), "+f"(d[102]), "+f"(d[103]),
      "+f"(d[104]), "+f"(d[105]), "+f"(d[106]), "+f"(d[107]), "+f"(d[108]), "+f"(d[109]), "+f"(d[110]), "+f"(d[111]),
      "+f"(d[112]), "+f"(d[113]), "+f"(d[114]), "+f"(d[115]), "+f"(d[116]), "+f"(d[117]), "+f"(d[118]), "+f"(d[119]),
      "+f"(d[120]), "+f"(d[121]), "+f"(d[122]), "+f"(d[123]), "+f"(d[124]), "+f"(d[125]), "+f"(d[126]), "+f"(d[127])
    : "r"(da), "r"(db), "r"(scale_d));
}

namespace {

constexpr int SEQ = 2048, DM = 1024, FF = 3584;
constexpr int NCTA = 128;

constexpr uint32_t STG_OFF = 196608;
constexpr uint32_t MISC_OFF = STG_OFF + 32768;
constexpr uint32_t SMEM_BYTES = MISC_OFF + 3072;
constexpr uint32_t RED_OFF = 2 * 49152;
constexpr uint32_t MODB_OFF = MISC_OFF + 512;

enum { B_FQ = 0, B_EQ = 4, B_FW = 8, B_EW = 14, B_FG = 20, B_EG = 24, B_FD = 28, B_ED = 34,
       B_STGF = 40, B_MODB = 42, B_MODA = 45, B_RDY = 46, B_STGE = 58, B_COUNT = 60 };
enum { C_H = 0, C_O = 1, C_H2 = 3, C_ACT = 4, C_HA = 8, C_H2A = 9, C_A0 = 10, C_SP = 12 };

struct Params {
  uint4* modll;
  uint4* halo;
  unsigned* cnt;
  CUtensorMap h, o_ld, o_st, h2, act, out, wqkv, wqkv32, wo, wg, wu, wd, act_st, h2_st, wm;
};

__device__ __align__(1024) bf16 g_h[SEQ * DM];
__device__ __align__(1024) bf16 g_o[SEQ * DM];
__device__ __align__(1024) bf16 g_act[SEQ * FF];
__device__ __align__(1024) uint4 g_modll[3072 / 2];
__device__ __align__(1024) uint4 g_halo[16 * 8 * 2 * 2 * 8 * 32];
__device__ __align__(1024) uint2 g_stats[SEQ * 8];
__device__ __align__(1024) unsigned g_cnt[16 * 32];
__device__ uint4 g_epoch;
#define TR(off)

__device__ __forceinline__ uint32_t smem_u32(const void* p) { return (uint32_t)__cvta_generic_to_shared(p); }
__device__ __forceinline__ void mbar_init(uint32_t bar, uint32_t count) {
  asm volatile("mbarrier.init.shared::cta.b64 [%0], %1;" ::"r"(bar), "r"(count));
}
__device__ __forceinline__ void mbar_arrive(uint32_t bar) {
  asm volatile("mbarrier.arrive.shared::cta.b64 _, [%0];" ::"r"(bar) : "memory");
}
__device__ __forceinline__ void mbar_arrive_cluster(uint32_t cluster_addr) {
  asm volatile("mbarrier.arrive.shared::cluster.b64 _, [%0];" ::"r"(cluster_addr) : "memory");
}
__device__ __forceinline__ uint32_t mapa(uint32_t addr, uint32_t cta) {
  uint32_t r;
  asm volatile("mapa.shared::cluster.u32 %0, %1, %2;" : "=r"(r) : "r"(addr), "r"(cta));
  return r;
}
__device__ __forceinline__ void jitter() {}
__device__ __forceinline__ void mbar_wait(uint32_t bar, uint32_t parity) {
  jitter();
  asm volatile(
      "{\n.reg .pred p;\n"
      "WAIT_%=:\n"
      "mbarrier.try_wait.parity.shared::cta.b64 p, [%0], %1;\n"
      "@!p bra WAIT_%=;\n}\n" ::"r"(bar), "r"(parity) : "memory");
}
__device__ __forceinline__ void mbar_wait_watchdog(uint32_t bar, uint32_t parity) {
  jitter();
  asm volatile(
      "{\n.reg .pred p;\n.reg .u64 t0, t1;\nmov.u64 t0, %%globaltimer;\n"
      "WAIT_%=:\n"
      "mbarrier.try_wait.parity.shared::cta.b64 p, [%0], %1;\n"
      "@p bra DONE_%=;\n"
      "mov.u64 t1, %%globaltimer;\n"
      "sub.u64 t1, t1, t0;\n"
      "setp.lt.u64 p, t1, 2000000000;\n"
      "@p bra WAIT_%=;\n"
      "trap;\n"
      "DONE_%=:\n}\n" ::"r"(bar), "r"(parity) : "memory");
}
__device__ __forceinline__ void cnt_wait(const unsigned* p, unsigned target) {
  asm volatile(
      "{\n.reg .pred p;\n.reg .u32 v;\n.reg .s32 d;\n"
      "WAIT_%=:\n"
      "ld.relaxed.gpu.global.u32 v, [%0];\n"
      "sub.s32 d, v, %1;\n"
      "setp.lt.s32 p, d, 0;\n"
      "@p bra WAIT_%=;\n"
      "fence.proxy.async.global;\n"
      "}\n" ::"l"(p), "r"(target) : "memory");
}
__device__ __forceinline__ void cnt_wait_lazy(const unsigned* p, unsigned target) {
  asm volatile(
      "{\n.reg .pred p;\n.reg .u32 v;\n.reg .s32 d;\n"
      "WAIT_%=:\n"
      "nanosleep.u32 400;\n"
      "ld.relaxed.gpu.global.u32 v, [%0];\n"
      "sub.s32 d, v, %1;\n"
      "setp.lt.s32 p, d, 0;\n"
      "@p bra WAIT_%=;\n"
      "fence.proxy.async.global;\n"
      "}\n" ::"l"(p), "r"(target) : "memory");
}
__device__ __forceinline__ void cnt_signal(unsigned* p) {
  jitter();
  asm volatile("{\n.reg .pred p;\nelect.sync _|p, 0xffffffff;\n@p red.relaxed.gpu.global.add.u32 [%0], 1;\n}\n" ::"l"(p) : "memory");
}
__device__ __forceinline__ void ll_store(uint4* p, uint32_t a, uint32_t b, uint32_t tag) {
  asm volatile("st.relaxed.gpu.global.v2.b64 [%0], {%1, %2};" ::"l"(p), "l"((uint64_t)a | ((uint64_t)tag << 32)),
               "l"((uint64_t)b | ((uint64_t)tag << 32)) : "memory");
}
__device__ __forceinline__ uint4 ll_peek(const uint4* p) {
  uint4 v;
  asm volatile("ld.relaxed.gpu.global.v4.u32 {%0, %1, %2, %3}, [%4];" : "=r"(v.x), "=r"(v.y), "=r"(v.z), "=r"(v.w) : "l"(p) : "memory");
  return v;
}
template <int N, int SLEEP = 0, class F>
__device__ __forceinline__ void ll_poll(F addr, uint32_t tag, uint32_t (&out)[2 * N]) {
  for (;;) {
    uint4 v[N];
#pragma unroll
    for (int i = 0; i < N; i++) v[i] = ll_peek(addr(i));
    uint32_t bad = 0;
#pragma unroll
    for (int i = 0; i < N; i++) {
      bad |= (v[i].y ^ tag) | (v[i].w ^ tag);
      out[2 * i] = v[i].x;
      out[2 * i + 1] = v[i].z;
    }
    if (__all_sync(~0u, bad == 0)) break;
    if (SLEEP) __nanosleep(SLEEP);
  }
}
constexpr uint64_t POLICY_EVICT_FIRST = 0x12F0000000000000ull;
__device__ __forceinline__ void expect_tx_elect(uint32_t bar, uint32_t bytes) {
  asm volatile("{\n.reg .pred p;\nelect.sync _|p, 0xffffffff;\n@p mbarrier.arrive.expect_tx.shared::cta.b64 _, [%0], %1;\n}\n" ::"r"(bar), "r"(bytes) : "memory");
}
__device__ __forceinline__ void arrive_elect(uint32_t bar) {
  asm volatile("{\n.reg .pred p;\nelect.sync _|p, 0xffffffff;\n@p mbarrier.arrive.shared::cta.b64 _, [%0];\n}\n" ::"r"(bar) : "memory");
}
__device__ __forceinline__ void tma_load(uint32_t dst, const CUtensorMap* m, uint32_t bar, int c0, int c1) {
  asm volatile("{\n.reg .pred p;\nelect.sync _|p, 0xffffffff;\n"
               "@p cp.async.bulk.tensor.2d.shared::cluster.global.mbarrier::complete_tx::bytes [%0], [%1, {%3, %4}], [%2];\n}\n"
               ::"r"(dst), "l"(m), "r"(bar), "r"(c0), "r"(c1) : "memory");
}
__device__ __forceinline__ void tma_load_mc(uint32_t dst, const CUtensorMap* m, uint32_t bar, int c0, int c1) {
  asm volatile("{\n.reg .pred p;\nelect.sync _|p, 0xffffffff;\n"
               "@p cp.async.bulk.tensor.2d.shared::cluster.global.mbarrier::complete_tx::bytes.multicast::cluster.L2::cache_hint [%0], [%1, {%3, %4}], [%2], %5, %6;\n}\n"
               ::"r"(dst), "l"(m), "r"(bar), "r"(c0), "r"(c1), "h"((uint16_t)3), "l"(POLICY_EVICT_FIRST) : "memory");
}
__device__ __forceinline__ void tma_load_ef(uint32_t dst, const CUtensorMap* m, uint32_t bar, int c0, int c1) {
  asm volatile("{\n.reg .pred p;\nelect.sync _|p, 0xffffffff;\n"
               "@p cp.async.bulk.tensor.2d.shared::cluster.global.mbarrier::complete_tx::bytes.L2::cache_hint [%0], [%1, {%3, %4}], [%2], %5;\n}\n"
               ::"r"(dst), "l"(m), "r"(bar), "r"(c0), "r"(c1), "l"(POLICY_EVICT_FIRST) : "memory");
}
__device__ __forceinline__ void tma_store2(const CUtensorMap* m, uint32_t src, int c0, int c1) {
  asm volatile("{\n.reg .pred p;\nelect.sync _|p, 0xffffffff;\n"
               "@p cp.async.bulk.tensor.2d.global.shared::cta.bulk_group [%0, {%2, %3}], [%1];\n}\n"
               ::"l"(m), "r"(src), "r"(c0), "r"(c1) : "memory");
}
__device__ __forceinline__ void tma_store3(const CUtensorMap* m, uint32_t src, int c0, int c1, int c2) {
  asm volatile("{\n.reg .pred p;\nelect.sync _|p, 0xffffffff;\n"
               "@p cp.async.bulk.tensor.3d.global.shared::cta.bulk_group [%0, {%2, %3, %4}], [%1];\n}\n"
               ::"l"(m), "r"(src), "r"(c0), "r"(c1), "r"(c2) : "memory");
}
__device__ __forceinline__ void tma_add3(const CUtensorMap* m, uint32_t src, int c0, int c1, int c2) {
  asm volatile("{\n.reg .pred p;\nelect.sync _|p, 0xffffffff;\n"
               "@p cp.reduce.async.bulk.tensor.3d.global.shared::cta.add.bulk_group [%0, {%2, %3, %4}], [%1];\n}\n"
               ::"l"(m), "r"(src), "r"(c0), "r"(c1), "r"(c2) : "memory");
}
__device__ __forceinline__ void store_pause(bool sleep) {
  asm volatile("cp.async.bulk.commit_group;" ::: "memory");
  asm volatile("cp.async.bulk.wait_group.read 0;" ::: "memory");
  if (sleep) __nanosleep(PAUSE);
}
__device__ __forceinline__ void l2_prefetch_tile(const CUtensorMap* m, int c0, int c1) {
  asm volatile("{\n.reg .pred p;\nelect.sync _|p, 0xffffffff;\n@p cp.async.bulk.prefetch.tensor.2d.L2.global [%0, {%1, %2}];\n}\n"
               ::"l"(m), "r"(c0), "r"(c1) : "memory");
}
__device__ __forceinline__ void prefetch_map(const CUtensorMap* m) {
  asm volatile("prefetch.tensormap [%0];" ::"l"(m) : "memory");
}
__device__ __forceinline__ void wg_fence() { asm volatile("wgmma.fence.sync.aligned;" ::: "memory"); }
__device__ __forceinline__ void wg_commit() { asm volatile("wgmma.commit_group.sync.aligned;" ::: "memory"); }
template <int N>
__device__ __forceinline__ void wg_wait() { asm volatile("wgmma.wait_group.sync.aligned %0;" ::"n"(N) : "memory"); }
__device__ __forceinline__ void bar_sync(int id, int n) { asm volatile("bar.sync %0, %1;" ::"r"(id), "r"(n) : "memory"); }
__device__ __forceinline__ void wg_bar(int cw) {
  asm volatile("{\n.reg .pred p;\nsetp.ne.s32 p, %0, 0;\n@p bar.sync 3, 128;\n@!p bar.sync 2, 128;\n}\n" ::"r"(cw) : "memory");
}
__device__ __forceinline__ void skew_pre(int cw) { if (cw == 1) bar_sync(5, 256); }
__device__ __forceinline__ void skew_post(int cw) { if (cw == 0) asm volatile("bar.arrive 5, 256;" ::: "memory"); }
__device__ __forceinline__ void cluster_arrive_relaxed() { asm volatile("barrier.cluster.arrive.relaxed.aligned;" ::: "memory"); }
__device__ __forceinline__ void cluster_wait() { asm volatile("barrier.cluster.wait.acquire.aligned;" ::: "memory"); }
__device__ __forceinline__ uint32_t load_epoch(const unsigned* p) {
  uint32_t e;
  asm volatile("ld.relaxed.gpu.global.u32 %0, [%1];" : "=r"(e) : "l"(p) : "memory");
  return e;
}
__device__ __forceinline__ uint32_t pack2(float lo, float hi) {
  uint32_t r;
  asm("cvt.rn.bf16x2.f32 %0, %1, %2;" : "=r"(r) : "f"(hi), "f"(lo));
  return r;
}
__device__ __forceinline__ float bf_lo(uint32_t v) { return __uint_as_float(v << 16); }
__device__ __forceinline__ float bf_hi(uint32_t v) { return __uint_as_float(v & 0xffff0000u); }
__device__ __forceinline__ uint32_t fma_bf2(uint32_t a, uint32_t b, uint32_t c) {
  uint32_t d;
  asm("fma.rn.bf16x2 %0, %1, %2, %3;" : "=r"(d) : "r"(a), "r"(b), "r"(c));
  return d;
}
__device__ __forceinline__ float bf_round(float v) { return __bfloat162float(__float2bfloat16_rn(v)); }
__device__ __forceinline__ float silu_f(float v) { return __fdividef(v, 1.0f + __expf(-v)); }
__device__ __forceinline__ uint4 ldg_nc(const void* p) {
  uint4 v;
  asm volatile("ld.global.nc.L1::no_allocate.v4.u32 {%0, %1, %2, %3}, [%4];" : "=r"(v.x), "=r"(v.y), "=r"(v.z), "=r"(v.w) : "l"(p));
  return v;
}
__device__ __forceinline__ void stmatrix4(uint32_t addr, uint32_t a, uint32_t b, uint32_t c, uint32_t d) {
  asm volatile("stmatrix.sync.aligned.m8n8.x4.shared.b16 [%0], {%1, %2, %3, %4};" ::"r"(addr), "r"(a), "r"(b), "r"(c), "r"(d) : "memory");
}
__device__ __forceinline__ void stmatrix2(uint32_t addr, uint32_t a, uint32_t b) {
  asm volatile("stmatrix.sync.aligned.m8n8.x2.shared.b16 [%0], {%1, %2};" ::"r"(addr), "r"(a), "r"(b) : "memory");
}
__device__ __forceinline__ void stmatrix1(uint32_t addr, uint32_t a) {
  asm volatile("stmatrix.sync.aligned.m8n8.x1.shared.b16 [%0], {%1};" ::"r"(addr), "r"(a) : "memory");
}
__device__ __forceinline__ uint32_t movmatrix(uint32_t a) {
  uint32_t d;
  asm("movmatrix.sync.aligned.m8n8.trans.b16 %0, %1;" : "=r"(d) : "r"(a));
  return d;
}
__device__ __forceinline__ void mma16816(float (&d)[4], uint32_t a0, uint32_t a1, uint32_t a2, uint32_t a3, uint32_t b0, uint32_t b1) {
  asm("mma.sync.aligned.m16n8k16.row.col.f32.bf16.bf16.f32 {%0, %1, %2, %3}, {%4, %5, %6, %7}, {%8, %9}, {%0, %1, %2, %3};"
               : "+f"(d[0]), "+f"(d[1]), "+f"(d[2]), "+f"(d[3]) : "r"(a0), "r"(a1), "r"(a2), "r"(a3), "r"(b0), "r"(b1));
}
__device__ __forceinline__ void mma1688(float (&d)[4], uint32_t a0, uint32_t a1, uint32_t b0) {
  asm("mma.sync.aligned.m16n8k8.row.col.f32.bf16.bf16.f32 {%0, %1, %2, %3}, {%4, %5}, {%6}, {%0, %1, %2, %3};"
               : "+f"(d[0]), "+f"(d[1]), "+f"(d[2]), "+f"(d[3]) : "r"(a0), "r"(a1), "r"(b0));
}
__device__ __forceinline__ void ldmatrix4t(uint32_t (&b)[4], uint32_t addr) {
  asm volatile("ldmatrix.sync.aligned.m8n8.x4.trans.shared.b16 {%0, %1, %2, %3}, [%4];" : "=r"(b[0]), "=r"(b[1]), "=r"(b[2]), "=r"(b[3]) : "r"(addr) : "memory");
}
__device__ __forceinline__ void ldmatrix4(uint32_t& a, uint32_t& b, uint32_t& c, uint32_t& d, uint32_t addr) {
  asm volatile("ldmatrix.sync.aligned.m8n8.x4.shared.b16 {%0, %1, %2, %3}, [%4];" : "=r"(a), "=r"(b), "=r"(c), "=r"(d) : "r"(addr) : "memory");
}
__device__ __forceinline__ void cp_async16(uint32_t dst, const void* src) {
  asm volatile("cp.async.cg.shared.global.L2::cache_hint [%0], [%1], 16, %2;" ::"r"(dst), "l"(src), "l"(POLICY_EVICT_FIRST) : "memory");
}
__device__ __forceinline__ uint32_t lds32(uint32_t addr) {
  uint32_t v;
  asm volatile("ld.shared.u32 %0, [%1];" : "=r"(v) : "r"(addr) : "memory");
  return v;
}
__device__ __forceinline__ void sts64f(uint32_t addr, float a, float b) {
  asm volatile("st.shared.v2.f32 [%0], {%1, %2};" ::"r"(addr), "f"(a), "f"(b) : "memory");
}
constexpr float QK_SCALE = 0.17677669529663687f;
__device__ __forceinline__ float softmax8(float& p0, float& p1) {
  float m = fmaxf(p0, p1);
  m = fmaxf(m, __shfl_xor_sync(~0u, m, 1));
  m = fmaxf(m, __shfl_xor_sync(~0u, m, 2));
  asm("ex2.approx.ftz.f32 %0, %1;" : "=f"(p0) : "f"((p0 - m) * 1.4426950408889634f));
  asm("ex2.approx.ftz.f32 %0, %1;" : "=f"(p1) : "f"((p1 - m) * 1.4426950408889634f));
  float s = p0 + p1;
  s += __shfl_xor_sync(~0u, s, 1);
  s += __shfl_xor_sync(~0u, s, 2);
  float r;
  asm("rcp.approx.ftz.f32 %0, %1;" : "=f"(r) : "f"(s));
  return r;
}
__device__ __forceinline__ void sts128(uint32_t addr, uint32_t a, uint32_t b, uint32_t c, uint32_t d) {
  asm volatile("st.shared.v4.u32 [%0], {%1, %2, %3, %4};" ::"r"(addr), "r"(a), "r"(b), "r"(c), "r"(d) : "memory");
}
__device__ __forceinline__ uint4 lds128(uint32_t addr) {
  uint4 v;
  asm volatile("ld.shared.v4.u32 {%0, %1, %2, %3}, [%4];" : "=r"(v.x), "=r"(v.y), "=r"(v.z), "=r"(v.w) : "r"(addr) : "memory");
  return v;
}
__device__ __forceinline__ float2 lds64f(uint32_t addr) {
  float2 v;
  asm volatile("ld.shared.v2.f32 {%0, %1}, [%2];" : "=f"(v.x), "=f"(v.y) : "r"(addr) : "memory");
  return v;
}
#define PROF_AT(cond, slot) do {} while (0)

constexpr uint32_t SMEM_BASE = 1024;
constexpr uint32_t DESC_A = (1u << 16) | (SMEM_BASE >> 4);
constexpr uint32_t DESC_B = ((8192u >> 4) << 16) | (SMEM_BASE >> 4);

template <int BN> struct Wg;
template <> struct Wg<128> { static __device__ __forceinline__ void mma(float (&d)[64], uint32_t a, uint32_t b, int s) { wgmma_ss_n128(d, a, b, s); } };
template <> struct Wg<192> { static __device__ __forceinline__ void mma(float (&d)[96], uint32_t a, uint32_t b, int s) { wgmma_ss_n192(d, a, b, s); } };
template <> struct Wg<256> { static __device__ __forceinline__ void mma(float (&d)[128], uint32_t a, uint32_t b, int s) { wgmma_ss_n256(d, a, b, s); } };

struct Ring {
  uint32_t full0, rel0;
  int s;
  uint32_t ph;
  uint32_t off;
  bool releaser;
};

template <int N>
__device__ __forceinline__ void fence_regs(float (&a)[N]) {
#pragma unroll
  for (int i = 0; i < N; i++) asm volatile("" : "+f"(a[i])::"memory");
}

template <int BN, int NST, uint32_t STAGE>
__device__ __forceinline__ void kblock(float (&acc)[BN / 2], Ring& g, uint32_t a_addr, bool zero, uint32_t& prev, uint32_t b_rel = 16384) {
  mbar_wait(g.full0 + 8 * g.s, g.ph);
  const uint32_t da = DESC_A + (a_addr >> 4);
  const uint32_t db = DESC_B + ((g.off + b_rel) >> 4);
  wg_fence();
#pragma unroll
  for (int k = 0; k < 4; k++) Wg<BN>::mma(acc, da + k * 2, db + k * 128, !(zero && k == 0));
  wg_commit();
  wg_wait<1>();
  jitter();
  if (prev != 0) mbar_arrive_cluster(prev);
  prev = g.releaser ? g.rel0 + 8 * g.s : 0u;
  if (++g.s == NST) { g.s = 0; g.ph ^= 1; }
  g.off += STAGE;
  if (g.off == NST * STAGE) g.off = 0;
}
template <int N>
__device__ __forceinline__ void tile_end(float (&acc)[N], uint32_t& prev) {
  wg_wait<0>();
  if (prev != 0) mbar_arrive_cluster(prev);
  prev = 0;
  fence_regs(acc);
}

__device__ __forceinline__ int other_kb(int q, int j) {
  const int ch = q >= 7, jj = q - 7 * ch;
  return 2 * (jj < j ? jj : jj + 1) + ch;
}
__device__ __forceinline__ int qkv_kb(int it, int j) {
  return it < 4 ? 2 * j + (it & 1) : other_kb(it < 18 ? it - 4 : it - 18, j);
}
__device__ __forceinline__ int wo_k(int it, int j) {
  return it < 8 ? it * 128 : (it == 8 ? j : (it - 9 < j ? it - 9 : it - 8)) * 128 + 64;
}
__device__ __forceinline__ int down_k(int d) {
  const int u = d + KH;
  if (u < 8) return u * 448 + 384;
  if (u < 40) return (((u - 8) & 15) >> 1) * 448 + ((u - 8) >> 4) * 128 + (u & 1) * 64;
  return (u & 7) * 448 + 256 + (u >= 48 ? 64 : 0);
}
__device__ __forceinline__ void wait_q_free(uint32_t empty, int i) {
  mbar_wait(empty + 8 * ((i * 2) / 3), 1);
  mbar_wait(empty + 8 * ((i * 2 + 1) / 3), 1);
}
__device__ __forceinline__ void wait_w_free(uint32_t empty, int i) {
  const int t = (i + 3) & 3, w0 = (t * 3) / 2, w1 = (t * 3 + 2) / 2;
  mbar_wait(empty + 8 * w0, w0 < 4);
  mbar_wait(empty + 8 * w1, w1 < 4);
}
__device__ __forceinline__ void wait_g_free(uint32_t empty, int i) {
  const int s = i < 4 ? i + 2 : i - 4, b0 = ((s * 2) / 3 + 1) & 3, b1 = ((s * 2 + 1) / 3 + 1) & 3;
  mbar_wait(empty + 8 * b0, b0 < 2);
  mbar_wait(empty + 8 * b1, b1 < 2);
}

__device__ __forceinline__ void chan(float& m, float& q, float m2, float q2, float n) {
  const float d = m2 - m;
  m = 0.5f * (m + m2);
  q = q + q2 + d * d * (0.5f * n);
}

__device__ __forceinline__ uint32_t tag16(uint32_t tag, uint32_t ln) { return (((tag & 0x3fffu) << 1) | ln) + 0x8000u; }
__device__ __forceinline__ void stat_store(uint2* slot, float m, float q, uint32_t t16) {
  const uint32_t a = ((__float_as_uint(m) + 0x80u) & 0xffffff00u) | (t16 & 0xffu), b = ((__float_as_uint(q) + 0x80u) & 0xffffff00u) | (t16 >> 8);
  asm volatile("st.relaxed.gpu.global.b64 [%0], %1;" ::"l"(slot), "l"((uint64_t)a | ((uint64_t)b << 32)) : "memory");
}
__device__ __forceinline__ void stat_gather(const uint2* rows, uint32_t t16, int lane, float (&rs)[2], float (&nb)[2]) {
  const uint4* sp = (const uint4*)(rows + (lane >> 3) * 128) + (lane & 7);
  const uint32_t want = (t16 & 0xffu) | ((t16 >> 8) << 8);
  uint4 a, b;
  for (;;) {
    a = ll_peek(sp);
    b = ll_peek(sp + 256);
    const uint32_t bad = (__byte_perm(a.x, a.y, 0x40) ^ want) | (__byte_perm(a.z, a.w, 0x40) ^ want) | (__byte_perm(b.x, b.y, 0x40) ^ want) |
                         (__byte_perm(b.z, b.w, 0x40) ^ want);
    if (__all_sync(~0u, (bad & 0xffffu) == 0)) break;
  }
  float m0 = __uint_as_float(a.x & 0xffffff00u), q0 = __uint_as_float(a.y & 0xffffff00u);
  float m1 = __uint_as_float(a.z & 0xffffff00u), q1 = __uint_as_float(a.w & 0xffffff00u);
  chan(m0, q0, __uint_as_float(b.x & 0xffffff00u), __uint_as_float(b.y & 0xffffff00u), 128.f);
  chan(m1, q1, __uint_as_float(b.z & 0xffffff00u), __uint_as_float(b.w & 0xffffff00u), 128.f);
  const bool hi = lane & 8;
  float m = hi ? m1 : m0, q = hi ? q1 : q0;
  chan(m, q, __shfl_xor_sync(~0u, hi ? m0 : m1, 8), __shfl_xor_sync(~0u, hi ? q0 : q1, 8), 256.f);
  chan(m, q, __shfl_xor_sync(~0u, m, 16), __shfl_xor_sync(~0u, q, 16), 512.f);
  const float rstd = rsqrtf(q * (1.0f / DM) + 1e-5f), nmr = -m * rstd;
  const int r = lane >> 2, src = (r >> 1) + (r & 1) * 8;
  rs[0] = __shfl_sync(~0u, rstd, src); nb[0] = __shfl_sync(~0u, nmr, src);
  rs[1] = __shfl_sync(~0u, rstd, src + 4); nb[1] = __shfl_sync(~0u, nmr, src + 4);
}

__device__ __forceinline__ void publish_stats(const uint32_t (&xl)[16], const uint32_t (&xh)[16], uint2* slot, int lane, uint32_t t16) {
  float ds[4] = {0.f, 0.f, 0.f, 0.f}, dl[4] = {0.f, 0.f, 0.f, 0.f}, dh[4] = {0.f, 0.f, 0.f, 0.f};
#pragma unroll
  for (int q = 0; q < 8; q++) {
    mma16816(ds, xl[2 * q], xh[2 * q], xl[2 * q + 1], xh[2 * q + 1], 0x3f803f80u, 0x3f803f80u);
    mma16816(dl, xl[2 * q], xh[2 * q], xl[2 * q + 1], xh[2 * q + 1], xl[2 * q], xl[2 * q + 1]);
    mma16816(dh, xl[2 * q], xh[2 * q], xl[2 * q + 1], xh[2 * q + 1], xh[2 * q], xh[2 * q + 1]);
  }
  const int r = lane >> 2;
  if ((lane & 3) == (r >> 1)) {
    const float ml = ds[0] * (1.0f / 128), mh = ds[2] * (1.0f / 128);
    const float ql = fmaxf(((r & 1) ? dl[1] : dl[0]) - ds[0] * ml, 0.f), qh = fmaxf(((r & 1) ? dh[3] : dh[2]) - ds[2] * mh, 0.f);
    stat_store(slot + r, ml, ql, t16);
    stat_store(slot + r + 8, mh, qh, t16);
  }
  __syncwarp();
}

__device__ __forceinline__ void stage_slab(uint32_t chunk, int warp, int lane, const uint32_t (&lo)[8], const uint32_t (&hi)[8]) {
  const int row = warp * 16 + (lane & 7) + ((lane >> 3) & 1) * 8;
  const uint32_t rbase = chunk + row * 128;
#pragma unroll
  for (int q = 0; q < 4; q++) {
    const int grp = 2 * q + (lane >> 4);
    stmatrix4(rbase + ((grp ^ (row & 7)) << 4), lo[2 * q], hi[2 * q], lo[2 * q + 1], hi[2 * q + 1]);
  }
}
__device__ __forceinline__ float silu_mul(float g, float u) {
  float e, r;
  asm("ex2.approx.ftz.f32 %0, %1;" : "=f"(e) : "f"(g * -1.4426950408889634f));
  asm("rcp.approx.ftz.f32 %0, %1;" : "=f"(r) : "f"(1.0f + e));
  return g * r * u;
}
__device__ __forceinline__ uint32_t swiglu2(uint32_t g2, uint32_t u2) {
  asm volatile("" : "+r"(g2));
  return pack2(silu_mul(bf_lo(g2), bf_lo(u2)), silu_mul(bf_hi(g2), bf_hi(u2)));
}
__device__ __forceinline__ void stage_done(uint32_t bar, int lane) {
  asm volatile("fence.proxy.async.shared::cta;" ::: "memory");
  __syncwarp();
  if (lane == 0) mbar_arrive(bar);
}

__device__ __forceinline__ int fresh_tid() {
  int t;
  asm volatile("mov.u32 %0, %%tid.x;" : "=r"(t));
  return t;
}
#define RING_IDS()                                                                                           \
  const int tid = fresh_tid() - 128;                                                                         \
  const int cw = __shfl_sync(~0u, tid >> 7, 0), warp = __shfl_sync(~0u, (tid >> 5) & 3, 0);                  \
  const bool releaser = (tid & 31) < 2;                                                                      \
  const uint32_t rbars = mapa(bars, tid & 1);                                                                \
  const uint32_t a_base = cw * 8192
#define LANE_IDS()                                                                                           \
  const int lane = fresh_tid() & 31, r = lane >> 2, c = lane & 3;                                            \
  const int srow = warp * 16 + (lane & 7) + ((lane >> 3) & 1) * 8;                                           \
  const uint32_t slab = stg + cw * 8192 + srow * 128, sw0 = (lane >> 4) ^ (srow & 7);                        \
  (void)r; (void)c; (void)slab; (void)sw0

template <int NPRE, bool EAGER, class Step>
__device__ __forceinline__ void attention(float (&acc)[96], const Params& p, int rho, int rb, int cta, int cw, int warp, uint32_t tag,
                                          uint32_t stg, uint32_t bars, uint32_t& prev, Step step) {
  uint32_t ql[8], qh[8], k0[8], k1[8], v0[8], v1[8], hp[16];
  mbar_wait(bars + 8 * B_STGE, rho);
  mbar_wait(bars + 8 * (B_STGE + 1), 0);
  if (EAGER) {
    tile_end(acc, prev);
  } else {
    step();
    fence_regs(acc);
  }
#pragma unroll
  for (int t = 0; t < 8; t++) {
    k0[t] = pack2(acc[4 * (8 + t)], acc[4 * (8 + t) + 1]);
    k1[t] = pack2(acc[4 * (8 + t) + 2], acc[4 * (8 + t) + 3]);
    v0[t] = pack2(acc[4 * (16 + t)], acc[4 * (16 + t) + 1]);
    v1[t] = pack2(acc[4 * (16 + t) + 2], acc[4 * (16 + t) + 3]);
    asm volatile("" : "+r"(k0[t]), "+r"(k1[t]), "+r"(v0[t]), "+r"(v1[t]));
  }
  const int lane = fresh_tid() & 31, r = lane >> 2, c = lane & 3;
#pragma unroll
  for (int t = 0; t < 8; t++) v1[t] = movmatrix(v1[t]);
  const uint32_t xch = stg + 16384 + (cw * 4 + warp) * 2048 + lane * 16;
  if (warp < 3) {
    sts128(xch, k1[0], k1[1], k1[2], k1[3]);
    sts128(xch + 512, k1[4], k1[5], k1[6], k1[7]);
    sts128(xch + 1024, v1[0], v1[1], v1[2], v1[3]);
    sts128(xch + 1536, v1[4], v1[5], v1[6], v1[7]);
  } else if (rb < 15) {
    uint4* dst = p.halo + ((cta * 2 + rho) * 2 + cw) * 256 + lane;
#pragma unroll
    for (int t = 0; t < 4; t++) {
      ll_store(dst + t * 32, k1[2 * t], k1[2 * t + 1], tag);
      ll_store(dst + (4 + t) * 32, v1[2 * t], v1[2 * t + 1], tag);
    }
  }
#pragma unroll
  for (int t = 0; t < 8; t++) {
    v0[t] = movmatrix(v0[t]);
    ql[t] = pack2(acc[4 * t], acc[4 * t + 1]);
    qh[t] = pack2(acc[4 * t + 2], acc[4 * t + 3]);
    asm volatile("" : "+r"(v0[t]), "+r"(ql[t]), "+r"(qh[t]));
  }
#pragma unroll 1
  for (int i = 0; i < NPRE; i++) step();
  const uint4* src = p.halo + (((cta - 8) * 2 + rho) * 2 + cw) * 256 + lane;
  uint4 early[8] = {};
  if (warp == 0 && rb > 0) {
#pragma unroll
    for (int i = 0; i < 8; i++) early[i] = ll_peek(src + i * 32);
  }
  step();
  wg_bar(cw);
  if (warp > 0) {
#pragma unroll
    for (int t = 0; t < 4; t++) {
      const uint4 a = lds128(xch - 2048 + t * 512);
      hp[4 * t] = a.x; hp[4 * t + 1] = a.y; hp[4 * t + 2] = a.z; hp[4 * t + 3] = a.w;
    }
  } else if (rb > 0) {
    uint32_t bad = 0;
#pragma unroll
    for (int i = 0; i < 8; i++) {
      bad |= (early[i].y ^ tag) | (early[i].w ^ tag);
      hp[2 * i] = early[i].x;
      hp[2 * i + 1] = early[i].z;
    }
    if (!__all_sync(~0u, bad == 0)) ll_poll<8>([&](int i) { return src + i * 32; }, tag, hp);
  } else {
#pragma unroll
    for (int t = 0; t < 16; t++) hp[t] = 0;
  }
  wg_wait<0>();
  if (prev != 0) mbar_arrive_cluster(prev);
  prev = 0;
#pragma unroll
  for (int t = 0; t < 8; t++) asm volatile("" : "+r"(ql[t])::"memory");
  const bool up0 = 2 * c > r, up1 = 2 * c + 1 > r;
  const bool first = (rb == 0) && (warp == 0);
  uint32_t a0[2], a2[2], a3[2], a5[2];
  float il[2], ih[2];
#pragma unroll
  for (int h = 0; h < 2; h++) {
    float sp[4] = {0.f, 0.f, 0.f, 0.f}, s0[4] = {0.f, 0.f, 0.f, 0.f}, s1[4] = {0.f, 0.f, 0.f, 0.f};
#pragma unroll
    for (int ks = 0; ks < 2; ks++) {
      const int t = 4 * h + 2 * ks;
      mma16816(sp, ql[t], qh[t], ql[t + 1], qh[t + 1], hp[t], hp[t + 1]);
      mma16816(s0, ql[t], qh[t], ql[t + 1], qh[t + 1], k0[t], k0[t + 1]);
      mma16816(s1, ql[t], qh[t], ql[t + 1], qh[t + 1], k1[t], k1[t + 1]);
    }
    float p0 = (up0 ? sp[0] : s0[0]) * QK_SCALE, p1 = (up1 ? sp[1] : s0[1]) * QK_SCALE;
    float p2 = (up0 ? s0[2] : s1[2]) * QK_SCALE, p3 = (up1 ? s0[3] : s1[3]) * QK_SCALE;
    if (first && up0) p0 = -1000000000.0f;
    if (first && up1) p1 = -1000000000.0f;
    il[h] = softmax8(p0, p1);
    ih[h] = softmax8(p2, p3);
    a0[h] = pack2(up0 ? p0 : 0.f, up1 ? p1 : 0.f);
    a2[h] = pack2(up0 ? 0.f : p0, up1 ? 0.f : p1);
    a3[h] = pack2(up0 ? p2 : 0.f, up1 ? p3 : 0.f);
    a5[h] = pack2(up0 ? 0.f : p2, up1 ? 0.f : p3);
  }
  float o[8][4];
#pragma unroll
  for (int t = 0; t < 8; t++) {
#pragma unroll
    for (int q = 0; q < 4; q++) o[t][q] = 0.f;
    mma1688(o[t], 0u, a5[t >> 2], v1[t]);
    mma16816(o[t], a0[t >> 2], 0u, a2[t >> 2], a3[t >> 2], hp[8 + t], v0[t]);
  }
#pragma unroll
  for (int t = 0; t < 8; t++) fence_regs(o[t]);
  if (!EAGER) step();
  uint32_t ol[8], oh[8];
#pragma unroll
  for (int t = 0; t < 8; t++) {
    ol[t] = pack2(o[t][0] * il[t >> 2], o[t][1] * il[t >> 2]);
    oh[t] = pack2(o[t][2] * ih[t >> 2], o[t][3] * ih[t >> 2]);
  }
  if (!EAGER) step();
  stage_slab(stg + cw * 8192, warp, lane, ol, oh);
  stage_done(bars + 8 * B_STGF, lane);
  if (!EAGER) step();
}

__global__ void __launch_bounds__(384, 1) fused_kernel(const bf16* __restrict__ gx, const bf16* __restrict__ gwmod, const bf16* __restrict__ gc,
                                                          unsigned* gepoch, uint2* gstats, const __grid_constant__ Params p) {
  extern __shared__ __align__(1024) uint8_t smem_raw[];
  const uint32_t sm = smem_u32(smem_raw);
  const uint32_t bars = sm + MISC_OFF;
  const uint32_t stg = sm + STG_OFF;
  const int rank = blockIdx.x & 1;
  const int cl = blockIdx.x >> 1;
  if (cl >= NCTA / 2) {
    const int e = blockIdx.x - NCTA, wid = __shfl_sync(~0u, (int)(threadIdx.x >> 5), 0), lane = threadIdx.x & 31;
    if (threadIdx.x == 0) {
      for (int i = 0; i < 6; i++) { mbar_init(bars + 8 * i, 1); mbar_init(bars + 8 * (6 + i), 8); }
      for (int i = 0; i < 8; i++) { mbar_init(bars + 8 * (16 + i), 1); mbar_init(bars + 8 * (24 + i), 4); }
      mbar_init(bars + 8 * 12, 1);
      asm volatile("fence.mbarrier_init.release.cluster;" ::: "memory");
    }
    const uint32_t tag = load_epoch(gepoch) + 1;
    for (int i = threadIdx.x; i < 1536; i += 384) {
      uint4 o = make_uint4(0u, 0u, 0u, 0u);
      if (i < 1024 && (i & 63) < 8) {
        const uint4 cv = ldg_nc(gc + (i >> 6) * 64 + (i & 7) * 8);
        o = make_uint4(pack2(silu_f(bf_lo(cv.x)), silu_f(bf_hi(cv.x))), pack2(silu_f(bf_lo(cv.y)), silu_f(bf_hi(cv.y))),
                       pack2(silu_f(bf_lo(cv.z)), silu_f(bf_hi(cv.z))), pack2(silu_f(bf_lo(cv.w)), silu_f(bf_hi(cv.w))));
      }
      sts128(stg + i * 16, o.x, o.y, o.z, o.w);
    }
    asm volatile("fence.proxy.async.shared::cta;" ::: "memory");
    __syncthreads();
    if (wid == 0) {
      __nanosleep(WMDELAY);
      uint32_t ph = 1;
#pragma unroll 1
      for (int it = 0, s = 0; it < 64; it++) {
        mbar_wait(bars + 8 * (6 + s), ph);
        expect_tx_elect(bars + 8 * s, 32768);
#pragma unroll
        for (int q = 0; q < 4; q++) tma_load_ef(sm + s * 32768 + q * 8192, &p.wm, bars + 8 * s, 2048 + (it >> 4) * 1024 + e * 256 + q * 64, (it & 15) * 64);
        if (++s == 6) { s = 0; ph ^= 1; }
      }
    } else if (wid == 1) {
      __nanosleep(PFW);
#pragma unroll 1
      for (int i = 0; i < 64; i++) {
        l2_prefetch_tile(&p.wo, (i & 15) * 64, (e * 4 + (i >> 4)) * 64);
      }
#pragma unroll 1
      for (int i = 0; i < 80; i++) {
        if (i < 64) l2_prefetch_tile((i & 1) ? &p.wu : &p.wg, ((i >> 1) & 7) * 448 + 384, ((i >> 4) * 4 + e) * 64);
        else l2_prefetch_tile((i & 2) ? &p.wu : &p.wg, (e * 2 + ((i >> 3) & 1)) * 448 + (i & 1) * 64, (e * 4 + ((i >> 2) & 3)) * 64);
      }
    } else if (wid >= 4) {
      const int hf = (wid >> 2) - 1;
      uint32_t ph = 0;
      int s = 0;
#pragma unroll 1
      for (int v = 0; v < 4; v++) {
        float acc[64];
#pragma unroll 1
        for (int kb = 0; kb < 16; kb++) {
          mbar_wait_watchdog(bars + 8 * s, ph);
          const uint32_t da = DESC_A + ((STG_OFF + kb * 1024) >> 4), db = DESC_B + ((s * 32768 + hf * 16384) >> 4);
          wg_fence();
#pragma unroll
          for (int k = 0; k < 4; k++) wgmma_ss_n128(acc, da + k * 2, db + k * 128, (kb | k) != 0);
          wg_commit();
          wg_wait<0>();
          if (lane == 0) mbar_arrive(bars + 8 * (6 + s));
          if (++s == 6) { s = 0; ph ^= 1; }
        }
        fence_regs(acc);
        if ((wid & 3) == 0) {
#pragma unroll
          for (int n = 0; n < 16; n++) {
            const uint32_t mine = pack2(acc[4 * n], acc[4 * n + 1]), next = __shfl_down_sync(~0u, mine, 1);
            if (lane < 4 && (lane & 1) == 0) ll_store(p.modll + 512 + v * 256 + e * 64 + hf * 32 + n * 2 + (lane >> 1), mine, next, tag);
            if (lane < 4) sts64f(sm + MODB_OFF + (hf * 128 + n * 8 + lane * 2) * 4, bf_lo(mine), bf_hi(mine));
          }
        }
      }
    }
    __syncthreads();
    if (wid == 0 || wid == 2) {
      const int w = wid >> 1;
      if (w == 0) {
        expect_tx_elect(bars + 8 * 12, KH * 32768);
#pragma unroll 1
        for (int q = 0; q < 4 * KH; q++) tma_load_ef(sm + q * 8192, &p.wd, bars + 8 * 12, e * 256 + (q & 3) * 64, (q >> 2) * 448 + 384);
      }
      cnt_wait_lazy(p.cnt + C_ACT, tag * 8);
      if (w == 1) __nanosleep(900);
      uint32_t ph = 1, ready = 0;
#pragma unroll 1
      for (int it = 0, s = 0; it < 16 * KH; it++) {
        const int rb = it / KH, kc = it - rb * KH;
        while (!((ready >> rb) & 1)) {
          ready = __ballot_sync(~0u, (int)(load_epoch(p.cnt + (lane & 15) * 32 + C_ACT) - tag * 8) >= 0);
          asm volatile("fence.proxy.async.global;" ::: "memory");
        }
        const uint32_t fb = bars + 8 * (16 + w * 4 + s), dst = sm + 98304 + w * 32768 + s * 8192;
        mbar_wait(fb + 64, ph);
        expect_tx_elect(fb, 8192);
        tma_load(dst, &p.act_st, fb, kc * 448 + 384, rb * 128 + w * 64);
        tma_load(dst + 4096, &p.act_st, fb, kc * 448 + 384, rb * 128 + w * 64 + 32);
        if (++s == 4) { s = 0; ph ^= 1; }
      }
    } else if (wid >= 4) {
      const int w = (wid >> 2) - 1, warp = wid & 3;
      const uint32_t out_stg = (w ? stg : sm + 163840) + warp * 2048;
      const uint32_t slab = out_stg + (lane & 15) * 128, sw0 = (lane >> 4) ^ (lane & 7);
      mbar_wait_watchdog(bars + 8 * 12, 0);
#pragma unroll 1
      for (int i = threadIdx.x - 128; i < KH * 2048; i += 256) {
        const uint32_t gp = sm + MODB_OFF + (((i >> 9) & 3) * 64 + ((i ^ (i >> 3)) & 7) * 8) * 4;
        const uint4 v = lds128(sm + i * 16), ga = lds128(gp), gc = lds128(gp + 16);
        sts128(sm + i * 16, pack2(bf_lo(v.x) * __uint_as_float(ga.x), bf_hi(v.x) * __uint_as_float(ga.y)),
               pack2(bf_lo(v.y) * __uint_as_float(ga.z), bf_hi(v.y) * __uint_as_float(ga.w)),
               pack2(bf_lo(v.z) * __uint_as_float(gc.x), bf_hi(v.z) * __uint_as_float(gc.y)),
               pack2(bf_lo(v.w) * __uint_as_float(gc.z), bf_hi(v.w) * __uint_as_float(gc.w)));
      }
      asm volatile("fence.proxy.async.shared::cta;" ::: "memory");
      bar_sync(1, 256);
      uint32_t ph = 0;
      int s = 0;
#pragma unroll 1
      for (int rb = 0; rb < 16; rb++) {
        float acc[128];
#pragma unroll 1
        for (int kc = 0; kc < KH; kc++) {
          mbar_wait_watchdog(bars + 8 * (16 + w * 4 + s), ph);
          const uint32_t da = DESC_A + ((98304 + w * 32768 + s * 8192) >> 4), db = DESC_B + ((kc * 32768) >> 4);
          wg_fence();
#pragma unroll
          for (int k = 0; k < 4; k++) wgmma_ss_n256(acc, da + k * 2, db + k * 128, (kc | k) != 0);
          wg_commit();
          wg_wait<1>();
          if (kc > 0 && lane == 0) mbar_arrive(bars + 8 * (24 + w * 4 + ((s + 3) & 3)));
          if (++s == 4) { s = 0; ph ^= 1; }
        }
        asm volatile("cp.async.bulk.wait_group 0;" ::: "memory");
        __syncwarp();
        if (rb > 0) cnt_signal(p.cnt + (rb - 1) * 32 + C_SP + e);
        wg_wait<0>();
        fence_regs(acc);
        __syncwarp();
        if (lane == 0) mbar_arrive(bars + 8 * (24 + w * 4 + ((s + 3) & 3)));
#pragma unroll
        for (int q = 0; q < 16; q++)
          stmatrix4(slab + (q >> 2) * 8192 + ((sw0 ^ ((q & 3) * 2)) << 4), pack2(acc[8 * q], acc[8 * q + 1]), pack2(acc[8 * q + 2], acc[8 * q + 3]),
                    pack2(acc[8 * q + 4], acc[8 * q + 5]), pack2(acc[8 * q + 6], acc[8 * q + 7]));
        asm volatile("fence.proxy.async.shared::cta;" ::: "memory");
        __syncwarp();
#pragma unroll
        for (int ch = 0; ch < 4; ch++) tma_add3(&p.out, out_stg + ch * 8192, e * 256 + ch * 64, rb * 64 + warp * 16, w);
        asm volatile("cp.async.bulk.commit_group;" ::: "memory");
      }
      asm volatile("cp.async.bulk.wait_group 0;" ::: "memory");
      __syncwarp();
      cnt_signal(p.cnt + 15 * 32 + C_SP + e);
    }
    return;
  }
  const int q7 = ((cl - 36) * 37) >> 8;
  const int j = cl < 4 ? 4 + cl : (cl < 36 ? (cl - 4) >> 3 : 4 + q7);
  const int rb = (cl < 4 ? 0 : (cl < 36 ? (cl - 4) & 7 : cl - 35 - 7 * q7)) * 2 + rank;
  const int cta = rb * 8 + j;
  PROF_AT(threadIdx.x == 0, 0);

  if (threadIdx.x < 128) {
    asm volatile("setmaxnreg.dec.sync.aligned.u32 40;");
    const int warp = __shfl_sync(~0u, (int)(threadIdx.x >> 5), 0), lane = threadIdx.x & 31;
    if (threadIdx.x == 0) {
      const uint32_t ep = load_epoch(gepoch);
      if ((sm & 0x3FFFF) != SMEM_BASE) asm volatile("trap;");
      for (int i = 0; i < 4; i++) { mbar_init(bars + 8 * (B_FQ + i), 1); mbar_init(bars + 8 * (B_EQ + i), 16); }
      for (int i = 0; i < 6; i++) { mbar_init(bars + 8 * (B_FW + i), 1); mbar_init(bars + 8 * (B_EW + i), 16); }
      for (int i = 0; i < 4; i++) { mbar_init(bars + 8 * (B_FG + i), 1); mbar_init(bars + 8 * (B_EG + i), 16); }
      for (int i = 0; i < 6; i++) { mbar_init(bars + 8 * (B_FD + i), 1); mbar_init(bars + 8 * (B_ED + i), 16); }
      for (int i = 0; i < 2; i++) { mbar_init(bars + 8 * (B_STGF + i), 8); mbar_init(bars + 8 * (B_STGE + i), 1); }
      mbar_init(bars + 8 * B_MODB, 1);
      mbar_init(bars + 8 * (B_MODB + 1), 1);
      mbar_init(bars + 8 * B_MODA, 1);
      for (int i = 0; i < 11; i++) mbar_init(bars + 8 * (B_RDY + i), 1);
      asm volatile("st.shared.u32 [%0], %1;" ::"r"(bars + 8 * B_COUNT), "r"(ep + 1) : "memory");
      asm volatile("fence.mbarrier_init.release.cluster;\nfence.acq_rel.cta;" ::: "memory");
    }
    __syncwarp();
    cluster_arrive_relaxed();
    unsigned* cnt = p.cnt + rb * 32;
    cluster_wait();
    const uint32_t tag = lds32(bars + 8 * B_COUNT);
    const unsigned target = tag * 8;
    if (warp == 0) {
      const CUtensorMap* wgu = rank ? &p.wu : &p.wg;
      uint32_t st = sm + 16384, fb = bars + 8 * B_FQ, ph = 1;
      __nanosleep(BDELAY);
#pragma unroll 1
      for (int it = 0; it < 32; it++) {
        const int kb = qkv_kb(it, j), col = j * 128 + ((it < 4 ? it >= 2 : it >= 18) ? 64 : 0);
        if (it == 2) mbar_wait(bars + 8 * B_MODA, 0);
        mbar_wait(fb + 8 * (B_EQ - B_FQ), ph);
        expect_tx_elect(fb, it < 4 ? 24576 : 40960);
        tma_load_mc(st + rank * 8192, &p.wqkv, fb, col + rank * 1024, kb * 64);
        tma_load_mc(st + 16384 + rank * 4096, &p.wqkv32, fb, col + 2048, kb * 64 + rank * 32);
        st += 49152; fb += 8;
        if ((it & 3) == 3) { st -= 4 * 49152; fb -= 32; ph ^= 1; }
      }
      fb = bars + 8 * B_FW; ph = 1;
#pragma unroll 1
      for (int it = 0, s = 0; it < 34; it++) {
        if (it < 6) wait_q_free(bars + 8 * B_EQ, it);
        if (it == 16) mbar_wait(bars + 8 * (B_FW + 3), 0);
        mbar_wait(fb + 8 * (B_EW - B_FW), ph);
        expect_tx_elect(fb, (it == 8 || it == 18 || it == 19) ? 16384 : 32768);
        const int k0 = it < 16 ? wo_k(it, j) : (it < 20 ? 2 * j + (it & 1) : other_kb(it - 20, j)) * 64;
        if (it == 16 || it == 17) {
          tma_load_mc(st - 16384 + rank * 16384, wgu, fb, j * 448, k0);
          tma_load_mc(st - 8192 + rank * 16384, wgu, fb, j * 448 + 64, k0);
        } else {
          tma_load_mc(st + rank * 8192, it < 16 ? &p.wo : wgu, fb, it < 16 ? j * 128 + rank * 64 : j * 448 + 384, k0);
        }
        st += 32768; fb += 8;
        if (++s == 6) { s = 0; st -= 6 * 32768; fb -= 48; ph ^= 1; }
      }
      st = sm + 16384 + 3 * 49152; fb = bars + 8 * B_FG; ph = 1;
#pragma unroll 1
      for (int it = 0; it < 46; it++) {
        const int kb = it < 14 ? other_kb(it, j) : (it + 2) & 15, col = j * 448 + ((it + 2) >> 4) * 128;
        if (it < 4) wait_w_free(bars + 8 * B_EW, it);
        mbar_wait(fb + 8 * (B_EG - B_FG), ph);
        expect_tx_elect(fb, 49152);
        tma_load_mc(st + rank * 16384, wgu, fb, col, kb * 64);
        tma_load_mc(st + rank * 16384 + 8192, wgu, fb, col + 64, kb * 64);
        st += (it & 3) == 0 ? -3 * 49152 : 49152; fb += 8;
        if ((it & 3) == 3) { fb -= 32; ph ^= 1; }
      }
      st = sm + 16384 + 2 * 32768; fb = bars + 8 * B_FD; ph = 1;
#pragma unroll 1
      for (int it = 0, s = 0; it < 56 - KH; it++) {
        if (it < 6) wait_g_free(bars + 8 * B_EG, it);
        mbar_wait(fb + 8 * (B_ED - B_FD), ph);
        expect_tx_elect(fb, 32768);
        tma_load_mc(st + rank * 8192, &p.wd, fb, j * 128 + rank * 64, down_k(it));
        st += s == 3 ? -5 * 32768 : 32768; fb += 8;
        if (++s == 6) { s = 0; fb -= 48; ph ^= 1; }
      }
    } else if (warp == 1) {
      const int arow = rb * 128;
      uint32_t st = sm, fb = bars + 8 * B_FQ, ph = 0;
      cnt_wait(cnt + C_HA, target);
      PROF_AT(lane == 0, 16);
#pragma unroll 1
      for (int it = 4; it < 32; it++) {
        if (it == 11) mbar_wait(bars + 8 * (B_RDY + C_H), 0);
        mbar_wait(fb + 8 * (B_EQ - B_FQ), ph);
        tma_load(st, &p.h, fb, qkv_kb(it, j) * 64, arow);
        st += 49152; fb += 8;
        if ((it & 3) == 3) { st -= 4 * 49152; fb -= 32; ph ^= 1; }
      }
      fb = bars + 8 * B_FW; ph = 1;
#pragma unroll 1
      for (int it = 0, s = 0; it < 34; it++) {
        if (it < 16 || it >= 20) {
          if (it < 6) wait_q_free(bars + 8 * B_EQ, it);
          mbar_wait(fb + 8 * (B_EW - B_FW), ph);
          if (it == 0) mbar_wait(bars + 8 * (B_RDY + C_O), 0);
          if (it == 9 || it == 20) cnt_wait(cnt + (it == 9 ? C_O + 1 : C_H2A), target * 8);
          if (it == 27) mbar_wait(bars + 8 * (B_RDY + C_H2), 0);
          PROF_AT(lane == 0 && (it == 0 || it == 9 || it == 20), 17 + (it >> 3));
          if (it != 8) tma_load(st, it < 16 ? &p.o_ld : &p.h2, fb, it < 16 ? wo_k(it, j) : other_kb(it - 20, j) * 64, arow);
        }
        st += 32768; fb += 8;
        if (++s == 6) { s = 0; st -= 6 * 32768; fb -= 48; ph ^= 1; }
      }
      st = sm + 3 * 49152; fb = bars + 8 * B_FG; ph = 1;
#pragma unroll 1
      for (int it = 0; it < 46; it++) {
        if (it < 4) wait_w_free(bars + 8 * B_EW, it);
        mbar_wait(fb + 8 * (B_EG - B_FG), ph);
        tma_load(st, &p.h2, fb, (it < 14 ? other_kb(it, j) : (it + 2) & 15) * 64, arow);
        st += (it & 3) == 0 ? -3 * 49152 : 49152; fb += 8;
        if ((it & 3) == 3) { fb -= 32; ph ^= 1; }
      }
      st = sm + 2 * 32768; fb = bars + 8 * B_FD; ph = 1;
#pragma unroll 1
      for (int it = 0, s = 0; it < 56 - KH; it++) {
        if (it < 6) wait_g_free(bars + 8 * B_EG, it);
        mbar_wait(fb + 8 * (B_ED - B_FD), ph);
        const int u = it + KH, dep = it == 0 ? C_ACT : (u == 8 ? C_ACT + 1 : (u == 24 ? C_ACT + 2 : (u == 40 ? C_A0 : (u == 48 ? C_ACT + 3 : -1))));
        if (dep >= 0) mbar_wait(bars + 8 * (B_RDY + dep), 0);
        tma_load(st, &p.act, fb, down_k(it), arow);
        st += s == 3 ? -5 * 32768 : 32768; fb += 8;
        if (++s == 6) { s = 0; fb -= 48; ph ^= 1; }
      }
    } else if (warp == 2) {
      if (lane < 14) prefetch_map(&p.h + lane);
      __syncwarp();
      uint32_t ph1 = 0;
#pragma unroll 1
      for (int n = 0; n < 8; n++) {
        const int nch = (n == 1 || n == 2 || n == 4) ? 1 : 2;
#pragma unroll 1
        for (int ch = 0; ch < nch; ch++) {
          mbar_wait_watchdog(bars + 8 * (B_STGF + ch), ch ? ph1 : (n & 1));
          const uint32_t src = stg + ch * 16384;
          if (n == 2 || n == 3) {
          } else if (n == 1) {
#pragma unroll 1
            for (int q = 0; q < 8; q++) {
              tma_store2(&p.o_st, src + q * 2048, j * 128, rb * 128 + q * 16);
              if (q & 1) store_pause(true);
            }
          } else if (n >= 4 && n < 8) {
#pragma unroll 1
            for (int q = 0; q < 4; q++) {
              tma_store2(&p.act_st, src + q * 4096, j * 448 + (n == 4 ? 384 : (n - 5) * 128 + ch * 64), rb * 128 + q * 32);
              store_pause(true);
            }
          } else {
            tma_store2(&p.h, src, j * 128 + ch * 64, rb * 128);
            asm volatile("cp.async.bulk.commit_group;" ::: "memory");
            if (ch == 1) {
              asm volatile("cp.async.bulk.wait_group 1;" ::: "memory");
              __syncwarp();
              cnt_signal(cnt + C_HA);
            }
          }
          if (n >= 5 && ch == 0) arrive_elect(bars + 8 * B_STGE);
          if (n == 7 && ch == 0) {
            asm volatile("cp.async.bulk.wait_group 0;" ::: "memory");
            __syncwarp();
            cnt_signal(cnt + C_A0);
          }
        }
        asm volatile("cp.async.bulk.commit_group;" ::: "memory");
        asm volatile("cp.async.bulk.wait_group 0;" ::: "memory");
        __syncwarp();
        if (n != 2 && n != 3) cnt_signal(cnt + n);
        PROF_AT(lane == 0, n == 0 ? 33 : 23 + n);
        if (n == 0) {
#pragma unroll 1
          for (int t = 0; t < 32; t++) {
            ll_store(p.halo + cta * 1024 + t * 32 + lane, 0u, 0u, 0u);
            __nanosleep(40);
          }
          __syncwarp();
        }
        if (n < 5) arrive_elect(bars + 8 * B_STGE);
        if (nch == 2) { arrive_elect(bars + 8 * (B_STGE + 1)); ph1 ^= 1; }
      }
      mbar_wait_watchdog(bars + 8 * B_STGF, 0);
      PROF_AT(lane == 0, 31);
    } else {
      if (lane < 4) ll_store(p.modll + cta * 4 + lane, 0u, 0u, 0u);
      bar_sync(1, 288);
      {
        const uint4 t4 = lds128(sm + RED_OFF + lane * 16);
        float a[4] = {__uint_as_float(t4.x), __uint_as_float(t4.y), __uint_as_float(t4.z), __uint_as_float(t4.w)};
#pragma unroll
        for (int o = 4; o < 32; o <<= 1)
#pragma unroll
          for (int q = 0; q < 4; q++) a[q] += __shfl_xor_sync(~0u, a[q], o);
        if (lane < 4) ll_store(p.modll + cta * 4 + lane, pack2(a[0], a[1]), pack2(a[2], a[3]), tag);
        PROF_AT(lane == 0, 1);
        uint32_t m[4];
        const uint4* mp = p.modll + j * 32 + lane;
        ll_poll<2>([&](int i) { return mp + i * 256; }, tag, m);
        const uint32_t c0 = pack2(1.0f + bf_lo(m[2]), 1.0f + bf_hi(m[2])), c1 = pack2(1.0f + bf_lo(m[3]), 1.0f + bf_hi(m[3]));
        sts128(sm + MODB_OFF + lane * 16, c0, m[0], c1, m[1]);
        __syncwarp();
        arrive_elect(bars + 8 * B_MODA);
      }
#pragma unroll 1
      for (int n = C_H; n <= C_O; n++) {
        cnt_wait_lazy(cnt + n, target);
        arrive_elect(bars + 8 * (B_RDY + n));
      }
      {
        uint32_t m[6];
        const uint4* src = p.modll + 512 + j * 32 + lane;
        ll_poll<3, 500>([&](int i) { return src + i * 256; }, tag, m);
#pragma unroll
        for (int vec = 0; vec < 3; vec++) {
          const float add = vec == 2 ? 1.0f : 0.0f;
          sts128(sm + MODB_OFF + (vec * 128 + lane * 4) * 4, __float_as_uint(bf_round(bf_lo(m[2 * vec]) + add)), __float_as_uint(bf_round(bf_hi(m[2 * vec]) + add)),
                 __float_as_uint(bf_round(bf_lo(m[2 * vec + 1]) + add)), __float_as_uint(bf_round(bf_hi(m[2 * vec + 1]) + add)));
        }
        __syncwarp();
        if (lane == 0) mbar_arrive(bars + 8 * B_MODB);
        PROF_AT(lane == 0, 15);
      }
      __syncwarp();
#pragma unroll 1
      for (int q = C_H2; q < 9; q++) {
        const int n = q < 7 ? q : (q == 7 ? C_A0 : C_ACT + 3);
        cnt_wait_lazy(cnt + n, n == C_H2 ? target * 8 : target);
        arrive_elect(bars + 8 * (B_RDY + n));
      }
      {
        uint32_t m[2];
        const uint4* src = p.modll + 512 + 768 + j * 32 + lane;
        ll_poll<1>([&](int) { return src; }, tag, m);
        sts128(sm + MODB_OFF + (384 + lane * 4) * 4, m[0] << 16, m[0] & 0xffff0000u, m[1] << 16, m[1] & 0xffff0000u);
        cnt_wait_lazy(cnt + C_SP + (j >> 1), target);
        __syncwarp();
        if (lane == 0) mbar_arrive(bars + 8 * (B_MODB + 1));
      }
    }
  } else {
    uint32_t tag;

    {
      const int tid = threadIdx.x - 128, cw = tid >> 7, warp = (tid >> 5) & 3, lane = tid & 31;
      const int l16 = lane & 15, half = lane >> 4, w8 = cw * 4 + warp;
      const uint32_t cbuf = sm + 3 * 49152 + w8 * 512;
      if (lane < 16) cp_async16(cbuf + lane * 16, gc + w8 * 128 + lane * 8);
      asm volatile("cp.async.commit_group;" ::: "memory");
      const uint32_t xbuf = sm + 40960 + (cw * 2 + (l16 >> 3)) * 49152 + (warp * 16 + half) * 128;
      {
        const char* xp = (const char*)gx + (uint32_t)((rb * 128 + (warp * 16 + half) * 2 + cw) * 2048 + j * 256 + l16 * 16);
#pragma unroll
        for (int i = 0; i < 8; i++) cp_async16(xbuf + i * 256 + (((l16 & 7) ^ ((i * 2 + half) & 7)) << 4), xp + i * 8192);
      }
      asm volatile("cp.async.commit_group;" ::: "memory");
      const uint32_t wbuf = sm + cw * 49152 + warp * 4096;
      {
        const char* wp = (const char*)gwmod + (uint32_t)(cta * 32 + (lane & 1) * 16 + (w8 * 128 + (lane >> 1)) * 12288);
#pragma unroll
        for (int i = 0; i < 8; i++) cp_async16(wbuf + i * 512 + lane * 16, wp + i * 16 * 12288);
      }
      asm volatile("cp.async.commit_group;" ::: "memory");
      PROF_AT(tid == 0, 32);
      uint2* st1 = gstats + (rb * 8 + j) * 128 + cw * 64 + warp * 16;
      cluster_arrive_relaxed();
      asm volatile("setmaxnreg.inc.sync.aligned.u32 232;");
      uint32_t sa[4][4];
      {
        asm volatile("cp.async.wait_group 2;" ::: "memory");
        __syncwarp();
        const float2 cv = lds64f(cbuf + lane * 8);
        const uint32_t c0 = __float_as_uint(cv.x), c1 = __float_as_uint(cv.y);
        sts64f(cbuf + lane * 8, __uint_as_float(pack2(silu_f(bf_lo(c0)), silu_f(bf_hi(c0)))), __uint_as_float(pack2(silu_f(bf_lo(c1)), silu_f(bf_hi(c1)))));
        __syncwarp();
#pragma unroll
        for (int q = 0; q < 4; q++) ldmatrix4(sa[q][0], sa[q][1], sa[q][2], sa[q][3], cbuf + q * 64 + (lane >> 3) * 16);
      }
      cluster_wait();
      tag = lds32(bars + 8 * B_COUNT);
      asm volatile("cp.async.wait_group 1;" ::: "memory");
      __syncwarp();
      uint32_t xl[16], xh[16];
      {
        const int srow = warp * 16 + (lane & 15);
#pragma unroll
        for (int q = 0; q < 8; q++)
          ldmatrix4(xl[2 * q], xh[2 * q], xl[2 * q + 1], xh[2 * q + 1],
                    sm + 40960 + (cw * 2 + (q >> 2)) * 49152 + srow * 128 + (((half + (q & 3) * 2) ^ (srow & 7)) << 4));
      }
      publish_stats(xl, xh, st1, lane, tag16(tag, 0));
      PROF_AT(tid == 0, 50);
      asm volatile("cp.async.wait_group 0;" ::: "memory");
      __syncwarp();
      PROF_AT(tid == 0, 51);
      {
        uint32_t b[8][4];
#pragma unroll
        for (int ks = 0; ks < 8; ks++) ldmatrix4t(b[ks], wbuf + (ks * 16 + (lane & 15)) * 32 + (lane >> 4) * 16);
        float d0[4] = {0.f, 0.f, 0.f, 0.f}, d1[4] = {0.f, 0.f, 0.f, 0.f}, d2[4] = {0.f, 0.f, 0.f, 0.f}, d3[4] = {0.f, 0.f, 0.f, 0.f};
#pragma unroll
        for (int q = 0; q < 4; q++) {
          mma16816(d0, sa[q][0], sa[q][0], sa[q][1], sa[q][1], b[2 * q][0], b[2 * q][1]);
          mma16816(d1, sa[q][0], sa[q][0], sa[q][1], sa[q][1], b[2 * q][2], b[2 * q][3]);
          mma16816(d2, sa[q][2], sa[q][2], sa[q][3], sa[q][3], b[2 * q + 1][0], b[2 * q + 1][1]);
          mma16816(d3, sa[q][2], sa[q][2], sa[q][3], sa[q][3], b[2 * q + 1][2], b[2 * q + 1][3]);
        }
        d0[0] += d2[0]; d0[1] += d2[1]; d1[0] += d3[0]; d1[1] += d3[1];
        if (lane < 4) {
          sts64f(sm + RED_OFF + (w8 * 16 + lane * 2) * 4, d0[0], d0[1]);
          sts64f(sm + RED_OFF + (w8 * 16 + 8 + lane * 2) * 4, d1[0], d1[1]);
        }
        asm volatile("bar.arrive 1, 288;" ::: "memory");
      }
      {
        const int c = lane & 3;
        float rs[2], nb[2];
        stat_gather(gstats + rb * 1024 + cw * 64 + warp * 16, tag16(tag, 0), lane, rs, nb);
#pragma unroll
        for (int n = 0; n < 16; n++) {
          xl[n] = pack2(bf_lo(xl[n]) * rs[0] + nb[0], bf_hi(xl[n]) * rs[0] + nb[0]);
          xh[n] = pack2(bf_lo(xh[n]) * rs[1] + nb[1], bf_hi(xh[n]) * rs[1] + nb[1]);
        }
        const int srow = warp * 16 + l16;
        const uint32_t slab = stg + cw * 8192 + srow * 128;
#pragma unroll
        for (int q = 0; q < 8; q++)
          stmatrix4(slab + (q >> 2) * 16384 + (((half + (q & 3) * 2) ^ (srow & 7)) << 4), xl[2 * q], xh[2 * q], xl[2 * q + 1], xh[2 * q + 1]);
        PROF_AT(tid == 0, 52);
        mbar_wait(bars + 8 * B_MODA, 0);
        PROF_AT(tid == 0, 2);
#pragma unroll
        for (int q = 0; q < 8; q++) {
          const float2 m0 = lds64f(sm + MODB_OFF + (8 * q + c) * 8), m1 = lds64f(sm + MODB_OFF + (8 * q + 4 + c) * 8);
          const uint32_t c0 = __float_as_uint(m0.x), s0 = __float_as_uint(m0.y), c1 = __float_as_uint(m1.x), s1 = __float_as_uint(m1.y);
          stmatrix4(slab + (q >> 2) * 16384 + (((half + (q & 3) * 2) ^ (srow & 7)) << 4), fma_bf2(xl[2 * q], c0, s0), fma_bf2(xh[2 * q], c0, s0),
                    fma_bf2(xl[2 * q + 1], c1, s1), fma_bf2(xh[2 * q + 1], c1, s1));
          if ((q & 3) == 3) stage_done(bars + 8 * (B_STGF + (q >> 2)), lane);
        }
      }
      PROF_AT(tid == 0, 3);
    }

    uint32_t xl[16], xh[16];
    {
      RING_IDS();
      uint32_t prev = 0;
      float acc1[96];
      {
        Ring g{bars + 8 * B_FQ, rbars + 8 * B_EQ, 0, 0u, 0u, releaser TR(0)};
        float acc0[96];
#pragma unroll 1
        for (int kb = 0; kb < 2; kb++) kblock<192, 4, 49152>(acc0, g, a_base + STG_OFF + kb * 16384, kb == 0, prev);
#pragma unroll 1
        for (int kb = 0; kb < 2; kb++) kblock<192, 4, 49152>(acc1, g, a_base + STG_OFF + kb * 16384, kb == 0, prev);
#pragma unroll 1
        for (int kb = 0; kb < 14; kb++) kblock<192, 4, 49152>(acc0, g, a_base + g.off, false, prev);
        PROF_AT(tid == 0, 4);
        attention<NPRE0, false>(acc0, p, 0, rb, cta, cw, warp, tag, stg, bars, prev, [&]() { kblock<192, 4, 49152>(acc1, g, a_base + g.off, false, prev); });
        PROF_AT(tid == 0, 5);
        {
          LANE_IDS();
#pragma unroll
          for (int q = 0; q < 8; q++)
            ldmatrix4(xl[2 * q], xh[2 * q], xl[2 * q + 1], xh[2 * q + 1], sm + 40960 + (cw * 2 + (q >> 2)) * 49152 + srow * 128 + ((sw0 ^ ((q & 3) * 2)) << 4));
#pragma unroll
          for (int q = 0; q < 16; q++) asm volatile("" : "+r"(xl[q]), "+r"(xh[q])::"memory");
        }
#pragma unroll 1
        for (int kb = 5 + NPRE0; kb < 14; kb++) kblock<192, 4, 49152>(acc1, g, a_base + g.off, false, prev);
        PROF_AT(tid == 0, 6);
      }
      float acc[64];
      Ring g{bars + 8 * B_FW, rbars + 8 * B_EW, 0, 0u, 0u, releaser TR(32)};
      attention<NPRE1, true>(acc1, p, 1, rb, cta, cw, warp, tag, stg, bars, prev, [&]() { kblock<128, 6, 32768>(acc, g, a_base + g.off, g.s == 0, prev); });
      PROF_AT(tid == 0, 7);
      LANE_IDS();
      unsigned* cnt = p.cnt + rb * 32;
      tma_store2(&p.o_st, stg + cw * 8192 + warp * 2048, j * 128 + 64, rb * 128 + cw * 64 + warp * 16);
      asm volatile("cp.async.bulk.commit_group;" ::: "memory");
#pragma unroll 1
      for (int kb = 1 + NPRE1; kb < 16; kb++) {
        if (kb == 8) wg_bar(cw);
        kblock<128, 6, 32768>(acc, g, a_base + (kb == 8 ? STG_OFF : g.off), false, prev);
        if (kb == 3 + NPRE1) {
          asm volatile("cp.async.bulk.wait_group 0;" ::: "memory");
          __syncwarp();
          cnt_signal(cnt + C_O + 1);
        }
      }
      mbar_wait(bars + 8 * B_STGE, 0);
      mbar_wait(bars + 8 * B_MODB, 0);
      float2 ga[16];
#pragma unroll
      for (int n = 0; n < 16; n++) ga[n] = lds64f(sm + MODB_OFF + (8 * n + 2 * c) * 4);
      tile_end(acc, prev);
      PROF_AT(tid == 0, 8);
#pragma unroll
      for (int n = 0; n < 16; n++) {
        acc[4 * n] = ga[n].x * acc[4 * n] + bf_lo(xl[n]); acc[4 * n + 1] = ga[n].y * acc[4 * n + 1] + bf_hi(xl[n]);
        acc[4 * n + 2] = ga[n].x * acc[4 * n + 2] + bf_lo(xh[n]); acc[4 * n + 3] = ga[n].y * acc[4 * n + 3] + bf_hi(xh[n]);
        xl[n] = pack2(acc[4 * n], acc[4 * n + 1]);
        xh[n] = pack2(acc[4 * n + 2], acc[4 * n + 3]);
      }
      publish_stats(xl, xh, gstats + (rb * 8 + j) * 128 + cw * 64 + warp * 16, lane, tag16(tag, 1));
      PROF_AT(tid == 0, 48);
      float2 sb[16], cb[16];
#pragma unroll
      for (int n = 0; n < 16; n++) {
        sb[n] = lds64f(sm + MODB_OFF + (128 + 8 * n + 2 * c) * 4);
        cb[n] = lds64f(sm + MODB_OFF + (256 + 8 * n + 2 * c) * 4);
      }
      PROF_AT(tid == 0, 49);
      float nb[2], rstd[2];
      stat_gather(gstats + rb * 1024 + cw * 64 + warp * 16, tag16(tag, 1), lane, rstd, nb);
      PROF_AT(tid == 0, 9);
#pragma unroll
      for (int ch = 0; ch < 2; ch++) {
        uint32_t lo[8], hi[8];
#pragma unroll
        for (int t = 0; t < 8; t++) {
          const int n = ch * 8 + t;
          lo[t] = pack2((acc[4 * n] * rstd[0] + nb[0]) * cb[n].x + sb[n].x, (acc[4 * n + 1] * rstd[0] + nb[0]) * cb[n].y + sb[n].y);
          hi[t] = pack2((acc[4 * n + 2] * rstd[1] + nb[1]) * cb[n].x + sb[n].x, (acc[4 * n + 3] * rstd[1] + nb[1]) * cb[n].y + sb[n].y);
        }
        stage_slab(sm + ch * 32768 + cw * 8192, warp, lane, lo, hi);
        stage_done(bars + 8 * (B_STGF + ch), lane);
        tma_store2(&p.h2_st, sm + ch * 32768 + cw * 8192 + warp * 2048, j * 128 + ch * 64, rb * 128 + cw * 64 + warp * 16);
        asm volatile("cp.async.bulk.commit_group;" ::: "memory");
      }
      PROF_AT(tid == 0, 10);
    }

    uint32_t pg[32], pu[32];
    {
      RING_IDS();
      float acc[128];
      uint32_t prev = 0;
      Ring g{bars + 8 * B_FG, rbars + 8 * B_EG, 0, 0u, 3 * 49152u, releaser TR(66)};
      {
        Ring w{bars + 8 * B_FW, rbars + 8 * B_EW, 4, 0u, 4 * 32768u, releaser TR(48)};
        float acn[64];
#pragma unroll 1
        for (int kb = 0; kb < 2; kb++) {
          kblock<256, 6, 32768>(acc, w, a_base + kb * 32768, kb == 0, prev, 0u);
          if (kb == 0) asm volatile("cp.async.bulk.wait_group 1;" ::: "memory");
          else asm volatile("cp.async.bulk.wait_group 0;" ::: "memory");
          __syncwarp();
          cnt_signal(p.cnt + rb * 32 + (kb == 0 ? C_H2A : C_H2));
        }
        {
          LANE_IDS();
#pragma unroll
          for (int q = 0; q < 8; q++)
            stmatrix4(slab + (q >> 2) * 16384 + ((sw0 ^ ((q & 3) * 2)) << 4), xl[2 * q], xh[2 * q], xl[2 * q + 1], xh[2 * q + 1]);
          __syncwarp();
        }
#pragma unroll 1
        for (int kb = 0; kb < 16; kb++) {
          kblock<128, 6, 32768>(acn, w, a_base + w.off, kb == 0, prev);
          if (kb == 4) {
            asm volatile("fence.proxy.async.shared::cta;" ::: "memory");
            __syncwarp();
          }
          if (kb == 6 + warp || kb == 10 + warp) {
            const int ch = kb != 6 + warp;
            tma_store3(&p.out, stg + ch * 16384 + cw * 8192 + warp * 2048, j * 128 + ch * 64, rb * 64 + warp * 16, cw);
            asm volatile("cp.async.bulk.commit_group;" ::: "memory");
          }
        }
        PROF_AT(tid == 0, 39);
        kblock<256, 4, 49152>(acc, g, a_base + g.off, false, prev);
        fence_regs(acn);
#pragma unroll
        for (int q = 0; q < 16; q++) {
          pg[q] = pack2(acn[2 * q], acn[2 * q + 1]);
          pu[q] = pack2(acn[32 + 2 * q], acn[32 + 2 * q + 1]);
          pg[16 + q] = 0; pu[16 + q] = 0;
        }
        asm volatile("cp.async.bulk.wait_group 0;" ::: "memory");
        kblock<256, 4, 49152>(acc, g, a_base + g.off, false, prev);
      }
      LANE_IDS();
#pragma unroll 1
      for (int t = 0; t < 3; t++) {
#pragma unroll 1
        for (int blk = 0; blk < (t == 0 ? 2 : 4); blk++) {
          g.s = 2;
#pragma unroll
          for (int i = 0; i < 4; i++) {
            g.off = ((i + 1) & 3) * 49152;
            if (i == 3 && blk == 3) skew_pre(cw);
            kblock<256, 4, 49152>(acc, g, a_base + g.off, t > 0 && blk == 0 && i == 0, prev);
            if (i == 3 && blk == 3) skew_post(cw);
            if ((blk & 1) == 0 && i == 0) mbar_wait(bars + 8 * (B_STGE + (blk >> 1)), (t + 1 + (blk >> 1)) & 1);
            stmatrix2(slab + (blk >> 1) * 16384 + (((srow & 7) ^ ((blk & 1) * 4 + i)) << 4), swiglu2(pg[2 * i], pu[2 * i]), swiglu2(pg[2 * i + 1], pu[2 * i + 1]));
          }
#pragma unroll
          for (int q = 0; q < 24; q++) { pg[q] = pg[q + 8]; pu[q] = pu[q + 8]; }
          if (blk & 1) stage_done(bars + 8 * (B_STGF + (blk >> 1)), lane);
        }
#pragma unroll 1
        for (int kb = t == 0 ? 0 : 4; kb < 4; kb++) {
          if (kb == 3) skew_pre(cw);
          kblock<256, 4, 49152>(acc, g, a_base + g.off, false, prev);
          if (kb == 3) skew_post(cw);
        }
        tile_end(acc, prev);
        PROF_AT(tid == 0, 36 + t);
#pragma unroll
        for (int q = 0; q < 32; q++) {
          pg[q] = pack2(acc[2 * q], acc[2 * q + 1]);
          pu[q] = pack2(acc[64 + 2 * q], acc[64 + 2 * q + 1]);
        }
      }
      PROF_AT(tid == 0, 11);
    }

    {
      RING_IDS();
      LANE_IDS();
      Ring g{bars + 8 * B_FD, rbars + 8 * B_ED, 0, 0u, 2 * 32768u, releaser TR(112)};
      float acc[64];
      uint32_t prev = 0;
#pragma unroll 1
      for (int blk = 0; blk < 4; blk++) {
#pragma unroll
        for (int i = 0; i < 8; i++) {
          kblock<128, 6, 32768>(acc, g, a_base + g.off, blk == 0 && i == 0, prev);
          if ((blk & 1) == 0 && i == 0) mbar_wait(bars + 8 * (B_STGE + (blk >> 1)), blk >> 1);
          stmatrix1(slab + (blk >> 1) * 16384 + (i & 1) * 1024 + (((srow & 7) ^ ((blk & 1) * 4 + (i >> 1))) << 4), swiglu2(pg[i], pu[i]));
        }
#pragma unroll
        for (int q = 0; q < 24; q++) { pg[q] = pg[q + 8]; pu[q] = pu[q + 8]; }
        if (blk & 1) stage_done(bars + 8 * (B_STGF + (blk >> 1)), lane);
      }
#pragma unroll 1
      for (int kb = 32; kb < 56 - KH; kb++) {
        if (kb == 50 - KH) g.releaser = false;
        if (kb == 52 - KH) skew_pre(cw);
        kblock<128, 6, 32768>(acc, g, a_base + g.off, false, prev);
      }
      skew_post(cw);
      mbar_wait(bars + 8 * (B_MODB + 1), 0);
      mbar_wait(bars + 8 * B_STGE, 1);
      mbar_wait(bars + 8 * (B_STGE + 1), 0);
      float2 gbv[16];
#pragma unroll
      for (int n = 0; n < 16; n++) gbv[n] = lds64f(sm + MODB_OFF + (384 + 8 * n + 2 * c) * 4);
      tile_end(acc, prev);
      PROF_AT(tid == 0, 13);
#pragma unroll
      for (int ch = 0; ch < 2; ch++) {
        uint32_t lo[8], hi[8];
#pragma unroll
        for (int t = 0; t < 8; t++) {
          const int n = ch * 8 + t;
          const float2 gb = gbv[n];
          lo[t] = pack2(gb.x * acc[4 * n], gb.y * acc[4 * n + 1]);
          hi[t] = pack2(gb.x * acc[4 * n + 2], gb.y * acc[4 * n + 3]);
        }
        stage_slab(stg + ch * 16384 + cw * 8192, warp, lane, lo, hi);
        asm volatile("fence.proxy.async.shared::cta;" ::: "memory");
        __syncwarp();
        tma_add3(&p.out, stg + ch * 16384 + cw * 8192 + warp * 2048, j * 128 + ch * 64, rb * 64 + warp * 16, cw);
      }
      asm volatile("cp.async.bulk.commit_group;" ::: "memory");
      if (lane == 0) mbar_arrive(bars + 8 * B_STGF);
      asm volatile("cp.async.bulk.wait_group.read 0;" ::: "memory");
      PROF_AT(tid == 0, 14);
    }
    if (blockIdx.x == 0 && threadIdx.x == 128) asm volatile("st.relaxed.gpu.global.u32 [%0], %1;" ::"l"(gepoch), "r"(tag) : "memory");
  }
}

typedef CUresult (*EncodeFn)(CUtensorMap*, CUtensorMapDataType, cuuint32_t, void*, const cuuint64_t*, const cuuint64_t*,
                             const cuuint32_t*, const cuuint32_t*, CUtensorMapInterleave, CUtensorMapSwizzle,
                             CUtensorMapL2promotion, CUtensorMapFloatOOBfill);

void encode2d(EncodeFn fn, CUtensorMap* m, const void* ptr, uint64_t cols, uint64_t rows, uint32_t box_rows) {
  cuuint64_t dims[2] = {cols, rows};
  cuuint64_t strides[1] = {cols * 2};
  cuuint32_t box[2] = {64, box_rows};
  cuuint32_t es[2] = {1, 1};
  fn(m, CU_TENSOR_MAP_DATA_TYPE_BFLOAT16, 2, (void*)ptr, dims, strides, box, es, CU_TENSOR_MAP_INTERLEAVE_NONE,
     CU_TENSOR_MAP_SWIZZLE_128B, CU_TENSOR_MAP_L2_PROMOTION_L2_128B, CU_TENSOR_MAP_FLOAT_OOB_FILL_NONE);
}

}

extern "C" void kernel_launch(void* const* d_in, const int* in_sizes, int n_in, void* d_out, int out_size) {
  (void)in_sizes; (void)n_in; (void)out_size;
  void* fp = nullptr;
  cudaDriverEntryPointQueryResult qr;
  cudaGetDriverEntryPoint("cuTensorMapEncodeTiled", &fp, cudaEnableDefault, &qr);
  EncodeFn fn = (EncodeFn)fp;
  void *ph, *po, *ph2, *pact;
  cudaGetSymbolAddress(&ph, g_h);
  cudaGetSymbolAddress(&po, g_o);
  ph2 = ph;
  cudaGetSymbolAddress(&pact, g_act);
  Params p;
  encode2d(fn, &p.h, ph, DM, SEQ, 128);
  encode2d(fn, &p.o_ld, po, DM, SEQ, 128);
  encode2d(fn, &p.h2, ph2, DM, SEQ, 128);
  encode2d(fn, &p.act, pact, FF, SEQ, 128);
  encode2d(fn, &p.act_st, pact, FF, SEQ, 32);
  encode2d(fn, &p.wm, d_in[8], 6 * DM, DM, 64);
  encode2d(fn, &p.o_st, po, DM, SEQ, 16);
  encode2d(fn, &p.h2_st, ph2, DM, SEQ, 16);
  encode2d(fn, &p.wqkv, d_in[1], 3 * DM, DM, 64);
  encode2d(fn, &p.wqkv32, d_in[1], 3 * DM, DM, 32);
  encode2d(fn, &p.wo, d_in[2], DM, DM, 64);
  encode2d(fn, &p.wg, d_in[4], FF, DM, 64);
  encode2d(fn, &p.wu, d_in[5], FF, DM, 64);
  encode2d(fn, &p.wd, d_in[6], DM, FF, 64);
  {
    cuuint64_t dims[3] = {DM, SEQ / 2, 2};
    cuuint64_t strides[2] = {DM * 4, DM * 2};
    cuuint32_t box[3] = {64, 16, 1};
    cuuint32_t es[3] = {1, 1, 1};
    fn(&p.out, CU_TENSOR_MAP_DATA_TYPE_BFLOAT16, 3, d_out, dims, strides, box, es, CU_TENSOR_MAP_INTERLEAVE_NONE,
       CU_TENSOR_MAP_SWIZZLE_128B, CU_TENSOR_MAP_L2_PROMOTION_L2_128B, CU_TENSOR_MAP_FLOAT_OOB_FILL_NONE);
  }
  void* q;
  cudaGetSymbolAddress(&q, g_modll); p.modll = (uint4*)q;
  cudaGetSymbolAddress(&q, g_halo); p.halo = (uint4*)q;
  cudaGetSymbolAddress(&q, g_stats); uint2* stats = (uint2*)q;
  cudaGetSymbolAddress(&q, g_cnt); p.cnt = (unsigned*)q;
  cudaGetSymbolAddress(&q, g_epoch); unsigned* epoch = (unsigned*)q;

  cudaFuncSetAttribute(fused_kernel, cudaFuncAttributeMaxDynamicSharedMemorySize, SMEM_BYTES);
  cudaLaunchConfig_t cfg = {};
  cfg.gridDim = dim3(NCTA + 4);
  cfg.blockDim = dim3(384);
  cfg.dynamicSmemBytes = SMEM_BYTES;
  cfg.stream = cudaStreamPerThread;
  cudaLaunchAttribute at[1];
  at[0].id = cudaLaunchAttributeClusterDimension;
  at[0].val.clusterDim.x = 2; at[0].val.clusterDim.y = 1; at[0].val.clusterDim.z = 1;
  cfg.attrs = at;
  cfg.numAttrs = 1;
  cudaLaunchKernelEx(&cfg, fused_kernel, (const bf16*)d_in[0], (const bf16*)d_in[8], (const bf16*)d_in[7], epoch, stats, p);
}
```

```cpp
#include <cuda_runtime.h>
#include <cuda_bf16.h>
#include <cuda.h>
#include <stdint.h>

typedef __nv_bfloat16 bf16;

#define PAUSE 200
#define WMDELAY 500
#define BDELAY 1500
#define NPRE0 3
#define NPRE1 1
#define ALIAS 1
#define PFW 8000
#define KH 3

#define WLD 200

#define H1D 500

__device__ __forceinline__ void wgmma_ss_n128(float (&d)[64], uint32_t da, uint32_t db, int scale_d) {
  asm volatile("{\n.reg .pred p;\n.reg .b64 da, db;\nsetp.ne.b32 p, %66, 0;\n"
    "mov.b64 da, {%64, 0x40000040};\nmov.b64 db, {%65, 0x40000040};\n"
    "wgmma.mma_async.sync.aligned.m64n128k16.f32.bf16.bf16 "
    "{%0, %1, %2, %3, %4, %5, %6, %7, %8, %9, %10, %11, %12, %13, %14, %15, "
    "%16, %17, %18, %19, %20, %21, %22, %23, %24, %25, %26, %27, %28, %29, %30, %31, "
    "%32, %33, %34, %35, %36, %37, %38, %39, %40, %41, %42, %43, %44, %45, %46, %47, "
    "%48, %49, %50, %51, %52, %53, %54, %55, %56, %57, %58, %59, %60, %61, %62, %63}, "
    "da, db, p, 1, 1, 0, 1;\n}\n"
    : "+f"(d[0]), "+f"(d[1]), "+f"(d[2]), "+f"(d[3]), "+f"(d[4]), "+f"(d[5]), "+f"(d[6]), "+f"(d[7]),
      "+f"(d[8]), "+f"(d[9]), "+f"(d[10]), "+f"(d[11]), "+f"(d[12]), "+f"(d[13]), "+f"(d[14]), "+f"(d[15]),
      "+f"(d[16]), "+f"(d[17]), "+f"(d[18]), "+f"(d[19]), "+f"(d[20]), "+f"(d[21]), "+f"(d[22]), "+f"(d[23]),
      "+f"(d[24]), "+f"(d[25]), "+f"(d[26]), "+f"(d[27]), "+f"(d[28]), "+f"(d[29]), "+f"(d[30]), "+f"(d[31]),
      "+f"(d[32]), "+f"(d[33]), "+f"(d[34]), "+f"(d[35]), "+f"(d[36]), "+f"(d[37]), "+f"(d[38]), "+f"(d[39]),
      "+f"(d[40]), "+f"(d[41]), "+f"(d[42]), "+f"(d[43]), "+f"(d[44]), "+f"(d[45]), "+f"(d[46]), "+f"(d[47]),
      "+f"(d[48]), "+f"(d[49]), "+f"(d[50]), "+f"(d[51]), "+f"(d[52]), "+f"(d[53]), "+f"(d[54]), "+f"(d[55]),
      "+f"(d[56]), "+f"(d[57]), "+f"(d[58]), "+f"(d[59]), "+f"(d[60]), "+f"(d[61]), "+f"(d[62]), "+f"(d[63])
    : "r"(da), "r"(db), "r"(scale_d));
}

__device__ __forceinline__ void wgmma_ss_n192(float (&d)[96], uint32_t da, uint32_t db, int scale_d) {
  asm volatile("{\n.reg .pred p;\n.reg .b64 da, db;\nsetp.ne.b32 p, %98, 0;\n"
    "mov.b64 da, {%96, 0x40000040};\nmov.b64 db, {%97, 0x40000040};\n"
    "wgmma.mma_async.sync.aligned.m64n192k16.f32.bf16.bf16 "
    "{%0, %1, %2, %3, %4, %5, %6, %7, %8, %9, %10, %11, %12, %13, %14, %15, "
    "%16, %17, %18, %19, %20, %21, %22, %23, %24, %25, %26, %27, %28, %29, %30, %31, "
    "%32, %33, %34, %35, %36, %37, %38, %39, %40, %41, %42, %43, %44, %45, %46, %47, "
    "%48, %49, %50, %51, %52, %53, %54, %55, %56, %57, %58, %59, %60, %61, %62, %63, "
    "%64, %65, %66, %67, %68, %69, %70, %71, %72, %73, %74, %75, %76, %77, %78, %79, "
    "%80, %81, %82, %83, %84, %85, %86, %87, %88, %89, %90, %91, %92, %93, %94, %95}, "
    "da, db, p, 1, 1, 0, 1;\n}\n"
    : "+f"(d[0]), "+f"(d[1]), "+f"(d[2]), "+f"(d[3]), "+f"(d[4]), "+f"(d[5]), "+f"(d[6]), "+f"(d[7]),
      "+f"(d[8]), "+f"(d[9]), "+f"(d[10]), "+f"(d[11]), "+f"(d[12]), "+f"(d[13]), "+f"(d[14]), "+f"(d[15]),
      "+f"(d[16]), "+f"(d[17]), "+f"(d[18]), "+f"(d[19]), "+f"(d[20]), "+f"(d[21]), "+f"(d[22]), "+f"(d[23]),
      "+f"(d[24]), "+f"(d[25]), "+f"(d[26]), "+f"(d[27]), "+f"(d[28]), "+f"(d[29]), "+f"(d[30]), "+f"(d[31]),
      "+f"(d[32]), "+f"(d[33]), "+f"(d[34]), "+f"(d[35]), "+f"(d[36]), "+f"(d[37]), "+f"(d[38]), "+f"(d[39]),
      "+f"(d[40]), "+f"(d[41]), "+f"(d[42]), "+f"(d[43]), "+f"(d[44]), "+f"(d[45]), "+f"(d[46]), "+f"(d[47]),
      "+f"(d[48]), "+f"(d[49]), "+f"(d[50]), "+f"(d[51]), "+f"(d[52]), "+f"(d[53]), "+f"(d[54]), "+f"(d[55]),
      "+f"(d[56]), "+f"(d[57]), "+f"(d[58]), "+f"(d[59]), "+f"(d[60]), "+f"(d[61]), "+f"(d[62]), "+f"(d[63]),
      "+f"(d[64]), "+f"(d[65]), "+f"(d[66]), "+f"(d[67]), "+f"(d[68]), "+f"(d[69]), "+f"(d[70]), "+f"(d[71]),
      "+f"(d[72]), "+f"(d[73]), "+f"(d[74]), "+f"(d[75]), "+f"(d[76]), "+f"(d[77]), "+f"(d[78]), "+f"(d[79]),
      "+f"(d[80]), "+f"(d[81]), "+f"(d[82]), "+f"(d[83]), "+f"(d[84]), "+f"(d[85]), "+f"(d[86]), "+f"(d[87]),
      "+f"(d[88]), "+f"(d[89]), "+f"(d[90]), "+f"(d[91]), "+f"(d[92]), "+f"(d[93]), "+f"(d[94]), "+f"(d[95])
    : "r"(da), "r"(db), "r"(scale_d));
}

__device__ __forceinline__ void wgmma_ss_n256(float (&d)[128], uint32_t da, uint32_t db, int scale_d) {
  asm volatile("{\n.reg .pred p;\n.reg .b64 da, db;\nsetp.ne.b32 p, %130, 0;\n"
    "mov.b64 da, {%128, 0x40000040};\nmov.b64 db, {%129, 0x40000040};\n"
    "wgmma.mma_async.sync.aligned.m64n256k16.f32.bf16.bf16 "
    "{%0, %1, %2, %3, %4, %5, %6, %7, %8, %9, %10, %11, %12, %13, %14, %15, "
    "%16, %17, %18, %19, %20, %21, %22, %23, %24, %25, %26, %27, %28, %29, %30, %31, "
    "%32, %33, %34, %35, %36, %37, %38, %39, %40, %41, %42, %43, %44, %45, %46, %47, "
    "%48, %49, %50, %51, %52, %53, %54, %55, %56, %57, %58, %59, %60, %61, %62, %63, "
    "%64, %65, %66, %67, %68, %69, %70, %71, %72, %73, %74, %75, %76, %77, %78, %79, "
    "%80, %81, %82, %83, %84, %85, %86, %87, %88, %89, %90, %91, %92, %93, %94, %95, "
    "%96, %97, %98, %99, %100, %101, %102, %103, %104, %105, %106, %107, %108, %109, %110, %111, "
    "%112, %113, %114, %115, %116, %117, %118, %119, %120, %121, %122, %123, %124, %125, %126, %127}, "
    "da, db, p, 1, 1, 0, 1;\n}\n"
    : "+f"(d[0]), "+f"(d[1]), "+f"(d[2]), "+f"(d[3]), "+f"(d[4]), "+f"(d[5]), "+f"(d[6]), "+f"(d[7]),
      "+f"(d[8]), "+f"(d[9]), "+f"(d[10]), "+f"(d[11]), "+f"(d[12]), "+f"(d[13]), "+f"(d[14]), "+f"(d[15]),
      "+f"(d[16]), "+f"(d[17]), "+f"(d[18]), "+f"(d[19]), "+f"(d[20]), "+f"(d[21]), "+f"(d[22]), "+f"(d[23]),
      "+f"(d[24]), "+f"(d[25]), "+f"(d[26]), "+f"(d[27]), "+f"(d[28]), "+f"(d[29]), "+f"(d[30]), "+f"(d[31]),
      "+f"(d[32]), "+f"(d[33]), "+f"(d[34]), "+f"(d[35]), "+f"(d[36]), "+f"(d[37]), "+f"(d[38]), "+f"(d[39]),
      "+f"(d[40]), "+f"(d[41]), "+f"(d[42]), "+f"(d[43]), "+f"(d[44]), "+f"(d[45]), "+f"(d[46]), "+f"(d[47]),
      "+f"(d[48]), "+f"(d[49]), "+f"(d[50]), "+f"(d[51]), "+f"(d[52]), "+f"(d[53]), "+f"(d[54]), "+f"(d[55]),
      "+f"(d[56]), "+f"(d[57]), "+f"(d[58]), "+f"(d[59]), "+f"(d[60]), "+f"(d[61]), "+f"(d[62]), "+f"(d[63]),
      "+f"(d[64]), "+f"(d[65]), "+f"(d[66]), "+f"(d[67]), "+f"(d[68]), "+f"(d[69]), "+f"(d[70]), "+f"(d[71]),
      "+f"(d[72]), "+f"(d[73]), "+f"(d[74]), "+f"(d[75]), "+f"(d[76]), "+f"(d[77]), "+f"(d[78]), "+f"(d[79]),
      "+f"(d[80]), "+f"(d[81]), "+f"(d[82]), "+f"(d[83]), "+f"(d[84]), "+f"(d[85]), "+f"(d[86]), "+f"(d[87]),
      "+f"(d[88]), "+f"(d[89]), "+f"(d[90]), "+f"(d[91]), "+f"(d[92]), "+f"(d[93]), "+f"(d[94]), "+f"(d[95]),
      "+f"(d[96]), "+f"(d[97]), "+f"(d[98]), "+f"(d[99]), "+f"(d[100]), "+f"(d[101]), "+f"(d[102]), "+f"(d[103]),
      "+f"(d[104]), "+f"(d[105]), "+f"(d[106]), "+f"(d[107]), "+f"(d[108]), "+f"(d[109]), "+f"(d[110]), "+f"(d[111]),
      "+f"(d[112]), "+f"(d[113]), "+f"(d[114]), "+f"(d[115]), "+f"(d[116]), "+f"(d[117]), "+f"(d[118]), "+f"(d[119]),
      "+f"(d[120]), "+f"(d[121]), "+f"(d[122]), "+f"(d[123]), "+f"(d[124]), "+f"(d[125]), "+f"(d[126]), "+f"(d[127])
    : "r"(da), "r"(db), "r"(scale_d));
}

namespace {

constexpr int SEQ = 2048, DM = 1024, FF = 3584;
constexpr int NCTA = 128;

constexpr uint32_t STG_OFF = 196608;
constexpr uint32_t MISC_OFF = STG_OFF + 32768;
constexpr uint32_t SMEM_BYTES = MISC_OFF + 3072;
constexpr uint32_t RED_OFF = 2 * 49152;
constexpr uint32_t MODB_OFF = MISC_OFF + 512;

enum { B_FQ = 0, B_EQ = 4, B_FW = 8, B_EW = 14, B_FG = 20, B_EG = 24, B_FD = 28, B_ED = 34,
       B_STGF = 40, B_MODB = 42, B_MODA = 44, B_RDY = 46, B_STGE = 58, B_COUNT = 60 };
enum { C_H = 0, C_O = 1, C_H2 = 3, C_ACT = 4, C_HA = 8, C_H2A = 9, C_A0 = 10, C_SP = 12 };

struct Params {
  uint4* modll;
  uint4* halo;
  unsigned* cnt;
  CUtensorMap h, o_ld, o_st, h2, act, out, wqkv, wqkv32, wo, wg, wu, wd, act_st, h2_st, h_st, wm;
};

__device__ __align__(1024) bf16 g_h[SEQ * DM];
__device__ __align__(1024) bf16 g_o[SEQ * DM];
__device__ __align__(1024) bf16 g_act[SEQ * FF];
__device__ __align__(1024) uint4 g_modll[3072 / 2];
__device__ __align__(1024) uint4 g_halo[16 * 8 * 2 * 2 * 8 * 32];
__device__ __align__(1024) uint2 g_stats[SEQ * 8];
__device__ __align__(1024) unsigned g_cnt[16 * 32];
__device__ uint4 g_epoch;
#define TR(off)

__device__ __forceinline__ uint32_t smem_u32(const void* p) { return (uint32_t)__cvta_generic_to_shared(p); }
__device__ __forceinline__ void mbar_init(uint32_t bar, uint32_t count) {
  asm volatile("mbarrier.init.shared::cta.b64 [%0], %1;" ::"r"(bar), "r"(count));
}
__device__ __forceinline__ void mbar_arrive(uint32_t bar) {
  asm volatile("mbarrier.arrive.shared::cta.b64 _, [%0];" ::"r"(bar) : "memory");
}
__device__ __forceinline__ void mbar_arrive_cluster(uint32_t cluster_addr) {
  asm volatile("mbarrier.arrive.shared::cluster.b64 _, [%0];" ::"r"(cluster_addr) : "memory");
}
__device__ __forceinline__ uint32_t mapa(uint32_t addr, uint32_t cta) {
  uint32_t r;
  asm volatile("mapa.shared::cluster.u32 %0, %1, %2;" : "=r"(r) : "r"(addr), "r"(cta));
  return r;
}
__device__ __forceinline__ void jitter() {}
__device__ __forceinline__ void mbar_wait(uint32_t bar, uint32_t parity) {
  jitter();
  asm volatile(
      "{\n.reg .pred p;\n"
      "WAIT_%=:\n"
      "mbarrier.try_wait.parity.shared::cta.b64 p, [%0], %1;\n"
      "@!p bra WAIT_%=;\n}\n" ::"r"(bar), "r"(parity) : "memory");
}
__device__ __forceinline__ void mbar_wait_watchdog(uint32_t bar, uint32_t parity) {
  jitter();
  asm volatile(
      "{\n.reg .pred p;\n.reg .u64 t0, t1;\nmov.u64 t0, %%globaltimer;\n"
      "WAIT_%=:\n"
      "mbarrier.try_wait.parity.shared::cta.b64 p, [%0], %1;\n"
      "@p bra DONE_%=;\n"
      "mov.u64 t1, %%globaltimer;\n"
      "sub.u64 t1, t1, t0;\n"
      "setp.lt.u64 p, t1, 2000000000;\n"
      "@p bra WAIT_%=;\n"
      "trap;\n"
      "DONE_%=:\n}\n" ::"r"(bar), "r"(parity) : "memory");
}
__device__ __forceinline__ void cnt_wait(const unsigned* p, unsigned target) {
  asm volatile(
      "{\n.reg .pred p;\n.reg .u32 v;\n.reg .s32 d;\n"
      "WAIT_%=:\n"
      "ld.relaxed.gpu.global.u32 v, [%0];\n"
      "sub.s32 d, v, %1;\n"
      "setp.lt.s32 p, d, 0;\n"
      "@p bra WAIT_%=;\n"
      "fence.proxy.async.global;\n"
      "}\n" ::"l"(p), "r"(target) : "memory");
}
__device__ __forceinline__ void cnt_wait_lazy(const unsigned* p, unsigned target) {
  asm volatile(
      "{\n.reg .pred p;\n.reg .u32 v;\n.reg .s32 d;\n"
      "WAIT_%=:\n"
      "nanosleep.u32 400;\n"
      "ld.relaxed.gpu.global.u32 v, [%0];\n"
      "sub.s32 d, v, %1;\n"
      "setp.lt.s32 p, d, 0;\n"
      "@p bra WAIT_%=;\n"
      "fence.proxy.async.global;\n"
      "}\n" ::"l"(p), "r"(target) : "memory");
}
__device__ __forceinline__ void cnt_signal(unsigned* p) {
  jitter();
  asm volatile("{\n.reg .pred p;\nelect.sync _|p, 0xffffffff;\n@p red.relaxed.gpu.global.add.u32 [%0], 1;\n}\n" ::"l"(p) : "memory");
}
__device__ __forceinline__ void ll_store(uint4* p, uint32_t a, uint32_t b, uint32_t tag) {
  asm volatile("st.relaxed.gpu.global.v2.b64 [%0], {%1, %2};" ::"l"(p), "l"((uint64_t)a | ((uint64_t)tag << 32)),
               "l"((uint64_t)b | ((uint64_t)tag << 32)) : "memory");
}
__device__ __forceinline__ uint4 ll_peek(const uint4* p) {
  uint4 v;
  asm volatile("ld.relaxed.gpu.global.v4.u32 {%0, %1, %2, %3}, [%4];" : "=r"(v.x), "=r"(v.y), "=r"(v.z), "=r"(v.w) : "l"(p) : "memory");
  return v;
}
template <int N, int SLEEP = 0, class F>
__device__ __forceinline__ void ll_poll(F addr, uint32_t tag, uint32_t (&out)[2 * N]) {
  for (;;) {
    uint4 v[N];
#pragma unroll
    for (int i = 0; i < N; i++) v[i] = ll_peek(addr(i));
    uint32_t bad = 0;
#pragma unroll
    for (int i = 0; i < N; i++) {
      bad |= (v[i].y ^ tag) | (v[i].w ^ tag);
      out[2 * i] = v[i].x;
      out[2 * i + 1] = v[i].z;
    }
    if (__all_sync(~0u, bad == 0)) break;
    if (SLEEP) __nanosleep(SLEEP);
  }
}
constexpr uint64_t POLICY_EVICT_FIRST = 0x12F0000000000000ull;
__device__ __forceinline__ void expect_tx_elect(uint32_t bar, uint32_t bytes) {
  asm volatile("{\n.reg .pred p;\nelect.sync _|p, 0xffffffff;\n@p mbarrier.arrive.expect_tx.shared::cta.b64 _, [%0], %1;\n}\n" ::"r"(bar), "r"(bytes) : "memory");
}
__device__ __forceinline__ void arrive_elect(uint32_t bar) {
  asm volatile("{\n.reg .pred p;\nelect.sync _|p, 0xffffffff;\n@p mbarrier.arrive.shared::cta.b64 _, [%0];\n}\n" ::"r"(bar) : "memory");
}
__device__ __forceinline__ void tma_load(uint32_t dst, const CUtensorMap* m, uint32_t bar, int c0, int c1) {
  asm volatile("{\n.reg .pred p;\nelect.sync _|p, 0xffffffff;\n"
               "@p cp.async.bulk.tensor.2d.shared::cluster.global.mbarrier::complete_tx::bytes [%0], [%1, {%3, %4}], [%2];\n}\n"
               ::"r"(dst), "l"(m), "r"(bar), "r"(c0), "r"(c1) : "memory");
}
__device__ __forceinline__ void tma_load_mc(uint32_t dst, const CUtensorMap* m, uint32_t bar, int c0, int c1) {
  asm volatile("{\n.reg .pred p;\nelect.sync _|p, 0xffffffff;\n"
               "@p cp.async.bulk.tensor.2d.shared::cluster.global.mbarrier::complete_tx::bytes.multicast::cluster.L2::cache_hint [%0], [%1, {%3, %4}], [%2], %5, %6;\n}\n"
               ::"r"(dst), "l"(m), "r"(bar), "r"(c0), "r"(c1), "h"((uint16_t)3), "l"(POLICY_EVICT_FIRST) : "memory");
}
__device__ __forceinline__ void tma_load_ef(uint32_t dst, const CUtensorMap* m, uint32_t bar, int c0, int c1) {
  asm volatile("{\n.reg .pred p;\nelect.sync _|p, 0xffffffff;\n"
               "@p cp.async.bulk.tensor.2d.shared::cluster.global.mbarrier::complete_tx::bytes.L2::cache_hint [%0], [%1, {%3, %4}], [%2], %5;\n}\n"
               ::"r"(dst), "l"(m), "r"(bar), "r"(c0), "r"(c1), "l"(POLICY_EVICT_FIRST) : "memory");
}
__device__ __forceinline__ void tma_store2(const CUtensorMap* m, uint32_t src, int c0, int c1) {
  asm volatile("{\n.reg .pred p;\nelect.sync _|p, 0xffffffff;\n"
               "@p cp.async.bulk.tensor.2d.global.shared::cta.bulk_group [%0, {%2, %3}], [%1];\n}\n"
               ::"l"(m), "r"(src), "r"(c0), "r"(c1) : "memory");
}
__device__ __forceinline__ void tma_store3(const CUtensorMap* m, uint32_t src, int c0, int c1, int c2) {
  asm volatile("{\n.reg .pred p;\nelect.sync _|p, 0xffffffff;\n"
               "@p cp.async.bulk.tensor.3d.global.shared::cta.bulk_group [%0, {%2, %3, %4}], [%1];\n}\n"
               ::"l"(m), "r"(src), "r"(c0), "r"(c1), "r"(c2) : "memory");
}
__device__ __forceinline__ void tma_add3(const CUtensorMap* m, uint32_t src, int c0, int c1, int c2) {
  asm volatile("{\n.reg .pred p;\nelect.sync _|p, 0xffffffff;\n"
               "@p cp.reduce.async.bulk.tensor.3d.global.shared::cta.add.bulk_group [%0, {%2, %3, %4}], [%1];\n}\n"
               ::"l"(m), "r"(src), "r"(c0), "r"(c1), "r"(c2) : "memory");
}
__device__ __forceinline__ void store_pause(bool sleep) {
  asm volatile("cp.async.bulk.commit_group;" ::: "memory");
  asm volatile("cp.async.bulk.wait_group.read 0;" ::: "memory");
  if (sleep) __nanosleep(PAUSE);
}
__device__ __forceinline__ void l2_prefetch_tile(const CUtensorMap* m, int c0, int c1) {
  asm volatile("{\n.reg .pred p;\nelect.sync _|p, 0xffffffff;\n@p cp.async.bulk.prefetch.tensor.2d.L2.global [%0, {%1, %2}];\n}\n"
               ::"l"(m), "r"(c0), "r"(c1) : "memory");
}
__device__ __forceinline__ void prefetch_map(const CUtensorMap* m) {
  asm volatile("prefetch.tensormap [%0];" ::"l"(m) : "memory");
}
__device__ __forceinline__ void wg_fence() { asm volatile("wgmma.fence.sync.aligned;" ::: "memory"); }
__device__ __forceinline__ void wg_commit() { asm volatile("wgmma.commit_group.sync.aligned;" ::: "memory"); }
template <int N>
__device__ __forceinline__ void wg_wait() { asm volatile("wgmma.wait_group.sync.aligned %0;" ::"n"(N) : "memory"); }
__device__ __forceinline__ void bar_sync(int id, int n) { asm volatile("bar.sync %0, %1;" ::"r"(id), "r"(n) : "memory"); }
__device__ __forceinline__ void wg_bar(int cw) {
  asm volatile("{\n.reg .pred p;\nsetp.ne.s32 p, %0, 0;\n@p bar.sync 3, 128;\n@!p bar.sync 2, 128;\n}\n" ::"r"(cw) : "memory");
}
__device__ __forceinline__ void skew_pre(int cw) { if (cw == 1) bar_sync(5, 256); }
__device__ __forceinline__ void skew_post(int cw) { if (cw == 0) asm volatile("bar.arrive 5, 256;" ::: "memory"); }
__device__ __forceinline__ void cluster_arrive_relaxed() { asm volatile("barrier.cluster.arrive.relaxed.aligned;" ::: "memory"); }
__device__ __forceinline__ void cluster_wait() { asm volatile("barrier.cluster.wait.acquire.aligned;" ::: "memory"); }
__device__ __forceinline__ uint32_t load_epoch(const unsigned* p) {
  uint32_t e;
  asm volatile("ld.relaxed.gpu.global.u32 %0, [%1];" : "=r"(e) : "l"(p) : "memory");
  return e;
}
__device__ __forceinline__ uint32_t pack2(float lo, float hi) {
  uint32_t r;
  asm("cvt.rn.bf16x2.f32 %0, %1, %2;" : "=r"(r) : "f"(hi), "f"(lo));
  return r;
}
__device__ __forceinline__ float bf_lo(uint32_t v) { return __uint_as_float(v << 16); }
__device__ __forceinline__ float bf_hi(uint32_t v) { return __uint_as_float(v & 0xffff0000u); }
__device__ __forceinline__ uint32_t fma_bf2(uint32_t a, uint32_t b, uint32_t c) {
  uint32_t d;
  asm("fma.rn.bf16x2 %0, %1, %2, %3;" : "=r"(d) : "r"(a), "r"(b), "r"(c));
  return d;
}
__device__ __forceinline__ float bf_round(float v) { return __bfloat162float(__float2bfloat16_rn(v)); }
__device__ __forceinline__ float silu_f(float v) { return __fdividef(v, 1.0f + __expf(-v)); }
__device__ __forceinline__ uint4 ldg_nc(const void* p) {
  uint4 v;
  asm volatile("ld.global.nc.L1::no_allocate.v4.u32 {%0, %1, %2, %3}, [%4];" : "=r"(v.x), "=r"(v.y), "=r"(v.z), "=r"(v.w) : "l"(p));
  return v;
}
__device__ __forceinline__ void stmatrix4(uint32_t addr, uint32_t a, uint32_t b, uint32_t c, uint32_t d) {
  asm volatile("stmatrix.sync.aligned.m8n8.x4.shared.b16 [%0], {%1, %2, %3, %4};" ::"r"(addr), "r"(a), "r"(b), "r"(c), "r"(d) : "memory");
}
__device__ __forceinline__ void stmatrix2(uint32_t addr, uint32_t a, uint32_t b) {
  asm volatile("stmatrix.sync.aligned.m8n8.x2.shared.b16 [%0], {%1, %2};" ::"r"(addr), "r"(a), "r"(b) : "memory");
}
__device__ __forceinline__ void stmatrix1(uint32_t addr, uint32_t a) {
  asm volatile("stmatrix.sync.aligned.m8n8.x1.shared.b16 [%0], {%1};" ::"r"(addr), "r"(a) : "memory");
}
__device__ __forceinline__ uint32_t movmatrix(uint32_t a) {
  uint32_t d;
  asm("movmatrix.sync.aligned.m8n8.trans.b16 %0, %1;" : "=r"(d) : "r"(a));
  return d;
}
__device__ __forceinline__ void mma16816(float (&d)[4], uint32_t a0, uint32_t a1, uint32_t a2, uint32_t a3, uint32_t b0, uint32_t b1) {
  asm("mma.sync.aligned.m16n8k16.row.col.f32.bf16.bf16.f32 {%0, %1, %2, %3}, {%4, %5, %6, %7}, {%8, %9}, {%0, %1, %2, %3};"
               : "+f"(d[0]), "+f"(d[1]), "+f"(d[2]), "+f"(d[3]) : "r"(a0), "r"(a1), "r"(a2), "r"(a3), "r"(b0), "r"(b1));
}
__device__ __forceinline__ void mma1688(float (&d)[4], uint32_t a0, uint32_t a1, uint32_t b0) {
  asm("mma.sync.aligned.m16n8k8.row.col.f32.bf16.bf16.f32 {%0, %1, %2, %3}, {%4, %5}, {%6}, {%0, %1, %2, %3};"
               : "+f"(d[0]), "+f"(d[1]), "+f"(d[2]), "+f"(d[3]) : "r"(a0), "r"(a1), "r"(b0));
}
__device__ __forceinline__ void ldmatrix4t(uint32_t (&b)[4], uint32_t addr) {
  asm volatile("ldmatrix.sync.aligned.m8n8.x4.trans.shared.b16 {%0, %1, %2, %3}, [%4];" : "=r"(b[0]), "=r"(b[1]), "=r"(b[2]), "=r"(b[3]) : "r"(addr) : "memory");
}
__device__ __forceinline__ void ldmatrix4(uint32_t& a, uint32_t& b, uint32_t& c, uint32_t& d, uint32_t addr) {
  asm volatile("ldmatrix.sync.aligned.m8n8.x4.shared.b16 {%0, %1, %2, %3}, [%4];" : "=r"(a), "=r"(b), "=r"(c), "=r"(d) : "r"(addr) : "memory");
}
__device__ __forceinline__ void cp_async16(uint32_t dst, const void* src) {
  asm volatile("cp.async.cg.shared.global.L2::cache_hint [%0], [%1], 16, %2;" ::"r"(dst), "l"(src), "l"(POLICY_EVICT_FIRST) : "memory");
}
__device__ __forceinline__ uint32_t lds32(uint32_t addr) {
  uint32_t v;
  asm volatile("ld.shared.u32 %0, [%1];" : "=r"(v) : "r"(addr) : "memory");
  return v;
}
__device__ __forceinline__ void sts64f(uint32_t addr, float a, float b) {
  asm volatile("st.shared.v2.f32 [%0], {%1, %2};" ::"r"(addr), "f"(a), "f"(b) : "memory");
}
constexpr float QK_SCALE = 0.17677669529663687f;
__device__ __forceinline__ float softmax8(float& p0, float& p1) {
  float m = fmaxf(p0, p1);
  m = fmaxf(m, __shfl_xor_sync(~0u, m, 1));
  m = fmaxf(m, __shfl_xor_sync(~0u, m, 2));
  asm("ex2.approx.ftz.f32 %0, %1;" : "=f"(p0) : "f"((p0 - m) * 1.4426950408889634f));
  asm("ex2.approx.ftz.f32 %0, %1;" : "=f"(p1) : "f"((p1 - m) * 1.4426950408889634f));
  float s = p0 + p1;
  s += __shfl_xor_sync(~0u, s, 1);
  s += __shfl_xor_sync(~0u, s, 2);
  float r;
  asm("rcp.approx.ftz.f32 %0, %1;" : "=f"(r) : "f"(s));
  return r;
}
__device__ __forceinline__ void sts128(uint32_t addr, uint32_t a, uint32_t b, uint32_t c, uint32_t d) {
  asm volatile("st.shared.v4.u32 [%0], {%1, %2, %3, %4};" ::"r"(addr), "r"(a), "r"(b), "r"(c), "r"(d) : "memory");
}
__device__ __forceinline__ uint4 lds128(uint32_t addr) {
  uint4 v;
  asm volatile("ld.shared.v4.u32 {%0, %1, %2, %3}, [%4];" : "=r"(v.x), "=r"(v.y), "=r"(v.z), "=r"(v.w) : "r"(addr) : "memory");
  return v;
}
__device__ __forceinline__ float2 lds64f(uint32_t addr) {
  float2 v;
  asm volatile("ld.shared.v2.f32 {%0, %1}, [%2];" : "=f"(v.x), "=f"(v.y) : "r"(addr) : "memory");
  return v;
}
#define PROF_AT(cond, slot) do {} while (0)

constexpr uint32_t SMEM_BASE = 1024;
constexpr uint32_t DESC_A = (1u << 16) | (SMEM_BASE >> 4);
constexpr uint32_t DESC_B = ((8192u >> 4) << 16) | (SMEM_BASE >> 4);

template <int BN> struct Wg;
template <> struct Wg<128> { static __device__ __forceinline__ void mma(float (&d)[64], uint32_t a, uint32_t b, int s) { wgmma_ss_n128(d, a, b, s); } };
template <> struct Wg<192> { static __device__ __forceinline__ void mma(float (&d)[96], uint32_t a, uint32_t b, int s) { wgmma_ss_n192(d, a, b, s); } };
template <> struct Wg<256> { static __device__ __forceinline__ void mma(float (&d)[128], uint32_t a, uint32_t b, int s) { wgmma_ss_n256(d, a, b, s); } };

struct Ring {
  uint32_t full0, rel0;
  int s;
  uint32_t ph;
  uint32_t off;
  bool releaser;
};

template <int N>
__device__ __forceinline__ void fence_regs(float (&a)[N]) {
#pragma unroll
  for (int i = 0; i < N; i++) asm volatile("" : "+f"(a[i])::"memory");
}

template <int BN, int NST, uint32_t STAGE>
__device__ __forceinline__ void kblock(float (&acc)[BN / 2], Ring& g, uint32_t a_addr, bool zero, uint32_t& prev, uint32_t b_rel = 16384) {
  mbar_wait(g.full0 + 8 * g.s, g.ph);
  const uint32_t da = DESC_A + (a_addr >> 4);
  const uint32_t db = DESC_B + ((g.off + b_rel) >> 4);
  wg_fence();
#pragma unroll
  for (int k = 0; k < 4; k++) Wg<BN>::mma(acc, da + k * 2, db + k * 128, !(zero && k == 0));
  wg_commit();
  wg_wait<1>();
  jitter();
  if (prev != 0) mbar_arrive_cluster(prev);
  prev = g.releaser ? g.rel0 + 8 * g.s : 0u;
  if (++g.s == NST) { g.s = 0; g.ph ^= 1; }
  g.off += STAGE;
  if (g.off == NST * STAGE) g.off = 0;
}
template <int N>
__device__ __forceinline__ void tile_end(float (&acc)[N], uint32_t& prev) {
  wg_wait<0>();
  if (prev != 0) mbar_arrive_cluster(prev);
  prev = 0;
  fence_regs(acc);
}

__device__ __forceinline__ int other_kb(int q, int j) {
  const int ch = q >= 7, jj = q - 7 * ch;
  return 2 * (jj < j ? jj : jj + 1) + ch;
}
__device__ __forceinline__ int qkv_kb(int it, int j) {
  return it < 4 ? 2 * j + (it >> 1) : other_kb(it < 18 ? it - 4 : it - 18, j);
}
__device__ __forceinline__ int wo_k(int it, int j) {
  return it < 8 ? it * 128 : (it == 8 ? j : (it - 9 < j ? it - 9 : it - 8)) * 128 + 64;
}
__device__ __forceinline__ int down_k(int d) {
  const int u = d + KH;
  if (u < 8) return u * 448 + 384;
  if (u < 40) return (((u - 8) & 15) >> 1) * 448 + ((u - 8) >> 4) * 128 + (u & 1) * 64;
  return (u & 7) * 448 + 256 + (u >= 48 ? 64 : 0);
}
__device__ __forceinline__ void wait_q_free(uint32_t empty, int i) {
  mbar_wait(empty + 8 * ((i * 2) / 3), 1);
  mbar_wait(empty + 8 * ((i * 2 + 1) / 3), 1);
}
__device__ __forceinline__ void wait_w_free(uint32_t empty, int i) {
  const int t = (i + 3) & 3, w0 = (t * 3) / 2, w1 = (t * 3 + 2) / 2;
  mbar_wait(empty + 8 * w0, w0 < 4);
  mbar_wait(empty + 8 * w1, w1 < 4);
}
__device__ __forceinline__ void wait_g_free(uint32_t empty, int i) {
  const int s = i < 4 ? i + 2 : i - 4, b0 = ((s * 2) / 3 + 1) & 3, b1 = ((s * 2 + 1) / 3 + 1) & 3;
  mbar_wait(empty + 8 * b0, b0 < 2);
  mbar_wait(empty + 8 * b1, b1 < 2);
}

__device__ __forceinline__ void chan(float& m, float& q, float m2, float q2, float n) {
  const float d = m2 - m;
  m = 0.5f * (m + m2);
  q = q + q2 + d * d * (0.5f * n);
}

__device__ __forceinline__ uint32_t tag16(uint32_t tag, uint32_t ln) { return (((tag & 0x3fffu) << 1) | ln) + 0x8000u; }
__device__ __forceinline__ void stat_store(uint2* slot, float m, float q, uint32_t t16) {
  const uint32_t a = ((__float_as_uint(m) + 0x80u) & 0xffffff00u) | (t16 & 0xffu), b = ((__float_as_uint(q) + 0x80u) & 0xffffff00u) | (t16 >> 8);
  asm volatile("st.relaxed.gpu.global.b64 [%0], %1;" ::"l"(slot), "l"((uint64_t)a | ((uint64_t)b << 32)) : "memory");
}
__device__ __forceinline__ void stat_gather(const uint2* rows, uint32_t t16, int lane, float (&rs)[2], float (&nb)[2]) {
  const uint4* sp = (const uint4*)(rows + (lane >> 3) * 128) + (lane & 7);
  const uint32_t want = (t16 & 0xffu) | ((t16 >> 8) << 8);
  uint4 a, b;
  for (;;) {
    a = ll_peek(sp);
    b = ll_peek(sp + 256);
    const uint32_t bad = (__byte_perm(a.x, a.y, 0x40) ^ want) | (__byte_perm(a.z, a.w, 0x40) ^ want) | (__byte_perm(b.x, b.y, 0x40) ^ want) |
                         (__byte_perm(b.z, b.w, 0x40) ^ want);
    if (__all_sync(~0u, (bad & 0xffffu) == 0)) break;
  }
  float m0 = __uint_as_float(a.x & 0xffffff00u), q0 = __uint_as_float(a.y & 0xffffff00u);
  float m1 = __uint_as_float(a.z & 0xffffff00u), q1 = __uint_as_float(a.w & 0xffffff00u);
  chan(m0, q0, __uint_as_float(b.x & 0xffffff00u), __uint_as_float(b.y & 0xffffff00u), 128.f);
  chan(m1, q1, __uint_as_float(b.z & 0xffffff00u), __uint_as_float(b.w & 0xffffff00u), 128.f);
  const bool hi = lane & 8;
  float m = hi ? m1 : m0, q = hi ? q1 : q0;
  chan(m, q, __shfl_xor_sync(~0u, hi ? m0 : m1, 8), __shfl_xor_sync(~0u, hi ? q0 : q1, 8), 256.f);
  chan(m, q, __shfl_xor_sync(~0u, m, 16), __shfl_xor_sync(~0u, q, 16), 512.f);
  const float rstd = rsqrtf(q * (1.0f / DM) + 1e-5f), nmr = -m * rstd;
  const int r = lane >> 2, src = (r >> 1) + (r & 1) * 8;
  rs[0] = __shfl_sync(~0u, rstd, src); nb[0] = __shfl_sync(~0u, nmr, src);
  rs[1] = __shfl_sync(~0u, rstd, src + 4); nb[1] = __shfl_sync(~0u, nmr, src + 4);
}

__device__ __forceinline__ void publish_stats(const uint32_t (&xl)[16], const uint32_t (&xh)[16], uint2* slot, int lane, uint32_t t16) {
  float ds[4] = {0.f, 0.f, 0.f, 0.f}, dl[4] = {0.f, 0.f, 0.f, 0.f}, dh[4] = {0.f, 0.f, 0.f, 0.f};
#pragma unroll
  for (int q = 0; q < 8; q++) {
    mma16816(ds, xl[2 * q], xh[2 * q], xl[2 * q + 1], xh[2 * q + 1], 0x3f803f80u, 0x3f803f80u);
    mma16816(dl, xl[2 * q], xh[2 * q], xl[2 * q + 1], xh[2 * q + 1], xl[2 * q], xl[2 * q + 1]);
    mma16816(dh, xl[2 * q], xh[2 * q], xl[2 * q + 1], xh[2 * q + 1], xh[2 * q], xh[2 * q + 1]);
  }
  const int r = lane >> 2;
  if ((lane & 3) == (r >> 1)) {
    const float ml = ds[0] * (1.0f / 128), mh = ds[2] * (1.0f / 128);
    const float ql = fmaxf(((r & 1) ? dl[1] : dl[0]) - ds[0] * ml, 0.f), qh = fmaxf(((r & 1) ? dh[3] : dh[2]) - ds[2] * mh, 0.f);
    stat_store(slot + r, ml, ql, t16);
    stat_store(slot + r + 8, mh, qh, t16);
  }
  __syncwarp();
}

__device__ __forceinline__ void stage_slab(uint32_t chunk, int warp, int lane, const uint32_t (&lo)[8], const uint32_t (&hi)[8]) {
  const int row = warp * 16 + (lane & 7) + ((lane >> 3) & 1) * 8;
  const uint32_t rbase = chunk + row * 128;
#pragma unroll
  for (int q = 0; q < 4; q++) {
    const int grp = 2 * q + (lane >> 4);
    stmatrix4(rbase + ((grp ^ (row & 7)) << 4), lo[2 * q], hi[2 * q], lo[2 * q + 1], hi[2 * q + 1]);
  }
}
__device__ __forceinline__ float silu_mul(float g, float u) {
  float e, r;
  asm("ex2.approx.ftz.f32 %0, %1;" : "=f"(e) : "f"(g * -1.4426950408889634f));
  asm("rcp.approx.ftz.f32 %0, %1;" : "=f"(r) : "f"(1.0f + e));
  return g * r * u;
}
__device__ __forceinline__ uint32_t swiglu2(uint32_t g2, uint32_t u2) {
  asm volatile("" : "+r"(g2));
  return pack2(silu_mul(bf_lo(g2), bf_lo(u2)), silu_mul(bf_hi(g2), bf_hi(u2)));
}
__device__ __forceinline__ void stage_done(uint32_t bar, int lane) {
  asm volatile("fence.proxy.async.shared::cta;" ::: "memory");
  __syncwarp();
  if (lane == 0) mbar_arrive(bar);
}

__device__ __forceinline__ int fresh_tid() {
  int t;
  asm volatile("mov.u32 %0, %%tid.x;" : "=r"(t));
  return t;
}
#define RING_IDS()                                                                                           \
  const int tid = fresh_tid() - 128;                                                                         \
  const int cw = __shfl_sync(~0u, tid >> 7, 0), warp = __shfl_sync(~0u, (tid >> 5) & 3, 0);                  \
  const bool releaser = (tid & 31) < 2;                                                                      \
  const uint32_t rbars = mapa(bars, tid & 1);                                                                \
  const uint32_t a_base = cw * 8192
#define LANE_IDS()                                                                                           \
  const int lane = fresh_tid() & 31, r = lane >> 2, c = lane & 3;                                            \
  const int srow = warp * 16 + (lane & 7) + ((lane >> 3) & 1) * 8;                                           \
  const uint32_t slab = stg + cw * 8192 + srow * 128, sw0 = (lane >> 4) ^ (srow & 7);                        \
  (void)r; (void)c; (void)slab; (void)sw0

template <int NPRE, bool EAGER, class Step>
__device__ __forceinline__ void attention(float (&acc)[96], const Params& p, int rho, int rb, int cta, int cw, int warp, uint32_t tag,
                                          uint32_t stg, uint32_t bars, uint32_t& prev, Step step) {
  uint32_t ql[8], qh[8], k0[8], k1[8], v0[8], v1[8], hp[16];
  mbar_wait(bars + 8 * B_STGE, rho);
  mbar_wait(bars + 8 * (B_STGE + 1), 0);
  if (EAGER) {
    tile_end(acc, prev);
  } else {
    step();
    fence_regs(acc);
  }
#pragma unroll
  for (int t = 0; t < 8; t++) {
    k0[t] = pack2(acc[4 * (8 + t)], acc[4 * (8 + t) + 1]);
    k1[t] = pack2(acc[4 * (8 + t) + 2], acc[4 * (8 + t) + 3]);
    v0[t] = pack2(acc[4 * (16 + t)], acc[4 * (16 + t) + 1]);
    v1[t] = pack2(acc[4 * (16 + t) + 2], acc[4 * (16 + t) + 3]);
    asm volatile("" : "+r"(k0[t]), "+r"(k1[t]), "+r"(v0[t]), "+r"(v1[t]));
  }
  const int lane = fresh_tid() & 31, r = lane >> 2, c = lane & 3;
#pragma unroll
  for (int t = 0; t < 8; t++) v1[t] = movmatrix(v1[t]);
  const uint32_t xch = stg + 16384 + (cw * 4 + warp) * 2048 + lane * 16;
  if (warp < 3) {
    sts128(xch, k1[0], k1[1], k1[2], k1[3]);
    sts128(xch + 512, k1[4], k1[5], k1[6], k1[7]);
    sts128(xch + 1024, v1[0], v1[1], v1[2], v1[3]);
    sts128(xch + 1536, v1[4], v1[5], v1[6], v1[7]);
  } else if (rb < 15) {
    uint4* dst = p.halo + ((cta * 2 + rho) * 2 + cw) * 256 + lane;
#pragma unroll
    for (int t = 0; t < 4; t++) {
      ll_store(dst + t * 32, k1[2 * t], k1[2 * t + 1], tag);
      ll_store(dst + (4 + t) * 32, v1[2 * t], v1[2 * t + 1], tag);
    }
  }
#pragma unroll
  for (int t = 0; t < 8; t++) {
    v0[t] = movmatrix(v0[t]);
    ql[t] = pack2(acc[4 * t], acc[4 * t + 1]);
    qh[t] = pack2(acc[4 * t + 2], acc[4 * t + 3]);
    asm volatile("" : "+r"(v0[t]), "+r"(ql[t]), "+r"(qh[t]));
  }
#pragma unroll 1
  for (int i = 0; i < NPRE; i++) step();
  const uint4* src = p.halo + (((cta - 8) * 2 + rho) * 2 + cw) * 256 + lane;
  uint4 early[8] = {};
  if (warp == 0 && rb > 0) {
#pragma unroll
    for (int i = 0; i < 8; i++) early[i] = ll_peek(src + i * 32);
  }
  step();
  wg_bar(cw);
  if (warp > 0) {
#pragma unroll
    for (int t = 0; t < 4; t++) {
      const uint4 a = lds128(xch - 2048 + t * 512);
      hp[4 * t] = a.x; hp[4 * t + 1] = a.y; hp[4 * t + 2] = a.z; hp[4 * t + 3] = a.w;
    }
  } else if (rb > 0) {
    uint32_t bad = 0;
#pragma unroll
    for (int i = 0; i < 8; i++) {
      bad |= (early[i].y ^ tag) | (early[i].w ^ tag);
      hp[2 * i] = early[i].x;
      hp[2 * i + 1] = early[i].z;
    }
    if (!__all_sync(~0u, bad == 0)) ll_poll<8>([&](int i) { return src + i * 32; }, tag, hp);
  } else {
#pragma unroll
    for (int t = 0; t < 16; t++) hp[t] = 0;
  }
  wg_wait<0>();
  if (prev != 0) mbar_arrive_cluster(prev);
  prev = 0;
#pragma unroll
  for (int t = 0; t < 8; t++) asm volatile("" : "+r"(ql[t])::"memory");
  const bool up0 = 2 * c > r, up1 = 2 * c + 1 > r;
  const bool first = (rb == 0) && (warp == 0);
  uint32_t a0[2], a2[2], a3[2], a5[2];
  float il[2], ih[2];
#pragma unroll
  for (int h = 0; h < 2; h++) {
    float sp[4] = {0.f, 0.f, 0.f, 0.f}, s0[4] = {0.f, 0.f, 0.f, 0.f}, s1[4] = {0.f, 0.f, 0.f, 0.f};
#pragma unroll
    for (int ks = 0; ks < 2; ks++) {
      const int t = 4 * h + 2 * ks;
      mma16816(sp, ql[t], qh[t], ql[t + 1], qh[t + 1], hp[t], hp[t + 1]);
      mma16816(s0, ql[t], qh[t], ql[t + 1], qh[t + 1], k0[t], k0[t + 1]);
      mma16816(s1, ql[t], qh[t], ql[t + 1], qh[t + 1], k1[t], k1[t + 1]);
    }
    float p0 = (up0 ? sp[0] : s0[0]) * QK_SCALE, p1 = (up1 ? sp[1] : s0[1]) * QK_SCALE;
    float p2 = (up0 ? s0[2] : s1[2]) * QK_SCALE, p3 = (up1 ? s0[3] : s1[3]) * QK_SCALE;
    if (first && up0) p0 = -1000000000.0f;
    if (first && up1) p1 = -1000000000.0f;
    il[h] = softmax8(p0, p1);
    ih[h] = softmax8(p2, p3);
    a0[h] = pack2(up0 ? p0 : 0.f, up1 ? p1 : 0.f);
    a2[h] = pack2(up0 ? 0.f : p0, up1 ? 0.f : p1);
    a3[h] = pack2(up0 ? p2 : 0.f, up1 ? p3 : 0.f);
    a5[h] = pack2(up0 ? 0.f : p2, up1 ? 0.f : p3);
  }
  float o[8][4];
#pragma unroll
  for (int t = 0; t < 8; t++) {
#pragma unroll
    for (int q = 0; q < 4; q++) o[t][q] = 0.f;
    mma1688(o[t], 0u, a5[t >> 2], v1[t]);
    mma16816(o[t], a0[t >> 2], 0u, a2[t >> 2], a3[t >> 2], hp[8 + t], v0[t]);
  }
#pragma unroll
  for (int t = 0; t < 8; t++) fence_regs(o[t]);
  if (!EAGER) step();
  uint32_t ol[8], oh[8];
#pragma unroll
  for (int t = 0; t < 8; t++) {
    ol[t] = pack2(o[t][0] * il[t >> 2], o[t][1] * il[t >> 2]);
    oh[t] = pack2(o[t][2] * ih[t >> 2], o[t][3] * ih[t >> 2]);
  }
  if (!EAGER) step();
  stage_slab(stg + cw * 8192, warp, lane, ol, oh);
  stage_done(bars + 8 * B_STGF, lane);
  if (!EAGER) step();
}

__global__ void __launch_bounds__(384, 1) fused_kernel(const bf16* __restrict__ gx, const bf16* __restrict__ gwmod, const bf16* __restrict__ gc,
                                                          unsigned* gepoch, uint2* gstats, const __grid_constant__ Params p) {
  extern __shared__ __align__(1024) uint8_t smem_raw[];
  const uint32_t sm = smem_u32(smem_raw);
  const uint32_t bars = sm + MISC_OFF;
  const uint32_t stg = sm + STG_OFF;
  const int rank = blockIdx.x & 1;
  const int cl = blockIdx.x >> 1;
  if (cl >= NCTA / 2) {
    const int e = blockIdx.x - NCTA, wid = __shfl_sync(~0u, (int)(threadIdx.x >> 5), 0), lane = threadIdx.x & 31;
    if (threadIdx.x == 0) {
      for (int i = 0; i < 6; i++) { mbar_init(bars + 8 * i, 1); mbar_init(bars + 8 * (6 + i), 8); }
      for (int i = 0; i < 8; i++) { mbar_init(bars + 8 * (16 + i), 1); mbar_init(bars + 8 * (24 + i), 4); }
      mbar_init(bars + 8 * 12, 1);
      asm volatile("fence.mbarrier_init.release.cluster;" ::: "memory");
    }
    const uint32_t tag = load_epoch(gepoch) + 1;
    for (int i = threadIdx.x; i < 1536; i += 384) {
      uint4 o = make_uint4(0u, 0u, 0u, 0u);
      if (i < 1024 && (i & 63) < 8) {
        const uint4 cv = ldg_nc(gc + (i >> 6) * 64 + (i & 7) * 8);
        o = make_uint4(pack2(silu_f(bf_lo(cv.x)), silu_f(bf_hi(cv.x))), pack2(silu_f(bf_lo(cv.y)), silu_f(bf_hi(cv.y))),
                       pack2(silu_f(bf_lo(cv.z)), silu_f(bf_hi(cv.z))), pack2(silu_f(bf_lo(cv.w)), silu_f(bf_hi(cv.w))));
      }
      sts128(stg + i * 16, o.x, o.y, o.z, o.w);
    }
    asm volatile("fence.proxy.async.shared::cta;" ::: "memory");
    __syncthreads();
    if (wid == 0) {
      __nanosleep(WMDELAY);
      uint32_t ph = 1;
#pragma unroll 1
      for (int it = 0, s = 0; it < 64; it++) {
        mbar_wait(bars + 8 * (6 + s), ph);
        expect_tx_elect(bars + 8 * s, 32768);
#pragma unroll
        for (int q = 0; q < 4; q++) tma_load_ef(sm + s * 32768 + q * 8192, &p.wm, bars + 8 * s, 2048 + (it >> 4) * 1024 + e * 256 + q * 64, (it & 15) * 64);
        if (++s == 6) { s = 0; ph ^= 1; }
      }
    } else if (wid == 1) {
      __nanosleep(PFW);
#pragma unroll 1
      for (int i = 0; i < 64; i++) {
        l2_prefetch_tile(&p.wo, (i & 15) * 64, (e * 4 + (i >> 4)) * 64);
      }
#pragma unroll 1
      for (int i = 0; i < 80; i++) {
        if (i < 64) l2_prefetch_tile((i & 1) ? &p.wu : &p.wg, ((i >> 1) & 7) * 448 + 384, ((i >> 4) * 4 + e) * 64);
        else l2_prefetch_tile((i & 2) ? &p.wu : &p.wg, (e * 2 + ((i >> 3) & 1)) * 448 + (i & 1) * 64, (e * 4 + ((i >> 2) & 3)) * 64);
      }
    } else if (wid >= 4) {
      const int hf = (wid >> 2) - 1;
      uint32_t ph = 0;
      int s = 0;
#pragma unroll 1
      for (int v = 0; v < 4; v++) {
        float acc[64];
#pragma unroll 1
        for (int kb = 0; kb < 16; kb++) {
          mbar_wait_watchdog(bars + 8 * s, ph);
          const uint32_t da = DESC_A + ((STG_OFF + kb * 1024) >> 4), db = DESC_B + ((s * 32768 + hf * 16384) >> 4);
          wg_fence();
#pragma unroll
          for (int k = 0; k < 4; k++) wgmma_ss_n128(acc, da + k * 2, db + k * 128, (kb | k) != 0);
          wg_commit();
          wg_wait<0>();
          if (lane == 0) mbar_arrive(bars + 8 * (6 + s));
          if (++s == 6) { s = 0; ph ^= 1; }
        }
        fence_regs(acc);
        if ((wid & 3) == 0) {
#pragma unroll
          for (int n = 0; n < 16; n++) {
            const uint32_t mine = pack2(acc[4 * n], acc[4 * n + 1]), next = __shfl_down_sync(~0u, mine, 1);
            if (lane < 4 && (lane & 1) == 0) ll_store(p.modll + 512 + v * 256 + e * 64 + hf * 32 + n * 2 + (lane >> 1), mine, next, tag);
            if (lane < 4) sts64f(sm + MODB_OFF + (hf * 128 + n * 8 + lane * 2) * 4, bf_lo(mine), bf_hi(mine));
          }
        }
      }
    }
    __syncthreads();
    if (wid == 0 || wid == 2) {
      const int w = wid >> 1;
      if (w == 0) {
        expect_tx_elect(bars + 8 * 12, KH * 32768);
#pragma unroll 1
        for (int q = 0; q < 4 * KH; q++) tma_load_ef(sm + q * 8192, &p.wd, bars + 8 * 12, e * 256 + (q & 3) * 64, (q >> 2) * 448 + 384);
      }
      cnt_wait_lazy(p.cnt + C_ACT, tag * 8);
      if (w == 1) __nanosleep(900);
      uint32_t ph = 1, ready = 0;
#pragma unroll 1
      for (int it = 0, s = 0; it < 16 * KH; it++) {
        const int rb = it / KH, kc = it - rb * KH;
        while (!((ready >> rb) & 1)) {
          ready = __ballot_sync(~0u, (int)(load_epoch(p.cnt + (lane & 15) * 32 + C_ACT) - tag * 8) >= 0);
          asm volatile("fence.proxy.async.global;" ::: "memory");
        }
        const uint32_t fb = bars + 8 * (16 + w * 4 + s), dst = sm + 98304 + w * 32768 + s * 8192;
        mbar_wait(fb + 64, ph);
        expect_tx_elect(fb, 8192);
        tma_load(dst, &p.act_st, fb, kc * 448 + 384, rb * 128 + w * 64);
        tma_load(dst + 4096, &p.act_st, fb, kc * 448 + 384, rb * 128 + w * 64 + 32);
        if (++s == 4) { s = 0; ph ^= 1; }
      }
    } else if (wid >= 4) {
      const int w = (wid >> 2) - 1, warp = wid & 3;
      const uint32_t out_stg = (w ? stg : sm + 163840) + warp * 2048;
      const uint32_t slab = out_stg + (lane & 15) * 128, sw0 = (lane >> 4) ^ (lane & 7);
      mbar_wait_watchdog(bars + 8 * 12, 0);
#pragma unroll 1
      for (int i = threadIdx.x - 128; i < KH * 2048; i += 256) {
        const uint32_t gp = sm + MODB_OFF + (((i >> 9) & 3) * 64 + ((i ^ (i >> 3)) & 7) * 8) * 4;
        const uint4 v = lds128(sm + i * 16), ga = lds128(gp), gc = lds128(gp + 16);
        sts128(sm + i * 16, pack2(bf_lo(v.x) * __uint_as_float(ga.x), bf_hi(v.x) * __uint_as_float(ga.y)),
               pack2(bf_lo(v.y) * __uint_as_float(ga.z), bf_hi(v.y) * __uint_as_float(ga.w)),
               pack2(bf_lo(v.z) * __uint_as_float(gc.x), bf_hi(v.z) * __uint_as_float(gc.y)),
               pack2(bf_lo(v.w) * __uint_as_float(gc.z), bf_hi(v.w) * __uint_as_float(gc.w)));
      }
      asm volatile("fence.proxy.async.shared::cta;" ::: "memory");
      bar_sync(1, 256);
      uint32_t ph = 0;
      int s = 0;
#pragma unroll 1
      for (int rb = 0; rb < 16; rb++) {
        float acc[128];
#pragma unroll 1
        for (int kc = 0; kc < KH; kc++) {
          mbar_wait_watchdog(bars + 8 * (16 + w * 4 + s), ph);
          const uint32_t da = DESC_A + ((98304 + w * 32768 + s * 8192) >> 4), db = DESC_B + ((kc * 32768) >> 4);
          wg_fence();
#pragma unroll
          for (int k = 0; k < 4; k++) wgmma_ss_n256(acc, da + k * 2, db + k * 128, (kc | k) != 0);
          wg_commit();
          wg_wait<1>();
          if (kc > 0 && lane == 0) mbar_arrive(bars + 8 * (24 + w * 4 + ((s + 3) & 3)));
          if (++s == 4) { s = 0; ph ^= 1; }
        }
        asm volatile("cp.async.bulk.wait_group 0;" ::: "memory");
        __syncwarp();
        if (rb > 0) cnt_signal(p.cnt + (rb - 1) * 32 + C_SP + e);
        wg_wait<0>();
        fence_regs(acc);
        __syncwarp();
        if (lane == 0) mbar_arrive(bars + 8 * (24 + w * 4 + ((s + 3) & 3)));
#pragma unroll
        for (int q = 0; q < 16; q++)
          stmatrix4(slab + (q >> 2) * 8192 + ((sw0 ^ ((q & 3) * 2)) << 4), pack2(acc[8 * q], acc[8 * q + 1]), pack2(acc[8 * q + 2], acc[8 * q + 3]),
                    pack2(acc[8 * q + 4], acc[8 * q + 5]), pack2(acc[8 * q + 6], acc[8 * q + 7]));
        asm volatile("fence.proxy.async.shared::cta;" ::: "memory");
        __syncwarp();
#pragma unroll
        for (int ch = 0; ch < 4; ch++) tma_add3(&p.out, out_stg + ch * 8192, e * 256 + ch * 64, rb * 64 + warp * 16, w);
        asm volatile("cp.async.bulk.commit_group;" ::: "memory");
      }
      asm volatile("cp.async.bulk.wait_group 0;" ::: "memory");
      __syncwarp();
      cnt_signal(p.cnt + 15 * 32 + C_SP + e);
    }
    return;
  }
  const int q7 = ((cl - 36) * 37) >> 8;
  const int j = cl < 4 ? 4 + cl : (cl < 36 ? (cl - 4) >> 3 : 4 + q7);
  const int rb = (cl < 4 ? 0 : (cl < 36 ? (cl - 4) & 7 : cl - 35 - 7 * q7)) * 2 + rank;
  const int cta = rb * 8 + j;
  PROF_AT(threadIdx.x == 0, 0);

  if (threadIdx.x < 128) {
    asm volatile("setmaxnreg.dec.sync.aligned.u32 40;");
    const int warp = __shfl_sync(~0u, (int)(threadIdx.x >> 5), 0), lane = threadIdx.x & 31;
    if (threadIdx.x == 0) {
      const uint32_t ep = load_epoch(gepoch);
      if ((sm & 0x3FFFF) != SMEM_BASE) asm volatile("trap;");
      for (int i = 0; i < 4; i++) { mbar_init(bars + 8 * (B_FQ + i), 1); mbar_init(bars + 8 * (B_EQ + i), 16); }
      for (int i = 0; i < 6; i++) { mbar_init(bars + 8 * (B_FW + i), 1); mbar_init(bars + 8 * (B_EW + i), 16); }
      for (int i = 0; i < 4; i++) { mbar_init(bars + 8 * (B_FG + i), 1); mbar_init(bars + 8 * (B_EG + i), 16); }
      for (int i = 0; i < 6; i++) { mbar_init(bars + 8 * (B_FD + i), 1); mbar_init(bars + 8 * (B_ED + i), 16); }
      for (int i = 0; i < 2; i++) { mbar_init(bars + 8 * (B_STGF + i), 8); mbar_init(bars + 8 * (B_STGE + i), 1); }
      mbar_init(bars + 8 * B_MODB, 1);
      mbar_init(bars + 8 * (B_MODB + 1), 1);
      mbar_init(bars + 8 * B_MODA, 1);
      mbar_init(bars + 8 * (B_MODA + 1), 1);
      for (int i = 0; i < 11; i++) mbar_init(bars + 8 * (B_RDY + i), 1);
      asm volatile("st.shared.u32 [%0], %1;" ::"r"(bars + 8 * B_COUNT), "r"(ep + 1) : "memory");
      asm volatile("fence.mbarrier_init.release.cluster;\nfence.acq_rel.cta;" ::: "memory");
    }
    __syncwarp();
    cluster_arrive_relaxed();
    unsigned* cnt = p.cnt + rb * 32;
    cluster_wait();
    const uint32_t tag = lds32(bars + 8 * B_COUNT);
    const unsigned target = tag * 8;
    if (warp == 0) {
      const CUtensorMap* wgu = rank ? &p.wu : &p.wg;
      uint32_t st = sm + 16384, fb = bars + 8 * B_FQ, ph = 1;
      __nanosleep(BDELAY);
#pragma unroll 1
      for (int it = 0; it < 32; it++) {
        const int kb = qkv_kb(it, j), col = j * 128 + ((it < 4 ? (it & 1) : it >= 18) ? 64 : 0);
        if (it == 2) mbar_wait(bars + 8 * B_MODA, 0);
        mbar_wait(fb + 8 * (B_EQ - B_FQ), ph);
        expect_tx_elect(fb, it < 4 ? 24576 : 40960);
        tma_load_mc(st + rank * 8192, &p.wqkv, fb, col + rank * 1024, kb * 64);
        tma_load_mc(st + 16384 + rank * 4096, &p.wqkv32, fb, col + 2048, kb * 64 + rank * 32);
        st += 49152; fb += 8;
        if ((it & 3) == 3) { st -= 4 * 49152; fb -= 32; ph ^= 1; }
      }
      fb = bars + 8 * B_FW; ph = 1;
#pragma unroll 1
      for (int it = 0, s = 0; it < 34; it++) {
        if (it < 6) wait_q_free(bars + 8 * B_EQ, it);
        if (it == 16) mbar_wait(bars + 8 * (B_FW + 3), 0);
        mbar_wait(fb + 8 * (B_EW - B_FW), ph);
        expect_tx_elect(fb, (it == 8 || it == 18 || it == 19) ? 16384 : 32768);
        const int k0 = it < 16 ? wo_k(it, j) : (it < 20 ? 2 * j + (it & 1) : other_kb(it - 20, j)) * 64;
        if (it == 16 || it == 17) {
          tma_load_mc(st - 16384 + rank * 16384, wgu, fb, j * 448, k0);
          tma_load_mc(st - 8192 + rank * 16384, wgu, fb, j * 448 + 64, k0);
        } else {
          tma_load_mc(st + rank * 8192, it < 16 ? &p.wo : wgu, fb, it < 16 ? j * 128 + rank * 64 : j * 448 + 384, k0);
        }
        st += 32768; fb += 8;
        if (++s == 6) { s = 0; st -= 6 * 32768; fb -= 48; ph ^= 1; }
      }
      st = sm + 16384 + 3 * 49152; fb = bars + 8 * B_FG; ph = 1;
#pragma unroll 1
      for (int it = 0; it < 46; it++) {
        const int kb = it < 14 ? other_kb(it, j) : (it + 2) & 15, col = j * 448 + ((it + 2) >> 4) * 128;
        if (it < 4) wait_w_free(bars + 8 * B_EW, it);
        mbar_wait(fb + 8 * (B_EG - B_FG), ph);
        expect_tx_elect(fb, 49152);
        tma_load_mc(st + rank * 16384, wgu, fb, col, kb * 64);
        tma_load_mc(st + rank * 16384 + 8192, wgu, fb, col + 64, kb * 64);
        st += (it & 3) == 0 ? -3 * 49152 : 49152; fb += 8;
        if ((it & 3) == 3) { fb -= 32; ph ^= 1; }
      }
      st = sm + 16384 + 2 * 32768; fb = bars + 8 * B_FD; ph = 1;
#pragma unroll 1
      for (int it = 0, s = 0; it < 56 - KH; it++) {
        if (it < 6) wait_g_free(bars + 8 * B_EG, it);
        mbar_wait(fb + 8 * (B_ED - B_FD), ph);
        expect_tx_elect(fb, 32768);
        tma_load_mc(st + rank * 8192, &p.wd, fb, j * 128 + rank * 64, down_k(it));
        st += s == 3 ? -5 * 32768 : 32768; fb += 8;
        if (++s == 6) { s = 0; fb -= 48; ph ^= 1; }
      }
    } else if (warp == 1) {
      const int arow = rb * 128;
      uint32_t st = sm, fb = bars + 8 * B_FQ, ph = 0;
      cnt_wait(cnt + C_HA, target);
      PROF_AT(lane == 0, 16);
#pragma unroll 1
      for (int it = 4; it < 32; it++) {
        if (it == 11) mbar_wait(bars + 8 * (B_RDY + C_H), 0);
        mbar_wait(fb + 8 * (B_EQ - B_FQ), ph);
        tma_load(st, &p.h, fb, qkv_kb(it, j) * 64, arow);
        st += 49152; fb += 8;
        if ((it & 3) == 3) { st -= 4 * 49152; fb -= 32; ph ^= 1; }
      }
      fb = bars + 8 * B_FW; ph = 1;
#pragma unroll 1
      for (int it = 0, s = 0; it < 34; it++) {
        if (it < 16 || it >= 20) {
          if (it < 6) wait_q_free(bars + 8 * B_EQ, it);
          mbar_wait(fb + 8 * (B_EW - B_FW), ph);
          if (it == 0) mbar_wait(bars + 8 * (B_RDY + C_O), 0);
          if (it == 9 || it == 20) cnt_wait(cnt + (it == 9 ? C_O + 1 : C_H2A), target * 8);
          if (it == 27) mbar_wait(bars + 8 * (B_RDY + C_H2), 0);
          PROF_AT(lane == 0 && (it == 0 || it == 9 || it == 20), 17 + (it >> 3));
          if (it != 8) tma_load(st, it < 16 ? &p.o_ld : &p.h2, fb, it < 16 ? wo_k(it, j) : other_kb(it - 20, j) * 64, arow);
        }
        st += 32768; fb += 8;
        if (++s == 6) { s = 0; st -= 6 * 32768; fb -= 48; ph ^= 1; }
      }
      st = sm + 3 * 49152; fb = bars + 8 * B_FG; ph = 1;
#pragma unroll 1
      for (int it = 0; it < 46; it++) {
        if (it < 4) wait_w_free(bars + 8 * B_EW, it);
        mbar_wait(fb + 8 * (B_EG - B_FG), ph);
        tma_load(st, &p.h2, fb, (it < 14 ? other_kb(it, j) : (it + 2) & 15) * 64, arow);
        st += (it & 3) == 0 ? -3 * 49152 : 49152; fb += 8;
        if ((it & 3) == 3) { fb -= 32; ph ^= 1; }
      }
      st = sm + 2 * 32768; fb = bars + 8 * B_FD; ph = 1;
#pragma unroll 1
      for (int it = 0, s = 0; it < 56 - KH; it++) {
        if (it < 6) wait_g_free(bars + 8 * B_EG, it);
        mbar_wait(fb + 8 * (B_ED - B_FD), ph);
        const int u = it + KH, dep = it == 0 ? C_ACT : (u == 8 ? C_ACT + 1 : (u == 24 ? C_ACT + 2 : (u == 40 ? C_A0 : (u == 48 ? C_ACT + 3 : -1))));
        if (dep >= 0) mbar_wait(bars + 8 * (B_RDY + dep), 0);
        tma_load(st, &p.act, fb, down_k(it), arow);
        st += s == 3 ? -5 * 32768 : 32768; fb += 8;
        if (++s == 6) { s = 0; fb -= 48; ph ^= 1; }
      }
    } else if (warp == 2) {
      if (lane < 15) prefetch_map(&p.h + lane);
      __syncwarp();
      uint32_t ph1 = 0;
#pragma unroll 1
      for (int n = 0; n < 8; n++) {
        const int nch = (n == 1 || n == 2 || n == 4) ? 1 : 2;
#pragma unroll 1
        for (int ch = 0; ch < nch; ch++) {
          mbar_wait_watchdog(bars + 8 * (B_STGF + ch), ch ? ph1 : (n & 1));
          const uint32_t src = stg + ch * 16384;
          if (n == 2 || n == 3) {
          } else if (n == 1) {
#pragma unroll 1
            for (int q = 0; q < 8; q++) {
              tma_store2(&p.o_st, src + q * 2048, j * 128, rb * 128 + q * 16);
              if (q & 1) store_pause(true);
            }
          } else if (n >= 4 && n < 8) {
#pragma unroll 1
            for (int q = 0; q < 4; q++) {
              tma_store2(&p.act_st, src + q * 4096, j * 448 + (n == 4 ? 384 : (n - 5) * 128 + ch * 64), rb * 128 + q * 32);
              store_pause(true);
            }
          } else if (ch == 0) {
            tma_store2(&p.h, src, j * 128, rb * 128);
            asm volatile("cp.async.bulk.commit_group;" ::: "memory");
            asm volatile("cp.async.bulk.wait_group 0;" ::: "memory");
            __syncwarp();
            cnt_signal(cnt + C_HA);
          } else {
            __nanosleep(H1D);
#pragma unroll 1
            for (int q = 0; q < 8; q++) {
              tma_store2(&p.h_st, src + q * 2048, j * 128 + 64, rb * 128 + q * 16);
              if (q & 1) store_pause(true);
            }
          }
          if (n >= 5 && ch == 0) arrive_elect(bars + 8 * B_STGE);
          if (n == 7 && ch == 0) {
            asm volatile("cp.async.bulk.wait_group 0;" ::: "memory");
            __syncwarp();
            cnt_signal(cnt + C_A0);
          }
        }
        asm volatile("cp.async.bulk.commit_group;" ::: "memory");
        asm volatile("cp.async.bulk.wait_group 0;" ::: "memory");
        __syncwarp();
        if (n != 2 && n != 3) cnt_signal(cnt + n);
        PROF_AT(lane == 0, n == 0 ? 33 : 23 + n);
        if (n == 0) {
#pragma unroll 1
          for (int t = 0; t < 32; t++) {
            ll_store(p.halo + cta * 1024 + t * 32 + lane, 0u, 0u, 0u);
            __nanosleep(40);
          }
          __syncwarp();
        }
        if (n < 5) arrive_elect(bars + 8 * B_STGE);
        if (nch == 2) { arrive_elect(bars + 8 * (B_STGE + 1)); ph1 ^= 1; }
      }
      mbar_wait_watchdog(bars + 8 * B_STGF, 0);
      PROF_AT(lane == 0, 31);
    } else {
      if (lane < 4) ll_store(p.modll + cta * 4 + lane, 0u, 0u, 0u);
#pragma unroll 1
      for (int ch = 0; ch < 2; ch++) {
        if (ch == 0) {
          bar_sync(1, 288);
          const uint4 t4 = lds128(sm + RED_OFF + lane * 16);
          float a[4] = {__uint_as_float(t4.x), __uint_as_float(t4.y), __uint_as_float(t4.z), __uint_as_float(t4.w)};
#pragma unroll
          for (int o = 4; o < 32; o <<= 1)
#pragma unroll
            for (int q = 0; q < 4; q++) a[q] += __shfl_xor_sync(~0u, a[q], o);
          if (lane < 4) ll_store(p.modll + cta * 4 + lane, pack2(a[0], a[1]), pack2(a[2], a[3]), tag);
          PROF_AT(lane == 0, 1);
        }
        uint32_t m[2];
        const uint4* mp = p.modll + j * 32 + ch * 16 + (lane & 15) + (lane >> 4) * 256;
        ll_poll<1>([&](int) { return mp; }, tag, m);
        if (lane >> 4) { m[0] = pack2(1.0f + bf_lo(m[0]), 1.0f + bf_hi(m[0])); m[1] = pack2(1.0f + bf_lo(m[1]), 1.0f + bf_hi(m[1])); }
        const uint32_t dst = sm + MODB_OFF + (ch * 16 + (lane & 15)) * 16 + ((lane >> 4) ? 0 : 4);
        asm volatile("st.shared.u32 [%0], %1;\nst.shared.u32 [%0 + 8], %2;" ::"r"(dst), "r"(m[0]), "r"(m[1]) : "memory");
        __syncwarp();
        arrive_elect(bars + 8 * (B_MODA + ch));
      }
#pragma unroll 1
      for (int n = C_H; n <= C_O; n++) {
        cnt_wait_lazy(cnt + n, target);
        arrive_elect(bars + 8 * (B_RDY + n));
      }
      {
        uint32_t m[6];
        const uint4* src = p.modll + 512 + j * 32 + lane;
        ll_poll<3, 500>([&](int i) { return src + i * 256; }, tag, m);
#pragma unroll
        for (int vec = 0; vec < 3; vec++) {
          const float add = vec == 2 ? 1.0f : 0.0f;
          sts128(sm + MODB_OFF + (vec * 128 + lane * 4) * 4, __float_as_uint(bf_round(bf_lo(m[2 * vec]) + add)), __float_as_uint(bf_round(bf_hi(m[2 * vec]) + add)),
                 __float_as_uint(bf_round(bf_lo(m[2 * vec + 1]) + add)), __float_as_uint(bf_round(bf_hi(m[2 * vec + 1]) + add)));
        }
        __syncwarp();
        if (lane == 0) mbar_arrive(bars + 8 * B_MODB);
        PROF_AT(lane == 0, 15);
      }
      __syncwarp();
#pragma unroll 1
      for (int q = C_H2; q < 9; q++) {
        const int n = q < 7 ? q : (q == 7 ? C_A0 : C_ACT + 3);
        cnt_wait_lazy(cnt + n, n == C_H2 ? target * 8 : target);
        arrive_elect(bars + 8 * (B_RDY + n));
      }
      {
        uint32_t m[2];
        const uint4* src = p.modll + 512 + 768 + j * 32 + lane;
        ll_poll<1>([&](int) { return src; }, tag, m);
        sts128(sm + MODB_OFF + (384 + lane * 4) * 4, m[0] << 16, m[0] & 0xffff0000u, m[1] << 16, m[1] & 0xffff0000u);
        cnt_wait_lazy(cnt + C_SP + (j >> 1), target);
        __syncwarp();
        if (lane == 0) mbar_arrive(bars + 8 * (B_MODB + 1));
      }
    }
  } else {
    uint32_t tag;

    {
      const int tid = threadIdx.x - 128, cw = tid >> 7, warp = (tid >> 5) & 3, lane = tid & 31;
      const int l16 = lane & 15, half = lane >> 4, w8 = cw * 4 + warp;
      if (lane < 8) ll_store((uint4*)(gstats + (rb * 8 + j) * 128 + w8 * 16) + lane, 0u, 0u, 0u);
      const uint32_t cbuf = sm + 3 * 49152 + w8 * 512;
      if (lane < 16) cp_async16(cbuf + lane * 16, gc + w8 * 128 + lane * 8);
      asm volatile("cp.async.commit_group;" ::: "memory");
      const uint32_t xbuf = sm + 40960 + (cw * 2 + (l16 >> 3)) * 49152 + (warp * 16 + half) * 128;
      {
        const char* xp = (const char*)gx + (uint32_t)((rb * 128 + (warp * 16 + half) * 2 + cw) * 2048 + j * 256 + l16 * 16);
#pragma unroll
        for (int i = 0; i < 8; i++) cp_async16(xbuf + i * 256 + (((l16 & 7) ^ ((i * 2 + half) & 7)) << 4), xp + i * 8192);
      }
      asm volatile("cp.async.commit_group;" ::: "memory");
      const uint32_t wbuf = sm + cw * 49152 + warp * 4096;
      const bool late = j >= 4;
      auto fetch_w = [&]() {
        const char* wp = (const char*)gwmod + (uint32_t)(cta * 32 + (lane & 1) * 16 + (w8 * 128 + (lane >> 1)) * 12288);
#pragma unroll
        for (int i = 0; i < 8; i++) cp_async16(wbuf + i * 512 + lane * 16, wp + i * 16 * 12288);
      };
      if (!late) fetch_w();
      PROF_AT(tid == 0, 32);
      uint2* st1 = gstats + (rb * 8 + j) * 128 + cw * 64 + warp * 16;
      cluster_arrive_relaxed();
      asm volatile("setmaxnreg.inc.sync.aligned.u32 232;");
      uint32_t sa[4][4];
      {
        asm volatile("cp.async.wait_group 1;" ::: "memory");
        __syncwarp();
        const float2 cv = lds64f(cbuf + lane * 8);
        const uint32_t c0 = __float_as_uint(cv.x), c1 = __float_as_uint(cv.y);
        sts64f(cbuf + lane * 8, __uint_as_float(pack2(silu_f(bf_lo(c0)), silu_f(bf_hi(c0)))), __uint_as_float(pack2(silu_f(bf_lo(c1)), silu_f(bf_hi(c1)))));
        __syncwarp();
#pragma unroll
        for (int q = 0; q < 4; q++) ldmatrix4(sa[q][0], sa[q][1], sa[q][2], sa[q][3], cbuf + q * 64 + (lane >> 3) * 16);
      }
      cluster_wait();
      tag = lds32(bars + 8 * B_COUNT);
      if (late) {
        if (WLD) __nanosleep(WLD);
        fetch_w();
      }
      asm volatile("cp.async.commit_group;" ::: "memory");
      asm volatile("cp.async.wait_group 1;" ::: "memory");
      __syncwarp();
      uint32_t xl[16], xh[16];
      {
        const int srow = warp * 16 + (lane & 15);
#pragma unroll
        for (int q = 0; q < 8; q++)
          ldmatrix4(xl[2 * q], xh[2 * q], xl[2 * q + 1], xh[2 * q + 1],
                    sm + 40960 + (cw * 2 + (q >> 2)) * 49152 + srow * 128 + (((half + (q & 3) * 2) ^ (srow & 7)) << 4));
      }
      publish_stats(xl, xh, st1, lane, tag16(tag, 0));
      PROF_AT(tid == 0, 50);
      auto gemv = [&]() {
      asm volatile("cp.async.wait_group 0;" ::: "memory");
      __syncwarp();
      PROF_AT(tid == 0, 51);
      {
        uint32_t b[8][4];
#pragma unroll
        for (int ks = 0; ks < 8; ks++) ldmatrix4t(b[ks], wbuf + (ks * 16 + (lane & 15)) * 32 + (lane >> 4) * 16);
        float d0[4] = {0.f, 0.f, 0.f, 0.f}, d1[4] = {0.f, 0.f, 0.f, 0.f}, d2[4] = {0.f, 0.f, 0.f, 0.f}, d3[4] = {0.f, 0.f, 0.f, 0.f};
#pragma unroll
        for (int q = 0; q < 4; q++) {
          mma16816(d0, sa[q][0], sa[q][0], sa[q][1], sa[q][1], b[2 * q][0], b[2 * q][1]);
          mma16816(d1, sa[q][0], sa[q][0], sa[q][1], sa[q][1], b[2 * q][2], b[2 * q][3]);
          mma16816(d2, sa[q][2], sa[q][2], sa[q][3], sa[q][3], b[2 * q + 1][0], b[2 * q + 1][1]);
          mma16816(d3, sa[q][2], sa[q][2], sa[q][3], sa[q][3], b[2 * q + 1][2], b[2 * q + 1][3]);
        }
        d0[0] += d2[0]; d0[1] += d2[1]; d1[0] += d3[0]; d1[1] += d3[1];
        if (lane < 4) {
          sts64f(sm + RED_OFF + (w8 * 16 + lane * 2) * 4, d0[0], d0[1]);
          sts64f(sm + RED_OFF + (w8 * 16 + 8 + lane * 2) * 4, d1[0], d1[1]);
        }
        asm volatile("bar.arrive 1, 288;" ::: "memory");
      }
      };
      gemv();
      {
        const int c = lane & 3;
        float rs[2], nb[2];
        stat_gather(gstats + rb * 1024 + cw * 64 + warp * 16, tag16(tag, 0), lane, rs, nb);
#pragma unroll
        for (int n = 0; n < 16; n++) {
          xl[n] = pack2(bf_lo(xl[n]) * rs[0] + nb[0], bf_hi(xl[n]) * rs[0] + nb[0]);
          xh[n] = pack2(bf_lo(xh[n]) * rs[1] + nb[1], bf_hi(xh[n]) * rs[1] + nb[1]);
        }
        const int srow = warp * 16 + l16;
        const uint32_t slab = stg + cw * 8192 + srow * 128;
#pragma unroll
        for (int q = 0; q < 8; q++)
          stmatrix4(slab + (q >> 2) * 16384 + (((half + (q & 3) * 2) ^ (srow & 7)) << 4), xl[2 * q], xh[2 * q], xl[2 * q + 1], xh[2 * q + 1]);
        PROF_AT(tid == 0, 52);
        mbar_wait(bars + 8 * B_MODA, 0);
        PROF_AT(tid == 0, 2);
#pragma unroll
        for (int q = 0; q < 4; q++) {
          const float2 m0 = lds64f(sm + MODB_OFF + (8 * q + c) * 8), m1 = lds64f(sm + MODB_OFF + (8 * q + 4 + c) * 8);
          const uint32_t c0 = __float_as_uint(m0.x), s0 = __float_as_uint(m0.y), c1 = __float_as_uint(m1.x), s1 = __float_as_uint(m1.y);
          stmatrix4(slab + (q >> 2) * 16384 + (((half + (q & 3) * 2) ^ (srow & 7)) << 4), fma_bf2(xl[2 * q], c0, s0), fma_bf2(xh[2 * q], c0, s0),
                    fma_bf2(xl[2 * q + 1], c1, s1), fma_bf2(xh[2 * q + 1], c1, s1));
          if ((q & 3) == 3) stage_done(bars + 8 * (B_STGF + (q >> 2)), lane);
        }
      }
      PROF_AT(tid == 0, 3);
    }

    uint32_t xl[16], xh[16];
    {
      RING_IDS();
      uint32_t prev = 0;
      float acc1[96];
      {
        Ring g{bars + 8 * B_FQ, rbars + 8 * B_EQ, 0, 0u, 0u, releaser TR(0)};
        float acc0[96];
#pragma unroll 1
        for (int kb = 0; kb < 2; kb++) {
          kblock<192, 4, 49152>(acc0, g, a_base + STG_OFF + kb * 16384, kb == 0, prev);
          kblock<192, 4, 49152>(acc1, g, a_base + STG_OFF + kb * 16384, kb == 0, prev);
          if (kb == 0) {
            LANE_IDS();
            mbar_wait(bars + 8 * (B_MODA + 1), 0);
#pragma unroll
            for (int q = 0; q < 4; q++) {
              const uint32_t a = slab + 16384 + ((sw0 ^ (q * 2)) << 4);
              uint32_t v0, v1, v2, v3;
              ldmatrix4(v0, v1, v2, v3, a);
              const float2 m0 = lds64f(sm + MODB_OFF + (32 + 8 * q + c) * 8), m1 = lds64f(sm + MODB_OFF + (36 + 8 * q + c) * 8);
              const uint32_t c0 = __float_as_uint(m0.x), s0 = __float_as_uint(m0.y), c1 = __float_as_uint(m1.x), s1 = __float_as_uint(m1.y);
              stmatrix4(a, fma_bf2(v0, c0, s0), fma_bf2(v1, c0, s0), fma_bf2(v2, c1, s1), fma_bf2(v3, c1, s1));
            }
            stage_done(bars + 8 * (B_STGF + 1), lane);
          }
        }
#pragma unroll 1
        for (int kb = 0; kb < 14; kb++) kblock<192, 4, 49152>(acc0, g, a_base + g.off, false, prev);
        PROF_AT(tid == 0, 4);
        attention<NPRE0, false>(acc0, p, 0, rb, cta, cw, warp, tag, stg, bars, prev, [&]() { kblock<192, 4, 49152>(acc1, g, a_base + g.off, false, prev); });
        PROF_AT(tid == 0, 5);
        {
          LANE_IDS();
#pragma unroll
          for (int q = 0; q < 8; q++)
            ldmatrix4(xl[2 * q], xh[2 * q], xl[2 * q + 1], xh[2 * q + 1], sm + 40960 + (cw * 2 + (q >> 2)) * 49152 + srow * 128 + ((sw0 ^ ((q & 3) * 2)) << 4));
#pragma unroll
          for (int q = 0; q < 16; q++) asm volatile("" : "+r"(xl[q]), "+r"(xh[q])::"memory");
        }
#pragma unroll 1
        for (int kb = 5 + NPRE0; kb < 14; kb++) kblock<192, 4, 49152>(acc1, g, a_base + g.off, false, prev);
        PROF_AT(tid == 0, 6);
      }
      float acc[64];
      Ring g{bars + 8 * B_FW, rbars + 8 * B_EW, 0, 0u, 0u, releaser TR(32)};
      attention<NPRE1, true>(acc1, p, 1, rb, cta, cw, warp, tag, stg, bars, prev, [&]() { kblock<128, 6, 32768>(acc, g, a_base + g.off, g.s == 0, prev); });
      PROF_AT(tid == 0, 7);
      LANE_IDS();
      unsigned* cnt = p.cnt + rb * 32;
      tma_store2(&p.o_st, stg + cw * 8192 + warp * 2048, j * 128 + 64, rb * 128 + cw * 64 + warp * 16);
      asm volatile("cp.async.bulk.commit_group;" ::: "memory");
#pragma unroll 1
      for (int kb = 1 + NPRE1; kb < 16; kb++) {
        if (kb == 8) wg_bar(cw);
        kblock<128, 6, 32768>(acc, g, a_base + (kb == 8 ? STG_OFF : g.off), false, prev);
        if (kb == 3 + NPRE1) {
          asm volatile("cp.async.bulk.wait_group 0;" ::: "memory");
          __syncwarp();
          cnt_signal(cnt + C_O + 1);
        }
      }
      mbar_wait(bars + 8 * B_STGE, 0);
      mbar_wait(bars + 8 * B_MODB, 0);
      float2 ga[16];
#pragma unroll
      for (int n = 0; n < 16; n++) ga[n] = lds64f(sm + MODB_OFF + (8 * n + 2 * c) * 4);
      tile_end(acc, prev);
      PROF_AT(tid == 0, 8);
#pragma unroll
      for (int n = 0; n < 16; n++) {
        acc[4 * n] = ga[n].x * acc[4 * n] + bf_lo(xl[n]); acc[4 * n + 1] = ga[n].y * acc[4 * n + 1] + bf_hi(xl[n]);
        acc[4 * n + 2] = ga[n].x * acc[4 * n + 2] + bf_lo(xh[n]); acc[4 * n + 3] = ga[n].y * acc[4 * n + 3] + bf_hi(xh[n]);
        xl[n] = pack2(acc[4 * n], acc[4 * n + 1]);
        xh[n] = pack2(acc[4 * n + 2], acc[4 * n + 3]);
      }
      publish_stats(xl, xh, gstats + (rb * 8 + j) * 128 + cw * 64 + warp * 16, lane, tag16(tag, 1));
      PROF_AT(tid == 0, 48);
      float2 sb[16], cb[16];
#pragma unroll
      for (int n = 0; n < 16; n++) {
        sb[n] = lds64f(sm + MODB_OFF + (128 + 8 * n + 2 * c) * 4);
        cb[n] = lds64f(sm + MODB_OFF + (256 + 8 * n + 2 * c) * 4);
      }
      PROF_AT(tid == 0, 49);
      float nb[2], rstd[2];
      stat_gather(gstats + rb * 1024 + cw * 64 + warp * 16, tag16(tag, 1), lane, rstd, nb);
      PROF_AT(tid == 0, 9);
#pragma unroll
      for (int ch = 0; ch < 2; ch++) {
        uint32_t lo[8], hi[8];
#pragma unroll
        for (int t = 0; t < 8; t++) {
          const int n = ch * 8 + t;
          lo[t] = pack2((acc[4 * n] * rstd[0] + nb[0]) * cb[n].x + sb[n].x, (acc[4 * n + 1] * rstd[0] + nb[0]) * cb[n].y + sb[n].y);
          hi[t] = pack2((acc[4 * n + 2] * rstd[1] + nb[1]) * cb[n].x + sb[n].x, (acc[4 * n + 3] * rstd[1] + nb[1]) * cb[n].y + sb[n].y);
        }
        stage_slab(sm + ch * 32768 + cw * 8192, warp, lane, lo, hi);
        stage_done(bars + 8 * (B_STGF + ch), lane);
        tma_store2(&p.h2_st, sm + ch * 32768 + cw * 8192 + warp * 2048, j * 128 + ch * 64, rb * 128 + cw * 64 + warp * 16);
        asm volatile("cp.async.bulk.commit_group;" ::: "memory");
      }
      PROF_AT(tid == 0, 10);
    }

    uint32_t pg[32], pu[32];
    {
      RING_IDS();
      float acc[128];
      uint32_t prev = 0;
      Ring g{bars + 8 * B_FG, rbars + 8 * B_EG, 0, 0u, 3 * 49152u, releaser TR(66)};
      {
        Ring w{bars + 8 * B_FW, rbars + 8 * B_EW, 4, 0u, 4 * 32768u, releaser TR(48)};
        float acn[64];
#pragma unroll 1
        for (int kb = 0; kb < 2; kb++) {
          kblock<256, 6, 32768>(acc, w, a_base + kb * 32768, kb == 0, prev, 0u);
          if (kb == 0) asm volatile("cp.async.bulk.wait_group 1;" ::: "memory");
          else asm volatile("cp.async.bulk.wait_group 0;" ::: "memory");
          __syncwarp();
          cnt_signal(p.cnt + rb * 32 + (kb == 0 ? C_H2A : C_H2));
        }
        {
          LANE_IDS();
#pragma unroll
          for (int q = 0; q < 8; q++)
            stmatrix4(slab + (q >> 2) * 16384 + ((sw0 ^ ((q & 3) * 2)) << 4), xl[2 * q], xh[2 * q], xl[2 * q + 1], xh[2 * q + 1]);
          __syncwarp();
        }
#pragma unroll 1
        for (int kb = 0; kb < 16; kb++) {
          kblock<128, 6, 32768>(acn, w, a_base + w.off, kb == 0, prev);
          if (kb == 4) {
            asm volatile("fence.proxy.async.shared::cta;" ::: "memory");
            __syncwarp();
          }
          if (kb == 6 + warp || kb == 10 + warp) {
            const int ch = kb != 6 + warp;
            tma_store3(&p.out, stg + ch * 16384 + cw * 8192 + warp * 2048, j * 128 + ch * 64, rb * 64 + warp * 16, cw);
            asm volatile("cp.async.bulk.commit_group;" ::: "memory");
          }
        }
        PROF_AT(tid == 0, 39);
        kblock<256, 4, 49152>(acc, g, a_base + g.off, false, prev);
        fence_regs(acn);
#pragma unroll
        for (int q = 0; q < 16; q++) {
          pg[q] = pack2(acn[2 * q], acn[2 * q + 1]);
          pu[q] = pack2(acn[32 + 2 * q], acn[32 + 2 * q + 1]);
          pg[16 + q] = 0; pu[16 + q] = 0;
        }
        asm volatile("cp.async.bulk.wait_group 0;" ::: "memory");
        kblock<256, 4, 49152>(acc, g, a_base + g.off, false, prev);
      }
      LANE_IDS();
#pragma unroll 1
      for (int t = 0; t < 3; t++) {
#pragma unroll 1
        for (int blk = 0; blk < (t == 0 ? 2 : 4); blk++) {
          g.s = 2;
#pragma unroll
          for (int i = 0; i < 4; i++) {
            g.off = ((i + 1) & 3) * 49152;
            if (i == 3 && blk == 3) skew_pre(cw);
            kblock<256, 4, 49152>(acc, g, a_base + g.off, t > 0 && blk == 0 && i == 0, prev);
            if (i == 3 && blk == 3) skew_post(cw);
            if ((blk & 1) == 0 && i == 0) mbar_wait(bars + 8 * (B_STGE + (blk >> 1)), (t + 1 + (blk >> 1)) & 1);
            stmatrix2(slab + (blk >> 1) * 16384 + (((srow & 7) ^ ((blk & 1) * 4 + i)) << 4), swiglu2(pg[2 * i], pu[2 * i]), swiglu2(pg[2 * i + 1], pu[2 * i + 1]));
          }
#pragma unroll
          for (int q = 0; q < 24; q++) { pg[q] = pg[q + 8]; pu[q] = pu[q + 8]; }
          if (blk & 1) stage_done(bars + 8 * (B_STGF + (blk >> 1)), lane);
        }
#pragma unroll 1
        for (int kb = t == 0 ? 0 : 4; kb < 4; kb++) {
          if (kb == 3) skew_pre(cw);
          kblock<256, 4, 49152>(acc, g, a_base + g.off, false, prev);
          if (kb == 3) skew_post(cw);
        }
        tile_end(acc, prev);
        PROF_AT(tid == 0, 36 + t);
#pragma unroll
        for (int q = 0; q < 32; q++) {
          pg[q] = pack2(acc[2 * q], acc[2 * q + 1]);
          pu[q] = pack2(acc[64 + 2 * q], acc[64 + 2 * q + 1]);
        }
      }
      PROF_AT(tid == 0, 11);
    }

    {
      RING_IDS();
      LANE_IDS();
      Ring g{bars + 8 * B_FD, rbars + 8 * B_ED, 0, 0u, 2 * 32768u, releaser TR(112)};
      float acc[64];
      uint32_t prev = 0;
#pragma unroll 1
      for (int blk = 0; blk < 4; blk++) {
#pragma unroll
        for (int i = 0; i < 8; i++) {
          kblock<128, 6, 32768>(acc, g, a_base + g.off, blk == 0 && i == 0, prev);
          if ((blk & 1) == 0 && i == 0) mbar_wait(bars + 8 * (B_STGE + (blk >> 1)), blk >> 1);
          stmatrix1(slab + (blk >> 1) * 16384 + (i & 1) * 1024 + (((srow & 7) ^ ((blk & 1) * 4 + (i >> 1))) << 4), swiglu2(pg[i], pu[i]));
        }
#pragma unroll
        for (int q = 0; q < 24; q++) { pg[q] = pg[q + 8]; pu[q] = pu[q + 8]; }
        if (blk & 1) stage_done(bars + 8 * (B_STGF + (blk >> 1)), lane);
      }
#pragma unroll 1
      for (int kb = 32; kb < 56 - KH; kb++) {
        if (kb == 50 - KH) g.releaser = false;
        if (kb == 52 - KH) skew_pre(cw);
        kblock<128, 6, 32768>(acc, g, a_base + g.off, false, prev);
      }
      skew_post(cw);
      mbar_wait(bars + 8 * (B_MODB + 1), 0);
      mbar_wait(bars + 8 * B_STGE, 1);
      mbar_wait(bars + 8 * (B_STGE + 1), 0);
      float2 gbv[16];
#pragma unroll
      for (int n = 0; n < 16; n++) gbv[n] = lds64f(sm + MODB_OFF + (384 + 8 * n + 2 * c) * 4);
      tile_end(acc, prev);
      PROF_AT(tid == 0, 13);
#pragma unroll
      for (int ch = 0; ch < 2; ch++) {
        uint32_t lo[8], hi[8];
#pragma unroll
        for (int t = 0; t < 8; t++) {
          const int n = ch * 8 + t;
          const float2 gb = gbv[n];
          lo[t] = pack2(gb.x * acc[4 * n], gb.y * acc[4 * n + 1]);
          hi[t] = pack2(gb.x * acc[4 * n + 2], gb.y * acc[4 * n + 3]);
        }
        stage_slab(stg + ch * 16384 + cw * 8192, warp, lane, lo, hi);
        asm volatile("fence.proxy.async.shared::cta;" ::: "memory");
        __syncwarp();
        tma_add3(&p.out, stg + ch * 16384 + cw * 8192 + warp * 2048, j * 128 + ch * 64, rb * 64 + warp * 16, cw);
      }
      asm volatile("cp.async.bulk.commit_group;" ::: "memory");
      if (lane == 0) mbar_arrive(bars + 8 * B_STGF);
      asm volatile("cp.async.bulk.wait_group.read 0;" ::: "memory");
      PROF_AT(tid == 0, 14);
    }
    if (blockIdx.x == 0 && threadIdx.x == 128) asm volatile("st.relaxed.gpu.global.u32 [%0], %1;" ::"l"(gepoch), "r"(tag) : "memory");
  }
}

typedef CUresult (*EncodeFn)(CUtensorMap*, CUtensorMapDataType, cuuint32_t, void*, const cuuint64_t*, const cuuint64_t*,
                             const cuuint32_t*, const cuuint32_t*, CUtensorMapInterleave, CUtensorMapSwizzle,
                             CUtensorMapL2promotion, CUtensorMapFloatOOBfill);

void encode2d(EncodeFn fn, CUtensorMap* m, const void* ptr, uint64_t cols, uint64_t rows, uint32_t box_rows) {
  cuuint64_t dims[2] = {cols, rows};
  cuuint64_t strides[1] = {cols * 2};
  cuuint32_t box[2] = {64, box_rows};
  cuuint32_t es[2] = {1, 1};
  fn(m, CU_TENSOR_MAP_DATA_TYPE_BFLOAT16, 2, (void*)ptr, dims, strides, box, es, CU_TENSOR_MAP_INTERLEAVE_NONE,
     CU_TENSOR_MAP_SWIZZLE_128B, CU_TENSOR_MAP_L2_PROMOTION_L2_128B, CU_TENSOR_MAP_FLOAT_OOB_FILL_NONE);
}

}

extern "C" void kernel_launch(void* const* d_in, const int* in_sizes, int n_in, void* d_out, int out_size) {
  (void)in_sizes; (void)n_in; (void)out_size;
  void* fp = nullptr;
  cudaDriverEntryPointQueryResult qr;
  cudaGetDriverEntryPoint("cuTensorMapEncodeTiled", &fp, cudaEnableDefault, &qr);
  EncodeFn fn = (EncodeFn)fp;
  void *ph, *po, *ph2, *pact;
  cudaGetSymbolAddress(&ph, g_h);
  cudaGetSymbolAddress(&po, g_o);
  ph2 = ph;
  cudaGetSymbolAddress(&pact, g_act);
  Params p;
  encode2d(fn, &p.h, ph, DM, SEQ, 128);
  encode2d(fn, &p.o_ld, po, DM, SEQ, 128);
  encode2d(fn, &p.h2, ph2, DM, SEQ, 128);
  encode2d(fn, &p.act, pact, FF, SEQ, 128);
  encode2d(fn, &p.act_st, pact, FF, SEQ, 32);
  encode2d(fn, &p.wm, d_in[8], 6 * DM, DM, 64);
  encode2d(fn, &p.o_st, po, DM, SEQ, 16);
  encode2d(fn, &p.h2_st, ph2, DM, SEQ, 16);
  encode2d(fn, &p.h_st, ph, DM, SEQ, 16);
  encode2d(fn, &p.wqkv, d_in[1], 3 * DM, DM, 64);
  encode2d(fn, &p.wqkv32, d_in[1], 3 * DM, DM, 32);
  encode2d(fn, &p.wo, d_in[2], DM, DM, 64);
  encode2d(fn, &p.wg, d_in[4], FF, DM, 64);
  encode2d(fn, &p.wu, d_in[5], FF, DM, 64);
  encode2d(fn, &p.wd, d_in[6], DM, FF, 64);
  {
    cuuint64_t dims[3] = {DM, SEQ / 2, 2};
    cuuint64_t strides[2] = {DM * 4, DM * 2};
    cuuint32_t box[3] = {64, 16, 1};
    cuuint32_t es[3] = {1, 1, 1};
    fn(&p.out, CU_TENSOR_MAP_DATA_TYPE_BFLOAT16, 3, d_out, dims, strides, box, es, CU_TENSOR_MAP_INTERLEAVE_NONE,
       CU_TENSOR_MAP_SWIZZLE_128B, CU_TENSOR_MAP_L2_PROMOTION_L2_128B, CU_TENSOR_MAP_FLOAT_OOB_FILL_NONE);
  }
  void* q;
  cudaGetSymbolAddress(&q, g_modll); p.modll = (uint4*)q;
  cudaGetSymbolAddress(&q, g_halo); p.halo = (uint4*)q;
  cudaGetSymbolAddress(&q, g_stats); uint2* stats = (uint2*)q;
  cudaGetSymbolAddress(&q, g_cnt); p.cnt = (unsigned*)q;
  cudaGetSymbolAddress(&q, g_epoch); unsigned* epoch = (unsigned*)q;

  cudaFuncSetAttribute(fused_kernel, cudaFuncAttributeMaxDynamicSharedMemorySize, SMEM_BYTES);
  cudaLaunchConfig_t cfg = {};
  cfg.gridDim = dim3(NCTA + 4);
  cfg.blockDim = dim3(384);
  cfg.dynamicSmemBytes = SMEM_BYTES;
  cfg.stream = cudaStreamPerThread;
  cudaLaunchAttribute at[1];
  at[0].id = cudaLaunchAttributeClusterDimension;
  at[0].val.clusterDim.x = 2; at[0].val.clusterDim.y = 1; at[0].val.clusterDim.z = 1;
  cfg.attrs = at;
  cfg.numAttrs = 1;
  cudaLaunchKernelEx(&cfg, fused_kernel, (const bf16*)d_in[0], (const bf16*)d_in[8], (const bf16*)d_in[7], epoch, stats, p);
}
```

```cpp
#include <cuda_runtime.h>
#include <cuda_bf16.h>
#include <cuda.h>
#include <stdint.h>

typedef __nv_bfloat16 bf16;

#define PAUSE 200
#define WMDELAY 500
#define BDELAY 1500
#define NPRE0 3
#define NPRE1 1
#define ALIAS 1
#define PFW 8000
#define KH 3

#define WLD 200
#define H1D 500

__device__ __forceinline__ void wgmma_ss_n128(float (&d)[64], uint32_t da, uint32_t db, int scale_d) {
  asm volatile("{\n.reg .pred p;\n.reg .b64 da, db;\nsetp.ne.b32 p, %66, 0;\n"
    "mov.b64 da, {%64, 0x40000040};\nmov.b64 db, {%65, 0x40000040};\n"
    "wgmma.mma_async.sync.aligned.m64n128k16.f32.bf16.bf16 "
    "{%0, %1, %2, %3, %4, %5, %6, %7, %8, %9, %10, %11, %12, %13, %14, %15, "
    "%16, %17, %18, %19, %20, %21, %22, %23, %24, %25, %26, %27, %28, %29, %30, %31, "
    "%32, %33, %34, %35, %36, %37, %38, %39, %40, %41, %42, %43, %44, %45, %46, %47, "
    "%48, %49, %50, %51, %52, %53, %54, %55, %56, %57, %58, %59, %60, %61, %62, %63}, "
    "da, db, p, 1, 1, 0, 1;\n}\n"
    : "+f"(d[0]), "+f"(d[1]), "+f"(d[2]), "+f"(d[3]), "+f"(d[4]), "+f"(d[5]), "+f"(d[6]), "+f"(d[7]),
      "+f"(d[8]), "+f"(d[9]), "+f"(d[10]), "+f"(d[11]), "+f"(d[12]), "+f"(d[13]), "+f"(d[14]), "+f"(d[15]),
      "+f"(d[16]), "+f"(d[17]), "+f"(d[18]), "+f"(d[19]), "+f"(d[20]), "+f"(d[21]), "+f"(d[22]), "+f"(d[23]),
      "+f"(d[24]), "+f"(d[25]), "+f"(d[26]), "+f"(d[27]), "+f"(d[28]), "+f"(d[29]), "+f"(d[30]), "+f"(d[31]),
      "+f"(d[32]), "+f"(d[33]), "+f"(d[34]), "+f"(d[35]), "+f"(d[36]), "+f"(d[37]), "+f"(d[38]), "+f"(d[39]),
      "+f"(d[40]), "+f"(d[41]), "+f"(d[42]), "+f"(d[43]), "+f"(d[44]), "+f"(d[45]), "+f"(d[46]), "+f"(d[47]),
      "+f"(d[48]), "+f"(d[49]), "+f"(d[50]), "+f"(d[51]), "+f"(d[52]), "+f"(d[53]), "+f"(d[54]), "+f"(d[55]),
      "+f"(d[56]), "+f"(d[57]), "+f"(d[58]), "+f"(d[59]), "+f"(d[60]), "+f"(d[61]), "+f"(d[62]), "+f"(d[63])
    : "r"(da), "r"(db), "r"(scale_d));
}

__device__ __forceinline__ void wgmma_ss_n192(float (&d)[96], uint32_t da, uint32_t db, int scale_d) {
  asm volatile("{\n.reg .pred p;\n.reg .b64 da, db;\nsetp.ne.b32 p, %98, 0;\n"
    "mov.b64 da, {%96, 0x40000040};\nmov.b64 db, {%97, 0x40000040};\n"
    "wgmma.mma_async.sync.aligned.m64n192k16.f32.bf16.bf16 "
    "{%0, %1, %2, %3, %4, %5, %6, %7, %8, %9, %10, %11, %12, %13, %14, %15, "
    "%16, %17, %18, %19, %20, %21, %22, %23, %24, %25, %26, %27, %28, %29, %30, %31, "
    "%32, %33, %34, %35, %36, %37, %38, %39, %40, %41, %42, %43, %44, %45, %46, %47, "
    "%48, %49, %50, %51, %52, %53, %54, %55, %56, %57, %58, %59, %60, %61, %62, %63, "
    "%64, %65, %66, %67, %68, %69, %70, %71, %72, %73, %74, %75, %76, %77, %78, %79, "
    "%80, %81, %82, %83, %84, %85, %86, %87, %88, %89, %90, %91, %92, %93, %94, %95}, "
    "da, db, p, 1, 1, 0, 1;\n}\n"
    : "+f"(d[0]), "+f"(d[1]), "+f"(d[2]), "+f"(d[3]), "+f"(d[4]), "+f"(d[5]), "+f"(d[6]), "+f"(d[7]),
      "+f"(d[8]), "+f"(d[9]), "+f"(d[10]), "+f"(d[11]), "+f"(d[12]), "+f"(d[13]), "+f"(d[14]), "+f"(d[15]),
      "+f"(d[16]), "+f"(d[17]), "+f"(d[18]), "+f"(d[19]), "+f"(d[20]), "+f"(d[21]), "+f"(d[22]), "+f"(d[23]),
      "+f"(d[24]), "+f"(d[25]), "+f"(d[26]), "+f"(d[27]), "+f"(d[28]), "+f"(d[29]), "+f"(d[30]), "+f"(d[31]),
      "+f"(d[32]), "+f"(d[33]), "+f"(d[34]), "+f"(d[35]), "+f"(d[36]), "+f"(d[37]), "+f"(d[38]), "+f"(d[39]),
      "+f"(d[40]), "+f"(d[41]), "+f"(d[42]), "+f"(d[43]), "+f"(d[44]), "+f"(d[45]), "+f"(d[46]), "+f"(d[47]),
      "+f"(d[48]), "+f"(d[49]), "+f"(d[50]), "+f"(d[51]), "+f"(d[52]), "+f"(d[53]), "+f"(d[54]), "+f"(d[55]),
      "+f"(d[56]), "+f"(d[57]), "+f"(d[58]), "+f"(d[59]), "+f"(d[60]), "+f"(d[61]), "+f"(d[62]), "+f"(d[63]),
      "+f"(d[64]), "+f"(d[65]), "+f"(d[66]), "+f"(d[67]), "+f"(d[68]), "+f"(d[69]), "+f"(d[70]), "+f"(d[71]),
      "+f"(d[72]), "+f"(d[73]), "+f"(d[74]), "+f"(d[75]), "+f"(d[76]), "+f"(d[77]), "+f"(d[78]), "+f"(d[79]),
      "+f"(d[80]), "+f"(d[81]), "+f"(d[82]), "+f"(d[83]), "+f"(d[84]), "+f"(d[85]), "+f"(d[86]), "+f"(d[87]),
      "+f"(d[88]), "+f"(d[89]), "+f"(d[90]), "+f"(d[91]), "+f"(d[92]), "+f"(d[93]), "+f"(d[94]), "+f"(d[95])
    : "r"(da), "r"(db), "r"(scale_d));
}

__device__ __forceinline__ void wgmma_ss_n256(float (&d)[128], uint32_t da, uint32_t db, int scale_d) {
  asm volatile("{\n.reg .pred p;\n.reg .b64 da, db;\nsetp.ne.b32 p, %130, 0;\n"
    "mov.b64 da, {%128, 0x40000040};\nmov.b64 db, {%129, 0x40000040};\n"
    "wgmma.mma_async.sync.aligned.m64n256k16.f32.bf16.bf16 "
    "{%0, %1, %2, %3, %4, %5, %6, %7, %8, %9, %10, %11, %12, %13, %14, %15, "
    "%16, %17, %18, %19, %20, %21, %22, %23, %24, %25, %26, %27, %28, %29, %30, %31, "
    "%32, %33, %34, %35, %36, %37, %38, %39, %40, %41, %42, %43, %44, %45, %46, %47, "
    "%48, %49, %50, %51, %52, %53, %54, %55, %56, %57, %58, %59, %60, %61, %62, %63, "
    "%64, %65, %66, %67, %68, %69, %70, %71, %72, %73, %74, %75, %76, %77, %78, %79, "
    "%80, %81, %82, %83, %84, %85, %86, %87, %88, %89, %90, %91, %92, %93, %94, %95, "
    "%96, %97, %98, %99, %100, %101, %102, %103, %104, %105, %106, %107, %108, %109, %110, %111, "
    "%112, %113, %114, %115, %116, %117, %118, %119, %120, %121, %122, %123, %124, %125, %126, %127}, "
    "da, db, p, 1, 1, 0, 1;\n}\n"
    : "+f"(d[0]), "+f"(d[1]), "+f"(d[2]), "+f"(d[3]), "+f"(d[4]), "+f"(d[5]), "+f"(d[6]), "+f"(d[7]),
      "+f"(d[8]), "+f"(d[9]), "+f"(d[10]), "+f"(d[11]), "+f"(d[12]), "+f"(d[13]), "+f"(d[14]), "+f"(d[15]),
      "+f"(d[16]), "+f"(d[17]), "+f"(d[18]), "+f"(d[19]), "+f"(d[20]), "+f"(d[21]), "+f"(d[22]), "+f"(d[23]),
      "+f"(d[24]), "+f"(d[25]), "+f"(d[26]), "+f"(d[27]), "+f"(d[28]), "+f"(d[29]), "+f"(d[30]), "+f"(d[31]),
      "+f"(d[32]), "+f"(d[33]), "+f"(d[34]), "+f"(d[35]), "+f"(d[36]), "+f"(d[37]), "+f"(d[38]), "+f"(d[39]),
      "+f"(d[40]), "+f"(d[41]), "+f"(d[42]), "+f"(d[43]), "+f"(d[44]), "+f"(d[45]), "+f"(d[46]), "+f"(d[47]),
      "+f"(d[48]), "+f"(d[49]), "+f"(d[50]), "+f"(d[51]), "+f"(d[52]), "+f"(d[53]), "+f"(d[54]), "+f"(d[55]),
      "+f"(d[56]), "+f"(d[57]), "+f"(d[58]), "+f"(d[59]), "+f"(d[60]), "+f"(d[61]), "+f"(d[62]), "+f"(d[63]),
      "+f"(d[64]), "+f"(d[65]), "+f"(d[66]), "+f"(d[67]), "+f"(d[68]), "+f"(d[69]), "+f"(d[70]), "+f"(d[71]),
      "+f"(d[72]), "+f"(d[73]), "+f"(d[74]), "+f"(d[75]), "+f"(d[76]), "+f"(d[77]), "+f"(d[78]), "+f"(d[79]),
      "+f"(d[80]), "+f"(d[81]), "+f"(d[82]), "+f"(d[83]), "+f"(d[84]), "+f"(d[85]), "+f"(d[86]), "+f"(d[87]),
      "+f"(d[88]), "+f"(d[89]), "+f"(d[90]), "+f"(d[91]), "+f"(d[92]), "+f"(d[93]), "+f"(d[94]), "+f"(d[95]),
      "+f"(d[96]), "+f"(d[97]), "+f"(d[98]), "+f"(d[99]), "+f"(d[100]), "+f"(d[101]), "+f"(d[102]), "+f"(d[103]),
      "+f"(d[104]), "+f"(d[105]), "+f"(d[106]), "+f"(d[107]), "+f"(d[108]), "+f"(d[109]), "+f"(d[110]), "+f"(d[111]),
      "+f"(d[112]), "+f"(d[113]), "+f"(d[114]), "+f"(d[115]), "+f"(d[116]), "+f"(d[117]), "+f"(d[118]), "+f"(d[119]),
      "+f"(d[120]), "+f"(d[121]), "+f"(d[122]), "+f"(d[123]), "+f"(d[124]), "+f"(d[125]), "+f"(d[126]), "+f"(d[127])
    : "r"(da), "r"(db), "r"(scale_d));
}

namespace {

constexpr int SEQ = 2048, DM = 1024, FF = 3584;
constexpr int NCTA = 128;

constexpr uint32_t STG_OFF = 196608;
constexpr uint32_t MISC_OFF = STG_OFF + 32768;
constexpr uint32_t SMEM_BYTES = MISC_OFF + 3072;
constexpr uint32_t RED_OFF = 2 * 49152;
constexpr uint32_t MODB_OFF = MISC_OFF + 512;

enum { B_FQ = 0, B_EQ = 4, B_FW = 8, B_EW = 14, B_FG = 20, B_EG = 24, B_FD = 28, B_ED = 34,
       B_STGF = 40, B_MODB = 42, B_MODA = 44, B_RDY = 46, B_STGE = 58, B_COUNT = 60 };
enum { C_H = 0, C_O = 1, C_H2 = 3, C_ACT = 4, C_HA = 8, C_H2A = 9, C_A0 = 10, C_SP = 12 };

struct Params {
  uint4* modll;
  uint4* halo;
  unsigned* cnt;
  CUtensorMap h, o_ld, o_st, h2, act, out, wqkv, wqkv32, wo, wg, wu, wd, act_st, h2_st, h_st, wm;
};

__device__ __align__(1024) bf16 g_h[SEQ * DM];
__device__ __align__(1024) bf16 g_o[SEQ * DM];
__device__ __align__(1024) bf16 g_act[SEQ * FF];
__device__ __align__(1024) uint4 g_modll[3072 / 2];
__device__ __align__(1024) uint4 g_halo[16 * 8 * 2 * 2 * 8 * 32];
__device__ __align__(1024) uint2 g_stats[SEQ * 8];
__device__ __align__(1024) unsigned g_cnt[16 * 32];
__device__ uint4 g_epoch;
#define TR(off)

__device__ __forceinline__ uint32_t smem_u32(const void* p) { return (uint32_t)__cvta_generic_to_shared(p); }
__device__ __forceinline__ void mbar_init(uint32_t bar, uint32_t count) {
  asm volatile("mbarrier.init.shared::cta.b64 [%0], %1;" ::"r"(bar), "r"(count));
}
__device__ __forceinline__ void mbar_arrive(uint32_t bar) {
  asm volatile("mbarrier.arrive.shared::cta.b64 _, [%0];" ::"r"(bar) : "memory");
}
__device__ __forceinline__ void mbar_arrive_cluster(uint32_t cluster_addr) {
  asm volatile("mbarrier.arrive.shared::cluster.b64 _, [%0];" ::"r"(cluster_addr) : "memory");
}
__device__ __forceinline__ uint32_t mapa(uint32_t addr, uint32_t cta) {
  uint32_t r;
  asm volatile("mapa.shared::cluster.u32 %0, %1, %2;" : "=r"(r) : "r"(addr), "r"(cta));
  return r;
}
__device__ __forceinline__ void jitter() {}
__device__ __forceinline__ void mbar_wait(uint32_t bar, uint32_t parity) {
  jitter();
  asm volatile(
      "{\n.reg .pred p;\n"
      "WAIT_%=:\n"
      "mbarrier.try_wait.parity.shared::cta.b64 p, [%0], %1;\n"
      "@!p bra WAIT_%=;\n}\n" ::"r"(bar), "r"(parity) : "memory");
}
__device__ __forceinline__ void mbar_wait_watchdog(uint32_t bar, uint32_t parity) {
  jitter();
  asm volatile(
      "{\n.reg .pred p;\n.reg .u64 t0, t1;\nmov.u64 t0, %%globaltimer;\n"
      "WAIT_%=:\n"
      "mbarrier.try_wait.parity.shared::cta.b64 p, [%0], %1;\n"
      "@p bra DONE_%=;\n"
      "mov.u64 t1, %%globaltimer;\n"
      "sub.u64 t1, t1, t0;\n"
      "setp.lt.u64 p, t1, 2000000000;\n"
      "@p bra WAIT_%=;\n"
      "trap;\n"
      "DONE_%=:\n}\n" ::"r"(bar), "r"(parity) : "memory");
}
__device__ __forceinline__ void cnt_wait(const unsigned* p, unsigned target) {
  asm volatile(
      "{\n.reg .pred p;\n.reg .u32 v;\n.reg .s32 d;\n"
      "WAIT_%=:\n"
      "ld.relaxed.gpu.global.u32 v, [%0];\n"
      "sub.s32 d, v, %1;\n"
      "setp.lt.s32 p, d, 0;\n"
      "@p bra WAIT_%=;\n"
      "fence.proxy.async.global;\n"
      "}\n" ::"l"(p), "r"(target) : "memory");
}
__device__ __forceinline__ void cnt_wait_lazy(const unsigned* p, unsigned target) {
  asm volatile(
      "{\n.reg .pred p;\n.reg .u32 v;\n.reg .s32 d;\n"
      "WAIT_%=:\n"
      "nanosleep.u32 400;\n"
      "ld.relaxed.gpu.global.u32 v, [%0];\n"
      "sub.s32 d, v, %1;\n"
      "setp.lt.s32 p, d, 0;\n"
      "@p bra WAIT_%=;\n"
      "fence.proxy.async.global;\n"
      "}\n" ::"l"(p), "r"(target) : "memory");
}
__device__ __forceinline__ void cnt_signal(unsigned* p) {
  jitter();
  asm volatile("{\n.reg .pred p;\nelect.sync _|p, 0xffffffff;\n@p red.relaxed.gpu.global.add.u32 [%0], 1;\n}\n" ::"l"(p) : "memory");
}
__device__ __forceinline__ void ll_store(uint4* p, uint32_t a, uint32_t b, uint32_t tag) {
  asm volatile("st.relaxed.gpu.global.v2.b64 [%0], {%1, %2};" ::"l"(p), "l"((uint64_t)a | ((uint64_t)tag << 32)),
               "l"((uint64_t)b | ((uint64_t)tag << 32)) : "memory");
}
__device__ __forceinline__ uint4 ll_peek(const uint4* p) {
  uint4 v;
  asm volatile("ld.relaxed.gpu.global.v4.u32 {%0, %1, %2, %3}, [%4];" : "=r"(v.x), "=r"(v.y), "=r"(v.z), "=r"(v.w) : "l"(p) : "memory");
  return v;
}
template <int N, int SLEEP = 0, class F>
__device__ __forceinline__ void ll_poll(F addr, uint32_t tag, uint32_t (&out)[2 * N]) {
  for (;;) {
    uint4 v[N];
#pragma unroll
    for (int i = 0; i < N; i++) v[i] = ll_peek(addr(i));
    uint32_t bad = 0;
#pragma unroll
    for (int i = 0; i < N; i++) {
      bad |= (v[i].y ^ tag) | (v[i].w ^ tag);
      out[2 * i] = v[i].x;
      out[2 * i + 1] = v[i].z;
    }
    if (__all_sync(~0u, bad == 0)) break;
    if (SLEEP) __nanosleep(SLEEP);
  }
}
constexpr uint64_t POLICY_EVICT_FIRST = 0x12F0000000000000ull;
__device__ __forceinline__ void expect_tx_elect(uint32_t bar, uint32_t bytes) {
  asm volatile("{\n.reg .pred p;\nelect.sync _|p, 0xffffffff;\n@p mbarrier.arrive.expect_tx.shared::cta.b64 _, [%0], %1;\n}\n" ::"r"(bar), "r"(bytes) : "memory");
}
__device__ __forceinline__ void arrive_elect(uint32_t bar) {
  asm volatile("{\n.reg .pred p;\nelect.sync _|p, 0xffffffff;\n@p mbarrier.arrive.shared::cta.b64 _, [%0];\n}\n" ::"r"(bar) : "memory");
}
__device__ __forceinline__ void tma_load(uint32_t dst, const CUtensorMap* m, uint32_t bar, int c0, int c1) {
  asm volatile("{\n.reg .pred p;\nelect.sync _|p, 0xffffffff;\n"
               "@p cp.async.bulk.tensor.2d.shared::cluster.global.mbarrier::complete_tx::bytes [%0], [%1, {%3, %4}], [%2];\n}\n"
               ::"r"(dst), "l"(m), "r"(bar), "r"(c0), "r"(c1) : "memory");
}
__device__ __forceinline__ void tma_load_mc(uint32_t dst, const CUtensorMap* m, uint32_t bar, int c0, int c1) {
  asm volatile("{\n.reg .pred p;\nelect.sync _|p, 0xffffffff;\n"
               "@p cp.async.bulk.tensor.2d.shared::cluster.global.mbarrier::complete_tx::bytes.multicast::cluster.L2::cache_hint [%0], [%1, {%3, %4}], [%2], %5, %6;\n}\n"
               ::"r"(dst), "l"(m), "r"(bar), "r"(c0), "r"(c1), "h"((uint16_t)3), "l"(POLICY_EVICT_FIRST) : "memory");
}
__device__ __forceinline__ void tma_load_ef(uint32_t dst, const CUtensorMap* m, uint32_t bar, int c0, int c1) {
  asm volatile("{\n.reg .pred p;\nelect.sync _|p, 0xffffffff;\n"
               "@p cp.async.bulk.tensor.2d.shared::cluster.global.mbarrier::complete_tx::bytes.L2::cache_hint [%0], [%1, {%3, %4}], [%2], %5;\n}\n"
               ::"r"(dst), "l"(m), "r"(bar), "r"(c0), "r"(c1), "l"(POLICY_EVICT_FIRST) : "memory");
}
__device__ __forceinline__ void tma_store2(const CUtensorMap* m, uint32_t src, int c0, int c1) {
  asm volatile("{\n.reg .pred p;\nelect.sync _|p, 0xffffffff;\n"
               "@p cp.async.bulk.tensor.2d.global.shared::cta.bulk_group [%0, {%2, %3}], [%1];\n}\n"
               ::"l"(m), "r"(src), "r"(c0), "r"(c1) : "memory");
}
__device__ __forceinline__ void tma_store3(const CUtensorMap* m, uint32_t src, int c0, int c1, int c2) {
  asm volatile("{\n.reg .pred p;\nelect.sync _|p, 0xffffffff;\n"
               "@p cp.async.bulk.tensor.3d.global.shared::cta.bulk_group [%0, {%2, %3, %4}], [%1];\n}\n"
               ::"l"(m), "r"(src), "r"(c0), "r"(c1), "r"(c2) : "memory");
}
__device__ __forceinline__ void tma_add3(const CUtensorMap* m, uint32_t src, int c0, int c1, int c2) {
  asm volatile("{\n.reg .pred p;\nelect.sync _|p, 0xffffffff;\n"
               "@p cp.reduce.async.bulk.tensor.3d.global.shared::cta.add.bulk_group [%0, {%2, %3, %4}], [%1];\n}\n"
               ::"l"(m), "r"(src), "r"(c0), "r"(c1), "r"(c2) : "memory");
}
__device__ __forceinline__ void store_pause(bool sleep) {
  asm volatile("cp.async.bulk.commit_group;" ::: "memory");
  asm volatile("cp.async.bulk.wait_group.read 0;" ::: "memory");
  if (sleep) __nanosleep(PAUSE);
}
__device__ __forceinline__ void l2_prefetch_tile(const CUtensorMap* m, int c0, int c1) {
  asm volatile("{\n.reg .pred p;\nelect.sync _|p, 0xffffffff;\n@p cp.async.bulk.prefetch.tensor.2d.L2.global [%0, {%1, %2}];\n}\n"
               ::"l"(m), "r"(c0), "r"(c1) : "memory");
}
__device__ __forceinline__ void prefetch_map(const CUtensorMap* m) {
  asm volatile("prefetch.tensormap [%0];" ::"l"(m) : "memory");
}
__device__ __forceinline__ void wg_fence() { asm volatile("wgmma.fence.sync.aligned;" ::: "memory"); }
__device__ __forceinline__ void wg_commit() { asm volatile("wgmma.commit_group.sync.aligned;" ::: "memory"); }
template <int N>
__device__ __forceinline__ void wg_wait() { asm volatile("wgmma.wait_group.sync.aligned %0;" ::"n"(N) : "memory"); }
__device__ __forceinline__ void bar_sync(int id, int n) { asm volatile("bar.sync %0, %1;" ::"r"(id), "r"(n) : "memory"); }
__device__ __forceinline__ void wg_bar(int cw) {
  asm volatile("{\n.reg .pred p;\nsetp.ne.s32 p, %0, 0;\n@p bar.sync 3, 128;\n@!p bar.sync 2, 128;\n}\n" ::"r"(cw) : "memory");
}
__device__ __forceinline__ void skew_pre(int cw) { if (cw == 1) bar_sync(5, 256); }
__device__ __forceinline__ void skew_post(int cw) { if (cw == 0) asm volatile("bar.arrive 5, 256;" ::: "memory"); }
__device__ __forceinline__ void cluster_arrive_relaxed() { asm volatile("barrier.cluster.arrive.relaxed.aligned;" ::: "memory"); }
__device__ __forceinline__ void cluster_wait() { asm volatile("barrier.cluster.wait.acquire.aligned;" ::: "memory"); }
__device__ __forceinline__ uint32_t load_epoch(const unsigned* p) {
  uint32_t e;
  asm volatile("ld.relaxed.gpu.global.u32 %0, [%1];" : "=r"(e) : "l"(p) : "memory");
  return e;
}
__device__ __forceinline__ uint32_t pack2(float lo, float hi) {
  uint32_t r;
  asm("cvt.rn.bf16x2.f32 %0, %1, %2;" : "=r"(r) : "f"(hi), "f"(lo));
  return r;
}
__device__ __forceinline__ float bf_lo(uint32_t v) { return __uint_as_float(v << 16); }
__device__ __forceinline__ float bf_hi(uint32_t v) { return __uint_as_float(v & 0xffff0000u); }
__device__ __forceinline__ uint32_t fma_bf2(uint32_t a, uint32_t b, uint32_t c) {
  uint32_t d;
  asm("fma.rn.bf16x2 %0, %1, %2, %3;" : "=r"(d) : "r"(a), "r"(b), "r"(c));
  return d;
}
__device__ __forceinline__ float bf_round(float v) { return __bfloat162float(__float2bfloat16_rn(v)); }
__device__ __forceinline__ float silu_f(float v) { return __fdividef(v, 1.0f + __expf(-v)); }
__device__ __forceinline__ uint4 ldg_nc(const void* p) {
  uint4 v;
  asm volatile("ld.global.nc.L1::no_allocate.v4.u32 {%0, %1, %2, %3}, [%4];" : "=r"(v.x), "=r"(v.y), "=r"(v.z), "=r"(v.w) : "l"(p));
  return v;
}
__device__ __forceinline__ void stmatrix4(uint32_t addr, uint32_t a, uint32_t b, uint32_t c, uint32_t d) {
  asm volatile("stmatrix.sync.aligned.m8n8.x4.shared.b16 [%0], {%1, %2, %3, %4};" ::"r"(addr), "r"(a), "r"(b), "r"(c), "r"(d) : "memory");
}
__device__ __forceinline__ void stmatrix2(uint32_t addr, uint32_t a, uint32_t b) {
  asm volatile("stmatrix.sync.aligned.m8n8.x2.shared.b16 [%0], {%1, %2};" ::"r"(addr), "r"(a), "r"(b) : "memory");
}
__device__ __forceinline__ void stmatrix1(uint32_t addr, uint32_t a) {
  asm volatile("stmatrix.sync.aligned.m8n8.x1.shared.b16 [%0], {%1};" ::"r"(addr), "r"(a) : "memory");
}
__device__ __forceinline__ uint32_t movmatrix(uint32_t a) {
  uint32_t d;
  asm("movmatrix.sync.aligned.m8n8.trans.b16 %0, %1;" : "=r"(d) : "r"(a));
  return d;
}
__device__ __forceinline__ void mma16816(float (&d)[4], uint32_t a0, uint32_t a1, uint32_t a2, uint32_t a3, uint32_t b0, uint32_t b1) {
  asm("mma.sync.aligned.m16n8k16.row.col.f32.bf16.bf16.f32 {%0, %1, %2, %3}, {%4, %5, %6, %7}, {%8, %9}, {%0, %1, %2, %3};"
               : "+f"(d[0]), "+f"(d[1]), "+f"(d[2]), "+f"(d[3]) : "r"(a0), "r"(a1), "r"(a2), "r"(a3), "r"(b0), "r"(b1));
}
__device__ __forceinline__ void mma1688(float (&d)[4], uint32_t a0, uint32_t a1, uint32_t b0) {
  asm("mma.sync.aligned.m16n8k8.row.col.f32.bf16.bf16.f32 {%0, %1, %2, %3}, {%4, %5}, {%6}, {%0, %1, %2, %3};"
               : "+f"(d[0]), "+f"(d[1]), "+f"(d[2]), "+f"(d[3]) : "r"(a0), "r"(a1), "r"(b0));
}
__device__ __forceinline__ void ldmatrix4t(uint32_t (&b)[4], uint32_t addr) {
  asm volatile("ldmatrix.sync.aligned.m8n8.x4.trans.shared.b16 {%0, %1, %2, %3}, [%4];" : "=r"(b[0]), "=r"(b[1]), "=r"(b[2]), "=r"(b[3]) : "r"(addr) : "memory");
}
__device__ __forceinline__ void ldmatrix4(uint32_t& a, uint32_t& b, uint32_t& c, uint32_t& d, uint32_t addr) {
  asm volatile("ldmatrix.sync.aligned.m8n8.x4.shared.b16 {%0, %1, %2, %3}, [%4];" : "=r"(a), "=r"(b), "=r"(c), "=r"(d) : "r"(addr) : "memory");
}
__device__ __forceinline__ void cp_async16(uint32_t dst, const void* src) {
  asm volatile("cp.async.cg.shared.global.L2::cache_hint [%0], [%1], 16, %2;" ::"r"(dst), "l"(src), "l"(POLICY_EVICT_FIRST) : "memory");
}
__device__ __forceinline__ uint32_t lds32(uint32_t addr) {
  uint32_t v;
  asm volatile("ld.shared.u32 %0, [%1];" : "=r"(v) : "r"(addr) : "memory");
  return v;
}
__device__ __forceinline__ void sts64f(uint32_t addr, float a, float b) {
  asm volatile("st.shared.v2.f32 [%0], {%1, %2};" ::"r"(addr), "f"(a), "f"(b) : "memory");
}
constexpr float QK_SCALE = 0.17677669529663687f;
__device__ __forceinline__ float softmax8(float& p0, float& p1) {
  float m = fmaxf(p0, p1);
  m = fmaxf(m, __shfl_xor_sync(~0u, m, 1));
  m = fmaxf(m, __shfl_xor_sync(~0u, m, 2));
  asm("ex2.approx.ftz.f32 %0, %1;" : "=f"(p0) : "f"((p0 - m) * 1.4426950408889634f));
  asm("ex2.approx.ftz.f32 %0, %1;" : "=f"(p1) : "f"((p1 - m) * 1.4426950408889634f));
  float s = p0 + p1;
  s += __shfl_xor_sync(~0u, s, 1);
  s += __shfl_xor_sync(~0u, s, 2);
  float r;
  asm("rcp.approx.ftz.f32 %0, %1;" : "=f"(r) : "f"(s));
  return r;
}
__device__ __forceinline__ void sts128(uint32_t addr, uint32_t a, uint32_t b, uint32_t c, uint32_t d) {
  asm volatile("st.shared.v4.u32 [%0], {%1, %2, %3, %4};" ::"r"(addr), "r"(a), "r"(b), "r"(c), "r"(d) : "memory");
}
__device__ __forceinline__ uint4 lds128(uint32_t addr) {
  uint4 v;
  asm volatile("ld.shared.v4.u32 {%0, %1, %2, %3}, [%4];" : "=r"(v.x), "=r"(v.y), "=r"(v.z), "=r"(v.w) : "r"(addr) : "memory");
  return v;
}
__device__ __forceinline__ float2 lds64f(uint32_t addr) {
  float2 v;
  asm volatile("ld.shared.v2.f32 {%0, %1}, [%2];" : "=f"(v.x), "=f"(v.y) : "r"(addr) : "memory");
  return v;
}
#define PROF_AT(cond, slot) do {} while (0)

constexpr uint32_t SMEM_BASE = 1024;
constexpr uint32_t DESC_A = (1u << 16) | (SMEM_BASE >> 4);
constexpr uint32_t DESC_B = ((8192u >> 4) << 16) | (SMEM_BASE >> 4);

template <int BN> struct Wg;
template <> struct Wg<128> { static __device__ __forceinline__ void mma(float (&d)[64], uint32_t a, uint32_t b, int s) { wgmma_ss_n128(d, a, b, s); } };
template <> struct Wg<192> { static __device__ __forceinline__ void mma(float (&d)[96], uint32_t a, uint32_t b, int s) { wgmma_ss_n192(d, a, b, s); } };
template <> struct Wg<256> { static __device__ __forceinline__ void mma(float (&d)[128], uint32_t a, uint32_t b, int s) { wgmma_ss_n256(d, a, b, s); } };

struct Ring {
  uint32_t full0, rel0;
  int s;
  uint32_t ph;
  uint32_t off;
  bool releaser;
};

template <int N>
__device__ __forceinline__ void fence_regs(float (&a)[N]) {
#pragma unroll
  for (int i = 0; i < N; i++) asm volatile("" : "+f"(a[i])::"memory");
}

template <int BN, int NST, uint32_t STAGE>
__device__ __forceinline__ void kblock(float (&acc)[BN / 2], Ring& g, uint32_t a_addr, bool zero, uint32_t& prev, uint32_t b_rel = 16384) {
  mbar_wait(g.full0 + 8 * g.s, g.ph);
  const uint32_t da = DESC_A + (a_addr >> 4);
  const uint32_t db = DESC_B + ((g.off + b_rel) >> 4);
  wg_fence();
#pragma unroll
  for (int k = 0; k < 4; k++) Wg<BN>::mma(acc, da + k * 2, db + k * 128, !(zero && k == 0));
  wg_commit();
  wg_wait<1>();
  jitter();
  if (prev != 0) mbar_arrive_cluster(prev);
  prev = g.releaser ? g.rel0 + 8 * g.s : 0u;
  if (++g.s == NST) { g.s = 0; g.ph ^= 1; }
  g.off += STAGE;
  if (g.off == NST * STAGE) g.off = 0;
}
template <int N>
__device__ __forceinline__ void tile_end(float (&acc)[N], uint32_t& prev) {
  wg_wait<0>();
  if (prev != 0) mbar_arrive_cluster(prev);
  prev = 0;
  fence_regs(acc);
}

__device__ __forceinline__ int other_kb(int q, int j) {
  const int ch = q >= 7, jj = q - 7 * ch;
  return 2 * (jj < j ? jj : jj + 1) + ch;
}
__device__ __forceinline__ int qkv_kb(int it, int j) {
  return it < 4 ? 2 * j + (it >> 1) : other_kb(it < 18 ? it - 4 : it - 18, j);
}
__device__ __forceinline__ int wo_k(int it, int j) {
  return it < 8 ? it * 128 : (it == 8 ? j : (it - 9 < j ? it - 9 : it - 8)) * 128 + 64;
}
__device__ __forceinline__ int down_k(int d) {
  const int u = d + KH;
  if (u < 8) return u * 448 + 384;
  if (u < 40) return (((u - 8) & 15) >> 1) * 448 + ((u - 8) >> 4) * 128 + (u & 1) * 64;
  return (u & 7) * 448 + 256 + (u >= 48 ? 64 : 0);
}
__device__ __forceinline__ void wait_q_free(uint32_t empty, int i) {
  mbar_wait(empty + 8 * ((i * 2) / 3), 1);
  mbar_wait(empty + 8 * ((i * 2 + 1) / 3), 1);
}
__device__ __forceinline__ void wait_w_free(uint32_t empty, int i) {
  const int t = (i + 3) & 3, w0 = (t * 3) / 2, w1 = (t * 3 + 2) / 2;
  mbar_wait(empty + 8 * w0, w0 < 4);
  mbar_wait(empty + 8 * w1, w1 < 4);
}
__device__ __forceinline__ void wait_g_free(uint32_t empty, int i) {
  const int s = i < 4 ? i + 2 : i - 4, b0 = ((s * 2) / 3 + 1) & 3, b1 = ((s * 2 + 1) / 3 + 1) & 3;
  mbar_wait(empty + 8 * b0, b0 < 2);
  mbar_wait(empty + 8 * b1, b1 < 2);
}

__device__ __forceinline__ void chan(float& m, float& q, float m2, float q2, float n) {
  const float d = m2 - m;
  m = 0.5f * (m + m2);
  q = q + q2 + d * d * (0.5f * n);
}

__device__ __forceinline__ uint32_t tag16(uint32_t tag, uint32_t ln) { return (((tag & 0x3fffu) << 1) | ln) + 0x8000u; }
__device__ __forceinline__ void stat_store(uint2* slot, float m, float q, uint32_t t16) {
  const uint32_t a = ((__float_as_uint(m) + 0x80u) & 0xffffff00u) | (t16 & 0xffu), b = ((__float_as_uint(q) + 0x80u) & 0xffffff00u) | (t16 >> 8);
  asm volatile("st.relaxed.gpu.global.b64 [%0], %1;" ::"l"(slot), "l"((uint64_t)a | ((uint64_t)b << 32)) : "memory");
}
__device__ __forceinline__ void stat_gather(const uint2* rows, uint32_t t16, int lane, float (&rs)[2], float (&nb)[2]) {
  const uint4* sp = (const uint4*)(rows + (lane >> 3) * 128) + (lane & 7);
  const uint32_t want = (t16 & 0xffu) | ((t16 >> 8) << 8);
  uint4 a, b;
  for (;;) {
    a = ll_peek(sp);
    b = ll_peek(sp + 256);
    const uint32_t bad = (__byte_perm(a.x, a.y, 0x40) ^ want) | (__byte_perm(a.z, a.w, 0x40) ^ want) | (__byte_perm(b.x, b.y, 0x40) ^ want) |
                         (__byte_perm(b.z, b.w, 0x40) ^ want);
    if (__all_sync(~0u, (bad & 0xffffu) == 0)) break;
  }
  float m0 = __uint_as_float(a.x & 0xffffff00u), q0 = __uint_as_float(a.y & 0xffffff00u);
  float m1 = __uint_as_float(a.z & 0xffffff00u), q1 = __uint_as_float(a.w & 0xffffff00u);
  chan(m0, q0, __uint_as_float(b.x & 0xffffff00u), __uint_as_float(b.y & 0xffffff00u), 128.f);
  chan(m1, q1, __uint_as_float(b.z & 0xffffff00u), __uint_as_float(b.w & 0xffffff00u), 128.f);
  const bool hi = lane & 8;
  float m = hi ? m1 : m0, q = hi ? q1 : q0;
  chan(m, q, __shfl_xor_sync(~0u, hi ? m0 : m1, 8), __shfl_xor_sync(~0u, hi ? q0 : q1, 8), 256.f);
  chan(m, q, __shfl_xor_sync(~0u, m, 16), __shfl_xor_sync(~0u, q, 16), 512.f);
  const float rstd = rsqrtf(q * (1.0f / DM) + 1e-5f), nmr = -m * rstd;
  const int r = lane >> 2, src = (r >> 1) + (r & 1) * 8;
  rs[0] = __shfl_sync(~0u, rstd, src); nb[0] = __shfl_sync(~0u, nmr, src);
  rs[1] = __shfl_sync(~0u, rstd, src + 4); nb[1] = __shfl_sync(~0u, nmr, src + 4);
}

__device__ __forceinline__ void publish_stats(const uint32_t (&xl)[16], const uint32_t (&xh)[16], uint2* slot, int lane, uint32_t t16) {
  float ds[4] = {0.f, 0.f, 0.f, 0.f}, dl[4] = {0.f, 0.f, 0.f, 0.f}, dh[4] = {0.f, 0.f, 0.f, 0.f};
#pragma unroll
  for (int q = 0; q < 8; q++) {
    mma16816(ds, xl[2 * q], xh[2 * q], xl[2 * q + 1], xh[2 * q + 1], 0x3f803f80u, 0x3f803f80u);
    mma16816(dl, xl[2 * q], xh[2 * q], xl[2 * q + 1], xh[2 * q + 1], xl[2 * q], xl[2 * q + 1]);
    mma16816(dh, xl[2 * q], xh[2 * q], xl[2 * q + 1], xh[2 * q + 1], xh[2 * q], xh[2 * q + 1]);
  }
  const int r = lane >> 2;
  if ((lane & 3) == (r >> 1)) {
    const float ml = ds[0] * (1.0f / 128), mh = ds[2] * (1.0f / 128);
    const float ql = fmaxf(((r & 1) ? dl[1] : dl[0]) - ds[0] * ml, 0.f), qh = fmaxf(((r & 1) ? dh[3] : dh[2]) - ds[2] * mh, 0.f);
    stat_store(slot + r, ml, ql, t16);
    stat_store(slot + r + 8, mh, qh, t16);
  }
  __syncwarp();
}

__device__ __forceinline__ void stage_slab(uint32_t chunk, int warp, int lane, const uint32_t (&lo)[8], const uint32_t (&hi)[8]) {
  const int row = warp * 16 + (lane & 7) + ((lane >> 3) & 1) * 8;
  const uint32_t rbase = chunk + row * 128;
#pragma unroll
  for (int q = 0; q < 4; q++) {
    const int grp = 2 * q + (lane >> 4);
    stmatrix4(rbase + ((grp ^ (row & 7)) << 4), lo[2 * q], hi[2 * q], lo[2 * q + 1], hi[2 * q + 1]);
  }
}
__device__ __forceinline__ float silu_mul(float g, float u) {
  float e, r;
  asm("ex2.approx.ftz.f32 %0, %1;" : "=f"(e) : "f"(g * -1.4426950408889634f));
  asm("rcp.approx.ftz.f32 %0, %1;" : "=f"(r) : "f"(1.0f + e));
  return g * r * u;
}
__device__ __forceinline__ uint32_t swiglu2(uint32_t g2, uint32_t u2) {
  asm volatile("" : "+r"(g2));
  return pack2(silu_mul(bf_lo(g2), bf_lo(u2)), silu_mul(bf_hi(g2), bf_hi(u2)));
}
__device__ __forceinline__ void stage_done(uint32_t bar, int lane) {
  asm volatile("fence.proxy.async.shared::cta;" ::: "memory");
  __syncwarp();
  if (lane == 0) mbar_arrive(bar);
}

__device__ __forceinline__ int fresh_tid() {
  int t;
  asm volatile("mov.u32 %0, %%tid.x;" : "=r"(t));
  return t;
}
#define RING_IDS()                                                                                           \
  const int tid = fresh_tid() - 128;                                                                         \
  const int cw = __shfl_sync(~0u, tid >> 7, 0), warp = __shfl_sync(~0u, (tid >> 5) & 3, 0);                  \
  const bool releaser = (tid & 31) < 2;                                                                      \
  const uint32_t rbars = mapa(bars, tid & 1);                                                                \
  const uint32_t a_base = cw * 8192
#define LANE_IDS()                                                                                           \
  const int lane = fresh_tid() & 31, r = lane >> 2, c = lane & 3;                                            \
  const int srow = warp * 16 + (lane & 7) + ((lane >> 3) & 1) * 8;                                           \
  const uint32_t slab = stg + cw * 8192 + srow * 128, sw0 = (lane >> 4) ^ (srow & 7);                        \
  (void)r; (void)c; (void)slab; (void)sw0

template <int NPRE, bool EAGER, class Step>
__device__ __forceinline__ void attention(float (&acc)[96], const Params& p, int rho, int rb, int cta, int cw, int warp, uint32_t tag,
                                          uint32_t stg, uint32_t bars, uint32_t& prev, Step step) {
  uint32_t ql[8], qh[8], k0[8], k1[8], v0[8], v1[8], hp[16];
  mbar_wait(bars + 8 * B_STGE, rho);
  mbar_wait(bars + 8 * (B_STGE + 1), 0);
  if (EAGER) {
    tile_end(acc, prev);
  } else {
    step();
    fence_regs(acc);
  }
#pragma unroll
  for (int t = 0; t < 8; t++) {
    k0[t] = pack2(acc[4 * (8 + t)], acc[4 * (8 + t) + 1]);
    k1[t] = pack2(acc[4 * (8 + t) + 2], acc[4 * (8 + t) + 3]);
    v0[t] = pack2(acc[4 * (16 + t)], acc[4 * (16 + t) + 1]);
    v1[t] = pack2(acc[4 * (16 + t) + 2], acc[4 * (16 + t) + 3]);
    asm volatile("" : "+r"(k0[t]), "+r"(k1[t]), "+r"(v0[t]), "+r"(v1[t]));
  }
  const int lane = fresh_tid() & 31, r = lane >> 2, c = lane & 3;
#pragma unroll
  for (int t = 0; t < 8; t++) v1[t] = movmatrix(v1[t]);
  const uint32_t xch = stg + 16384 + (cw * 4 + warp) * 2048 + lane * 16;
  if (warp < 3) {
    sts128(xch, k1[0], k1[1], k1[2], k1[3]);
    sts128(xch + 512, k1[4], k1[5], k1[6], k1[7]);
    sts128(xch + 1024, v1[0], v1[1], v1[2], v1[3]);
    sts128(xch + 1536, v1[4], v1[5], v1[6], v1[7]);
  } else if (rb < 15) {
    uint4* dst = p.halo + ((cta * 2 + rho) * 2 + cw) * 256 + lane;
#pragma unroll
    for (int t = 0; t < 4; t++) {
      ll_store(dst + t * 32, k1[2 * t], k1[2 * t + 1], tag);
      ll_store(dst + (4 + t) * 32, v1[2 * t], v1[2 * t + 1], tag);
    }
  }
#pragma unroll
  for (int t = 0; t < 8; t++) {
    v0[t] = movmatrix(v0[t]);
    ql[t] = pack2(acc[4 * t], acc[4 * t + 1]);
    qh[t] = pack2(acc[4 * t + 2], acc[4 * t + 3]);
    asm volatile("" : "+r"(v0[t]), "+r"(ql[t]), "+r"(qh[t]));
  }
#pragma unroll 1
  for (int i = 0; i < NPRE; i++) step();
  const uint4* src = p.halo + (((cta - 8) * 2 + rho) * 2 + cw) * 256 + lane;
  uint4 early[8] = {};
  if (warp == 0 && rb > 0) {
#pragma unroll
    for (int i = 0; i < 8; i++) early[i] = ll_peek(src + i * 32);
  }
  step();
  wg_bar(cw);
  if (warp > 0) {
#pragma unroll
    for (int t = 0; t < 4; t++) {
      const uint4 a = lds128(xch - 2048 + t * 512);
      hp[4 * t] = a.x; hp[4 * t + 1] = a.y; hp[4 * t + 2] = a.z; hp[4 * t + 3] = a.w;
    }
  } else if (rb > 0) {
    uint32_t bad = 0;
#pragma unroll
    for (int i = 0; i < 8; i++) {
      bad |= (early[i].y ^ tag) | (early[i].w ^ tag);
      hp[2 * i] = early[i].x;
      hp[2 * i + 1] = early[i].z;
    }
    if (!__all_sync(~0u, bad == 0)) ll_poll<8>([&](int i) { return src + i * 32; }, tag, hp);
  } else {
#pragma unroll
    for (int t = 0; t < 16; t++) hp[t] = 0;
  }
  wg_wait<0>();
  if (prev != 0) mbar_arrive_cluster(prev);
  prev = 0;
#pragma unroll
  for (int t = 0; t < 8; t++) asm volatile("" : "+r"(ql[t])::"memory");
  const bool up0 = 2 * c > r, up1 = 2 * c + 1 > r;
  const bool first = (rb == 0) && (warp == 0);
  uint32_t a0[2], a2[2], a3[2], a5[2];
  float il[2], ih[2];
#pragma unroll
  for (int h = 0; h < 2; h++) {
    float sp[4] = {0.f, 0.f, 0.f, 0.f}, s0[4] = {0.f, 0.f, 0.f, 0.f}, s1[4] = {0.f, 0.f, 0.f, 0.f};
#pragma unroll
    for (int ks = 0; ks < 2; ks++) {
      const int t = 4 * h + 2 * ks;
      mma16816(sp, ql[t], qh[t], ql[t + 1], qh[t + 1], hp[t], hp[t + 1]);
      mma16816(s0, ql[t], qh[t], ql[t + 1], qh[t + 1], k0[t], k0[t + 1]);
      mma16816(s1, ql[t], qh[t], ql[t + 1], qh[t + 1], k1[t], k1[t + 1]);
    }
    float p0 = (up0 ? sp[0] : s0[0]) * QK_SCALE, p1 = (up1 ? sp[1] : s0[1]) * QK_SCALE;
    float p2 = (up0 ? s0[2] : s1[2]) * QK_SCALE, p3 = (up1 ? s0[3] : s1[3]) * QK_SCALE;
    if (first && up0) p0 = -1000000000.0f;
    if (first && up1) p1 = -1000000000.0f;
    il[h] = softmax8(p0, p1);
    ih[h] = softmax8(p2, p3);
    a0[h] = pack2(up0 ? p0 : 0.f, up1 ? p1 : 0.f);
    a2[h] = pack2(up0 ? 0.f : p0, up1 ? 0.f : p1);
    a3[h] = pack2(up0 ? p2 : 0.f, up1 ? p3 : 0.f);
    a5[h] = pack2(up0 ? 0.f : p2, up1 ? 0.f : p3);
  }
  float o[8][4];
#pragma unroll
  for (int t = 0; t < 8; t++) {
#pragma unroll
    for (int q = 0; q < 4; q++) o[t][q] = 0.f;
    mma1688(o[t], 0u, a5[t >> 2], v1[t]);
    mma16816(o[t], a0[t >> 2], 0u, a2[t >> 2], a3[t >> 2], hp[8 + t], v0[t]);
  }
#pragma unroll
  for (int t = 0; t < 8; t++) fence_regs(o[t]);
  if (!EAGER) step();
  uint32_t ol[8], oh[8];
#pragma unroll
  for (int t = 0; t < 8; t++) {
    ol[t] = pack2(o[t][0] * il[t >> 2], o[t][1] * il[t >> 2]);
    oh[t] = pack2(o[t][2] * ih[t >> 2], o[t][3] * ih[t >> 2]);
  }
  if (!EAGER) step();
  stage_slab(stg + cw * 8192, warp, lane, ol, oh);
  stage_done(bars + 8 * B_STGF, lane);
  if (!EAGER) step();
}

__global__ void __launch_bounds__(384, 1) fused_kernel(const bf16* __restrict__ gx, const bf16* __restrict__ gwmod, const bf16* __restrict__ gc,
                                                          unsigned* gepoch, uint2* gstats, const __grid_constant__ Params p) {
  extern __shared__ __align__(1024) uint8_t smem_raw[];
  const uint32_t sm = smem_u32(smem_raw);
  const uint32_t bars = sm + MISC_OFF;
  const uint32_t stg = sm + STG_OFF;
  const int rank = blockIdx.x & 1;
  const int cl = blockIdx.x >> 1;
  if (cl >= NCTA / 2) {
    const int e = blockIdx.x - NCTA, wid = __shfl_sync(~0u, (int)(threadIdx.x >> 5), 0), lane = threadIdx.x & 31;
    if (threadIdx.x == 0) {
      for (int i = 0; i < 6; i++) { mbar_init(bars + 8 * i, 1); mbar_init(bars + 8 * (6 + i), 8); }
      for (int i = 0; i < 8; i++) { mbar_init(bars + 8 * (16 + i), 1); mbar_init(bars + 8 * (24 + i), 4); }
      mbar_init(bars + 8 * 12, 1);
      asm volatile("fence.mbarrier_init.release.cluster;" ::: "memory");
    }
    const uint32_t tag = load_epoch(gepoch) + 1;
    for (int i = threadIdx.x; i < 1536; i += 384) {
      uint4 o = make_uint4(0u, 0u, 0u, 0u);
      if (i < 1024 && (i & 63) < 8) {
        const uint4 cv = ldg_nc(gc + (i >> 6) * 64 + (i & 7) * 8);
        o = make_uint4(pack2(silu_f(bf_lo(cv.x)), silu_f(bf_hi(cv.x))), pack2(silu_f(bf_lo(cv.y)), silu_f(bf_hi(cv.y))),
                       pack2(silu_f(bf_lo(cv.z)), silu_f(bf_hi(cv.z))), pack2(silu_f(bf_lo(cv.w)), silu_f(bf_hi(cv.w))));
      }
      sts128(stg + i * 16, o.x, o.y, o.z, o.w);
    }
    asm volatile("fence.proxy.async.shared::cta;" ::: "memory");
    __syncthreads();
    if (wid == 0) {
      __nanosleep(WMDELAY);
      uint32_t ph = 1;
#pragma unroll 1
      for (int it = 0, s = 0; it < 64; it++) {
        mbar_wait(bars + 8 * (6 + s), ph);
        expect_tx_elect(bars + 8 * s, 32768);
#pragma unroll
        for (int q = 0; q < 4; q++) tma_load_ef(sm + s * 32768 + q * 8192, &p.wm, bars + 8 * s, 2048 + (it >> 4) * 1024 + e * 256 + q * 64, (it & 15) * 64);
        if (++s == 6) { s = 0; ph ^= 1; }
      }
    } else if (wid == 1) {
      __nanosleep(PFW);
#pragma unroll 1
      for (int i = 0; i < 64; i++) {
        l2_prefetch_tile(&p.wo, (i & 15) * 64, (e * 4 + (i >> 4)) * 64);
      }
#pragma unroll 1
      for (int i = 0; i < 80; i++) {
        if (i < 64) l2_prefetch_tile((i & 1) ? &p.wu : &p.wg, ((i >> 1) & 7) * 448 + 384, ((i >> 4) * 4 + e) * 64);
        else l2_prefetch_tile((i & 2) ? &p.wu : &p.wg, (e * 2 + ((i >> 3) & 1)) * 448 + (i & 1) * 64, (e * 4 + ((i >> 2) & 3)) * 64);
      }
    } else if (wid >= 4) {
      const int hf = (wid >> 2) - 1;
      uint32_t ph = 0;
      int s = 0;
#pragma unroll 1
      for (int v = 0; v < 4; v++) {
        float acc[64];
#pragma unroll 1
        for (int kb = 0; kb < 16; kb++) {
          mbar_wait_watchdog(bars + 8 * s, ph);
          const uint32_t da = DESC_A + ((STG_OFF + kb * 1024) >> 4), db = DESC_B + ((s * 32768 + hf * 16384) >> 4);
          wg_fence();
#pragma unroll
          for (int k = 0; k < 4; k++) wgmma_ss_n128(acc, da + k * 2, db + k * 128, (kb | k) != 0);
          wg_commit();
          wg_wait<0>();
          if (lane == 0) mbar_arrive(bars + 8 * (6 + s));
          if (++s == 6) { s = 0; ph ^= 1; }
        }
        fence_regs(acc);
        if ((wid & 3) == 0) {
#pragma unroll
          for (int n = 0; n < 16; n++) {
            const uint32_t mine = pack2(acc[4 * n], acc[4 * n + 1]), next = __shfl_down_sync(~0u, mine, 1);
            if (lane < 4 && (lane & 1) == 0) ll_store(p.modll + 512 + v * 256 + e * 64 + hf * 32 + n * 2 + (lane >> 1), mine, next, tag);
            if (lane < 4) sts64f(sm + MODB_OFF + (hf * 128 + n * 8 + lane * 2) * 4, bf_lo(mine), bf_hi(mine));
          }
        }
      }
    }
    __syncthreads();
    if (wid == 0 || wid == 2) {
      const int w = wid >> 1;
      if (w == 0) {
        expect_tx_elect(bars + 8 * 12, KH * 32768);
#pragma unroll 1
        for (int q = 0; q < 4 * KH; q++) tma_load_ef(sm + q * 8192, &p.wd, bars + 8 * 12, e * 256 + (q & 3) * 64, (q >> 2) * 448 + 384);
      }
      cnt_wait_lazy(p.cnt + C_ACT, tag * 8);
      if (w == 1) __nanosleep(900);
      uint32_t ph = 1, ready = 0;
#pragma unroll 1
      for (int it = 0, s = 0; it < 16 * KH; it++) {
        const int rb = it / KH, kc = it - rb * KH;
        while (!((ready >> rb) & 1)) {
          ready = __ballot_sync(~0u, (int)(load_epoch(p.cnt + (lane & 15) * 32 + C_ACT) - tag * 8) >= 0);
          asm volatile("fence.proxy.async.global;" ::: "memory");
        }
        const uint32_t fb = bars + 8 * (16 + w * 4 + s), dst = sm + 98304 + w * 32768 + s * 8192;
        mbar_wait(fb + 64, ph);
        expect_tx_elect(fb, 8192);
        tma_load(dst, &p.act_st, fb, kc * 448 + 384, rb * 128 + w * 64);
        tma_load(dst + 4096, &p.act_st, fb, kc * 448 + 384, rb * 128 + w * 64 + 32);
        if (++s == 4) { s = 0; ph ^= 1; }
      }
    } else if (wid >= 4) {
      const int w = (wid >> 2) - 1, warp = wid & 3;
      const uint32_t out_stg = (w ? stg : sm + 163840) + warp * 2048;
      const uint32_t slab = out_stg + (lane & 15) * 128, sw0 = (lane >> 4) ^ (lane & 7);
      mbar_wait_watchdog(bars + 8 * 12, 0);
#pragma unroll 1
      for (int i = threadIdx.x - 128; i < KH * 2048; i += 256) {
        const uint32_t gp = sm + MODB_OFF + (((i >> 9) & 3) * 64 + ((i ^ (i >> 3)) & 7) * 8) * 4;
        const uint4 v = lds128(sm + i * 16), ga = lds128(gp), gc = lds128(gp + 16);
        sts128(sm + i * 16, pack2(bf_lo(v.x) * __uint_as_float(ga.x), bf_hi(v.x) * __uint_as_float(ga.y)),
               pack2(bf_lo(v.y) * __uint_as_float(ga.z), bf_hi(v.y) * __uint_as_float(ga.w)),
               pack2(bf_lo(v.z) * __uint_as_float(gc.x), bf_hi(v.z) * __uint_as_float(gc.y)),
               pack2(bf_lo(v.w) * __uint_as_float(gc.z), bf_hi(v.w) * __uint_as_float(gc.w)));
      }
      asm volatile("fence.proxy.async.shared::cta;" ::: "memory");
      bar_sync(1, 256);
      uint32_t ph = 0;
      int s = 0;
#pragma unroll 1
      for (int rb = 0; rb < 16; rb++) {
        float acc[128];
#pragma unroll 1
        for (int kc = 0; kc < KH; kc++) {
          mbar_wait_watchdog(bars + 8 * (16 + w * 4 + s), ph);
          const uint32_t da = DESC_A + ((98304 + w * 32768 + s * 8192) >> 4), db = DESC_B + ((kc * 32768) >> 4);
          wg_fence();
#pragma unroll
          for (int k = 0; k < 4; k++) wgmma_ss_n256(acc, da + k * 2, db + k * 128, (kc | k) != 0);
          wg_commit();
          wg_wait<1>();
          if (kc > 0 && lane == 0) mbar_arrive(bars + 8 * (24 + w * 4 + ((s + 3) & 3)));
          if (++s == 4) { s = 0; ph ^= 1; }
        }
        asm volatile("cp.async.bulk.wait_group 0;" ::: "memory");
        __syncwarp();
        if (rb > 0) cnt_signal(p.cnt + (rb - 1) * 32 + C_SP + e);
        wg_wait<0>();
        fence_regs(acc);
        __syncwarp();
        if (lane == 0) mbar_arrive(bars + 8 * (24 + w * 4 + ((s + 3) & 3)));
#pragma unroll
        for (int q = 0; q < 16; q++)
          stmatrix4(slab + (q >> 2) * 8192 + ((sw0 ^ ((q & 3) * 2)) << 4), pack2(acc[8 * q], acc[8 * q + 1]), pack2(acc[8 * q + 2], acc[8 * q + 3]),
                    pack2(acc[8 * q + 4], acc[8 * q + 5]), pack2(acc[8 * q + 6], acc[8 * q + 7]));
        asm volatile("fence.proxy.async.shared::cta;" ::: "memory");
        __syncwarp();
#pragma unroll
        for (int ch = 0; ch < 4; ch++) tma_add3(&p.out, out_stg + ch * 8192, e * 256 + ch * 64, rb * 64 + warp * 16, w);
        asm volatile("cp.async.bulk.commit_group;" ::: "memory");
      }
      asm volatile("cp.async.bulk.wait_group 0;" ::: "memory");
      __syncwarp();
      cnt_signal(p.cnt + 15 * 32 + C_SP + e);
    }
    return;
  }
  const int q7 = ((cl - 36) * 37) >> 8;
  const int j = cl < 4 ? 4 + cl : (cl < 36 ? (cl - 4) >> 3 : 4 + q7);
  const int rb = (cl < 4 ? 0 : (cl < 36 ? (cl - 4) & 7 : cl - 35 - 7 * q7)) * 2 + rank;
  const int cta = rb * 8 + j;
  PROF_AT(threadIdx.x == 0, 0);

  if (threadIdx.x < 128) {
    asm volatile("setmaxnreg.dec.sync.aligned.u32 40;");
    const int warp = __shfl_sync(~0u, (int)(threadIdx.x >> 5), 0), lane = threadIdx.x & 31;
    if (threadIdx.x == 0) {
      const uint32_t ep = load_epoch(gepoch);
      if ((sm & 0x3FFFF) != SMEM_BASE) asm volatile("trap;");
      for (int i = 0; i < 4; i++) { mbar_init(bars + 8 * (B_FQ + i), 1); mbar_init(bars + 8 * (B_EQ + i), 16); }
      for (int i = 0; i < 6; i++) { mbar_init(bars + 8 * (B_FW + i), 1); mbar_init(bars + 8 * (B_EW + i), 16); }
      for (int i = 0; i < 4; i++) { mbar_init(bars + 8 * (B_FG + i), 1); mbar_init(bars + 8 * (B_EG + i), 16); }
      for (int i = 0; i < 6; i++) { mbar_init(bars + 8 * (B_FD + i), 1); mbar_init(bars + 8 * (B_ED + i), 16); }
      for (int i = 0; i < 2; i++) { mbar_init(bars + 8 * (B_STGF + i), 8); mbar_init(bars + 8 * (B_STGE + i), 1); }
      mbar_init(bars + 8 * B_MODB, 1);
      mbar_init(bars + 8 * (B_MODB + 1), 1);
      mbar_init(bars + 8 * B_MODA, 1);
      mbar_init(bars + 8 * (B_MODA + 1), 1);
      for (int i = 0; i < 11; i++) mbar_init(bars + 8 * (B_RDY + i), 1);
      asm volatile("st.shared.u32 [%0], %1;" ::"r"(bars + 8 * B_COUNT), "r"(ep + 1) : "memory");
      asm volatile("fence.mbarrier_init.release.cluster;\nfence.acq_rel.cta;" ::: "memory");
    }
    __syncwarp();
    cluster_arrive_relaxed();
    unsigned* cnt = p.cnt + rb * 32;
    cluster_wait();
    const uint32_t tag = lds32(bars + 8 * B_COUNT);
    const unsigned target = tag * 8;
    if (warp == 0) {
      const CUtensorMap* wgu = rank ? &p.wu : &p.wg;
      uint32_t st = sm + 16384, fb = bars + 8 * B_FQ, ph = 1;
      __nanosleep(BDELAY);
#pragma unroll 1
      for (int it = 0; it < 32; it++) {
        const int kb = qkv_kb(it, j), col = j * 128 + ((it < 4 ? (it & 1) : it >= 18) ? 64 : 0);
        if (it == 2) mbar_wait(bars + 8 * B_MODA, 0);
        mbar_wait(fb + 8 * (B_EQ - B_FQ), ph);
        expect_tx_elect(fb, it < 4 ? 24576 : 40960);
        tma_load_mc(st + rank * 8192, &p.wqkv, fb, col + rank * 1024, kb * 64);
        tma_load_mc(st + 16384 + rank * 4096, &p.wqkv32, fb, col + 2048, kb * 64 + rank * 32);
        st += 49152; fb += 8;
        if ((it & 3) == 3) { st -= 4 * 49152; fb -= 32; ph ^= 1; }
      }
      fb = bars + 8 * B_FW; ph = 1;
#pragma unroll 1
      for (int it = 0, s = 0; it < 34; it++) {
        if (it < 6) wait_q_free(bars + 8 * B_EQ, it);
        if (it == 16) mbar_wait(bars + 8 * (B_FW + 3), 0);
        mbar_wait(fb + 8 * (B_EW - B_FW), ph);
        expect_tx_elect(fb, (it == 8 || it == 18 || it == 19) ? 16384 : 32768);
        const int k0 = it < 16 ? wo_k(it, j) : (it < 20 ? 2 * j + (it & 1) : other_kb(it - 20, j)) * 64;
        if (it == 16 || it == 17) {
          tma_load_mc(st - 16384 + rank * 16384, wgu, fb, j * 448, k0);
          tma_load_mc(st - 8192 + rank * 16384, wgu, fb, j * 448 + 64, k0);
        } else {
          tma_load_mc(st + rank * 8192, it < 16 ? &p.wo : wgu, fb, it < 16 ? j * 128 + rank * 64 : j * 448 + 384, k0);
        }
        st += 32768; fb += 8;
        if (++s == 6) { s = 0; st -= 6 * 32768; fb -= 48; ph ^= 1; }
      }
      st = sm + 16384 + 3 * 49152; fb = bars + 8 * B_FG; ph = 1;
#pragma unroll 1
      for (int it = 0; it < 46; it++) {
        const int kb = it < 14 ? other_kb(it, j) : (it + 2) & 15, col = j * 448 + ((it + 2) >> 4) * 128;
        if (it < 4) wait_w_free(bars + 8 * B_EW, it);
        mbar_wait(fb + 8 * (B_EG - B_FG), ph);
        expect_tx_elect(fb, 49152);
        tma_load_mc(st + rank * 16384, wgu, fb, col, kb * 64);
        tma_load_mc(st + rank * 16384 + 8192, wgu, fb, col + 64, kb * 64);
        st += (it & 3) == 0 ? -3 * 49152 : 49152; fb += 8;
        if ((it & 3) == 3) { fb -= 32; ph ^= 1; }
      }
      st = sm + 16384 + 2 * 32768; fb = bars + 8 * B_FD; ph = 1;
#pragma unroll 1
      for (int it = 0, s = 0; it < 56 - KH; it++) {
        if (it < 6) wait_g_free(bars + 8 * B_EG, it);
        mbar_wait(fb + 8 * (B_ED - B_FD), ph);
        expect_tx_elect(fb, 32768);
        tma_load_mc(st + rank * 8192, &p.wd, fb, j * 128 + rank * 64, down_k(it));
        st += s == 3 ? -5 * 32768 : 32768; fb += 8;
        if (++s == 6) { s = 0; fb -= 48; ph ^= 1; }
      }
    } else if (warp == 1) {
      const int arow = rb * 128;
      uint32_t st = sm, fb = bars + 8 * B_FQ, ph = 0;
      cnt_wait(cnt + C_HA, target);
      PROF_AT(lane == 0, 16);
#pragma unroll 1
      for (int it = 4; it < 32; it++) {
        if (it == 11) mbar_wait(bars + 8 * (B_RDY + C_H), 0);
        mbar_wait(fb + 8 * (B_EQ - B_FQ), ph);
        tma_load(st, &p.h, fb, qkv_kb(it, j) * 64, arow);
        st += 49152; fb += 8;
        if ((it & 3) == 3) { st -= 4 * 49152; fb -= 32; ph ^= 1; }
      }
      fb = bars + 8 * B_FW; ph = 1;
#pragma unroll 1
      for (int it = 0, s = 0; it < 34; it++) {
        if (it < 16 || it >= 20) {
          if (it < 6) wait_q_free(bars + 8 * B_EQ, it);
          mbar_wait(fb + 8 * (B_EW - B_FW), ph);
          if (it == 0) mbar_wait(bars + 8 * (B_RDY + C_O), 0);
          if (it == 9 || it == 20) cnt_wait(cnt + (it == 9 ? C_O + 1 : C_H2A), target * 8);
          if (it == 27) mbar_wait(bars + 8 * (B_RDY + C_H2), 0);
          PROF_AT(lane == 0 && (it == 0 || it == 9 || it == 20), 17 + (it >> 3));
          if (it != 8) tma_load(st, it < 16 ? &p.o_ld : &p.h2, fb, it < 16 ? wo_k(it, j) : other_kb(it - 20, j) * 64, arow);
        }
        st += 32768; fb += 8;
        if (++s == 6) { s = 0; st -= 6 * 32768; fb -= 48; ph ^= 1; }
      }
      st = sm + 3 * 49152; fb = bars + 8 * B_FG; ph = 1;
#pragma unroll 1
      for (int it = 0; it < 46; it++) {
        if (it < 4) wait_w_free(bars + 8 * B_EW, it);
        mbar_wait(fb + 8 * (B_EG - B_FG), ph);
        tma_load(st, &p.h2, fb, (it < 14 ? other_kb(it, j) : (it + 2) & 15) * 64, arow);
        st += (it & 3) == 0 ? -3 * 49152 : 49152; fb += 8;
        if ((it & 3) == 3) { fb -= 32; ph ^= 1; }
      }
      st = sm + 2 * 32768; fb = bars + 8 * B_FD; ph = 1;
#pragma unroll 1
      for (int it = 0, s = 0; it < 56 - KH; it++) {
        if (it < 6) wait_g_free(bars + 8 * B_EG, it);
        mbar_wait(fb + 8 * (B_ED - B_FD), ph);
        const int u = it + KH, dep = it == 0 ? C_ACT : (u == 8 ? C_ACT + 1 : (u == 24 ? C_ACT + 2 : (u == 40 ? C_A0 : (u == 48 ? C_ACT + 3 : -1))));
        if (dep >= 0) mbar_wait(bars + 8 * (B_RDY + dep), 0);
        tma_load(st, &p.act, fb, down_k(it), arow);
        st += s == 3 ? -5 * 32768 : 32768; fb += 8;
        if (++s == 6) { s = 0; fb -= 48; ph ^= 1; }
      }
    } else if (warp == 2) {
      if (lane < 15) prefetch_map(&p.h + lane);
      __syncwarp();
      uint32_t ph1 = 0;
#pragma unroll 1
      for (int n = 0; n < 8; n++) {
        const int nch = (n == 1 || n == 2 || n == 4) ? 1 : 2;
#pragma unroll 1
        for (int ch = 0; ch < nch; ch++) {
          mbar_wait_watchdog(bars + 8 * (B_STGF + ch), ch ? ph1 : (n & 1));
          const uint32_t src = stg + ch * 16384;
          if (n == 2 || n == 3) {
          } else if (n == 1) {
#pragma unroll 1
            for (int q = 0; q < 8; q++) {
              tma_store2(&p.o_st, src + q * 2048, j * 128, rb * 128 + q * 16);
              if (q & 1) store_pause(true);
            }
          } else if (n >= 4 && n < 8) {
#pragma unroll 1
            for (int q = 0; q < 4; q++) {
              tma_store2(&p.act_st, src + q * 4096, j * 448 + (n == 4 ? 384 : (n - 5) * 128 + ch * 64), rb * 128 + q * 32);
              store_pause(true);
            }
          } else if (ch == 0) {
            tma_store2(&p.h, src, j * 128, rb * 128);
            asm volatile("cp.async.bulk.commit_group;" ::: "memory");
            asm volatile("cp.async.bulk.wait_group 0;" ::: "memory");
            __syncwarp();
            cnt_signal(cnt + C_HA);
          } else {
            __nanosleep(H1D);
#pragma unroll 1
            for (int q = 0; q < 8; q++) {
              tma_store2(&p.h_st, src + q * 2048, j * 128 + 64, rb * 128 + q * 16);
              if (q & 1) store_pause(true);
            }
          }
          if (n >= 5 && ch == 0) arrive_elect(bars + 8 * B_STGE);
          if (n == 7 && ch == 0) {
            asm volatile("cp.async.bulk.wait_group 0;" ::: "memory");
            __syncwarp();
            cnt_signal(cnt + C_A0);
          }
        }
        asm volatile("cp.async.bulk.commit_group;" ::: "memory");
        asm volatile("cp.async.bulk.wait_group 0;" ::: "memory");
        __syncwarp();
        if (n != 2 && n != 3) cnt_signal(cnt + n);
        PROF_AT(lane == 0, n == 0 ? 33 : 23 + n);
        if (n == 0) {
#pragma unroll 1
          for (int t = 0; t < 32; t++) {
            ll_store(p.halo + cta * 1024 + t * 32 + lane, 0u, 0u, 0u);
            __nanosleep(40);
          }
          __syncwarp();
        }
        if (n < 5) arrive_elect(bars + 8 * B_STGE);
        if (nch == 2) { arrive_elect(bars + 8 * (B_STGE + 1)); ph1 ^= 1; }
      }
      mbar_wait_watchdog(bars + 8 * B_STGF, 0);
      PROF_AT(lane == 0, 31);
    } else {
      if (lane < 4) ll_store(p.modll + cta * 4 + lane, 0u, 0u, 0u);
#pragma unroll 1
      for (int ch = 0; ch < 2; ch++) {
        if (ch == 0) {
          bar_sync(1, 288);
          const uint4 t4 = lds128(sm + RED_OFF + lane * 16);
          float a[4] = {__uint_as_float(t4.x), __uint_as_float(t4.y), __uint_as_float(t4.z), __uint_as_float(t4.w)};
#pragma unroll
          for (int o = 4; o < 32; o <<= 1)
#pragma unroll
            for (int q = 0; q < 4; q++) a[q] += __shfl_xor_sync(~0u, a[q], o);
          if (lane < 4) ll_store(p.modll + cta * 4 + lane, pack2(a[0], a[1]), pack2(a[2], a[3]), tag);
          PROF_AT(lane == 0, 1);
        }
        uint32_t m[2];
        const uint4* mp = p.modll + j * 32 + ch * 16 + (lane & 15) + (lane >> 4) * 256;
        ll_poll<1>([&](int) { return mp; }, tag, m);
        if (lane >> 4) { m[0] = pack2(1.0f + bf_lo(m[0]), 1.0f + bf_hi(m[0])); m[1] = pack2(1.0f + bf_lo(m[1]), 1.0f + bf_hi(m[1])); }
        const uint32_t dst = sm + MODB_OFF + ch * 256 + ((lane >> 2) & 3) * 64 + (lane & 1) * 32 + (lane & 2) * 4 + ((lane >> 4) ? 0 : 4);
        asm volatile("st.shared.u32 [%0], %1;\nst.shared.u32 [%0 + 16], %2;" ::"r"(dst), "r"(m[0]), "r"(m[1]) : "memory");
        __syncwarp();
        arrive_elect(bars + 8 * (B_MODA + ch));
      }
#pragma unroll 1
      for (int n = C_H; n <= C_O; n++) {
        cnt_wait_lazy(cnt + n, target);
        arrive_elect(bars + 8 * (B_RDY + n));
      }
      {
        uint32_t m[6];
        const uint4* src = p.modll + 512 + j * 32 + lane;
        ll_poll<3, 500>([&](int i) { return src + i * 256; }, tag, m);
#pragma unroll
        for (int vec = 0; vec < 3; vec++) {
          const float add = vec == 2 ? 1.0f : 0.0f;
          sts128(sm + MODB_OFF + (vec * 128 + lane * 4) * 4, __float_as_uint(bf_round(bf_lo(m[2 * vec]) + add)), __float_as_uint(bf_round(bf_hi(m[2 * vec]) + add)),
                 __float_as_uint(bf_round(bf_lo(m[2 * vec + 1]) + add)), __float_as_uint(bf_round(bf_hi(m[2 * vec + 1]) + add)));
        }
        __syncwarp();
        if (lane == 0) mbar_arrive(bars + 8 * B_MODB);
        PROF_AT(lane == 0, 15);
      }
      __syncwarp();
#pragma unroll 1
      for (int q = C_H2; q < 9; q++) {
        const int n = q < 7 ? q : (q == 7 ? C_A0 : C_ACT + 3);
        cnt_wait_lazy(cnt + n, n == C_H2 ? target * 8 : target);
        arrive_elect(bars + 8 * (B_RDY + n));
      }
      {
        uint32_t m[2];
        const uint4* src = p.modll + 512 + 768 + j * 32 + lane;
        ll_poll<1>([&](int) { return src; }, tag, m);
        sts128(sm + MODB_OFF + (384 + lane * 4) * 4, m[0] << 16, m[0] & 0xffff0000u, m[1] << 16, m[1] & 0xffff0000u);
        cnt_wait_lazy(cnt + C_SP + (j >> 1), target);
        __syncwarp();
        if (lane == 0) mbar_arrive(bars + 8 * (B_MODB + 1));
      }
    }
  } else {
    uint32_t tag;

    {
      const int tid = threadIdx.x - 128, cw = tid >> 7, warp = (tid >> 5) & 3, lane = tid & 31;
      const int l16 = lane & 15, half = lane >> 4, w8 = cw * 4 + warp;
      if (lane < 8) ll_store((uint4*)(gstats + (rb * 8 + j) * 128 + w8 * 16) + lane, 0u, 0u, 0u);
      const uint32_t cbuf = sm + 3 * 49152 + w8 * 512;
      if (lane < 16) cp_async16(cbuf + lane * 16, gc + w8 * 128 + lane * 8);
      asm volatile("cp.async.commit_group;" ::: "memory");
      const uint32_t xbuf = sm + 40960 + (cw * 2 + (l16 >> 3)) * 49152 + (warp * 16 + half) * 128;
      {
        const char* xp = (const char*)gx + (uint32_t)((rb * 128 + (warp * 16 + half) * 2 + cw) * 2048 + j * 256 + l16 * 16);
#pragma unroll
        for (int i = 0; i < 8; i++) cp_async16(xbuf + i * 256 + (((l16 & 7) ^ ((i * 2 + half) & 7)) << 4), xp + i * 8192);
      }
      asm volatile("cp.async.commit_group;" ::: "memory");
      const uint32_t wbuf = sm + cw * 49152 + warp * 4096;
      const bool late = j >= 4;
      auto fetch_w = [&]() {
        const char* wp = (const char*)gwmod + (uint32_t)(cta * 32 + (lane & 1) * 16 + (w8 * 128 + (lane >> 1)) * 12288);
#pragma unroll
        for (int i = 0; i < 8; i++) cp_async16(wbuf + i * 512 + lane * 16, wp + i * 16 * 12288);
      };
      if (!late) fetch_w();
      PROF_AT(tid == 0, 32);
      uint2* st1 = gstats + (rb * 8 + j) * 128 + cw * 64 + warp * 16;
      cluster_arrive_relaxed();
      asm volatile("setmaxnreg.inc.sync.aligned.u32 232;");
      uint32_t sa[4][4];
      {
        asm volatile("cp.async.wait_group 1;" ::: "memory");
        __syncwarp();
        const float2 cv = lds64f(cbuf + lane * 8);
        const uint32_t c0 = __float_as_uint(cv.x), c1 = __float_as_uint(cv.y);
        sts64f(cbuf + lane * 8, __uint_as_float(pack2(silu_f(bf_lo(c0)), silu_f(bf_hi(c0)))), __uint_as_float(pack2(silu_f(bf_lo(c1)), silu_f(bf_hi(c1)))));
        __syncwarp();
#pragma unroll
        for (int q = 0; q < 4; q++) ldmatrix4(sa[q][0], sa[q][1], sa[q][2], sa[q][3], cbuf + q * 64 + (lane >> 3) * 16);
      }
      cluster_wait();
      tag = lds32(bars + 8 * B_COUNT);
      if (late) {
        if (WLD) __nanosleep(WLD);
        fetch_w();
      }
      asm volatile("cp.async.commit_group;" ::: "memory");
      asm volatile("cp.async.wait_group 1;" ::: "memory");
      __syncwarp();
      uint32_t xl[16], xh[16];
      {
        const int srow = warp * 16 + (lane & 15);
#pragma unroll
        for (int q = 0; q < 8; q++)
          ldmatrix4(xl[2 * q], xh[2 * q], xl[2 * q + 1], xh[2 * q + 1],
                    sm + 40960 + (cw * 2 + (q >> 2)) * 49152 + srow * 128 + (((half + (q & 3) * 2) ^ (srow & 7)) << 4));
      }
      publish_stats(xl, xh, st1, lane, tag16(tag, 0));
      PROF_AT(tid == 0, 50);
      auto gemv = [&]() {
      asm volatile("cp.async.wait_group 0;" ::: "memory");
      __syncwarp();
      PROF_AT(tid == 0, 51);
      {
        uint32_t b[8][4];
#pragma unroll
        for (int ks = 0; ks < 8; ks++) ldmatrix4t(b[ks], wbuf + (ks * 16 + (lane & 15)) * 32 + (lane >> 4) * 16);
        float d0[4] = {0.f, 0.f, 0.f, 0.f}, d1[4] = {0.f, 0.f, 0.f, 0.f}, d2[4] = {0.f, 0.f, 0.f, 0.f}, d3[4] = {0.f, 0.f, 0.f, 0.f};
#pragma unroll
        for (int q = 0; q < 4; q++) {
          mma16816(d0, sa[q][0], sa[q][0], sa[q][1], sa[q][1], b[2 * q][0], b[2 * q][1]);
          mma16816(d1, sa[q][0], sa[q][0], sa[q][1], sa[q][1], b[2 * q][2], b[2 * q][3]);
          mma16816(d2, sa[q][2], sa[q][2], sa[q][3], sa[q][3], b[2 * q + 1][0], b[2 * q + 1][1]);
          mma16816(d3, sa[q][2], sa[q][2], sa[q][3], sa[q][3], b[2 * q + 1][2], b[2 * q + 1][3]);
        }
        d0[0] += d2[0]; d0[1] += d2[1]; d1[0] += d3[0]; d1[1] += d3[1];
        if (lane < 4) {
          sts64f(sm + RED_OFF + (w8 * 16 + lane * 2) * 4, d0[0], d0[1]);
          sts64f(sm + RED_OFF + (w8 * 16 + 8 + lane * 2) * 4, d1[0], d1[1]);
        }
        asm volatile("bar.arrive 1, 288;" ::: "memory");
      }
      };
      gemv();
      {
        const int c = lane & 3;
        float rs[2], nb[2];
        stat_gather(gstats + rb * 1024 + cw * 64 + warp * 16, tag16(tag, 0), lane, rs, nb);
#pragma unroll
        for (int n = 0; n < 16; n++) {
          xl[n] = pack2(bf_lo(xl[n]) * rs[0] + nb[0], bf_hi(xl[n]) * rs[0] + nb[0]);
          xh[n] = pack2(bf_lo(xh[n]) * rs[1] + nb[1], bf_hi(xh[n]) * rs[1] + nb[1]);
        }
        const int srow = warp * 16 + l16;
        const uint32_t slab = stg + cw * 8192 + srow * 128;
#pragma unroll
        for (int q = 0; q < 8; q++)
          stmatrix4(slab + (q >> 2) * 16384 + (((half + (q & 3) * 2) ^ (srow & 7)) << 4), xl[2 * q], xh[2 * q], xl[2 * q + 1], xh[2 * q + 1]);
        PROF_AT(tid == 0, 52);
        mbar_wait(bars + 8 * B_MODA, 0);
        PROF_AT(tid == 0, 2);
#pragma unroll
        for (int q = 0; q < 4; q++) {
          const uint4 mv = lds128(sm + MODB_OFF + (4 * q + c) * 16);
          const uint32_t c0 = mv.x, s0 = mv.y, c1 = mv.z, s1 = mv.w;
          stmatrix4(slab + (q >> 2) * 16384 + (((half + (q & 3) * 2) ^ (srow & 7)) << 4), fma_bf2(xl[2 * q], c0, s0), fma_bf2(xh[2 * q], c0, s0),
                    fma_bf2(xl[2 * q + 1], c1, s1), fma_bf2(xh[2 * q + 1], c1, s1));
          if ((q & 3) == 3) stage_done(bars + 8 * (B_STGF + (q >> 2)), lane);
        }
      }
      PROF_AT(tid == 0, 3);
    }

    uint32_t xl[16], xh[16];
    {
      RING_IDS();
      uint32_t prev = 0;
      float acc1[96];
      {
        Ring g{bars + 8 * B_FQ, rbars + 8 * B_EQ, 0, 0u, 0u, releaser TR(0)};
        float acc0[96];
#pragma unroll 1
        for (int kb = 0; kb < 2; kb++) {
          kblock<192, 4, 49152>(acc0, g, a_base + STG_OFF + kb * 16384, kb == 0, prev);
          kblock<192, 4, 49152>(acc1, g, a_base + STG_OFF + kb * 16384, kb == 0, prev);
          if (kb == 0) {
            LANE_IDS();
            mbar_wait(bars + 8 * (B_MODA + 1), 0);
#pragma unroll
            for (int hh = 0; hh < 2; hh++) {
              uint32_t v[2][4];
              uint4 mv[2];
#pragma unroll
              for (int q = 0; q < 2; q++) {
                ldmatrix4(v[q][0], v[q][1], v[q][2], v[q][3], slab + 16384 + ((sw0 ^ (hh * 4 + q * 2)) << 4));
                mv[q] = lds128(sm + MODB_OFF + (16 + 8 * hh + 4 * q + c) * 16);
              }
#pragma unroll
              for (int q = 0; q < 2; q++)
                stmatrix4(slab + 16384 + ((sw0 ^ (hh * 4 + q * 2)) << 4), fma_bf2(v[q][0], mv[q].x, mv[q].y), fma_bf2(v[q][1], mv[q].x, mv[q].y),
                          fma_bf2(v[q][2], mv[q].z, mv[q].w), fma_bf2(v[q][3], mv[q].z, mv[q].w));
            }
            stage_done(bars + 8 * (B_STGF + 1), lane);
          }
        }
#pragma unroll 1
        for (int kb = 0; kb < 14; kb++) kblock<192, 4, 49152>(acc0, g, a_base + g.off, false, prev);
        PROF_AT(tid == 0, 4);
        attention<NPRE0, false>(acc0, p, 0, rb, cta, cw, warp, tag, stg, bars, prev, [&]() { kblock<192, 4, 49152>(acc1, g, a_base + g.off, false, prev); });
        PROF_AT(tid == 0, 5);
        {
          LANE_IDS();
#pragma unroll
          for (int q = 0; q < 8; q++)
            ldmatrix4(xl[2 * q], xh[2 * q], xl[2 * q + 1], xh[2 * q + 1], sm + 40960 + (cw * 2 + (q >> 2)) * 49152 + srow * 128 + ((sw0 ^ ((q & 3) * 2)) << 4));
#pragma unroll
          for (int q = 0; q < 16; q++) asm volatile("" : "+r"(xl[q]), "+r"(xh[q])::"memory");
        }
#pragma unroll 1
        for (int kb = 5 + NPRE0; kb < 14; kb++) kblock<192, 4, 49152>(acc1, g, a_base + g.off, false, prev);
        PROF_AT(tid == 0, 6);
      }
      float acc[64];
      Ring g{bars + 8 * B_FW, rbars + 8 * B_EW, 0, 0u, 0u, releaser TR(32)};
      attention<NPRE1, true>(acc1, p, 1, rb, cta, cw, warp, tag, stg, bars, prev, [&]() { kblock<128, 6, 32768>(acc, g, a_base + g.off, g.s == 0, prev); });
      PROF_AT(tid == 0, 7);
      LANE_IDS();
      unsigned* cnt = p.cnt + rb * 32;
      tma_store2(&p.o_st, stg + cw * 8192 + warp * 2048, j * 128 + 64, rb * 128 + cw * 64 + warp * 16);
      asm volatile("cp.async.bulk.commit_group;" ::: "memory");
#pragma unroll 1
      for (int kb = 1 + NPRE1; kb < 16; kb++) {
        if (kb == 8) wg_bar(cw);
        kblock<128, 6, 32768>(acc, g, a_base + (kb == 8 ? STG_OFF : g.off), false, prev);
        if (kb == 3 + NPRE1) {
          asm volatile("cp.async.bulk.wait_group 0;" ::: "memory");
          __syncwarp();
          cnt_signal(cnt + C_O + 1);
        }
      }
      mbar_wait(bars + 8 * B_STGE, 0);
      mbar_wait(bars + 8 * B_MODB, 0);
      float2 ga[16];
#pragma unroll
      for (int n = 0; n < 16; n++) ga[n] = lds64f(sm + MODB_OFF + (8 * n + 2 * c) * 4);
      tile_end(acc, prev);
      PROF_AT(tid == 0, 8);
#pragma unroll
      for (int n = 0; n < 16; n++) {
        acc[4 * n] = ga[n].x * acc[4 * n] + bf_lo(xl[n]); acc[4 * n + 1] = ga[n].y * acc[4 * n + 1] + bf_hi(xl[n]);
        acc[4 * n + 2] = ga[n].x * acc[4 * n + 2] + bf_lo(xh[n]); acc[4 * n + 3] = ga[n].y * acc[4 * n + 3] + bf_hi(xh[n]);
        xl[n] = pack2(acc[4 * n], acc[4 * n + 1]);
        xh[n] = pack2(acc[4 * n + 2], acc[4 * n + 3]);
      }
      publish_stats(xl, xh, gstats + (rb * 8 + j) * 128 + cw * 64 + warp * 16, lane, tag16(tag, 1));
      PROF_AT(tid == 0, 48);
      float2 sb[16], cb[16];
#pragma unroll
      for (int n = 0; n < 16; n++) {
        sb[n] = lds64f(sm + MODB_OFF + (128 + 8 * n + 2 * c) * 4);
        cb[n] = lds64f(sm + MODB_OFF + (256 + 8 * n + 2 * c) * 4);
      }
      PROF_AT(tid == 0, 49);
      float nb[2], rstd[2];
      stat_gather(gstats + rb * 1024 + cw * 64 + warp * 16, tag16(tag, 1), lane, rstd, nb);
      PROF_AT(tid == 0, 9);
#pragma unroll
      for (int ch = 0; ch < 2; ch++) {
        uint32_t lo[8], hi[8];
#pragma unroll
        for (int t = 0; t < 8; t++) {
          const int n = ch * 8 + t;
          lo[t] = pack2((acc[4 * n] * rstd[0] + nb[0]) * cb[n].x + sb[n].x, (acc[4 * n + 1] * rstd[0] + nb[0]) * cb[n].y + sb[n].y);
          hi[t] = pack2((acc[4 * n + 2] * rstd[1] + nb[1]) * cb[n].x + sb[n].x, (acc[4 * n + 3] * rstd[1] + nb[1]) * cb[n].y + sb[n].y);
        }
        stage_slab(sm + ch * 32768 + cw * 8192, warp, lane, lo, hi);
        stage_done(bars + 8 * (B_STGF + ch), lane);
        tma_store2(&p.h2_st, sm + ch * 32768 + cw * 8192 + warp * 2048, j * 128 + ch * 64, rb * 128 + cw * 64 + warp * 16);
        asm volatile("cp.async.bulk.commit_group;" ::: "memory");
      }
      PROF_AT(tid == 0, 10);
    }

    uint32_t pg[32], pu[32];
    {
      RING_IDS();
      float acc[128];
      uint32_t prev = 0;
      Ring g{bars + 8 * B_FG, rbars + 8 * B_EG, 0, 0u, 3 * 49152u, releaser TR(66)};
      {
        Ring w{bars + 8 * B_FW, rbars + 8 * B_EW, 4, 0u, 4 * 32768u, releaser TR(48)};
        float acn[64];
#pragma unroll 1
        for (int kb = 0; kb < 2; kb++) {
          kblock<256, 6, 32768>(acc, w, a_base + kb * 32768, kb == 0, prev, 0u);
          if (kb == 0) asm volatile("cp.async.bulk.wait_group 1;" ::: "memory");
          else asm volatile("cp.async.bulk.wait_group 0;" ::: "memory");
          __syncwarp();
          cnt_signal(p.cnt + rb * 32 + (kb == 0 ? C_H2A : C_H2));
        }
        {
          LANE_IDS();
#pragma unroll
          for (int q = 0; q < 8; q++)
            stmatrix4(slab + (q >> 2) * 16384 + ((sw0 ^ ((q & 3) * 2)) << 4), xl[2 * q], xh[2 * q], xl[2 * q + 1], xh[2 * q + 1]);
          __syncwarp();
        }
#pragma unroll 1
        for (int kb = 0; kb < 16; kb++) {
          kblock<128, 6, 32768>(acn, w, a_base + w.off, kb == 0, prev);
          if (kb == 4) {
            asm volatile("fence.proxy.async.shared::cta;" ::: "memory");
            __syncwarp();
          }
          if (kb == 6 + warp || kb == 10 + warp) {
            const int ch = kb != 6 + warp;
            tma_store3(&p.out, stg + ch * 16384 + cw * 8192 + warp * 2048, j * 128 + ch * 64, rb * 64 + warp * 16, cw);
            asm volatile("cp.async.bulk.commit_group;" ::: "memory");
          }
        }
        PROF_AT(tid == 0, 39);
        kblock<256, 4, 49152>(acc, g, a_base + g.off, false, prev);
        fence_regs(acn);
#pragma unroll
        for (int q = 0; q < 16; q++) {
          pg[q] = pack2(acn[2 * q], acn[2 * q + 1]);
          pu[q] = pack2(acn[32 + 2 * q], acn[32 + 2 * q + 1]);
          pg[16 + q] = 0; pu[16 + q] = 0;
        }
        asm volatile("cp.async.bulk.wait_group 0;" ::: "memory");
        kblock<256, 4, 49152>(acc, g, a_base + g.off, false, prev);
      }
      LANE_IDS();
#pragma unroll 1
      for (int t = 0; t < 3; t++) {
#pragma unroll 1
        for (int blk = 0; blk < (t == 0 ? 2 : 4); blk++) {
          g.s = 2;
#pragma unroll
          for (int i = 0; i < 4; i++) {
            g.off = ((i + 1) & 3) * 49152;
            if (i == 3 && blk == 3) skew_pre(cw);
            kblock<256, 4, 49152>(acc, g, a_base + g.off, t > 0 && blk == 0 && i == 0, prev);
            if (i == 3 && blk == 3) skew_post(cw);
            if ((blk & 1) == 0 && i == 0) mbar_wait(bars + 8 * (B_STGE + (blk >> 1)), (t + 1 + (blk >> 1)) & 1);
            stmatrix2(slab + (blk >> 1) * 16384 + (((srow & 7) ^ ((blk & 1) * 4 + i)) << 4), swiglu2(pg[2 * i], pu[2 * i]), swiglu2(pg[2 * i + 1], pu[2 * i + 1]));
          }
#pragma unroll
          for (int q = 0; q < 24; q++) { pg[q] = pg[q + 8]; pu[q] = pu[q + 8]; }
          if (blk & 1) stage_done(bars + 8 * (B_STGF + (blk >> 1)), lane);
        }
#pragma unroll 1
        for (int kb = t == 0 ? 0 : 4; kb < 4; kb++) {
          if (kb == 3) skew_pre(cw);
          kblock<256, 4, 49152>(acc, g, a_base + g.off, false, prev);
          if (kb == 3) skew_post(cw);
        }
        tile_end(acc, prev);
        PROF_AT(tid == 0, 36 + t);
#pragma unroll
        for (int q = 0; q < 32; q++) {
          pg[q] = pack2(acc[2 * q], acc[2 * q + 1]);
          pu[q] = pack2(acc[64 + 2 * q], acc[64 + 2 * q + 1]);
        }
      }
      PROF_AT(tid == 0, 11);
    }

    {
      RING_IDS();
      LANE_IDS();
      Ring g{bars + 8 * B_FD, rbars + 8 * B_ED, 0, 0u, 2 * 32768u, releaser TR(112)};
      float acc[64];
      uint32_t prev = 0;
#pragma unroll 1
      for (int blk = 0; blk < 4; blk++) {
#pragma unroll
        for (int i = 0; i < 8; i++) {
          kblock<128, 6, 32768>(acc, g, a_base + g.off, blk == 0 && i == 0, prev);
          if ((blk & 1) == 0 && i == 0) mbar_wait(bars + 8 * (B_STGE + (blk >> 1)), blk >> 1);
          stmatrix1(slab + (blk >> 1) * 16384 + (i & 1) * 1024 + (((srow & 7) ^ ((blk & 1) * 4 + (i >> 1))) << 4), swiglu2(pg[i], pu[i]));
        }
#pragma unroll
        for (int q = 0; q < 24; q++) { pg[q] = pg[q + 8]; pu[q] = pu[q + 8]; }
        if (blk & 1) stage_done(bars + 8 * (B_STGF + (blk >> 1)), lane);
      }
#pragma unroll 1
      for (int kb = 32; kb < 56 - KH; kb++) {
        if (kb == 50 - KH) g.releaser = false;
        if (kb == 52 - KH) skew_pre(cw);
        kblock<128, 6, 32768>(acc, g, a_base + g.off, false, prev);
      }
      skew_post(cw);
      mbar_wait(bars + 8 * (B_MODB + 1), 0);
      mbar_wait(bars + 8 * B_STGE, 1);
      mbar_wait(bars + 8 * (B_STGE + 1), 0);
      float2 gbv[16];
#pragma unroll
      for (int n = 0; n < 16; n++) gbv[n] = lds64f(sm + MODB_OFF + (384 + 8 * n + 2 * c) * 4);
      tile_end(acc, prev);
      PROF_AT(tid == 0, 13);
#pragma unroll
      for (int ch = 0; ch < 2; ch++) {
        uint32_t lo[8], hi[8];
#pragma unroll
        for (int t = 0; t < 8; t++) {
          const int n = ch * 8 + t;
          const float2 gb = gbv[n];
          lo[t] = pack2(gb.x * acc[4 * n], gb.y * acc[4 * n + 1]);
          hi[t] = pack2(gb.x * acc[4 * n + 2], gb.y * acc[4 * n + 3]);
        }
        stage_slab(stg + ch * 16384 + cw * 8192, warp, lane, lo, hi);
        asm volatile("fence.proxy.async.shared::cta;" ::: "memory");
        __syncwarp();
        tma_add3(&p.out, stg + ch * 16384 + cw * 8192 + warp * 2048, j * 128 + ch * 64, rb * 64 + warp * 16, cw);
      }
      asm volatile("cp.async.bulk.commit_group;" ::: "memory");
      if (lane == 0) mbar_arrive(bars + 8 * B_STGF);
      asm volatile("cp.async.bulk.wait_group.read 0;" ::: "memory");
      PROF_AT(tid == 0, 14);
    }
    if (blockIdx.x == 0 && threadIdx.x == 128) asm volatile("st.relaxed.gpu.global.u32 [%0], %1;" ::"l"(gepoch), "r"(tag) : "memory");
  }
}

typedef CUresult (*EncodeFn)(CUtensorMap*, CUtensorMapDataType, cuuint32_t, void*, const cuuint64_t*, const cuuint64_t*,
                             const cuuint32_t*, const cuuint32_t*, CUtensorMapInterleave, CUtensorMapSwizzle,
                             CUtensorMapL2promotion, CUtensorMapFloatOOBfill);

void encode2d(EncodeFn fn, CUtensorMap* m, const void* ptr, uint64_t cols, uint64_t rows, uint32_t box_rows) {
  cuuint64_t dims[2] = {cols, rows};
  cuuint64_t strides[1] = {cols * 2};
  cuuint32_t box[2] = {64, box_rows};
  cuuint32_t es[2] = {1, 1};
  fn(m, CU_TENSOR_MAP_DATA_TYPE_BFLOAT16, 2, (void*)ptr, dims, strides, box, es, CU_TENSOR_MAP_INTERLEAVE_NONE,
     CU_TENSOR_MAP_SWIZZLE_128B, CU_TENSOR_MAP_L2_PROMOTION_L2_128B, CU_TENSOR_MAP_FLOAT_OOB_FILL_NONE);
}

}

extern "C" void kernel_launch(void* const* d_in, const int* in_sizes, int n_in, void* d_out, int out_size) {
  (void)in_sizes; (void)n_in; (void)out_size;
  void* fp = nullptr;
  cudaDriverEntryPointQueryResult qr;
  cudaGetDriverEntryPoint("cuTensorMapEncodeTiled", &fp, cudaEnableDefault, &qr);
  EncodeFn fn = (EncodeFn)fp;
  void *ph, *po, *ph2, *pact;
  cudaGetSymbolAddress(&ph, g_h);
  cudaGetSymbolAddress(&po, g_o);
  ph2 = ph;
  cudaGetSymbolAddress(&pact, g_act);
  Params p;
  encode2d(fn, &p.h, ph, DM, SEQ, 128);
  encode2d(fn, &p.o_ld, po, DM, SEQ, 128);
  encode2d(fn, &p.h2, ph2, DM, SEQ, 128);
  encode2d(fn, &p.act, pact, FF, SEQ, 128);
  encode2d(fn, &p.act_st, pact, FF, SEQ, 32);
  encode2d(fn, &p.wm, d_in[8], 6 * DM, DM, 64);
  encode2d(fn, &p.o_st, po, DM, SEQ, 16);
  encode2d(fn, &p.h2_st, ph2, DM, SEQ, 16);
  encode2d(fn, &p.h_st, ph, DM, SEQ, 16);
  encode2d(fn, &p.wqkv, d_in[1], 3 * DM, DM, 64);
  encode2d(fn, &p.wqkv32, d_in[1], 3 * DM, DM, 32);
  encode2d(fn, &p.wo, d_in[2], DM, DM, 64);
  encode2d(fn, &p.wg, d_in[4], FF, DM, 64);
  encode2d(fn, &p.wu, d_in[5], FF, DM, 64);
  encode2d(fn, &p.wd, d_in[6], DM, FF, 64);
  {
    cuuint64_t dims[3] = {DM, SEQ / 2, 2};
    cuuint64_t strides[2] = {DM * 4, DM * 2};
    cuuint32_t box[3] = {64, 16, 1};
    cuuint32_t es[3] = {1, 1, 1};
    fn(&p.out, CU_TENSOR_MAP_DATA_TYPE_BFLOAT16, 3, d_out, dims, strides, box, es, CU_TENSOR_MAP_INTERLEAVE_NONE,
       CU_TENSOR_MAP_SWIZZLE_128B, CU_TENSOR_MAP_L2_PROMOTION_L2_128B, CU_TENSOR_MAP_FLOAT_OOB_FILL_NONE);
  }
  void* q;
  cudaGetSymbolAddress(&q, g_modll); p.modll = (uint4*)q;
  cudaGetSymbolAddress(&q, g_halo); p.halo = (uint4*)q;
  cudaGetSymbolAddress(&q, g_stats); uint2* stats = (uint2*)q;
  cudaGetSymbolAddress(&q, g_cnt); p.cnt = (unsigned*)q;
  cudaGetSymbolAddress(&q, g_epoch); unsigned* epoch = (unsigned*)q;

  cudaFuncSetAttribute(fused_kernel, cudaFuncAttributeMaxDynamicSharedMemorySize, SMEM_BYTES);
  cudaLaunchConfig_t cfg = {};
  cfg.gridDim = dim3(NCTA + 4);
  cfg.blockDim = dim3(384);
  cfg.dynamicSmemBytes = SMEM_BYTES;
  cfg.stream = cudaStreamPerThread;
  cudaLaunchAttribute at[1];
  at[0].id = cudaLaunchAttributeClusterDimension;
  at[0].val.clusterDim.x = 2; at[0].val.clusterDim.y = 1; at[0].val.clusterDim.z = 1;
  cfg.attrs = at;
  cfg.numAttrs = 1;
  cudaLaunchKernelEx(&cfg, fused_kernel, (const bf16*)d_in[0], (const bf16*)d_in[8], (const bf16*)d_in[7], epoch, stats, p);
}
```

```cpp
#include <cuda_runtime.h>
#include <cuda_bf16.h>
#include <cuda.h>
#include <stdint.h>

typedef __nv_bfloat16 bf16;

#define PAUSE 200
#define WMDELAY 500
#define BDELAY 1500
#define NPRE0 3
#define NPRE1 1
#define ALIAS 1
#define PFW 8000
#define KH 3

#define WLD 200
#define H1D 500

__device__ __forceinline__ void wgmma_ss_n128(float (&d)[64], uint32_t da, uint32_t db, int scale_d) {
  asm volatile("{\n.reg .pred p;\n.reg .b64 da, db;\nsetp.ne.b32 p, %66, 0;\n"
    "mov.b64 da, {%64, 0x40000040};\nmov.b64 db, {%65, 0x40000040};\n"
    "wgmma.mma_async.sync.aligned.m64n128k16.f32.bf16.bf16 "
    "{%0, %1, %2, %3, %4, %5, %6, %7, %8, %9, %10, %11, %12, %13, %14, %15, "
    "%16, %17, %18, %19, %20, %21, %22, %23, %24, %25, %26, %27, %28, %29, %30, %31, "
    "%32, %33, %34, %35, %36, %37, %38, %39, %40, %41, %42, %43, %44, %45, %46, %47, "
    "%48, %49, %50, %51, %52, %53, %54, %55, %56, %57, %58, %59, %60, %61, %62, %63}, "
    "da, db, p, 1, 1, 0, 1;\n}\n"
    : "+f"(d[0]), "+f"(d[1]), "+f"(d[2]), "+f"(d[3]), "+f"(d[4]), "+f"(d[5]), "+f"(d[6]), "+f"(d[7]),
      "+f"(d[8]), "+f"(d[9]), "+f"(d[10]), "+f"(d[11]), "+f"(d[12]), "+f"(d[13]), "+f"(d[14]), "+f"(d[15]),
      "+f"(d[16]), "+f"(d[17]), "+f"(d[18]), "+f"(d[19]), "+f"(d[20]), "+f"(d[21]), "+f"(d[22]), "+f"(d[23]),
      "+f"(d[24]), "+f"(d[25]), "+f"(d[26]), "+f"(d[27]), "+f"(d[28]), "+f"(d[29]), "+f"(d[30]), "+f"(d[31]),
      "+f"(d[32]), "+f"(d[33]), "+f"(d[34]), "+f"(d[35]), "+f"(d[36]), "+f"(d[37]), "+f"(d[38]), "+f"(d[39]),
      "+f"(d[40]), "+f"(d[41]), "+f"(d[42]), "+f"(d[43]), "+f"(d[44]), "+f"(d[45]), "+f"(d[46]), "+f"(d[47]),
      "+f"(d[48]), "+f"(d[49]), "+f"(d[50]), "+f"(d[51]), "+f"(d[52]), "+f"(d[53]), "+f"(d[54]), "+f"(d[55]),
      "+f"(d[56]), "+f"(d[57]), "+f"(d[58]), "+f"(d[59]), "+f"(d[60]), "+f"(d[61]), "+f"(d[62]), "+f"(d[63])
    : "r"(da), "r"(db), "r"(scale_d));
}

__device__ __forceinline__ void wgmma_ss_n192(float (&d)[96], uint32_t da, uint32_t db, int scale_d) {
  asm volatile("{\n.reg .pred p;\n.reg .b64 da, db;\nsetp.ne.b32 p, %98, 0;\n"
    "mov.b64 da, {%96, 0x40000040};\nmov.b64 db, {%97, 0x40000040};\n"
    "wgmma.mma_async.sync.aligned.m64n192k16.f32.bf16.bf16 "
    "{%0, %1, %2, %3, %4, %5, %6, %7, %8, %9, %10, %11, %12, %13, %14, %15, "
    "%16, %17, %18, %19, %20, %21, %22, %23, %24, %25, %26, %27, %28, %29, %30, %31, "
    "%32, %33, %34, %35, %36, %37, %38, %39, %40, %41, %42, %43, %44, %45, %46, %47, "
    "%48, %49, %50, %51, %52, %53, %54, %55, %56, %57, %58, %59, %60, %61, %62, %63, "
    "%64, %65, %66, %67, %68, %69, %70, %71, %72, %73, %74, %75, %76, %77, %78, %79, "
    "%80, %81, %82, %83, %84, %85, %86, %87, %88, %89, %90, %91, %92, %93, %94, %95}, "
    "da, db, p, 1, 1, 0, 1;\n}\n"
    : "+f"(d[0]), "+f"(d[1]), "+f"(d[2]), "+f"(d[3]), "+f"(d[4]), "+f"(d[5]), "+f"(d[6]), "+f"(d[7]),
      "+f"(d[8]), "+f"(d[9]), "+f"(d[10]), "+f"(d[11]), "+f"(d[12]), "+f"(d[13]), "+f"(d[14]), "+f"(d[15]),
      "+f"(d[16]), "+f"(d[17]), "+f"(d[18]), "+f"(d[19]), "+f"(d[20]), "+f"(d[21]), "+f"(d[22]), "+f"(d[23]),
      "+f"(d[24]), "+f"(d[25]), "+f"(d[26]), "+f"(d[27]), "+f"(d[28]), "+f"(d[29]), "+f"(d[30]), "+f"(d[31]),
      "+f"(d[32]), "+f"(d[33]), "+f"(d[34]), "+f"(d[35]), "+f"(d[36]), "+f"(d[37]), "+f"(d[38]), "+f"(d[39]),
      "+f"(d[40]), "+f"(d[41]), "+f"(d[42]), "+f"(d[43]), "+f"(d[44]), "+f"(d[45]), "+f"(d[46]), "+f"(d[47]),
      "+f"(d[48]), "+f"(d[49]), "+f"(d[50]), "+f"(d[51]), "+f"(d[52]), "+f"(d[53]), "+f"(d[54]), "+f"(d[55]),
      "+f"(d[56]), "+f"(d[57]), "+f"(d[58]), "+f"(d[59]), "+f"(d[60]), "+f"(d[61]), "+f"(d[62]), "+f"(d[63]),
      "+f"(d[64]), "+f"(d[65]), "+f"(d[66]), "+f"(d[67]), "+f"(d[68]), "+f"(d[69]), "+f"(d[70]), "+f"(d[71]),
      "+f"(d[72]), "+f"(d[73]), "+f"(d[74]), "+f"(d[75]), "+f"(d[76]), "+f"(d[77]), "+f"(d[78]), "+f"(d[79]),
      "+f"(d[80]), "+f"(d[81]), "+f"(d[82]), "+f"(d[83]), "+f"(d[84]), "+f"(d[85]), "+f"(d[86]), "+f"(d[87]),
      "+f"(d[88]), "+f"(d[89]), "+f"(d[90]), "+f"(d[91]), "+f"(d[92]), "+f"(d[93]), "+f"(d[94]), "+f"(d[95])
    : "r"(da), "r"(db), "r"(scale_d));
}

__device__ __forceinline__ void wgmma_ss_n256(float (&d)[128], uint32_t da, uint32_t db, int scale_d) {
  asm volatile("{\n.reg .pred p;\n.reg .b64 da, db;\nsetp.ne.b32 p, %130, 0;\n"
    "mov.b64 da, {%128, 0x40000040};\nmov.b64 db, {%129, 0x40000040};\n"
    "wgmma.mma_async.sync.aligned.m64n256k16.f32.bf16.bf16 "
    "{%0, %1, %2, %3, %4, %5, %6, %7, %8, %9, %10, %11, %12, %13, %14, %15, "
    "%16, %17, %18, %19, %20, %21, %22, %23, %24, %25, %26, %27, %28, %29, %30, %31, "
    "%32, %33, %34, %35, %36, %37, %38, %39, %40, %41, %42, %43, %44, %45, %46, %47, "
    "%48, %49, %50, %51, %52, %53, %54, %55, %56, %57, %58, %59, %60, %61, %62, %63, "
    "%64, %65, %66, %67, %68, %69, %70, %71, %72, %73, %74, %75, %76, %77, %78, %79, "
    "%80, %81, %82, %83, %84, %85, %86, %87, %88, %89, %90, %91, %92, %93, %94, %95, "
    "%96, %97, %98, %99, %100, %101, %102, %103, %104, %105, %106, %107, %108, %109, %110, %111, "
    "%112, %113, %114, %115, %116, %117, %118, %119, %120, %121, %122, %123, %124, %125, %126, %127}, "
    "da, db, p, 1, 1, 0, 1;\n}\n"
    : "+f"(d[0]), "+f"(d[1]), "+f"(d[2]), "+f"(d[3]), "+f"(d[4]), "+f"(d[5]), "+f"(d[6]), "+f"(d[7]),
      "+f"(d[8]), "+f"(d[9]), "+f"(d[10]), "+f"(d[11]), "+f"(d[12]), "+f"(d[13]), "+f"(d[14]), "+f"(d[15]),
      "+f"(d[16]), "+f"(d[17]), "+f"(d[18]), "+f"(d[19]), "+f"(d[20]), "+f"(d[21]), "+f"(d[22]), "+f"(d[23]),
      "+f"(d[24]), "+f"(d[25]), "+f"(d[26]), "+f"(d[27]), "+f"(d[28]), "+f"(d[29]), "+f"(d[30]), "+f"(d[31]),
      "+f"(d[32]), "+f"(d[33]), "+f"(d[34]), "+f"(d[35]), "+f"(d[36]), "+f"(d[37]), "+f"(d[38]), "+f"(d[39]),
      "+f"(d[40]), "+f"(d[41]), "+f"(d[42]), "+f"(d[43]), "+f"(d[44]), "+f"(d[45]), "+f"(d[46]), "+f"(d[47]),
      "+f"(d[48]), "+f"(d[49]), "+f"(d[50]), "+f"(d[51]), "+f"(d[52]), "+f"(d[53]), "+f"(d[54]), "+f"(d[55]),
      "+f"(d[56]), "+f"(d[57]), "+f"(d[58]), "+f"(d[59]), "+f"(d[60]), "+f"(d[61]), "+f"(d[62]), "+f"(d[63]),
      "+f"(d[64]), "+f"(d[65]), "+f"(d[66]), "+f"(d[67]), "+f"(d[68]), "+f"(d[69]), "+f"(d[70]), "+f"(d[71]),
      "+f"(d[72]), "+f"(d[73]), "+f"(d[74]), "+f"(d[75]), "+f"(d[76]), "+f"(d[77]), "+f"(d[78]), "+f"(d[79]),
      "+f"(d[80]), "+f"(d[81]), "+f"(d[82]), "+f"(d[83]), "+f"(d[84]), "+f"(d[85]), "+f"(d[86]), "+f"(d[87]),
      "+f"(d[88]), "+f"(d[89]), "+f"(d[90]), "+f"(d[91]), "+f"(d[92]), "+f"(d[93]), "+f"(d[94]), "+f"(d[95]),
      "+f"(d[96]), "+f"(d[97]), "+f"(d[98]), "+f"(d[99]), "+f"(d[100]), "+f"(d[101]), "+f"(d[102]), "+f"(d[103]),
      "+f"(d[104]), "+f"(d[105]), "+f"(d[106]), "+f"(d[107]), "+f"(d[108]), "+f"(d[109]), "+f"(d[110]), "+f"(d[111]),
      "+f"(d[112]), "+f"(d[113]), "+f"(d[114]), "+f"(d[115]), "+f"(d[116]), "+f"(d[117]), "+f"(d[118]), "+f"(d[119]),
      "+f"(d[120]), "+f"(d[121]), "+f"(d[122]), "+f"(d[123]), "+f"(d[124]), "+f"(d[125]), "+f"(d[126]), "+f"(d[127])
    : "r"(da), "r"(db), "r"(scale_d));
}

namespace {

constexpr int SEQ = 2048, DM = 1024, FF = 3584;
constexpr int NCTA = 128;

constexpr uint32_t STG_OFF = 196608;
constexpr uint32_t MISC_OFF = STG_OFF + 32768;
constexpr uint32_t SMEM_BYTES = MISC_OFF + 3072;
constexpr uint32_t RED_OFF = 2 * 49152;
constexpr uint32_t MODB_OFF = MISC_OFF + 512;

enum { B_FQ = 0, B_EQ = 4, B_FW = 8, B_EW = 14, B_FG = 20, B_EG = 24, B_FD = 28, B_ED = 34,
       B_STGF = 40, B_MODB = 42, B_MODA = 44, B_RDY = 46, B_STGE = 58, B_COUNT = 60 };
enum { C_H = 0, C_O = 1, C_H2 = 3, C_ACT = 4, C_HA = 8, C_H2A = 9, C_A0 = 10, C_SP = 12 };

struct Params {
  uint4* modll;
  uint4* halo;
  unsigned* cnt;
  CUtensorMap h, o_ld, o_st, h2, act, out, wqkv, wqkv32, wo, wg, wu, wd, act_st, h2_st, h_st, wm;
};

__device__ __align__(1024) bf16 g_h[SEQ * DM];
__device__ __align__(1024) bf16 g_o[SEQ * DM];
__device__ __align__(1024) bf16 g_act[SEQ * FF];
__device__ __align__(1024) uint4 g_modll[3072 / 2];
__device__ __align__(1024) uint4 g_halo[16 * 8 * 2 * 2 * 8 * 32];
__device__ __align__(1024) uint2 g_stats[SEQ * 8];
__device__ __align__(1024) unsigned g_cnt[16 * 32];
__device__ uint4 g_epoch;
#define TR(off)

__device__ __forceinline__ uint32_t smem_u32(const void* p) { return (uint32_t)__cvta_generic_to_shared(p); }
__device__ __forceinline__ void mbar_init(uint32_t bar, uint32_t count) {
  asm volatile("mbarrier.init.shared::cta.b64 [%0], %1;" ::"r"(bar), "r"(count));
}
__device__ __forceinline__ void mbar_arrive(uint32_t bar) {
  asm volatile("mbarrier.arrive.shared::cta.b64 _, [%0];" ::"r"(bar) : "memory");
}
__device__ __forceinline__ void mbar_arrive_cluster(uint32_t cluster_addr) {
  asm volatile("mbarrier.arrive.shared::cluster.b64 _, [%0];" ::"r"(cluster_addr) : "memory");
}
__device__ __forceinline__ uint32_t mapa(uint32_t addr, uint32_t cta) {
  uint32_t r;
  asm volatile("mapa.shared::cluster.u32 %0, %1, %2;" : "=r"(r) : "r"(addr), "r"(cta));
  return r;
}
__device__ __forceinline__ void jitter() {}
__device__ __forceinline__ void mbar_wait(uint32_t bar, uint32_t parity) {
  jitter();
  asm volatile(
      "{\n.reg .pred p;\n"
      "WAIT_%=:\n"
      "mbarrier.try_wait.parity.shared::cta.b64 p, [%0], %1;\n"
      "@!p bra WAIT_%=;\n}\n" ::"r"(bar), "r"(parity) : "memory");
}
__device__ __forceinline__ void mbar_wait_watchdog(uint32_t bar, uint32_t parity) {
  jitter();
  asm volatile(
      "{\n.reg .pred p;\n.reg .u64 t0, t1;\nmov.u64 t0, %%globaltimer;\n"
      "WAIT_%=:\n"
      "mbarrier.try_wait.parity.shared::cta.b64 p, [%0], %1;\n"
      "@p bra DONE_%=;\n"
      "mov.u64 t1, %%globaltimer;\n"
      "sub.u64 t1, t1, t0;\n"
      "setp.lt.u64 p, t1, 2000000000;\n"
      "@p bra WAIT_%=;\n"
      "trap;\n"
      "DONE_%=:\n}\n" ::"r"(bar), "r"(parity) : "memory");
}
__device__ __forceinline__ void cnt_wait(const unsigned* p, unsigned target) {
  asm volatile(
      "{\n.reg .pred p;\n.reg .u32 v;\n.reg .s32 d;\n"
      "WAIT_%=:\n"
      "ld.relaxed.gpu.global.u32 v, [%0];\n"
      "sub.s32 d, v, %1;\n"
      "setp.lt.s32 p, d, 0;\n"
      "@p bra WAIT_%=;\n"
      "fence.proxy.async.global;\n"
      "}\n" ::"l"(p), "r"(target) : "memory");
}
__device__ __forceinline__ void cnt_wait_lazy(const unsigned* p, unsigned target) {
  asm volatile(
      "{\n.reg .pred p;\n.reg .u32 v;\n.reg .s32 d;\n"
      "WAIT_%=:\n"
      "nanosleep.u32 400;\n"
      "ld.relaxed.gpu.global.u32 v, [%0];\n"
      "sub.s32 d, v, %1;\n"
      "setp.lt.s32 p, d, 0;\n"
      "@p bra WAIT_%=;\n"
      "fence.proxy.async.global;\n"
      "}\n" ::"l"(p), "r"(target) : "memory");
}
__device__ __forceinline__ void cnt_signal(unsigned* p) {
  jitter();
  asm volatile("{\n.reg .pred p;\nelect.sync _|p, 0xffffffff;\n@p red.relaxed.gpu.global.add.u32 [%0], 1;\n}\n" ::"l"(p) : "memory");
}
__device__ __forceinline__ void ll_store(uint4* p, uint32_t a, uint32_t b, uint32_t tag) {
  asm volatile("st.relaxed.gpu.global.v2.b64 [%0], {%1, %2};" ::"l"(p), "l"((uint64_t)a | ((uint64_t)tag << 32)),
               "l"((uint64_t)b | ((uint64_t)tag << 32)) : "memory");
}
__device__ __forceinline__ uint4 ll_peek(const uint4* p) {
  uint4 v;
  asm volatile("ld.relaxed.gpu.global.v4.u32 {%0, %1, %2, %3}, [%4];" : "=r"(v.x), "=r"(v.y), "=r"(v.z), "=r"(v.w) : "l"(p) : "memory");
  return v;
}
template <int N, int SLEEP = 0, class F>
__device__ __forceinline__ void ll_poll(F addr, uint32_t tag, uint32_t (&out)[2 * N]) {
  for (;;) {
    uint4 v[N];
#pragma unroll
    for (int i = 0; i < N; i++) v[i] = ll_peek(addr(i));
    uint32_t bad = 0;
#pragma unroll
    for (int i = 0; i < N; i++) {
      bad |= (v[i].y ^ tag) | (v[i].w ^ tag);
      out[2 * i] = v[i].x;
      out[2 * i + 1] = v[i].z;
    }
    if (__all_sync(~0u, bad == 0)) break;
    if (SLEEP) __nanosleep(SLEEP);
  }
}
constexpr uint64_t POLICY_EVICT_FIRST = 0x12F0000000000000ull;
__device__ __forceinline__ void expect_tx_elect(uint32_t bar, uint32_t bytes) {
  asm volatile("{\n.reg .pred p;\nelect.sync _|p, 0xffffffff;\n@p mbarrier.arrive.expect_tx.shared::cta.b64 _, [%0], %1;\n}\n" ::"r"(bar), "r"(bytes) : "memory");
}
__device__ __forceinline__ void arrive_elect(uint32_t bar) {
  asm volatile("{\n.reg .pred p;\nelect.sync _|p, 0xffffffff;\n@p mbarrier.arrive.shared::cta.b64 _, [%0];\n}\n" ::"r"(bar) : "memory");
}
__device__ __forceinline__ void tma_load(uint32_t dst, const CUtensorMap* m, uint32_t bar, int c0, int c1) {
  asm volatile("{\n.reg .pred p;\nelect.sync _|p, 0xffffffff;\n"
               "@p cp.async.bulk.tensor.2d.shared::cluster.global.mbarrier::complete_tx::bytes [%0], [%1, {%3, %4}], [%2];\n}\n"
               ::"r"(dst), "l"(m), "r"(bar), "r"(c0), "r"(c1) : "memory");
}
__device__ __forceinline__ void tma_load_mc(uint32_t dst, const CUtensorMap* m, uint32_t bar, int c0, int c1) {
  asm volatile("{\n.reg .pred p;\nelect.sync _|p, 0xffffffff;\n"
               "@p cp.async.bulk.tensor.2d.shared::cluster.global.mbarrier::complete_tx::bytes.multicast::cluster.L2::cache_hint [%0], [%1, {%3, %4}], [%2], %5, %6;\n}\n"
               ::"r"(dst), "l"(m), "r"(bar), "r"(c0), "r"(c1), "h"((uint16_t)3), "l"(POLICY_EVICT_FIRST) : "memory");
}
__device__ __forceinline__ void tma_load_ef(uint32_t dst, const CUtensorMap* m, uint32_t bar, int c0, int c1) {
  asm volatile("{\n.reg .pred p;\nelect.sync _|p, 0xffffffff;\n"
               "@p cp.async.bulk.tensor.2d.shared::cluster.global.mbarrier::complete_tx::bytes.L2::cache_hint [%0], [%1, {%3, %4}], [%2], %5;\n}\n"
               ::"r"(dst), "l"(m), "r"(bar), "r"(c0), "r"(c1), "l"(POLICY_EVICT_FIRST) : "memory");
}
__device__ __forceinline__ void tma_store2(const CUtensorMap* m, uint32_t src, int c0, int c1) {
  asm volatile("{\n.reg .pred p;\nelect.sync _|p, 0xffffffff;\n"
               "@p cp.async.bulk.tensor.2d.global.shared::cta.bulk_group [%0, {%2, %3}], [%1];\n}\n"
               ::"l"(m), "r"(src), "r"(c0), "r"(c1) : "memory");
}
__device__ __forceinline__ void tma_store3(const CUtensorMap* m, uint32_t src, int c0, int c1, int c2) {
  asm volatile("{\n.reg .pred p;\nelect.sync _|p, 0xffffffff;\n"
               "@p cp.async.bulk.tensor.3d.global.shared::cta.bulk_group [%0, {%2, %3, %4}], [%1];\n}\n"
               ::"l"(m), "r"(src), "r"(c0), "r"(c1), "r"(c2) : "memory");
}
__device__ __forceinline__ void tma_add3(const CUtensorMap* m, uint32_t src, int c0, int c1, int c2) {
  asm volatile("{\n.reg .pred p;\nelect.sync _|p, 0xffffffff;\n"
               "@p cp.reduce.async.bulk.tensor.3d.global.shared::cta.add.bulk_group [%0, {%2, %3, %4}], [%1];\n}\n"
               ::"l"(m), "r"(src), "r"(c0), "r"(c1), "r"(c2) : "memory");
}
__device__ __forceinline__ void store_pause(bool sleep) {
  asm volatile("cp.async.bulk.commit_group;" ::: "memory");
  asm volatile("cp.async.bulk.wait_group.read 0;" ::: "memory");
  if (sleep) __nanosleep(PAUSE);
}
__device__ __forceinline__ void l2_prefetch_tile(const CUtensorMap* m, int c0, int c1) {
  asm volatile("{\n.reg .pred p;\nelect.sync _|p, 0xffffffff;\n@p cp.async.bulk.prefetch.tensor.2d.L2.global [%0, {%1, %2}];\n}\n"
               ::"l"(m), "r"(c0), "r"(c1) : "memory");
}
__device__ __forceinline__ void prefetch_map(const CUtensorMap* m) {
  asm volatile("prefetch.tensormap [%0];" ::"l"(m) : "memory");
}
__device__ __forceinline__ void wg_fence() { asm volatile("wgmma.fence.sync.aligned;" ::: "memory"); }
__device__ __forceinline__ void wg_commit() { asm volatile("wgmma.commit_group.sync.aligned;" ::: "memory"); }
template <int N>
__device__ __forceinline__ void wg_wait() { asm volatile("wgmma.wait_group.sync.aligned %0;" ::"n"(N) : "memory"); }
__device__ __forceinline__ void bar_sync(int id, int n) { asm volatile("bar.sync %0, %1;" ::"r"(id), "r"(n) : "memory"); }
__device__ __forceinline__ void wg_bar(int cw) {
  asm volatile("{\n.reg .pred p;\nsetp.ne.s32 p, %0, 0;\n@p bar.sync 3, 128;\n@!p bar.sync 2, 128;\n}\n" ::"r"(cw) : "memory");
}
__device__ __forceinline__ void skew_pre(int cw) { if (cw == 1) bar_sync(5, 256); }
__device__ __forceinline__ void skew_post(int cw) { if (cw == 0) asm volatile("bar.arrive 5, 256;" ::: "memory"); }
__device__ __forceinline__ void cluster_arrive_relaxed() { asm volatile("barrier.cluster.arrive.relaxed.aligned;" ::: "memory"); }
__device__ __forceinline__ void cluster_wait() { asm volatile("barrier.cluster.wait.acquire.aligned;" ::: "memory"); }
__device__ __forceinline__ uint32_t load_epoch(const unsigned* p) {
  uint32_t e;
  asm volatile("ld.relaxed.gpu.global.u32 %0, [%1];" : "=r"(e) : "l"(p) : "memory");
  return e;
}
__device__ __forceinline__ uint32_t pack2(float lo, float hi) {
  uint32_t r;
  asm("cvt.rn.bf16x2.f32 %0, %1, %2;" : "=r"(r) : "f"(hi), "f"(lo));
  return r;
}
__device__ __forceinline__ float bf_lo(uint32_t v) { return __uint_as_float(v << 16); }
__device__ __forceinline__ float bf_hi(uint32_t v) { return __uint_as_float(v & 0xffff0000u); }
__device__ __forceinline__ uint32_t fma_bf2(uint32_t a, uint32_t b, uint32_t c) {
  uint32_t d;
  asm("fma.rn.bf16x2 %0, %1, %2, %3;" : "=r"(d) : "r"(a), "r"(b), "r"(c));
  return d;
}
__device__ __forceinline__ float bf_round(float v) { return __bfloat162float(__float2bfloat16_rn(v)); }
__device__ __forceinline__ float silu_f(float v) { return __fdividef(v, 1.0f + __expf(-v)); }
__device__ __forceinline__ uint4 ldg_nc(const void* p) {
  uint4 v;
  asm volatile("ld.global.nc.L1::no_allocate.v4.u32 {%0, %1, %2, %3}, [%4];" : "=r"(v.x), "=r"(v.y), "=r"(v.z), "=r"(v.w) : "l"(p));
  return v;
}
__device__ __forceinline__ void stmatrix4(uint32_t addr, uint32_t a, uint32_t b, uint32_t c, uint32_t d) {
  asm volatile("stmatrix.sync.aligned.m8n8.x4.shared.b16 [%0], {%1, %2, %3, %4};" ::"r"(addr), "r"(a), "r"(b), "r"(c), "r"(d) : "memory");
}
__device__ __forceinline__ void stmatrix2(uint32_t addr, uint32_t a, uint32_t b) {
  asm volatile("stmatrix.sync.aligned.m8n8.x2.shared.b16 [%0], {%1, %2};" ::"r"(addr), "r"(a), "r"(b) : "memory");
}
__device__ __forceinline__ void stmatrix1(uint32_t addr, uint32_t a) {
  asm volatile("stmatrix.sync.aligned.m8n8.x1.shared.b16 [%0], {%1};" ::"r"(addr), "r"(a) : "memory");
}
__device__ __forceinline__ uint32_t movmatrix(uint32_t a) {
  uint32_t d;
  asm("movmatrix.sync.aligned.m8n8.trans.b16 %0, %1;" : "=r"(d) : "r"(a));
  return d;
}
__device__ __forceinline__ void mma16816(float (&d)[4], uint32_t a0, uint32_t a1, uint32_t a2, uint32_t a3, uint32_t b0, uint32_t b1) {
  asm("mma.sync.aligned.m16n8k16.row.col.f32.bf16.bf16.f32 {%0, %1, %2, %3}, {%4, %5, %6, %7}, {%8, %9}, {%0, %1, %2, %3};"
               : "+f"(d[0]), "+f"(d[1]), "+f"(d[2]), "+f"(d[3]) : "r"(a0), "r"(a1), "r"(a2), "r"(a3), "r"(b0), "r"(b1));
}
__device__ __forceinline__ void mma1688(float (&d)[4], uint32_t a0, uint32_t a1, uint32_t b0) {
  asm("mma.sync.aligned.m16n8k8.row.col.f32.bf16.bf16.f32 {%0, %1, %2, %3}, {%4, %5}, {%6}, {%0, %1, %2, %3};"
               : "+f"(d[0]), "+f"(d[1]), "+f"(d[2]), "+f"(d[3]) : "r"(a0), "r"(a1), "r"(b0));
}
__device__ __forceinline__ void ldmatrix4t(uint32_t (&b)[4], uint32_t addr) {
  asm volatile("ldmatrix.sync.aligned.m8n8.x4.trans.shared.b16 {%0, %1, %2, %3}, [%4];" : "=r"(b[0]), "=r"(b[1]), "=r"(b[2]), "=r"(b[3]) : "r"(addr) : "memory");
}
__device__ __forceinline__ void ldmatrix4(uint32_t& a, uint32_t& b, uint32_t& c, uint32_t& d, uint32_t addr) {
  asm volatile("ldmatrix.sync.aligned.m8n8.x4.shared.b16 {%0, %1, %2, %3}, [%4];" : "=r"(a), "=r"(b), "=r"(c), "=r"(d) : "r"(addr) : "memory");
}
__device__ __forceinline__ void cp_async16(uint32_t dst, const void* src) {
  asm volatile("cp.async.cg.shared.global.L2::cache_hint [%0], [%1], 16, %2;" ::"r"(dst), "l"(src), "l"(POLICY_EVICT_FIRST) : "memory");
}
__device__ __forceinline__ uint32_t lds32(uint32_t addr) {
  uint32_t v;
  asm volatile("ld.shared.u32 %0, [%1];" : "=r"(v) : "r"(addr) : "memory");
  return v;
}
__device__ __forceinline__ void sts64f(uint32_t addr, float a, float b) {
  asm volatile("st.shared.v2.f32 [%0], {%1, %2};" ::"r"(addr), "f"(a), "f"(b) : "memory");
}
constexpr float QK_SCALE = 0.17677669529663687f;
__device__ __forceinline__ float softmax8(float& p0, float& p1) {
  float m = fmaxf(p0, p1);
  m = fmaxf(m, __shfl_xor_sync(~0u, m, 1));
  m = fmaxf(m, __shfl_xor_sync(~0u, m, 2));
  asm("ex2.approx.ftz.f32 %0, %1;" : "=f"(p0) : "f"((p0 - m) * 1.4426950408889634f));
  asm("ex2.approx.ftz.f32 %0, %1;" : "=f"(p1) : "f"((p1 - m) * 1.4426950408889634f));
  float s = p0 + p1;
  s += __shfl_xor_sync(~0u, s, 1);
  s += __shfl_xor_sync(~0u, s, 2);
  float r;
  asm("rcp.approx.ftz.f32 %0, %1;" : "=f"(r) : "f"(s));
  return r;
}
__device__ __forceinline__ void sts128(uint32_t addr, uint32_t a, uint32_t b, uint32_t c, uint32_t d) {
  asm volatile("st.shared.v4.u32 [%0], {%1, %2, %3, %4};" ::"r"(addr), "r"(a), "r"(b), "r"(c), "r"(d) : "memory");
}
__device__ __forceinline__ uint4 lds128(uint32_t addr) {
  uint4 v;
  asm volatile("ld.shared.v4.u32 {%0, %1, %2, %3}, [%4];" : "=r"(v.x), "=r"(v.y), "=r"(v.z), "=r"(v.w) : "r"(addr) : "memory");
  return v;
}
__device__ __forceinline__ float2 lds64f(uint32_t addr) {
  float2 v;
  asm volatile("ld.shared.v2.f32 {%0, %1}, [%2];" : "=f"(v.x), "=f"(v.y) : "r"(addr) : "memory");
  return v;
}
#define PROF_AT(cond, slot) do {} while (0)

constexpr uint32_t SMEM_BASE = 1024;
constexpr uint32_t DESC_A = (1u << 16) | (SMEM_BASE >> 4);
constexpr uint32_t DESC_B = ((8192u >> 4) << 16) | (SMEM_BASE >> 4);

template <int BN> struct Wg;
template <> struct Wg<128> { static __device__ __forceinline__ void mma(float (&d)[64], uint32_t a, uint32_t b, int s) { wgmma_ss_n128(d, a, b, s); } };
template <> struct Wg<192> { static __device__ __forceinline__ void mma(float (&d)[96], uint32_t a, uint32_t b, int s) { wgmma_ss_n192(d, a, b, s); } };
template <> struct Wg<256> { static __device__ __forceinline__ void mma(float (&d)[128], uint32_t a, uint32_t b, int s) { wgmma_ss_n256(d, a, b, s); } };

struct Ring {
  uint32_t full0, rel0;
  int s;
  uint32_t ph;
  uint32_t off;
  bool releaser;
};

template <int N>
__device__ __forceinline__ void fence_regs(float (&a)[N]) {
#pragma unroll
  for (int i = 0; i < N; i++) asm volatile("" : "+f"(a[i])::"memory");
}

template <int BN, int NST, uint32_t STAGE>
__device__ __forceinline__ void kblock(float (&acc)[BN / 2], Ring& g, uint32_t a_addr, bool zero, uint32_t& prev, uint32_t b_rel = 16384) {
  mbar_wait(g.full0 + 8 * g.s, g.ph);
  const uint32_t da = DESC_A + (a_addr >> 4);
  const uint32_t db = DESC_B + ((g.off + b_rel) >> 4);
  wg_fence();
#pragma unroll
  for (int k = 0; k < 4; k++) Wg<BN>::mma(acc, da + k * 2, db + k * 128, !(zero && k == 0));
  wg_commit();
  wg_wait<1>();
  jitter();
  if (prev != 0) mbar_arrive_cluster(prev);
  prev = g.releaser ? g.rel0 + 8 * g.s : 0u;
  if (++g.s == NST) { g.s = 0; g.ph ^= 1; }
  g.off += STAGE;
  if (g.off == NST * STAGE) g.off = 0;
}
template <int N>
__device__ __forceinline__ void tile_end(float (&acc)[N], uint32_t& prev) {
  wg_wait<0>();
  if (prev != 0) mbar_arrive_cluster(prev);
  prev = 0;
  fence_regs(acc);
}

__device__ __forceinline__ int other_kb(int q, int j) {
  const int ch = q >= 7, jj = q - 7 * ch;
  return 2 * (jj < j ? jj : jj + 1) + ch;
}
__device__ __forceinline__ int qkv_kb(int it, int j) {
  return it < 4 ? 2 * j + (it >> 1) : other_kb(it < 18 ? it - 4 : it - 18, j);
}
__device__ __forceinline__ int wo_k(int it, int j) {
  return it < 8 ? it * 128 : (it == 8 ? j : (it - 9 < j ? it - 9 : it - 8)) * 128 + 64;
}
__device__ __forceinline__ int down_k(int d) {
  const int u = d + KH;
  if (u < 8) return u * 448 + 384;
  if (u < 40) return (((u - 8) & 15) >> 1) * 448 + ((u - 8) >> 4) * 128 + (u & 1) * 64;
  return (u & 7) * 448 + 256 + (u >= 48 ? 64 : 0);
}
__device__ __forceinline__ void wait_q_free(uint32_t empty, int i) {
  mbar_wait(empty + 8 * ((i * 2) / 3), 1);
  mbar_wait(empty + 8 * ((i * 2 + 1) / 3), 1);
}
__device__ __forceinline__ void wait_w_free(uint32_t empty, int i) {
  const int t = (i + 3) & 3, w0 = (t * 3) / 2, w1 = (t * 3 + 2) / 2;
  mbar_wait(empty + 8 * w0, w0 < 4);
  mbar_wait(empty + 8 * w1, w1 < 4);
}
__device__ __forceinline__ void wait_g_free(uint32_t empty, int i) {
  const int s = i < 4 ? i + 2 : i - 4, b0 = ((s * 2) / 3 + 1) & 3, b1 = ((s * 2 + 1) / 3 + 1) & 3;
  mbar_wait(empty + 8 * b0, b0 < 2);
  mbar_wait(empty + 8 * b1, b1 < 2);
}

__device__ __forceinline__ void chan(float& m, float& q, float m2, float q2, float n) {
  const float d = m2 - m;
  m = 0.5f * (m + m2);
  q = q + q2 + d * d * (0.5f * n);
}

__device__ __forceinline__ uint32_t tag16(uint32_t tag, uint32_t ln) { return (((tag & 0x3fffu) << 1) | ln) + 0x8000u; }
__device__ __forceinline__ void stat_store(uint2* slot, float m, float q, uint32_t t16) {
  const uint32_t a = ((__float_as_uint(m) + 0x80u) & 0xffffff00u) | (t16 & 0xffu), b = ((__float_as_uint(q) + 0x80u) & 0xffffff00u) | (t16 >> 8);
  asm volatile("st.relaxed.gpu.global.b64 [%0], %1;" ::"l"(slot), "l"((uint64_t)a | ((uint64_t)b << 32)) : "memory");
}
__device__ __forceinline__ void stat_gather(const uint2* rows, uint32_t t16, int lane, float (&rs)[2], float (&nb)[2]) {
  const uint4* sp = (const uint4*)(rows + (lane >> 3) * 128) + (lane & 7);
  const uint32_t want = (t16 & 0xffu) | ((t16 >> 8) << 8);
  uint4 a, b;
  for (;;) {
    a = ll_peek(sp);
    b = ll_peek(sp + 256);
    const uint32_t bad = (__byte_perm(a.x, a.y, 0x40) ^ want) | (__byte_perm(a.z, a.w, 0x40) ^ want) | (__byte_perm(b.x, b.y, 0x40) ^ want) |
                         (__byte_perm(b.z, b.w, 0x40) ^ want);
    if (__all_sync(~0u, (bad & 0xffffu) == 0)) break;
  }
  float m0 = __uint_as_float(a.x & 0xffffff00u), q0 = __uint_as_float(a.y & 0xffffff00u);
  float m1 = __uint_as_float(a.z & 0xffffff00u), q1 = __uint_as_float(a.w & 0xffffff00u);
  chan(m0, q0, __uint_as_float(b.x & 0xffffff00u), __uint_as_float(b.y & 0xffffff00u), 128.f);
  chan(m1, q1, __uint_as_float(b.z & 0xffffff00u), __uint_as_float(b.w & 0xffffff00u), 128.f);
  const bool hi = lane & 8;
  float m = hi ? m1 : m0, q = hi ? q1 : q0;
  chan(m, q, __shfl_xor_sync(~0u, hi ? m0 : m1, 8), __shfl_xor_sync(~0u, hi ? q0 : q1, 8), 256.f);
  chan(m, q, __shfl_xor_sync(~0u, m, 16), __shfl_xor_sync(~0u, q, 16), 512.f);
  const float rstd = rsqrtf(q * (1.0f / DM) + 1e-5f), nmr = -m * rstd;
  const int r = lane >> 2, src = (r >> 1) + (r & 1) * 8;
  rs[0] = __shfl_sync(~0u, rstd, src); nb[0] = __shfl_sync(~0u, nmr, src);
  rs[1] = __shfl_sync(~0u, rstd, src + 4); nb[1] = __shfl_sync(~0u, nmr, src + 4);
}

__device__ __forceinline__ void publish_stats(const uint32_t (&xl)[16], const uint32_t (&xh)[16], uint2* slot, int lane, uint32_t t16) {
  float ds[4] = {0.f, 0.f, 0.f, 0.f}, dl[4] = {0.f, 0.f, 0.f, 0.f}, dh[4] = {0.f, 0.f, 0.f, 0.f};
#pragma unroll
  for (int q = 0; q < 8; q++) {
    mma16816(ds, xl[2 * q], xh[2 * q], xl[2 * q + 1], xh[2 * q + 1], 0x3f803f80u, 0x3f803f80u);
    mma16816(dl, xl[2 * q], xh[2 * q], xl[2 * q + 1], xh[2 * q + 1], xl[2 * q], xl[2 * q + 1]);
    mma16816(dh, xl[2 * q], xh[2 * q], xl[2 * q + 1], xh[2 * q + 1], xh[2 * q], xh[2 * q + 1]);
  }
  const int r = lane >> 2;
  if ((lane & 3) == (r >> 1)) {
    const float ml = ds[0] * (1.0f / 128), mh = ds[2] * (1.0f / 128);
    const float ql = fmaxf(((r & 1) ? dl[1] : dl[0]) - ds[0] * ml, 0.f), qh = fmaxf(((r & 1) ? dh[3] : dh[2]) - ds[2] * mh, 0.f);
    stat_store(slot + r, ml, ql, t16);
    stat_store(slot + r + 8, mh, qh, t16);
  }
  __syncwarp();
}

__device__ __forceinline__ void stage_slab(uint32_t chunk, int warp, int lane, const uint32_t (&lo)[8], const uint32_t (&hi)[8]) {
  const int row = warp * 16 + (lane & 7) + ((lane >> 3) & 1) * 8;
  const uint32_t rbase = chunk + row * 128;
#pragma unroll
  for (int q = 0; q < 4; q++) {
    const int grp = 2 * q + (lane >> 4);
    stmatrix4(rbase + ((grp ^ (row & 7)) << 4), lo[2 * q], hi[2 * q], lo[2 * q + 1], hi[2 * q + 1]);
  }
}
__device__ __forceinline__ float silu_mul(float g, float u) {
  float e, r;
  asm("ex2.approx.ftz.f32 %0, %1;" : "=f"(e) : "f"(g * -1.4426950408889634f));
  asm("rcp.approx.ftz.f32 %0, %1;" : "=f"(r) : "f"(1.0f + e));
  return g * r * u;
}
__device__ __forceinline__ uint32_t swiglu2(uint32_t g2, uint32_t u2) {
  asm volatile("" : "+r"(g2));
  return pack2(silu_mul(bf_lo(g2), bf_lo(u2)), silu_mul(bf_hi(g2), bf_hi(u2)));
}
__device__ __forceinline__ void stage_done(uint32_t bar, int lane) {
  asm volatile("fence.proxy.async.shared::cta;" ::: "memory");
  __syncwarp();
  if (lane == 0) mbar_arrive(bar);
}

__device__ __forceinline__ int fresh_tid() {
  int t;
  asm volatile("mov.u32 %0, %%tid.x;" : "=r"(t));
  return t;
}
#define RING_IDS()                                                                                           \
  const int tid = fresh_tid() - 128;                                                                         \
  const int cw = __shfl_sync(~0u, tid >> 7, 0), warp = __shfl_sync(~0u, (tid >> 5) & 3, 0);                  \
  const bool releaser = (tid & 31) < 2;                                                                      \
  const uint32_t rbars = mapa(bars, tid & 1);                                                                \
  const uint32_t a_base = cw * 8192
#define LANE_IDS()                                                                                           \
  const int lane = fresh_tid() & 31, r = lane >> 2, c = lane & 3;                                            \
  const int srow = warp * 16 + (lane & 7) + ((lane >> 3) & 1) * 8;                                           \
  const uint32_t slab = stg + cw * 8192 + srow * 128, sw0 = (lane >> 4) ^ (srow & 7);                        \
  (void)r; (void)c; (void)slab; (void)sw0

template <int NPRE, bool EAGER, class Step>
__device__ __forceinline__ void attention(float (&acc)[96], const Params& p, int rho, int rb, int cta, int cw, int warp, uint32_t tag,
                                          uint32_t stg, uint32_t bars, uint32_t& prev, Step step) {
  uint32_t ql[8], qh[8], k0[8], k1[8], v0[8], v1[8], hp[16];
  mbar_wait(bars + 8 * B_STGE, rho);
  mbar_wait(bars + 8 * (B_STGE + 1), 0);
  if (EAGER) {
    tile_end(acc, prev);
  } else {
    step();
    fence_regs(acc);
  }
#pragma unroll
  for (int t = 0; t < 8; t++) {
    k0[t] = pack2(acc[4 * (8 + t)], acc[4 * (8 + t) + 1]);
    k1[t] = pack2(acc[4 * (8 + t) + 2], acc[4 * (8 + t) + 3]);
    v0[t] = pack2(acc[4 * (16 + t)], acc[4 * (16 + t) + 1]);
    v1[t] = pack2(acc[4 * (16 + t) + 2], acc[4 * (16 + t) + 3]);
    asm volatile("" : "+r"(k0[t]), "+r"(k1[t]), "+r"(v0[t]), "+r"(v1[t]));
  }
  const int lane = fresh_tid() & 31, r = lane >> 2, c = lane & 3;
#pragma unroll
  for (int t = 0; t < 8; t++) v1[t] = movmatrix(v1[t]);
  const uint32_t xch = stg + 16384 + (cw * 4 + warp) * 2048 + lane * 16;
  if (warp < 3) {
    sts128(xch, k1[0], k1[1], k1[2], k1[3]);
    sts128(xch + 512, k1[4], k1[5], k1[6], k1[7]);
    sts128(xch + 1024, v1[0], v1[1], v1[2], v1[3]);
    sts128(xch + 1536, v1[4], v1[5], v1[6], v1[7]);
  } else if (rb < 15) {
    uint4* dst = p.halo + ((cta * 2 + rho) * 2 + cw) * 256 + lane;
#pragma unroll
    for (int t = 0; t < 4; t++) {
      ll_store(dst + t * 32, k1[2 * t], k1[2 * t + 1], tag);
      ll_store(dst + (4 + t) * 32, v1[2 * t], v1[2 * t + 1], tag);
    }
  }
#pragma unroll
  for (int t = 0; t < 8; t++) {
    v0[t] = movmatrix(v0[t]);
    ql[t] = pack2(acc[4 * t], acc[4 * t + 1]);
    qh[t] = pack2(acc[4 * t + 2], acc[4 * t + 3]);
    asm volatile("" : "+r"(v0[t]), "+r"(ql[t]), "+r"(qh[t]));
  }
#pragma unroll 1
  for (int i = 0; i < NPRE; i++) step();
  const uint4* src = p.halo + (((cta - 8) * 2 + rho) * 2 + cw) * 256 + lane;
  uint4 early[8] = {};
  if (warp == 0 && rb > 0) {
#pragma unroll
    for (int i = 0; i < 8; i++) early[i] = ll_peek(src + i * 32);
  }
  step();
  wg_bar(cw);
  if (warp > 0) {
#pragma unroll
    for (int t = 0; t < 4; t++) {
      const uint4 a = lds128(xch - 2048 + t * 512);
      hp[4 * t] = a.x; hp[4 * t + 1] = a.y; hp[4 * t + 2] = a.z; hp[4 * t + 3] = a.w;
    }
  } else if (rb > 0) {
    for (;;) {
      uint32_t bad = 0;
#pragma unroll
      for (int i = 0; i < 8; i++) bad |= (early[i].y ^ tag) | (early[i].w ^ tag);
      if (__all_sync(~0u, bad == 0)) break;
#pragma unroll
      for (int i = 0; i < 8; i++) early[i] = ll_peek(src + i * 32);
    }
#pragma unroll
    for (int i = 0; i < 8; i++) { hp[2 * i] = early[i].x; hp[2 * i + 1] = early[i].z; }
  } else {
#pragma unroll
    for (int t = 0; t < 16; t++) hp[t] = 0;
  }
  wg_wait<0>();
  if (prev != 0) mbar_arrive_cluster(prev);
  prev = 0;
#pragma unroll
  for (int t = 0; t < 8; t++) asm volatile("" : "+r"(ql[t])::"memory");
  const bool up0 = 2 * c > r, up1 = 2 * c + 1 > r;
  const bool first = (rb == 0) && (warp == 0);
  uint32_t a0[2], a2[2], a3[2], a5[2];
  float il[2], ih[2];
#pragma unroll
  for (int h = 0; h < 2; h++) {
    float sp[4] = {0.f, 0.f, 0.f, 0.f}, s0[4] = {0.f, 0.f, 0.f, 0.f}, s1[4] = {0.f, 0.f, 0.f, 0.f};
#pragma unroll
    for (int ks = 0; ks < 2; ks++) {
      const int t = 4 * h + 2 * ks;
      mma16816(sp, ql[t], qh[t], ql[t + 1], qh[t + 1], hp[t], hp[t + 1]);
      mma16816(s0, ql[t], qh[t], ql[t + 1], qh[t + 1], k0[t], k0[t + 1]);
      mma16816(s1, ql[t], qh[t], ql[t + 1], qh[t + 1], k1[t], k1[t + 1]);
    }
    float p0 = (up0 ? sp[0] : s0[0]) * QK_SCALE, p1 = (up1 ? sp[1] : s0[1]) * QK_SCALE;
    float p2 = (up0 ? s0[2] : s1[2]) * QK_SCALE, p3 = (up1 ? s0[3] : s1[3]) * QK_SCALE;
    if (first && up0) p0 = -1000000000.0f;
    if (first && up1) p1 = -1000000000.0f;
    il[h] = softmax8(p0, p1);
    ih[h] = softmax8(p2, p3);
    a0[h] = pack2(up0 ? p0 : 0.f, up1 ? p1 : 0.f);
    a2[h] = pack2(up0 ? 0.f : p0, up1 ? 0.f : p1);
    a3[h] = pack2(up0 ? p2 : 0.f, up1 ? p3 : 0.f);
    a5[h] = pack2(up0 ? 0.f : p2, up1 ? 0.f : p3);
  }
  float o[8][4];
#pragma unroll
  for (int t = 0; t < 8; t++) {
#pragma unroll
    for (int q = 0; q < 4; q++) o[t][q] = 0.f;
    mma1688(o[t], 0u, a5[t >> 2], v1[t]);
    mma16816(o[t], a0[t >> 2], 0u, a2[t >> 2], a3[t >> 2], hp[8 + t], v0[t]);
  }
#pragma unroll
  for (int t = 0; t < 8; t++) fence_regs(o[t]);
  if (!EAGER) step();
  uint32_t ol[8], oh[8];
#pragma unroll
  for (int t = 0; t < 8; t++) {
    ol[t] = pack2(o[t][0] * il[t >> 2], o[t][1] * il[t >> 2]);
    oh[t] = pack2(o[t][2] * ih[t >> 2], o[t][3] * ih[t >> 2]);
  }
  if (!EAGER) step();
  stage_slab(stg + cw * 8192, warp, lane, ol, oh);
  stage_done(bars + 8 * B_STGF, lane);
  if (!EAGER) step();
}

__global__ void __launch_bounds__(384, 1) fused_kernel(const bf16* __restrict__ gx, const bf16* __restrict__ gwmod, const bf16* __restrict__ gc,
                                                          unsigned* gepoch, uint2* gstats, const __grid_constant__ Params p) {
  extern __shared__ __align__(1024) uint8_t smem_raw[];
  const uint32_t sm = smem_u32(smem_raw);
  const uint32_t bars = sm + MISC_OFF;
  const uint32_t stg = sm + STG_OFF;
  const int rank = blockIdx.x & 1;
  const int cl = blockIdx.x >> 1;
  if (cl >= NCTA / 2) {
    const int e = blockIdx.x - NCTA, wid = __shfl_sync(~0u, (int)(threadIdx.x >> 5), 0), lane = threadIdx.x & 31;
    if (threadIdx.x < 32) {
      mbar_init(bars + 8 * lane, lane >= 24 ? 4 : (lane >= 6 && lane < 12) ? 8 : 1);
      asm volatile("fence.mbarrier_init.release.cluster;" ::: "memory");
    }
    const uint32_t tag = load_epoch(gepoch) + 1;
#pragma unroll 1
    for (int i = threadIdx.x; i < 1536; i += 384) {
      uint4 o = make_uint4(0u, 0u, 0u, 0u);
      if (i < 1024 && (i & 63) < 8) {
        const uint4 cv = ldg_nc(gc + (i >> 6) * 64 + (i & 7) * 8);
        o = make_uint4(pack2(silu_f(bf_lo(cv.x)), silu_f(bf_hi(cv.x))), pack2(silu_f(bf_lo(cv.y)), silu_f(bf_hi(cv.y))),
                       pack2(silu_f(bf_lo(cv.z)), silu_f(bf_hi(cv.z))), pack2(silu_f(bf_lo(cv.w)), silu_f(bf_hi(cv.w))));
      }
      sts128(stg + i * 16, o.x, o.y, o.z, o.w);
    }
    asm volatile("fence.proxy.async.shared::cta;" ::: "memory");
    __syncthreads();
    if (wid == 0) {
      __nanosleep(WMDELAY);
      uint32_t ph = 1;
#pragma unroll 1
      for (int it = 0, s = 0; it < 64; it++) {
        mbar_wait(bars + 8 * (6 + s), ph);
        expect_tx_elect(bars + 8 * s, 32768);
#pragma unroll
        for (int q = 0; q < 4; q++) tma_load_ef(sm + s * 32768 + q * 8192, &p.wm, bars + 8 * s, 2048 + (it >> 4) * 1024 + e * 256 + q * 64, (it & 15) * 64);
        if (++s == 6) { s = 0; ph ^= 1; }
      }
    } else if (wid == 1) {
      __nanosleep(PFW);
#pragma unroll 1
      for (int i = 0; i < 64; i++) {
        l2_prefetch_tile(&p.wo, (i & 15) * 64, (e * 4 + (i >> 4)) * 64);
      }
#pragma unroll 1
      for (int i = 0; i < 80; i++) {
        if (i < 64) l2_prefetch_tile((i & 1) ? &p.wu : &p.wg, ((i >> 1) & 7) * 448 + 384, ((i >> 4) * 4 + e) * 64);
        else l2_prefetch_tile((i & 2) ? &p.wu : &p.wg, (e * 2 + ((i >> 3) & 1)) * 448 + (i & 1) * 64, (e * 4 + ((i >> 2) & 3)) * 64);
      }
    } else if (wid >= 4) {
      const int hf = (wid >> 2) - 1;
      uint32_t ph = 0;
      int s = 0;
#pragma unroll 1
      for (int v = 0; v < 4; v++) {
        float acc[64];
#pragma unroll 1
        for (int kb = 0; kb < 16; kb++) {
          mbar_wait_watchdog(bars + 8 * s, ph);
          const uint32_t da = DESC_A + ((STG_OFF + kb * 1024) >> 4), db = DESC_B + ((s * 32768 + hf * 16384) >> 4);
          wg_fence();
#pragma unroll
          for (int k = 0; k < 4; k++) wgmma_ss_n128(acc, da + k * 2, db + k * 128, (kb | k) != 0);
          wg_commit();
          wg_wait<0>();
          if (lane == 0) mbar_arrive(bars + 8 * (6 + s));
          if (++s == 6) { s = 0; ph ^= 1; }
        }
        fence_regs(acc);
        if ((wid & 3) == 0) {
#pragma unroll
          for (int n = 0; n < 16; n++) {
            const uint32_t mine = pack2(acc[4 * n], acc[4 * n + 1]), next = __shfl_down_sync(~0u, mine, 1);
            if (lane < 4 && (lane & 1) == 0) ll_store(p.modll + 512 + v * 256 + e * 64 + hf * 32 + n * 2 + (lane >> 1), mine, next, tag);
            if (lane < 4) sts64f(sm + MODB_OFF + (hf * 128 + n * 8 + lane * 2) * 4, bf_lo(mine), bf_hi(mine));
          }
        }
      }
    }
    __syncthreads();
    if (wid == 0 || wid == 2) {
      const int w = wid >> 1;
      if (w == 0) {
        expect_tx_elect(bars + 8 * 12, KH * 32768);
#pragma unroll 1
        for (int q = 0; q < 4 * KH; q++) tma_load_ef(sm + q * 8192, &p.wd, bars + 8 * 12, e * 256 + (q & 3) * 64, (q >> 2) * 448 + 384);
      }
      cnt_wait_lazy(p.cnt + C_ACT, tag * 8);
      if (w == 1) __nanosleep(900);
      uint32_t ph = 1, ready = 0;
#pragma unroll 1
      for (int it = 0, s = 0; it < 16 * KH; it++) {
        const int rb = it / KH, kc = it - rb * KH;
        while (!((ready >> rb) & 1)) {
          ready = __ballot_sync(~0u, (int)(load_epoch(p.cnt + (lane & 15) * 32 + C_ACT) - tag * 8) >= 0);
          asm volatile("fence.proxy.async.global;" ::: "memory");
        }
        const uint32_t fb = bars + 8 * (16 + w * 4 + s), dst = sm + 98304 + w * 32768 + s * 8192;
        mbar_wait(fb + 64, ph);
        expect_tx_elect(fb, 8192);
        tma_load(dst, &p.act_st, fb, kc * 448 + 384, rb * 128 + w * 64);
        tma_load(dst + 4096, &p.act_st, fb, kc * 448 + 384, rb * 128 + w * 64 + 32);
        if (++s == 4) { s = 0; ph ^= 1; }
      }
    } else if (wid >= 4) {
      const int w = (wid >> 2) - 1, warp = wid & 3;
      const uint32_t out_stg = (w ? stg : sm + 163840) + warp * 2048;
      const uint32_t slab = out_stg + (lane & 15) * 128, sw0 = (lane >> 4) ^ (lane & 7);
      mbar_wait_watchdog(bars + 8 * 12, 0);
#pragma unroll 1
      for (int i = threadIdx.x - 128; i < KH * 2048; i += 256) {
        const uint32_t gp = sm + MODB_OFF + (((i >> 9) & 3) * 64 + ((i ^ (i >> 3)) & 7) * 8) * 4;
        const uint4 v = lds128(sm + i * 16), ga = lds128(gp), gc = lds128(gp + 16);
        sts128(sm + i * 16, pack2(bf_lo(v.x) * __uint_as_float(ga.x), bf_hi(v.x) * __uint_as_float(ga.y)),
               pack2(bf_lo(v.y) * __uint_as_float(ga.z), bf_hi(v.y) * __uint_as_float(ga.w)),
               pack2(bf_lo(v.z) * __uint_as_float(gc.x), bf_hi(v.z) * __uint_as_float(gc.y)),
               pack2(bf_lo(v.w) * __uint_as_float(gc.z), bf_hi(v.w) * __uint_as_float(gc.w)));
      }
      asm volatile("fence.proxy.async.shared::cta;" ::: "memory");
      bar_sync(1, 256);
      uint32_t ph = 0;
      int s = 0;
#pragma unroll 1
      for (int rb = 0; rb < 16; rb++) {
        float acc[128];
#pragma unroll 1
        for (int kc = 0; kc < KH; kc++) {
          mbar_wait_watchdog(bars + 8 * (16 + w * 4 + s), ph);
          const uint32_t da = DESC_A + ((98304 + w * 32768 + s * 8192) >> 4), db = DESC_B + ((kc * 32768) >> 4);
          wg_fence();
#pragma unroll
          for (int k = 0; k < 4; k++) wgmma_ss_n256(acc, da + k * 2, db + k * 128, (kc | k) != 0);
          wg_commit();
          wg_wait<1>();
          if (kc > 0 && lane == 0) mbar_arrive(bars + 8 * (24 + w * 4 + ((s + 3) & 3)));
          if (++s == 4) { s = 0; ph ^= 1; }
        }
        asm volatile("cp.async.bulk.wait_group 0;" ::: "memory");
        __syncwarp();
        if (rb > 0) cnt_signal(p.cnt + (rb - 1) * 32 + C_SP + e);
        wg_wait<0>();
        fence_regs(acc);
        __syncwarp();
        if (lane == 0) mbar_arrive(bars + 8 * (24 + w * 4 + ((s + 3) & 3)));
#pragma unroll
        for (int q = 0; q < 16; q++)
          stmatrix4(slab + (q >> 2) * 8192 + ((sw0 ^ ((q & 3) * 2)) << 4), pack2(acc[8 * q], acc[8 * q + 1]), pack2(acc[8 * q + 2], acc[8 * q + 3]),
                    pack2(acc[8 * q + 4], acc[8 * q + 5]), pack2(acc[8 * q + 6], acc[8 * q + 7]));
        asm volatile("fence.proxy.async.shared::cta;" ::: "memory");
        __syncwarp();
#pragma unroll
        for (int ch = 0; ch < 4; ch++) tma_add3(&p.out, out_stg + ch * 8192, e * 256 + ch * 64, rb * 64 + warp * 16, w);
        asm volatile("cp.async.bulk.commit_group;" ::: "memory");
      }
      asm volatile("cp.async.bulk.wait_group 0;" ::: "memory");
      __syncwarp();
      cnt_signal(p.cnt + 15 * 32 + C_SP + e);
    }
    return;
  }
  const int q7 = ((cl - 36) * 37) >> 8;
  const int j = cl < 4 ? 4 + cl : (cl < 36 ? (cl - 4) >> 3 : 4 + q7);
  const int rb = (cl < 4 ? 0 : (cl < 36 ? (cl - 4) & 7 : cl - 35 - 7 * q7)) * 2 + rank;
  const int cta = rb * 8 + j;
  PROF_AT(threadIdx.x == 0, 0);

  if (threadIdx.x < 128) {
    asm volatile("setmaxnreg.dec.sync.aligned.u32 40;");
    const int warp = __shfl_sync(~0u, (int)(threadIdx.x >> 5), 0), lane = threadIdx.x & 31;
    uint32_t ep = 0;
    if (threadIdx.x == 0) ep = load_epoch(gepoch);
    if (threadIdx.x < B_COUNT) {
      const int i = threadIdx.x;
      const bool empty = (i >= B_EQ && i < B_FW) || (i >= B_EW && i < B_FG) || (i >= B_EG && i < B_FD) || (i >= B_ED && i < B_STGF);
      mbar_init(bars + 8 * i, empty ? 16 : (i == B_STGF || i == B_STGF + 1) ? 8 : 1);
      asm volatile("fence.mbarrier_init.release.cluster;" ::: "memory");
    }
    if (threadIdx.x == 0) {
      if ((sm & 0x3FFFF) != SMEM_BASE) asm volatile("trap;");
      asm volatile("st.shared.u32 [%0], %1;" ::"r"(bars + 8 * B_COUNT), "r"(ep + 1) : "memory");
      asm volatile("fence.acq_rel.cta;" ::: "memory");
    }
    __syncwarp();
    cluster_arrive_relaxed();
    unsigned* cnt = p.cnt + rb * 32;
    cluster_wait();
    const uint32_t tag = lds32(bars + 8 * B_COUNT);
    const unsigned target = tag * 8;
    if (warp == 0) {
      const CUtensorMap* wgu = rank ? &p.wu : &p.wg;
      uint32_t st = sm + 16384, fb = bars + 8 * B_FQ, ph = 1;
      __nanosleep(BDELAY);
#pragma unroll 1
      for (int it = 0; it < 32; it++) {
        const int kb = qkv_kb(it, j), col = j * 128 + ((it < 4 ? (it & 1) : it >= 18) ? 64 : 0);
        if (it == 2) mbar_wait(bars + 8 * B_MODA, 0);
        mbar_wait(fb + 8 * (B_EQ - B_FQ), ph);
        expect_tx_elect(fb, it < 4 ? 24576 : 40960);
        tma_load_mc(st + rank * 8192, &p.wqkv, fb, col + rank * 1024, kb * 64);
        tma_load_mc(st + 16384 + rank * 4096, &p.wqkv32, fb, col + 2048, kb * 64 + rank * 32);
        st += 49152; fb += 8;
        if ((it & 3) == 3) { st -= 4 * 49152; fb -= 32; ph ^= 1; }
      }
      fb = bars + 8 * B_FW; ph = 1;
#pragma unroll 1
      for (int it = 0, s = 0; it < 34; it++) {
        if (it < 6) wait_q_free(bars + 8 * B_EQ, it);
        if (it == 16) mbar_wait(bars + 8 * (B_FW + 3), 0);
        mbar_wait(fb + 8 * (B_EW - B_FW), ph);
        expect_tx_elect(fb, (it == 8 || it == 18 || it == 19) ? 16384 : 32768);
        const int k0 = it < 16 ? wo_k(it, j) : (it < 20 ? 2 * j + (it & 1) : other_kb(it - 20, j)) * 64;
        if (it == 16 || it == 17) {
          tma_load_mc(st - 16384 + rank * 16384, wgu, fb, j * 448, k0);
          tma_load_mc(st - 8192 + rank * 16384, wgu, fb, j * 448 + 64, k0);
        } else {
          tma_load_mc(st + rank * 8192, it < 16 ? &p.wo : wgu, fb, it < 16 ? j * 128 + rank * 64 : j * 448 + 384, k0);
        }
        st += 32768; fb += 8;
        if (++s == 6) { s = 0; st -= 6 * 32768; fb -= 48; ph ^= 1; }
      }
      st = sm + 16384 + 3 * 49152; fb = bars + 8 * B_FG; ph = 1;
#pragma unroll 1
      for (int it = 0; it < 46; it++) {
        const int kb = it < 14 ? other_kb(it, j) : (it + 2) & 15, col = j * 448 + ((it + 2) >> 4) * 128;
        if (it < 4) wait_w_free(bars + 8 * B_EW, it);
        mbar_wait(fb + 8 * (B_EG - B_FG), ph);
        expect_tx_elect(fb, 49152);
        tma_load_mc(st + rank * 16384, wgu, fb, col, kb * 64);
        tma_load_mc(st + rank * 16384 + 8192, wgu, fb, col + 64, kb * 64);
        st += (it & 3) == 0 ? -3 * 49152 : 49152; fb += 8;
        if ((it & 3) == 3) { fb -= 32; ph ^= 1; }
      }
      st = sm + 16384 + 2 * 32768; fb = bars + 8 * B_FD; ph = 1;
#pragma unroll 1
      for (int it = 0, s = 0; it < 56 - KH; it++) {
        if (it < 6) wait_g_free(bars + 8 * B_EG, it);
        mbar_wait(fb + 8 * (B_ED - B_FD), ph);
        expect_tx_elect(fb, 32768);
        tma_load_mc(st + rank * 8192, &p.wd, fb, j * 128 + rank * 64, down_k(it));
        st += s == 3 ? -5 * 32768 : 32768; fb += 8;
        if (++s == 6) { s = 0; fb -= 48; ph ^= 1; }
      }
    } else if (warp == 1) {
      const int arow = rb * 128;
      uint32_t st = sm, fb = bars + 8 * B_FQ, ph = 0;
      cnt_wait(cnt + C_HA, target);
      PROF_AT(lane == 0, 16);
#pragma unroll 1
      for (int it = 4; it < 32; it++) {
        if (it == 11) mbar_wait(bars + 8 * (B_RDY + C_H), 0);
        mbar_wait(fb + 8 * (B_EQ - B_FQ), ph);
        tma_load(st, &p.h, fb, qkv_kb(it, j) * 64, arow);
        st += 49152; fb += 8;
        if ((it & 3) == 3) { st -= 4 * 49152; fb -= 32; ph ^= 1; }
      }
      fb = bars + 8 * B_FW; ph = 1;
#pragma unroll 1
      for (int it = 0, s = 0; it < 34; it++) {
        if (it < 16 || it >= 20) {
          if (it < 6) wait_q_free(bars + 8 * B_EQ, it);
          mbar_wait(fb + 8 * (B_EW - B_FW), ph);
          if (it == 0) mbar_wait(bars + 8 * (B_RDY + C_O), 0);
          if (it == 9 || it == 20) cnt_wait(cnt + (it == 9 ? C_O + 1 : C_H2A), target * 8);
          if (it == 27) mbar_wait(bars + 8 * (B_RDY + C_H2), 0);
          PROF_AT(lane == 0 && (it == 0 || it == 9 || it == 20), 17 + (it >> 3));
          if (it != 8) tma_load(st, it < 16 ? &p.o_ld : &p.h2, fb, it < 16 ? wo_k(it, j) : other_kb(it - 20, j) * 64, arow);
        }
        st += 32768; fb += 8;
        if (++s == 6) { s = 0; st -= 6 * 32768; fb -= 48; ph ^= 1; }
      }
      st = sm + 3 * 49152; fb = bars + 8 * B_FG; ph = 1;
#pragma unroll 1
      for (int it = 0; it < 46; it++) {
        if (it < 4) wait_w_free(bars + 8 * B_EW, it);
        mbar_wait(fb + 8 * (B_EG - B_FG), ph);
        tma_load(st, &p.h2, fb, (it < 14 ? other_kb(it, j) : (it + 2) & 15) * 64, arow);
        st += (it & 3) == 0 ? -3 * 49152 : 49152; fb += 8;
        if ((it & 3) == 3) { fb -= 32; ph ^= 1; }
      }
      st = sm + 2 * 32768; fb = bars + 8 * B_FD; ph = 1;
#pragma unroll 1
      for (int it = 0, s = 0; it < 56 - KH; it++) {
        if (it < 6) wait_g_free(bars + 8 * B_EG, it);
        mbar_wait(fb + 8 * (B_ED - B_FD), ph);
        const int u = it + KH, dep = it == 0 ? C_ACT : (u == 8 ? C_ACT + 1 : (u == 24 ? C_ACT + 2 : (u == 40 ? C_A0 : (u == 48 ? C_ACT + 3 : -1))));
        if (dep >= 0) mbar_wait(bars + 8 * (B_RDY + dep), 0);
        tma_load(st, &p.act, fb, down_k(it), arow);
        st += s == 3 ? -5 * 32768 : 32768; fb += 8;
        if (++s == 6) { s = 0; fb -= 48; ph ^= 1; }
      }
    } else if (warp == 2) {
      if (lane < 15) prefetch_map(&p.h + lane);
      __syncwarp();
      uint32_t ph1 = 0;
#pragma unroll 1
      for (int n = 0; n < 8; n++) {
        const int nch = (n == 1 || n == 2 || n == 4) ? 1 : 2;
#pragma unroll 1
        for (int ch = 0; ch < nch; ch++) {
          mbar_wait_watchdog(bars + 8 * (B_STGF + ch), ch ? ph1 : (n & 1));
          const uint32_t src = stg + ch * 16384;
          if (n == 2 || n == 3) {
          } else if (n == 1) {
#pragma unroll 1
            for (int q = 0; q < 8; q++) {
              tma_store2(&p.o_st, src + q * 2048, j * 128, rb * 128 + q * 16);
              if (q & 1) store_pause(true);
            }
          } else if (n >= 4 && n < 8) {
#pragma unroll 1
            for (int q = 0; q < 4; q++) {
              tma_store2(&p.act_st, src + q * 4096, j * 448 + (n == 4 ? 384 : (n - 5) * 128 + ch * 64), rb * 128 + q * 32);
              store_pause(true);
            }
          } else if (ch == 0) {
            tma_store2(&p.h, src, j * 128, rb * 128);
            asm volatile("cp.async.bulk.commit_group;" ::: "memory");
            asm volatile("cp.async.bulk.wait_group 0;" ::: "memory");
            __syncwarp();
            cnt_signal(cnt + C_HA);
          } else {
            __nanosleep(H1D);
#pragma unroll 1
            for (int q = 0; q < 8; q++) {
              tma_store2(&p.h_st, src + q * 2048, j * 128 + 64, rb * 128 + q * 16);
              if (q & 1) store_pause(true);
            }
          }
          if (n >= 5 && ch == 0) arrive_elect(bars + 8 * B_STGE);
          if (n == 7 && ch == 0) {
            asm volatile("cp.async.bulk.wait_group 0;" ::: "memory");
            __syncwarp();
            cnt_signal(cnt + C_A0);
          }
        }
        asm volatile("cp.async.bulk.commit_group;" ::: "memory");
        asm volatile("cp.async.bulk.wait_group 0;" ::: "memory");
        __syncwarp();
        if (n != 2 && n != 3) cnt_signal(cnt + n);
        PROF_AT(lane == 0, n == 0 ? 33 : 23 + n);
        if (n == 0) {
#pragma unroll 1
          for (int t = 0; t < 32; t++) {
            ll_store(p.halo + cta * 1024 + t * 32 + lane, 0u, 0u, 0u);
            __nanosleep(40);
          }
          __syncwarp();
        }
        if (n < 5) arrive_elect(bars + 8 * B_STGE);
        if (nch == 2) { arrive_elect(bars + 8 * (B_STGE + 1)); ph1 ^= 1; }
      }
      mbar_wait_watchdog(bars + 8 * B_STGF, 0);
      PROF_AT(lane == 0, 31);
    } else {
      if (lane < 4) ll_store(p.modll + cta * 4 + lane, 0u, 0u, 0u);
#pragma unroll 1
      for (int ch = 0; ch < 2; ch++) {
        if (ch == 0) {
          bar_sync(1, 288);
          const uint4 t4 = lds128(sm + RED_OFF + lane * 16);
          float a[4] = {__uint_as_float(t4.x), __uint_as_float(t4.y), __uint_as_float(t4.z), __uint_as_float(t4.w)};
#pragma unroll
          for (int o = 4; o < 32; o <<= 1)
#pragma unroll
            for (int q = 0; q < 4; q++) a[q] += __shfl_xor_sync(~0u, a[q], o);
          if (lane < 4) ll_store(p.modll + cta * 4 + lane, pack2(a[0], a[1]), pack2(a[2], a[3]), tag);
          PROF_AT(lane == 0, 1);
        }
        uint32_t m[2];
        const uint4* mp = p.modll + j * 32 + ch * 16 + (lane & 15) + (lane >> 4) * 256;
        ll_poll<1>([&](int) { return mp; }, tag, m);
        if (lane >> 4) { m[0] = pack2(1.0f + bf_lo(m[0]), 1.0f + bf_hi(m[0])); m[1] = pack2(1.0f + bf_lo(m[1]), 1.0f + bf_hi(m[1])); }
        const uint32_t dst = sm + MODB_OFF + ch * 256 + ((lane >> 2) & 3) * 64 + (lane & 1) * 32 + (lane & 2) * 4 + ((lane >> 4) ? 0 : 4);
        asm volatile("st.shared.u32 [%0], %1;\nst.shared.u32 [%0 + 16], %2;" ::"r"(dst), "r"(m[0]), "r"(m[1]) : "memory");
        __syncwarp();
        arrive_elect(bars + 8 * (B_MODA + ch));
      }
#pragma unroll 1
      for (int n = C_H; n <= C_O; n++) {
        cnt_wait_lazy(cnt + n, target);
        arrive_elect(bars + 8 * (B_RDY + n));
      }
      {
        uint32_t m[6];
        const uint4* src = p.modll + 512 + j * 32 + lane;
        ll_poll<3, 500>([&](int i) { return src + i * 256; }, tag, m);
#pragma unroll
        for (int vec = 0; vec < 3; vec++) {
          const float add = vec == 2 ? 1.0f : 0.0f;
          sts128(sm + MODB_OFF + (vec * 128 + lane * 4) * 4, __float_as_uint(bf_round(bf_lo(m[2 * vec]) + add)), __float_as_uint(bf_round(bf_hi(m[2 * vec]) + add)),
                 __float_as_uint(bf_round(bf_lo(m[2 * vec + 1]) + add)), __float_as_uint(bf_round(bf_hi(m[2 * vec + 1]) + add)));
        }
        __syncwarp();
        if (lane == 0) mbar_arrive(bars + 8 * B_MODB);
        PROF_AT(lane == 0, 15);
      }
      __syncwarp();
#pragma unroll 1
      for (int q = C_H2; q < 9; q++) {
        const int n = q < 7 ? q : (q == 7 ? C_A0 : C_ACT + 3);
        cnt_wait_lazy(cnt + n, n == C_H2 ? target * 8 : target);
        arrive_elect(bars + 8 * (B_RDY + n));
      }
      {
        uint32_t m[2];
        const uint4* src = p.modll + 512 + 768 + j * 32 + lane;
        ll_poll<1>([&](int) { return src; }, tag, m);
        sts128(sm + MODB_OFF + (384 + lane * 4) * 4, m[0] << 16, m[0] & 0xffff0000u, m[1] << 16, m[1] & 0xffff0000u);
        cnt_wait_lazy(cnt + C_SP + (j >> 1), target);
        __syncwarp();
        if (lane == 0) mbar_arrive(bars + 8 * (B_MODB + 1));
      }
    }
  } else {
    uint32_t tag;

    {
      const int tid = threadIdx.x - 128, cw = tid >> 7, warp = (tid >> 5) & 3, lane = tid & 31;
      const int l16 = lane & 15, half = lane >> 4, w8 = cw * 4 + warp;
      if (lane < 8) ll_store((uint4*)(gstats + (rb * 8 + j) * 128 + w8 * 16) + lane, 0u, 0u, 0u);
      const uint32_t cbuf = sm + 3 * 49152 + w8 * 512;
      if (lane < 16) cp_async16(cbuf + lane * 16, gc + w8 * 128 + lane * 8);
      asm volatile("cp.async.commit_group;" ::: "memory");
      const uint32_t xbuf = sm + 40960 + (cw * 2 + (l16 >> 3)) * 49152 + (warp * 16 + half) * 128;
      {
        const char* xp = (const char*)gx + (uint32_t)((rb * 128 + (warp * 16 + half) * 2 + cw) * 2048 + j * 256 + l16 * 16);
#pragma unroll
        for (int i = 0; i < 8; i++) cp_async16(xbuf + i * 256 + (((l16 & 7) ^ ((i * 2 + half) & 7)) << 4), xp + i * 8192);
      }
      asm volatile("cp.async.commit_group;" ::: "memory");
      const uint32_t wbuf = sm + cw * 49152 + warp * 4096;
      const bool late = j >= 4;
      auto fetch_w = [&]() {
        const char* wp = (const char*)gwmod + (uint32_t)(cta * 32 + (lane & 1) * 16 + (w8 * 128 + (lane >> 1)) * 12288);
#pragma unroll
        for (int i = 0; i < 8; i++) cp_async16(wbuf + i * 512 + lane * 16, wp + i * 16 * 12288);
      };
      if (!late) fetch_w();
      PROF_AT(tid == 0, 32);
      uint2* st1 = gstats + (rb * 8 + j) * 128 + cw * 64 + warp * 16;
      cluster_arrive_relaxed();
      asm volatile("setmaxnreg.inc.sync.aligned.u32 232;");
      uint32_t sa[4][4];
      {
        asm volatile("cp.async.wait_group 1;" ::: "memory");
        __syncwarp();
        const float2 cv = lds64f(cbuf + lane * 8);
        const uint32_t c0 = __float_as_uint(cv.x), c1 = __float_as_uint(cv.y);
        sts64f(cbuf + lane * 8, __uint_as_float(pack2(silu_f(bf_lo(c0)), silu_f(bf_hi(c0)))), __uint_as_float(pack2(silu_f(bf_lo(c1)), silu_f(bf_hi(c1)))));
        __syncwarp();
#pragma unroll
        for (int q = 0; q < 4; q++) ldmatrix4(sa[q][0], sa[q][1], sa[q][2], sa[q][3], cbuf + q * 64 + (lane >> 3) * 16);
      }
      cluster_wait();
      tag = lds32(bars + 8 * B_COUNT);
      if (late) {
        __nanosleep(WLD);
        fetch_w();
      }
      asm volatile("cp.async.commit_group;" ::: "memory");
      asm volatile("cp.async.wait_group 1;" ::: "memory");
      __syncwarp();
      uint32_t xl[16], xh[16];
      {
        const int srow = warp * 16 + (lane & 15);
#pragma unroll
        for (int q = 0; q < 8; q++)
          ldmatrix4(xl[2 * q], xh[2 * q], xl[2 * q + 1], xh[2 * q + 1],
                    sm + 40960 + (cw * 2 + (q >> 2)) * 49152 + srow * 128 + (((half + (q & 3) * 2) ^ (srow & 7)) << 4));
      }
      publish_stats(xl, xh, st1, lane, tag16(tag, 0));
      PROF_AT(tid == 0, 50);
      auto gemv = [&]() {
      asm volatile("cp.async.wait_group 0;" ::: "memory");
      __syncwarp();
      PROF_AT(tid == 0, 51);
      {
        uint32_t b[8][4];
#pragma unroll
        for (int ks = 0; ks < 8; ks++) ldmatrix4t(b[ks], wbuf + (ks * 16 + (lane & 15)) * 32 + (lane >> 4) * 16);
        float d0[4] = {0.f, 0.f, 0.f, 0.f}, d1[4] = {0.f, 0.f, 0.f, 0.f}, d2[4] = {0.f, 0.f, 0.f, 0.f}, d3[4] = {0.f, 0.f, 0.f, 0.f};
#pragma unroll
        for (int q = 0; q < 4; q++) {
          mma16816(d0, sa[q][0], sa[q][0], sa[q][1], sa[q][1], b[2 * q][0], b[2 * q][1]);
          mma16816(d1, sa[q][0], sa[q][0], sa[q][1], sa[q][1], b[2 * q][2], b[2 * q][3]);
          mma16816(d2, sa[q][2], sa[q][2], sa[q][3], sa[q][3], b[2 * q + 1][0], b[2 * q + 1][1]);
          mma16816(d3, sa[q][2], sa[q][2], sa[q][3], sa[q][3], b[2 * q + 1][2], b[2 * q + 1][3]);
        }
        d0[0] += d2[0]; d0[1] += d2[1]; d1[0] += d3[0]; d1[1] += d3[1];
        if (lane < 4) {
          sts64f(sm + RED_OFF + (w8 * 16 + lane * 2) * 4, d0[0], d0[1]);
          sts64f(sm + RED_OFF + (w8 * 16 + 8 + lane * 2) * 4, d1[0], d1[1]);
        }
        asm volatile("bar.arrive 1, 288;" ::: "memory");
      }
      };
      gemv();
      {
        const int c = lane & 3;
        float rs[2], nb[2];
        stat_gather(gstats + rb * 1024 + cw * 64 + warp * 16, tag16(tag, 0), lane, rs, nb);
#pragma unroll
        for (int n = 0; n < 16; n++) {
          xl[n] = pack2(bf_lo(xl[n]) * rs[0] + nb[0], bf_hi(xl[n]) * rs[0] + nb[0]);
          xh[n] = pack2(bf_lo(xh[n]) * rs[1] + nb[1], bf_hi(xh[n]) * rs[1] + nb[1]);
        }
        const int srow = warp * 16 + l16;
        const uint32_t slab = stg + cw * 8192 + srow * 128;
#pragma unroll
        for (int q = 0; q < 8; q++)
          stmatrix4(slab + (q >> 2) * 16384 + (((half + (q & 3) * 2) ^ (srow & 7)) << 4), xl[2 * q], xh[2 * q], xl[2 * q + 1], xh[2 * q + 1]);
        PROF_AT(tid == 0, 52);
        mbar_wait(bars + 8 * B_MODA, 0);
        PROF_AT(tid == 0, 2);
#pragma unroll
        for (int q = 0; q < 4; q++) {
          const uint4 mv = lds128(sm + MODB_OFF + (4 * q + c) * 16);
          const uint32_t c0 = mv.x, s0 = mv.y, c1 = mv.z, s1 = mv.w;
          stmatrix4(slab + (q >> 2) * 16384 + (((half + (q & 3) * 2) ^ (srow & 7)) << 4), fma_bf2(xl[2 * q], c0, s0), fma_bf2(xh[2 * q], c0, s0),
                    fma_bf2(xl[2 * q + 1], c1, s1), fma_bf2(xh[2 * q + 1], c1, s1));
          if ((q & 3) == 3) stage_done(bars + 8 * (B_STGF + (q >> 2)), lane);
        }
      }
      PROF_AT(tid == 0, 3);
    }

    uint32_t xl[16], xh[16];
    {
      RING_IDS();
      uint32_t prev = 0;
      float acc1[96];
      {
        Ring g{bars + 8 * B_FQ, rbars + 8 * B_EQ, 0, 0u, 0u, releaser TR(0)};
        float acc0[96];
#pragma unroll 1
        for (int kb = 0; kb < 2; kb++) {
          kblock<192, 4, 49152>(acc0, g, a_base + STG_OFF + kb * 16384, kb == 0, prev);
          kblock<192, 4, 49152>(acc1, g, a_base + STG_OFF + kb * 16384, kb == 0, prev);
          if (kb == 0) {
            LANE_IDS();
            mbar_wait(bars + 8 * (B_MODA + 1), 0);
#pragma unroll
            for (int hh = 0; hh < 2; hh++) {
              uint32_t v[2][4];
              uint4 mv[2];
#pragma unroll
              for (int q = 0; q < 2; q++) {
                ldmatrix4(v[q][0], v[q][1], v[q][2], v[q][3], slab + 16384 + ((sw0 ^ (hh * 4 + q * 2)) << 4));
                mv[q] = lds128(sm + MODB_OFF + (16 + 8 * hh + 4 * q + c) * 16);
              }
#pragma unroll
              for (int q = 0; q < 2; q++)
                stmatrix4(slab + 16384 + ((sw0 ^ (hh * 4 + q * 2)) << 4), fma_bf2(v[q][0], mv[q].x, mv[q].y), fma_bf2(v[q][1], mv[q].x, mv[q].y),
                          fma_bf2(v[q][2], mv[q].z, mv[q].w), fma_bf2(v[q][3], mv[q].z, mv[q].w));
            }
            stage_done(bars + 8 * (B_STGF + 1), lane);
          }
        }
#pragma unroll 1
        for (int kb = 0; kb < 14; kb++) kblock<192, 4, 49152>(acc0, g, a_base + g.off, false, prev);
        PROF_AT(tid == 0, 4);
        attention<NPRE0, false>(acc0, p, 0, rb, cta, cw, warp, tag, stg, bars, prev, [&]() { kblock<192, 4, 49152>(acc1, g, a_base + g.off, false, prev); });
        PROF_AT(tid == 0, 5);
        {
          LANE_IDS();
#pragma unroll
          for (int q = 0; q < 8; q++)
            ldmatrix4(xl[2 * q], xh[2 * q], xl[2 * q + 1], xh[2 * q + 1], sm + 40960 + (cw * 2 + (q >> 2)) * 49152 + srow * 128 + ((sw0 ^ ((q & 3) * 2)) << 4));
#pragma unroll
          for (int q = 0; q < 16; q++) asm volatile("" : "+r"(xl[q]), "+r"(xh[q])::"memory");
        }
#pragma unroll 1
        for (int kb = 5 + NPRE0; kb < 14; kb++) kblock<192, 4, 49152>(acc1, g, a_base + g.off, false, prev);
        PROF_AT(tid == 0, 6);
      }
      float acc[64];
      Ring g{bars + 8 * B_FW, rbars + 8 * B_EW, 0, 0u, 0u, releaser TR(32)};
      attention<NPRE1, true>(acc1, p, 1, rb, cta, cw, warp, tag, stg, bars, prev, [&]() { kblock<128, 6, 32768>(acc, g, a_base + g.off, g.s == 0, prev); });
      PROF_AT(tid == 0, 7);
      LANE_IDS();
      unsigned* cnt = p.cnt + rb * 32;
      tma_store2(&p.o_st, stg + cw * 8192 + warp * 2048, j * 128 + 64, rb * 128 + cw * 64 + warp * 16);
      asm volatile("cp.async.bulk.commit_group;" ::: "memory");
#pragma unroll 1
      for (int kb = 1 + NPRE1; kb < 16; kb++) {
        if (kb == 8) wg_bar(cw);
        kblock<128, 6, 32768>(acc, g, a_base + (kb == 8 ? STG_OFF : g.off), false, prev);
        if (kb == 3 + NPRE1) {
          asm volatile("cp.async.bulk.wait_group 0;" ::: "memory");
          __syncwarp();
          cnt_signal(cnt + C_O + 1);
        }
      }
      mbar_wait(bars + 8 * B_STGE, 0);
      mbar_wait(bars + 8 * B_MODB, 0);
      float2 ga[16];
#pragma unroll
      for (int n = 0; n < 16; n++) ga[n] = lds64f(sm + MODB_OFF + (8 * n + 2 * c) * 4);
      tile_end(acc, prev);
      PROF_AT(tid == 0, 8);
#pragma unroll
      for (int n = 0; n < 16; n++) {
        acc[4 * n] = ga[n].x * acc[4 * n] + bf_lo(xl[n]); acc[4 * n + 1] = ga[n].y * acc[4 * n + 1] + bf_hi(xl[n]);
        acc[4 * n + 2] = ga[n].x * acc[4 * n + 2] + bf_lo(xh[n]); acc[4 * n + 3] = ga[n].y * acc[4 * n + 3] + bf_hi(xh[n]);
        xl[n] = pack2(acc[4 * n], acc[4 * n + 1]);
        xh[n] = pack2(acc[4 * n + 2], acc[4 * n + 3]);
      }
      publish_stats(xl, xh, gstats + (rb * 8 + j) * 128 + cw * 64 + warp * 16, lane, tag16(tag, 1));
      PROF_AT(tid == 0, 48);
      float2 sb[16], cb[16];
#pragma unroll
      for (int n = 0; n < 16; n++) {
        sb[n] = lds64f(sm + MODB_OFF + (128 + 8 * n + 2 * c) * 4);
        cb[n] = lds64f(sm + MODB_OFF + (256 + 8 * n + 2 * c) * 4);
      }
      PROF_AT(tid == 0, 49);
      float nb[2], rstd[2];
      stat_gather(gstats + rb * 1024 + cw * 64 + warp * 16, tag16(tag, 1), lane, rstd, nb);
      PROF_AT(tid == 0, 9);
#pragma unroll
      for (int ch = 0; ch < 2; ch++) {
        uint32_t lo[8], hi[8];
#pragma unroll
        for (int t = 0; t < 8; t++) {
          const int n = ch * 8 + t;
          lo[t] = pack2((acc[4 * n] * rstd[0] + nb[0]) * cb[n].x + sb[n].x, (acc[4 * n + 1] * rstd[0] + nb[0]) * cb[n].y + sb[n].y);
          hi[t] = pack2((acc[4 * n + 2] * rstd[1] + nb[1]) * cb[n].x + sb[n].x, (acc[4 * n + 3] * rstd[1] + nb[1]) * cb[n].y + sb[n].y);
        }
        stage_slab(sm + ch * 32768 + cw * 8192, warp, lane, lo, hi);
        stage_done(bars + 8 * (B_STGF + ch), lane);
        tma_store2(&p.h2_st, sm + ch * 32768 + cw * 8192 + warp * 2048, j * 128 + ch * 64, rb * 128 + cw * 64 + warp * 16);
        asm volatile("cp.async.bulk.commit_group;" ::: "memory");
      }
      PROF_AT(tid == 0, 10);
    }

    uint32_t pg[32], pu[32];
    {
      RING_IDS();
      float acc[128];
      uint32_t prev = 0;
      Ring g{bars + 8 * B_FG, rbars + 8 * B_EG, 0, 0u, 3 * 49152u, releaser TR(66)};
      {
        Ring w{bars + 8 * B_FW, rbars + 8 * B_EW, 4, 0u, 4 * 32768u, releaser TR(48)};
        float acn[64];
#pragma unroll 1
        for (int kb = 0; kb < 2; kb++) {
          kblock<256, 6, 32768>(acc, w, a_base + kb * 32768, kb == 0, prev, 0u);
          if (kb == 0) asm volatile("cp.async.bulk.wait_group 1;" ::: "memory");
          else asm volatile("cp.async.bulk.wait_group 0;" ::: "memory");
          __syncwarp();
          cnt_signal(p.cnt + rb * 32 + (kb == 0 ? C_H2A : C_H2));
        }
        {
          LANE_IDS();
#pragma unroll
          for (int q = 0; q < 8; q++)
            stmatrix4(slab + (q >> 2) * 16384 + ((sw0 ^ ((q & 3) * 2)) << 4), xl[2 * q], xh[2 * q], xl[2 * q + 1], xh[2 * q + 1]);
          __syncwarp();
        }
#pragma unroll 1
        for (int kb = 0; kb < 16; kb++) {
          kblock<128, 6, 32768>(acn, w, a_base + w.off, kb == 0, prev);
          if (kb == 4) {
            asm volatile("fence.proxy.async.shared::cta;" ::: "memory");
            __syncwarp();
          }
          if (kb == 6 + warp || kb == 10 + warp) {
            const int ch = kb != 6 + warp;
            tma_store3(&p.out, stg + ch * 16384 + cw * 8192 + warp * 2048, j * 128 + ch * 64, rb * 64 + warp * 16, cw);
            asm volatile("cp.async.bulk.commit_group;" ::: "memory");
          }
        }
        PROF_AT(tid == 0, 39);
        kblock<256, 4, 49152>(acc, g, a_base + g.off, false, prev);
        fence_regs(acn);
#pragma unroll
        for (int q = 0; q < 16; q++) {
          pg[q] = pack2(acn[2 * q], acn[2 * q + 1]);
          pu[q] = pack2(acn[32 + 2 * q], acn[32 + 2 * q + 1]);
          pg[16 + q] = 0; pu[16 + q] = 0;
        }
        asm volatile("cp.async.bulk.wait_group 0;" ::: "memory");
        kblock<256, 4, 49152>(acc, g, a_base + g.off, false, prev);
      }
      LANE_IDS();
#pragma unroll 1
      for (int t = 0; t < 3; t++) {
#pragma unroll 1
        for (int blk = 0; blk < (t == 0 ? 2 : 4); blk++) {
          g.s = 2;
#pragma unroll
          for (int i = 0; i < 4; i++) {
            g.off = ((i + 1) & 3) * 49152;
            if (i == 3 && blk == 3) skew_pre(cw);
            kblock<256, 4, 49152>(acc, g, a_base + g.off, t > 0 && blk == 0 && i == 0, prev);
            if (i == 3 && blk == 3) skew_post(cw);
            if ((blk & 1) == 0 && i == 0) mbar_wait(bars + 8 * (B_STGE + (blk >> 1)), (t + 1 + (blk >> 1)) & 1);
            stmatrix2(slab + (blk >> 1) * 16384 + (((srow & 7) ^ ((blk & 1) * 4 + i)) << 4), swiglu2(pg[2 * i], pu[2 * i]), swiglu2(pg[2 * i + 1], pu[2 * i + 1]));
          }
#pragma unroll
          for (int q = 0; q < 24; q++) { pg[q] = pg[q + 8]; pu[q] = pu[q + 8]; }
          if (blk & 1) stage_done(bars + 8 * (B_STGF + (blk >> 1)), lane);
        }
#pragma unroll 1
        for (int kb = t == 0 ? 0 : 4; kb < 4; kb++) {
          if (kb == 3) skew_pre(cw);
          kblock<256, 4, 49152>(acc, g, a_base + g.off, false, prev);
          if (kb == 3) skew_post(cw);
        }
        tile_end(acc, prev);
        PROF_AT(tid == 0, 36 + t);
#pragma unroll
        for (int q = 0; q < 32; q++) {
          pg[q] = pack2(acc[2 * q], acc[2 * q + 1]);
          pu[q] = pack2(acc[64 + 2 * q], acc[64 + 2 * q + 1]);
        }
      }
      PROF_AT(tid == 0, 11);
    }

    {
      RING_IDS();
      LANE_IDS();
      Ring g{bars + 8 * B_FD, rbars + 8 * B_ED, 0, 0u, 2 * 32768u, releaser TR(112)};
      float acc[64];
      uint32_t prev = 0;
#pragma unroll 1
      for (int blk = 0; blk < 4; blk++) {
#pragma unroll
        for (int i = 0; i < 8; i++) {
          kblock<128, 6, 32768>(acc, g, a_base + g.off, blk == 0 && i == 0, prev);
          if ((blk & 1) == 0 && i == 0) mbar_wait(bars + 8 * (B_STGE + (blk >> 1)), blk >> 1);
          stmatrix1(slab + (blk >> 1) * 16384 + (i & 1) * 1024 + (((srow & 7) ^ ((blk & 1) * 4 + (i >> 1))) << 4), swiglu2(pg[i], pu[i]));
        }
#pragma unroll
        for (int q = 0; q < 24; q++) { pg[q] = pg[q + 8]; pu[q] = pu[q + 8]; }
        if (blk & 1) stage_done(bars + 8 * (B_STGF + (blk >> 1)), lane);
      }
#pragma unroll 1
      for (int kb = 32; kb < 56 - KH; kb++) {
        if (kb == 50 - KH) g.releaser = false;
        if (kb == 52 - KH) skew_pre(cw);
        kblock<128, 6, 32768>(acc, g, a_base + g.off, false, prev);
      }
      skew_post(cw);
      mbar_wait(bars + 8 * (B_MODB + 1), 0);
      mbar_wait(bars + 8 * B_STGE, 1);
      mbar_wait(bars + 8 * (B_STGE + 1), 0);
      float2 gbv[16];
#pragma unroll
      for (int n = 0; n < 16; n++) gbv[n] = lds64f(sm + MODB_OFF + (384 + 8 * n + 2 * c) * 4);
      tile_end(acc, prev);
      PROF_AT(tid == 0, 13);
#pragma unroll
      for (int ch = 0; ch < 2; ch++) {
        uint32_t lo[8], hi[8];
#pragma unroll
        for (int t = 0; t < 8; t++) {
          const int n = ch * 8 + t;
          const float2 gb = gbv[n];
          lo[t] = pack2(gb.x * acc[4 * n], gb.y * acc[4 * n + 1]);
          hi[t] = pack2(gb.x * acc[4 * n + 2], gb.y * acc[4 * n + 3]);
        }
        stage_slab(stg + ch * 16384 + cw * 8192, warp, lane, lo, hi);
        asm volatile("fence.proxy.async.shared::cta;" ::: "memory");
        __syncwarp();
        tma_add3(&p.out, stg + ch * 16384 + cw * 8192 + warp * 2048, j * 128 + ch * 64, rb * 64 + warp * 16, cw);
      }
      asm volatile("cp.async.bulk.commit_group;" ::: "memory");
      if (lane == 0) mbar_arrive(bars + 8 * B_STGF);
      asm volatile("cp.async.bulk.wait_group.read 0;" ::: "memory");
      PROF_AT(tid == 0, 14);
    }
    if (blockIdx.x == 0 && threadIdx.x == 128) asm volatile("st.relaxed.gpu.global.u32 [%0], %1;" ::"l"(gepoch), "r"(tag) : "memory");
  }
}

typedef CUresult (*EncodeFn)(CUtensorMap*, CUtensorMapDataType, cuuint32_t, void*, const cuuint64_t*, const cuuint64_t*,
                             const cuuint32_t*, const cuuint32_t*, CUtensorMapInterleave, CUtensorMapSwizzle,
                             CUtensorMapL2promotion, CUtensorMapFloatOOBfill);

void encode2d(EncodeFn fn, CUtensorMap* m, const void* ptr, uint64_t cols, uint64_t rows, uint32_t box_rows) {
  cuuint64_t dims[2] = {cols, rows};
  cuuint64_t strides[1] = {cols * 2};
  cuuint32_t box[2] = {64, box_rows};
  cuuint32_t es[2] = {1, 1};
  fn(m, CU_TENSOR_MAP_DATA_TYPE_BFLOAT16, 2, (void*)ptr, dims, strides, box, es, CU_TENSOR_MAP_INTERLEAVE_NONE,
     CU_TENSOR_MAP_SWIZZLE_128B, CU_TENSOR_MAP_L2_PROMOTION_L2_128B, CU_TENSOR_MAP_FLOAT_OOB_FILL_NONE);
}

}

extern "C" void kernel_launch(void* const* d_in, const int* in_sizes, int n_in, void* d_out, int out_size) {
  (void)in_sizes; (void)n_in; (void)out_size;
  void* fp = nullptr;
  cudaDriverEntryPointQueryResult qr;
  cudaGetDriverEntryPoint("cuTensorMapEncodeTiled", &fp, cudaEnableDefault, &qr);
  EncodeFn fn = (EncodeFn)fp;
  void *ph, *po, *ph2, *pact;
  cudaGetSymbolAddress(&ph, g_h);
  cudaGetSymbolAddress(&po, g_o);
  ph2 = ph;
  cudaGetSymbolAddress(&pact, g_act);
  Params p;
  encode2d(fn, &p.h, ph, DM, SEQ, 128);
  encode2d(fn, &p.o_ld, po, DM, SEQ, 128);
  encode2d(fn, &p.h2, ph2, DM, SEQ, 128);
  encode2d(fn, &p.act, pact, FF, SEQ, 128);
  encode2d(fn, &p.act_st, pact, FF, SEQ, 32);
  encode2d(fn, &p.wm, d_in[8], 6 * DM, DM, 64);
  encode2d(fn, &p.o_st, po, DM, SEQ, 16);
  encode2d(fn, &p.h2_st, ph2, DM, SEQ, 16);
  encode2d(fn, &p.h_st, ph, DM, SEQ, 16);
  encode2d(fn, &p.wqkv, d_in[1], 3 * DM, DM, 64);
  encode2d(fn, &p.wqkv32, d_in[1], 3 * DM, DM, 32);
  encode2d(fn, &p.wo, d_in[2], DM, DM, 64);
  encode2d(fn, &p.wg, d_in[4], FF, DM, 64);
  encode2d(fn, &p.wu, d_in[5], FF, DM, 64);
  encode2d(fn, &p.wd, d_in[6], DM, FF, 64);
  {
    cuuint64_t dims[3] = {DM, SEQ / 2, 2};
    cuuint64_t strides[2] = {DM * 4, DM * 2};
    cuuint32_t box[3] = {64, 16, 1};
    cuuint32_t es[3] = {1, 1, 1};
    fn(&p.out, CU_TENSOR_MAP_DATA_TYPE_BFLOAT16, 3, d_out, dims, strides, box, es, CU_TENSOR_MAP_INTERLEAVE_NONE,
       CU_TENSOR_MAP_SWIZZLE_128B, CU_TENSOR_MAP_L2_PROMOTION_L2_128B, CU_TENSOR_MAP_FLOAT_OOB_FILL_NONE);
  }
  void* q;
  cudaGetSymbolAddress(&q, g_modll); p.modll = (uint4*)q;
  cudaGetSymbolAddress(&q, g_halo); p.halo = (uint4*)q;
  cudaGetSymbolAddress(&q, g_stats); uint2* stats = (uint2*)q;
  cudaGetSymbolAddress(&q, g_cnt); p.cnt = (unsigned*)q;
  cudaGetSymbolAddress(&q, g_epoch); unsigned* epoch = (unsigned*)q;

  cudaFuncSetAttribute(fused_kernel, cudaFuncAttributeMaxDynamicSharedMemorySize, SMEM_BYTES);
  cudaLaunchConfig_t cfg = {};
  cfg.gridDim = dim3(NCTA + 4);
  cfg.blockDim = dim3(384);
  cfg.dynamicSmemBytes = SMEM_BYTES;
  cfg.stream = cudaStreamPerThread;
  cudaLaunchAttribute at[1];
  at[0].id = cudaLaunchAttributeClusterDimension;
  at[0].val.clusterDim.x = 2; at[0].val.clusterDim.y = 1; at[0].val.clusterDim.z = 1;
  cfg.attrs = at;
  cfg.numAttrs = 1;
  cudaLaunchKernelEx(&cfg, fused_kernel, (const bf16*)d_in[0], (const bf16*)d_in[8], (const bf16*)d_in[7], epoch, stats, p);
}
```
